```python
import torch

def _softmax(x, axis=-1):
    return torch.softmax(x, dim=axis)
def _gelu(x):
    return torch.nn.functional.gelu(x, approximate="tanh")
def _silu(x):
    return torch.nn.functional.silu(x)
def _sigmoid(x):
    return torch.sigmoid(x)
def _layernorm(x, axis=-1, eps=1e-5):
    m = x.mean(dim=axis, keepdim=True)
    v = x.var(dim=axis, keepdim=True, unbiased=False)
    return (x - m) / torch.sqrt(v + eps)
def _scatter_add(tgt, idx, src, axis=0):
    return tgt.clone().index_add_(axis, idx, src)
def _segment_sum(src, seg, n):
    out = torch.zeros((n,) + src.shape[1:], dtype=src.dtype)
    return out.index_add_(0, seg, src)
def _pad(x, pw):
    flat = tuple(v for pair in reversed(pw) for v in pair)
    return torch.nn.functional.pad(x, flat)

kernel_name = 'sequential_preLN__sliding_local_dilated__glu_gated_swiglu__prompt'

def setup_inputs():

    _w = (lambda a: (lambda t: t.to(torch.bfloat16) if t.is_floating_point() else t)(torch.as_tensor(a)))
    def _A_setup():
        B, S, D = 1, 2048, 512
        return {
            "x": _w((lambda *s: torch.randn(*s, dtype=torch.bfloat16) * 0.05)(B, S, D)),
            "wqkv": _w((lambda *s: torch.randn(*s, dtype=torch.bfloat16) * 0.05)(D, 3 * D)),
            "wo": _w((lambda *s: torch.randn(*s, dtype=torch.bfloat16) * 0.05)(D, D)),
        }
    _A_in = _A_setup()

    def _B_setup():
        B, S, D, F = 1, 2048, 512, 1792
        return {
            "x": _w((lambda *s: torch.randn(*s, dtype=torch.bfloat16) * 0.05)(B, S, D)),
            "w1": _w((lambda *s: torch.randn(*s, dtype=torch.bfloat16) * 0.8)(D, F) * (2.0 / D) ** 0.5),
            "w3": _w((lambda *s: torch.randn(*s, dtype=torch.bfloat16) * 0.8)(D, F) * (2.0 / D) ** 0.5),
            "w2": _w((lambda *s: torch.randn(*s, dtype=torch.bfloat16) * 0.8)(F, D) * (2.0 / F) ** 0.5),
        }
    _B_in = _B_setup()

    return {
        "A_x": _A_in["x"],
        "A_wqkv": _A_in["wqkv"],
        "A_wo": _A_in["wo"],
        "B_x": _B_in["x"],
        "B_w1": _B_in["w1"],
        "B_w3": _B_in["w3"],
        "B_w2": _B_in["w2"],
    }

def reference(A_x, A_wqkv, A_wo, B_x, B_w1, B_w3, B_w2):
    def _A_ref(x, wqkv, wo):
        B, S, D = x.shape
        H = 32; Dh = D // H
        W, dil = 8, 2
        qkv = (lambda x, *d: x.permute(*d))((x @ wqkv).reshape(B, S, 3, H, Dh), 2, 0, 3, 1, 4)
        q, k, v = qkv[0], qkv[1], qkv[2]
        scale = Dh ** -0.5
        pos = torch.arange(S)
        off = torch.arange(W) * dil
        idx = pos[:, None] - off[None, :]
        mask = idx >= 0
        idx_c = torch.where(mask, idx, 0).reshape(-1)
        kg = k[:, :, idx_c, :].reshape(B, H, S, W, Dh)
        vg = v[:, :, idx_c, :].reshape(B, H, S, W, Dh)
        logits = torch.einsum("bhsd,bhswd->bhsw", q, kg) * scale
        logits = torch.where(mask[None, None, :, :], logits, -1e9)
        attn = _softmax(logits, axis=-1)
        o = torch.einsum("bhsw,bhswd->bhsd", attn, vg)
        return (lambda x, *d: x.permute(*d))(o, 0, 2, 1, 3).reshape(B, S, D) @ wo

    def _B_ref(x, w1, w3, w2):
        gate = torch.einsum("bsd,df->bsf", x, w1)
        up = torch.einsum("bsd,df->bsf", x, w3)
        h = _silu(gate) * up
        out = torch.einsum("bsf,fd->bsd", h, w2)
        return out

    x = A_x
    h = x + _A_ref(_layernorm(x, axis=-1), A_wqkv, A_wo)
    h2 = h + _B_ref(_layernorm(h, axis=-1), B_w1, B_w3, B_w2)
    return h2
```

```cpp
#include <cuda_runtime.h>
#include <cuda.h>
#include <cuda_bf16.h>
#include <stdint.h>

namespace {

constexpr int S_ = 2048, D_ = 512, F_ = 1792;
#define LAG_KB 3

constexpr uint32_t SPIN_LIMIT = 1u << 18;

__device__ unsigned g_epoch[128];
__device__ uint4 g_e0s[2048];
__device__ uint4 g_e0c[8 * 3 * 16 * 16];
__device__ uint4 g_e1[16 * 8 * 2 * 4 * 32];
__device__ uint4 g_e2[16 * 2 * 4 * 32 * 32];
__device__ uint4 g_e3s[16 * 2 * 4 * 8 * 8];
__device__ uint4 g_e3h[16 * 2 * 4 * 32 * 32];
__device__ uint4 g_e4[16 * 2 * 4 * 8 * 8 * 4 * 32];
#define PSTAMP(i)
#define PSTAMPW(slot, i)

struct alignas(64) Params {
  CUtensorMap x, out, wqkv, wo, w1, w3, w1h, w3h, w2;
  const __nv_bfloat16 *xp, *wqkvp, *wop, *w1p, *w3p, *w2p;
};

constexpr uint32_t OFF_H = 0;
constexpr uint32_t OFF_RING = 131072;
constexpr uint32_t OFF_BAR = 229376;
constexpr uint32_t OFF_CS = OFF_BAR + 1024;
constexpr uint32_t OFF_ST = OFF_CS + 768;
constexpr uint32_t SMEM_BYTES = 232448;
static_assert(OFF_ST + 1024 <= SMEM_BYTES, "smem");

enum : int {
  B_FX = 0,
  B_FKV = 16, B_FQ = 24, B_FWO = 32, B_FA = 40, B_FB = 48, B_FT = 56,
  B_EKV = 64, B_EQ = 72, B_EA = 80, B_EB = 88,
  B_ET0 = 96, B_XCHG = 97, B_WODONE = 98, B_READY = 99, B_PUB = 100, B_LAG = 101,
  B_COUNT = 102
};

__device__ __forceinline__ uint32_t smem_u32(const void* p) { return (uint32_t)__cvta_generic_to_shared(p); }
__device__ __forceinline__ void mbar_init(uint32_t b, uint32_t c) { asm volatile("mbarrier.init.shared::cta.b64 [%0], %1;" ::"r"(b), "r"(c) : "memory"); }
__device__ __forceinline__ void mbar_expect_tx(uint32_t b, uint32_t bytes) { asm volatile("mbarrier.arrive.expect_tx.shared::cta.b64 _, [%0], %1;" ::"r"(b), "r"(bytes) : "memory"); }
__device__ __forceinline__ void mbar_arrive(uint32_t b) { asm volatile("mbarrier.arrive.shared::cta.b64 _, [%0];" ::"r"(b) : "memory"); }
__device__ __forceinline__ bool mbar_try(uint32_t b) {
  uint32_t ok;
  asm volatile("{\n.reg .pred p;\nmbarrier.try_wait.parity.shared::cta.b64 p, [%1], 0;\nselp.u32 %0, 1, 0, p;\n}\n" : "=r"(ok) : "r"(b) : "memory");
  return ok;
}
__device__ __forceinline__ void mbar_wait(uint32_t b) {
  if (mbar_try(b)) return;
  uint32_t it = 0;
  while (!mbar_try(b)) { if (++it > SPIN_LIMIT) break; }
}
__device__ __forceinline__ bool elect_one() {
  uint32_t p;
  asm volatile("{\n.reg .pred P;\nelect.sync _|P, 0xffffffff;\nselp.u32 %0, 1, 0, P;\n}\n" : "=r"(p));
  return p;
}
__device__ __forceinline__ void tma2d(uint32_t dst, const CUtensorMap* m, int c0, int c1, uint32_t bar) {
  asm volatile("cp.async.bulk.tensor.2d.shared::cluster.global.mbarrier::complete_tx::bytes [%0], [%1, {%3, %4}], [%2];"
               ::"r"(dst), "l"(m), "r"(bar), "r"(c0), "r"(c1) : "memory");
}
__device__ __forceinline__ void tma3d(uint32_t dst, const CUtensorMap* m, int c0, int c1, int c2, uint32_t bar) {
  asm volatile("cp.async.bulk.tensor.3d.shared::cluster.global.mbarrier::complete_tx::bytes [%0], [%1, {%3, %4, %5}], [%2];"
               ::"r"(dst), "l"(m), "r"(bar), "r"(c0), "r"(c1), "r"(c2) : "memory");
}
__device__ __forceinline__ void tma3d_store(const CUtensorMap* m, uint32_t src, int c0, int c1, int c2) {
  asm volatile("cp.async.bulk.tensor.3d.global.shared::cta.bulk_group [%0, {%2, %3, %4}], [%1];"
               ::"l"(m), "r"(src), "r"(c0), "r"(c1), "r"(c2) : "memory");
}
__device__ __forceinline__ void l2_prefetch(const void* p, uint32_t bytes) {
  asm volatile("cp.async.bulk.prefetch.L2.global [%0], %1;" ::"l"(p), "r"(bytes) : "memory");
}
__device__ __forceinline__ void prefetch_map(const CUtensorMap* m) { asm volatile("prefetch.tensormap [%0];" ::"l"(m) : "memory"); }
__device__ __forceinline__ void fence_async_smem() { asm volatile("fence.proxy.async.shared::cta;" ::: "memory"); }
__device__ __forceinline__ void wg_fence() { asm volatile("wgmma.fence.sync.aligned;" ::: "memory"); }
__device__ __forceinline__ void wg_commit() { asm volatile("wgmma.commit_group.sync.aligned;" ::: "memory"); }
template <int N> __device__ __forceinline__ void wg_wait() { asm volatile("wgmma.wait_group.sync.aligned %0;" ::"n"(N) : "memory"); }
__device__ __forceinline__ void wg_bar(int p) {
  if (p == 0) asm volatile("bar.sync 1, 128;" ::: "memory"); else asm volatile("bar.sync 2, 128;" ::: "memory");
}
__device__ __forceinline__ uint64_t mkdesc(uint32_t addr, uint32_t lbo, uint32_t sbo, uint32_t sw) {
  return (uint64_t)((addr & 0x3FFFF) >> 4) | ((uint64_t)(lbo >> 4) << 16) | ((uint64_t)(sbo >> 4) << 32) | ((uint64_t)sw << 62);
}
__device__ __forceinline__ uint64_t descA(uint32_t addr) { return mkdesc(addr, 16, 1024, 1); }
__device__ __forceinline__ uint64_t descB(uint32_t addr) { return mkdesc(addr, 8192, 1024, 1); }
__device__ __forceinline__ uint64_t descBh(uint32_t addr) { return mkdesc(addr, 4096, 512, 2); }

__device__ __forceinline__ void wgmma_ss_n64(float (&d)[32], uint64_t da, uint64_t db, int sc) {
  asm volatile("{\n.reg .pred p;\nsetp.ne.b32 p, %34, 0;\n"
    "wgmma.mma_async.sync.aligned.m64n64k16.f32.bf16.bf16 {%0, %1, %2, %3, %4, %5, %6, %7, %8, %9, %10, %11, %12, %13, %14, %15, %16, %17, %18, %19, %20, %21, %22, %23, %24, %25, %26, %27, %28, %29, %30, %31}, %32, %33, p, 1, 1, 0, 1;\n}\n"
    : "+f"(d[0]), "+f"(d[1]), "+f"(d[2]), "+f"(d[3]), "+f"(d[4]), "+f"(d[5]), "+f"(d[6]), "+f"(d[7]),
      "+f"(d[8]), "+f"(d[9]), "+f"(d[10]), "+f"(d[11]), "+f"(d[12]), "+f"(d[13]), "+f"(d[14]), "+f"(d[15]),
      "+f"(d[16]), "+f"(d[17]), "+f"(d[18]), "+f"(d[19]), "+f"(d[20]), "+f"(d[21]), "+f"(d[22]), "+f"(d[23]),
      "+f"(d[24]), "+f"(d[25]), "+f"(d[26]), "+f"(d[27]), "+f"(d[28]), "+f"(d[29]), "+f"(d[30]), "+f"(d[31])
    : "l"(da), "l"(db), "r"(sc));
}
__device__ __forceinline__ void wgmma_ss_n128(float (&d)[64], uint64_t da, uint64_t db, int sc) {
  asm volatile("{\n.reg .pred p;\nsetp.ne.b32 p, %66, 0;\n"
    "wgmma.mma_async.sync.aligned.m64n128k16.f32.bf16.bf16 {%0, %1, %2, %3, %4, %5, %6, %7, %8, %9, %10, %11, %12, %13, %14, %15, %16, %17, %18, %19, %20, %21, %22, %23, %24, %25, %26, %27, %28, %29, %30, %31, %32, %33, %34, %35, %36, %37, %38, %39, %40, %41, %42, %43, %44, %45, %46, %47, %48, %49, %50, %51, %52, %53, %54, %55, %56, %57, %58, %59, %60, %61, %62, %63}, %64, %65, p, 1, 1, 0, 1;\n}\n"
    : "+f"(d[0]), "+f"(d[1]), "+f"(d[2]), "+f"(d[3]), "+f"(d[4]), "+f"(d[5]), "+f"(d[6]), "+f"(d[7]),
      "+f"(d[8]), "+f"(d[9]), "+f"(d[10]), "+f"(d[11]), "+f"(d[12]), "+f"(d[13]), "+f"(d[14]), "+f"(d[15]),
      "+f"(d[16]), "+f"(d[17]), "+f"(d[18]), "+f"(d[19]), "+f"(d[20]), "+f"(d[21]), "+f"(d[22]), "+f"(d[23]),
      "+f"(d[24]), "+f"(d[25]), "+f"(d[26]), "+f"(d[27]), "+f"(d[28]), "+f"(d[29]), "+f"(d[30]), "+f"(d[31]),
      "+f"(d[32]), "+f"(d[33]), "+f"(d[34]), "+f"(d[35]), "+f"(d[36]), "+f"(d[37]), "+f"(d[38]), "+f"(d[39]),
      "+f"(d[40]), "+f"(d[41]), "+f"(d[42]), "+f"(d[43]), "+f"(d[44]), "+f"(d[45]), "+f"(d[46]), "+f"(d[47]),
      "+f"(d[48]), "+f"(d[49]), "+f"(d[50]), "+f"(d[51]), "+f"(d[52]), "+f"(d[53]), "+f"(d[54]), "+f"(d[55]),
      "+f"(d[56]), "+f"(d[57]), "+f"(d[58]), "+f"(d[59]), "+f"(d[60]), "+f"(d[61]), "+f"(d[62]), "+f"(d[63])
    : "l"(da), "l"(db), "r"(sc));
}
__device__ __forceinline__ void wgmma_ss_n256(float (&d)[128], uint64_t da, uint64_t db, int sc) {
  asm volatile("{\n.reg .pred p;\nsetp.ne.b32 p, %130, 0;\n"
    "wgmma.mma_async.sync.aligned.m64n256k16.f32.bf16.bf16 {%0, %1, %2, %3, %4, %5, %6, %7, %8, %9, %10, %11, %12, %13, %14, %15, %16, %17, %18, %19, %20, %21, %22, %23, %24, %25, %26, %27, %28, %29, %30, %31, %32, %33, %34, %35, %36, %37, %38, %39, %40, %41, %42, %43, %44, %45, %46, %47, %48, %49, %50, %51, %52, %53, %54, %55, %56, %57, %58, %59, %60, %61, %62, %63, %64, %65, %66, %67, %68, %69, %70, %71, %72, %73, %74, %75, %76, %77, %78, %79, %80, %81, %82, %83, %84, %85, %86, %87, %88, %89, %90, %91, %92, %93, %94, %95, %96, %97, %98, %99, %100, %101, %102, %103, %104, %105, %106, %107, %108, %109, %110, %111, %112, %113, %114, %115, %116, %117, %118, %119, %120, %121, %122, %123, %124, %125, %126, %127}, %128, %129, p, 1, 1, 0, 1;\n}\n"
    : "+f"(d[0]), "+f"(d[1]), "+f"(d[2]), "+f"(d[3]), "+f"(d[4]), "+f"(d[5]), "+f"(d[6]), "+f"(d[7]),
      "+f"(d[8]), "+f"(d[9]), "+f"(d[10]), "+f"(d[11]), "+f"(d[12]), "+f"(d[13]), "+f"(d[14]), "+f"(d[15]),
      "+f"(d[16]), "+f"(d[17]), "+f"(d[18]), "+f"(d[19]), "+f"(d[20]), "+f"(d[21]), "+f"(d[22]), "+f"(d[23]),
      "+f"(d[24]), "+f"(d[25]), "+f"(d[26]), "+f"(d[27]), "+f"(d[28]), "+f"(d[29]), "+f"(d[30]), "+f"(d[31]),
      "+f"(d[32]), "+f"(d[33]), "+f"(d[34]), "+f"(d[35]), "+f"(d[36]), "+f"(d[37]), "+f"(d[38]), "+f"(d[39]),
      "+f"(d[40]), "+f"(d[41]), "+f"(d[42]), "+f"(d[43]), "+f"(d[44]), "+f"(d[45]), "+f"(d[46]), "+f"(d[47]),
      "+f"(d[48]), "+f"(d[49]), "+f"(d[50]), "+f"(d[51]), "+f"(d[52]), "+f"(d[53]), "+f"(d[54]), "+f"(d[55]),
      "+f"(d[56]), "+f"(d[57]), "+f"(d[58]), "+f"(d[59]), "+f"(d[60]), "+f"(d[61]), "+f"(d[62]), "+f"(d[63]),
      "+f"(d[64]), "+f"(d[65]), "+f"(d[66]), "+f"(d[67]), "+f"(d[68]), "+f"(d[69]), "+f"(d[70]), "+f"(d[71]),
      "+f"(d[72]), "+f"(d[73]), "+f"(d[74]), "+f"(d[75]), "+f"(d[76]), "+f"(d[77]), "+f"(d[78]), "+f"(d[79]),
      "+f"(d[80]), "+f"(d[81]), "+f"(d[82]), "+f"(d[83]), "+f"(d[84]), "+f"(d[85]), "+f"(d[86]), "+f"(d[87]),
      "+f"(d[88]), "+f"(d[89]), "+f"(d[90]), "+f"(d[91]), "+f"(d[92]), "+f"(d[93]), "+f"(d[94]), "+f"(d[95]),
      "+f"(d[96]), "+f"(d[97]), "+f"(d[98]), "+f"(d[99]), "+f"(d[100]), "+f"(d[101]), "+f"(d[102]), "+f"(d[103]),
      "+f"(d[104]), "+f"(d[105]), "+f"(d[106]), "+f"(d[107]), "+f"(d[108]), "+f"(d[109]), "+f"(d[110]), "+f"(d[111]),
      "+f"(d[112]), "+f"(d[113]), "+f"(d[114]), "+f"(d[115]), "+f"(d[116]), "+f"(d[117]), "+f"(d[118]), "+f"(d[119]),
      "+f"(d[120]), "+f"(d[121]), "+f"(d[122]), "+f"(d[123]), "+f"(d[124]), "+f"(d[125]), "+f"(d[126]), "+f"(d[127])
    : "l"(da), "l"(db), "r"(sc));
}
__device__ __forceinline__ void wgmma_rs_n64(float (&d)[32], const uint32_t (&a)[4], uint64_t db, int sc) {
  asm volatile("{\n.reg .pred p;\nsetp.ne.b32 p, %37, 0;\n"
    "wgmma.mma_async.sync.aligned.m64n64k16.f32.bf16.bf16 {%0, %1, %2, %3, %4, %5, %6, %7, %8, %9, %10, %11, %12, %13, %14, %15, %16, %17, %18, %19, %20, %21, %22, %23, %24, %25, %26, %27, %28, %29, %30, %31}, {%32, %33, %34, %35}, %36, p, 1, 1, 1;\n}\n"
    : "+f"(d[0]), "+f"(d[1]), "+f"(d[2]), "+f"(d[3]), "+f"(d[4]), "+f"(d[5]), "+f"(d[6]), "+f"(d[7]),
      "+f"(d[8]), "+f"(d[9]), "+f"(d[10]), "+f"(d[11]), "+f"(d[12]), "+f"(d[13]), "+f"(d[14]), "+f"(d[15]),
      "+f"(d[16]), "+f"(d[17]), "+f"(d[18]), "+f"(d[19]), "+f"(d[20]), "+f"(d[21]), "+f"(d[22]), "+f"(d[23]),
      "+f"(d[24]), "+f"(d[25]), "+f"(d[26]), "+f"(d[27]), "+f"(d[28]), "+f"(d[29]), "+f"(d[30]), "+f"(d[31])
    : "r"(a[0]), "r"(a[1]), "r"(a[2]), "r"(a[3]), "l"(db), "r"(sc));
}
__device__ __forceinline__ void wgmma_rs_n128(float (&d)[64], const uint32_t (&a)[4], uint64_t db, int sc) {
  asm volatile("{\n.reg .pred p;\nsetp.ne.b32 p, %69, 0;\n"
    "wgmma.mma_async.sync.aligned.m64n128k16.f32.bf16.bf16 {%0, %1, %2, %3, %4, %5, %6, %7, %8, %9, %10, %11, %12, %13, %14, %15, %16, %17, %18, %19, %20, %21, %22, %23, %24, %25, %26, %27, %28, %29, %30, %31, %32, %33, %34, %35, %36, %37, %38, %39, %40, %41, %42, %43, %44, %45, %46, %47, %48, %49, %50, %51, %52, %53, %54, %55, %56, %57, %58, %59, %60, %61, %62, %63}, {%64, %65, %66, %67}, %68, p, 1, 1, 1;\n}\n"
    : "+f"(d[0]), "+f"(d[1]), "+f"(d[2]), "+f"(d[3]), "+f"(d[4]), "+f"(d[5]), "+f"(d[6]), "+f"(d[7]),
      "+f"(d[8]), "+f"(d[9]), "+f"(d[10]), "+f"(d[11]), "+f"(d[12]), "+f"(d[13]), "+f"(d[14]), "+f"(d[15]),
      "+f"(d[16]), "+f"(d[17]), "+f"(d[18]), "+f"(d[19]), "+f"(d[20]), "+f"(d[21]), "+f"(d[22]), "+f"(d[23]),
      "+f"(d[24]), "+f"(d[25]), "+f"(d[26]), "+f"(d[27]), "+f"(d[28]), "+f"(d[29]), "+f"(d[30]), "+f"(d[31]),
      "+f"(d[32]), "+f"(d[33]), "+f"(d[34]), "+f"(d[35]), "+f"(d[36]), "+f"(d[37]), "+f"(d[38]), "+f"(d[39]),
      "+f"(d[40]), "+f"(d[41]), "+f"(d[42]), "+f"(d[43]), "+f"(d[44]), "+f"(d[45]), "+f"(d[46]), "+f"(d[47]),
      "+f"(d[48]), "+f"(d[49]), "+f"(d[50]), "+f"(d[51]), "+f"(d[52]), "+f"(d[53]), "+f"(d[54]), "+f"(d[55]),
      "+f"(d[56]), "+f"(d[57]), "+f"(d[58]), "+f"(d[59]), "+f"(d[60]), "+f"(d[61]), "+f"(d[62]), "+f"(d[63])
    : "r"(a[0]), "r"(a[1]), "r"(a[2]), "r"(a[3]), "l"(db), "r"(sc));
}

template <int N> __device__ __forceinline__ void keep(float (&d)[N]) {
#pragma unroll
  for (int i = 0; i < N; i++) asm volatile("" : "+f"(d[i])::"memory");
}

template <int N> __device__ __forceinline__ void keep(uint32_t (&d)[N][4]) {
#pragma unroll
  for (int i = 0; i < N; i++) asm volatile("" : "+r"(d[i][0]), "+r"(d[i][1]), "+r"(d[i][2]), "+r"(d[i][3])::"memory");
}

__device__ __forceinline__ uint32_t pack2(float lo, float hi) {
  uint32_t r;
  asm("cvt.rn.bf16x2.f32 %0, %1, %2;" : "=r"(r) : "f"(hi), "f"(lo));
  return r;
}
__device__ __forceinline__ float bf_lo(uint32_t v) { return __uint_as_float(v << 16); }
__device__ __forceinline__ float bf_hi(uint32_t v) { return __uint_as_float(v & 0xffff0000u); }
__device__ __forceinline__ uint32_t hsub2(uint32_t a, uint32_t b) {
  uint32_t r;
  asm("sub.rn.bf16x2 %0, %1, %2;" : "=r"(r) : "r"(a), "r"(b));
  return r;
}
__device__ __forceinline__ uint32_t movm(uint32_t a) {
  uint32_t r;
  asm volatile("movmatrix.sync.aligned.m8n8.trans.b16 %0, %1;" : "=r"(r) : "r"(a));
  return r;
}
__device__ __forceinline__ void ldsm4(uint32_t (&v)[4], uint32_t a) {
  asm volatile("ldmatrix.sync.aligned.m8n8.x4.shared.b16 {%0,%1,%2,%3}, [%4];" : "=r"(v[0]), "=r"(v[1]), "=r"(v[2]), "=r"(v[3]) : "r"(a) : "memory");
}
__device__ __forceinline__ void stsm4(uint32_t a, const uint32_t (&v)[4]) {
  asm volatile("stmatrix.sync.aligned.m8n8.x4.shared.b16 [%0], {%1,%2,%3,%4};" ::"r"(a), "r"(v[0]), "r"(v[1]), "r"(v[2]), "r"(v[3]) : "memory");
}
__device__ __forceinline__ void mma16816(float (&d)[4], const uint32_t (&a)[4], uint32_t b0, uint32_t b1) {
  asm volatile("mma.sync.aligned.m16n8k16.row.col.f32.bf16.bf16.f32 {%0,%1,%2,%3}, {%4,%5,%6,%7}, {%8,%9}, {%10,%10,%10,%10};"
               : "=f"(d[0]), "=f"(d[1]), "=f"(d[2]), "=f"(d[3])
               : "r"(a[0]), "r"(a[1]), "r"(a[2]), "r"(a[3]), "r"(b0), "r"(b1), "f"(0.f));
}
__device__ __forceinline__ void mma1688_acc(float (&d)[4], uint32_t a0, uint32_t a1, uint32_t b0) {
  asm volatile("mma.sync.aligned.m16n8k8.row.col.f32.bf16.bf16.f32 {%0,%1,%2,%3}, {%4,%5}, {%6}, {%0,%1,%2,%3};"
               : "+f"(d[0]), "+f"(d[1]), "+f"(d[2]), "+f"(d[3]) : "r"(a0), "r"(a1), "r"(b0));
}
__device__ __forceinline__ float ex2(float x) { float y; asm("ex2.approx.ftz.f32 %0, %1;" : "=f"(y) : "f"(x)); return y; }
__device__ __forceinline__ float rcp(float x) { float y; asm("rcp.approx.ftz.f32 %0, %1;" : "=f"(y) : "f"(x)); return y; }
__device__ __forceinline__ float tanhf_hw(float x) { float y; asm("tanh.approx.f32 %0, %1;" : "=f"(y) : "f"(x)); return y; }
__device__ __forceinline__ float2 lds64(uint32_t a) { float2 v; asm volatile("ld.shared.v2.f32 {%0,%1}, [%2];" : "=f"(v.x), "=f"(v.y) : "r"(a) : "memory"); return v; }
__device__ __forceinline__ void lds128(uint32_t (&v)[4], uint32_t a) { asm volatile("ld.shared.v4.u32 {%0,%1,%2,%3}, [%4];" : "=r"(v[0]), "=r"(v[1]), "=r"(v[2]), "=r"(v[3]) : "r"(a) : "memory"); }
__device__ __forceinline__ void sts128(uint32_t a, const uint32_t (&v)[4]) { asm volatile("st.shared.v4.u32 [%0], {%1,%2,%3,%4};" ::"r"(a), "r"(v[0]), "r"(v[1]), "r"(v[2]), "r"(v[3]) : "memory"); }
__device__ __forceinline__ void ldg128_nc(uint32_t (&v)[4], const void* p) {
  asm volatile("ld.global.nc.L1::no_allocate.v4.u32 {%0,%1,%2,%3}, [%4];" : "=r"(v[0]), "=r"(v[1]), "=r"(v[2]), "=r"(v[3]) : "l"(p));
}
__device__ __forceinline__ void ll_st(uint4* p, uint32_t a, uint32_t b, uint32_t c, uint32_t d, uint32_t tag) {
  asm volatile("{\n.reg .b128 t;\n.reg .b64 lo, hi;\nmov.b64 lo, {%1, %2};\nmov.b64 hi, {%3, %4};\nmov.b128 t, {lo, hi};\n"
               "st.relaxed.gpu.global.b128 [%0], t;\n}\n" ::"l"(p), "r"((a & ~1u) | tag), "r"(b), "r"(c), "r"(d) : "memory");
}
__device__ __forceinline__ void ll_ld(uint32_t (&v)[4], const uint4* p) {
  asm volatile("{\n.reg .b128 t;\n.reg .b64 lo, hi;\nld.relaxed.gpu.global.b128 t, [%4];\nmov.b128 {lo, hi}, t;\n"
               "mov.b64 {%0, %1}, lo;\nmov.b64 {%2, %3}, hi;\n}\n"
               : "=r"(v[0]), "=r"(v[1]), "=r"(v[2]), "=r"(v[3]) : "l"(p) : "memory");
}
template <int N> __device__ __forceinline__ void ll_issue(uint32_t (&v)[N][4], const uint4* p, int stride) {
#pragma unroll
  for (int i = 0; i < N; i++) ll_ld(v[i], p + i * stride);
}
template <int N> __device__ __forceinline__ void ll_wait(uint32_t (&v)[N][4], const uint4* p, int stride, uint32_t tag) {
  uint32_t it = 0;
  while (true) {
    uint32_t bad = 0;
#pragma unroll
    for (int i = 0; i < N; i++) bad |= (v[i][0] ^ tag);
    if (!__any_sync(0xffffffffu, bad & 1u)) break;
    if (++it > SPIN_LIMIT) break;
    ll_issue<N>(v, p, stride);
  }
#pragma unroll
  for (int i = 0; i < N; i++) v[i][0] &= ~1u;
}

__device__ __forceinline__ int kb_at(int i, int j) { return i == 0 ? j : (i - 1 + (i - 1 >= j ? 1 : 0)); }

__global__ void __launch_bounds__(384, 1) fused_block_kernel(const __grid_constant__ Params P) {
  extern __shared__ __align__(1024) uint8_t smem_raw[];
  const uint32_t sb = smem_u32(smem_raw);
  const uint32_t bar = sb + OFF_BAR;
  const int tid = threadIdx.x;
  const int warp = __shfl_sync(0xffffffffu, tid >> 5, 0);
  const int lane = tid & 31;
  const int cta = blockIdx.x;
  const int j = (cta >> 6) * 4 + (cta & 3);
  const int g = (cta & 63) >> 2;

  if (tid < B_COUNT) {
    uint32_t cnt = 1;
    if (tid >= B_EKV) cnt = 8;
    if (tid == B_XCHG || tid == B_PUB || tid == B_LAG) cnt = 4;
    if (tid == B_READY) cnt = 3;
    mbar_init(bar + tid * 8, cnt);
    asm volatile("fence.mbarrier_init.release.cluster;" ::: "memory");
    fence_async_smem();
  }
  if (tid == 256) {
    prefetch_map(&P.x); prefetch_map(&P.wqkv);
  }
  __syncthreads();

  if (warp >= 8) {
    asm volatile("setmaxnreg.dec.sync.aligned.u32 56;");
    if (warp == 8) {
      const uint32_t ring = sb + OFF_RING, H0 = sb + OFF_H, H1 = sb + OFF_H + 65536;
      const int f0 = 224 * j + ((j & 1) ? 32 : 0);
      const int fh = 224 * j + ((j & 1) ? 0 : 192);
      PSTAMPW(2, 0);
      if (elect_one()) {
        auto ldx = [&](int p, int kb) {
          mbar_expect_tx(bar + (B_FX + p * 8 + kb) * 8, 8192);
          tma3d((p ? H1 : H0) + kb * 8192, &P.x, kb * 64, p, g * 64, bar + (B_FX + p * 8 + kb) * 8);
        };
        auto ldkv = [&](int kb) {
          const uint32_t b = bar + (B_FKV + kb) * 8, d = ring + (kb % 6) * 16384;
          mbar_expect_tx(b, 16384);
          tma2d(d, &P.wqkv, 512 + 64 * j, kb * 64, b);
          tma2d(d + 8192, &P.wqkv, 1024 + 64 * j, kb * 64, b);
        };
        auto ldq = [&](int kb) {
          const uint32_t b = bar + (B_FQ + kb) * 8;
          mbar_expect_tx(b, 8192);
          tma2d(ring + (4 + kb) * 8192, &P.wqkv, 64 * j, kb * 64, b);
        };
        auto ldwo = [&](int i) {
          const uint32_t b = bar + (B_FWO + i) * 8;
          mbar_expect_tx(b, 8192);
          tma2d(H1 + ((i + 1) & 7) * 8192, &P.wo, 64 * j, kb_at(i, j) * 64, b);
        };
        auto lda = [&](int i) {
          const uint32_t b = bar + (B_FA + i) * 8, d = ring + (i & 3) * 24576;
          const int k0 = kb_at(i, j) * 64;
          mbar_expect_tx(b, 24576);
          tma2d(d, &P.w1, f0, k0, b);
          tma2d(d + 8192, &P.w3, f0, k0, b);
          tma2d(d + 16384, &P.w1h, fh, k0, b);
          tma2d(d + 20480, &P.w3h, fh, k0, b);
        };
        auto ldb = [&](int i) {
          const uint32_t b = bar + (B_FB + i) * 8, d = ring + (i % 3) * 32768;
          const int k0 = kb_at(i, j) * 64;
          mbar_expect_tx(b, 32768);
          tma2d(d, &P.w1, f0 + 64, k0, b);
          tma2d(d + 8192, &P.w3, f0 + 64, k0, b);
          tma2d(d + 16384, &P.w1, f0 + 128, k0, b);
          tma2d(d + 24576, &P.w3, f0 + 128, k0, b);
        };
        auto ldt = [&](int m, uint32_t d) {
          const uint32_t b = bar + (B_FT + m) * 8;
          mbar_expect_tx(b, 28672);
          tma2d(d, &P.w2, 64 * ((j + 1 + m) & 7), 224 * j, b);
        };
        auto wt = [&](int b) { mbar_wait(bar + b * 8); };

        ldx(0, 0); ldkv(0); ldx(0, 1); ldkv(1); ldx(0, 2); ldkv(2); ldx(1, 0);
        ldx(0, 3); ldkv(3); ldx(1, 1); ldx(0, 4); ldkv(4); ldx(1, 2); ldx(0, 5); ldkv(5); ldx(1, 3);
        ldx(0, 6); ldx(1, 4); ldx(0, 7); ldx(1, 5); ldx(1, 6); ldx(1, 7);
        prefetch_map(&P.wo); prefetch_map(&P.w1); prefetch_map(&P.w3); prefetch_map(&P.w1h);
        prefetch_map(&P.w3h); prefetch_map(&P.w2); prefetch_map(&P.out);
        wt(B_EKV + 0); ldkv(6);
        wt(B_EKV + 1); ldkv(7);
        wt(B_EKV + 2); ldq(0); ldq(1);
        wt(B_EKV + 3); ldq(2); ldq(3);
        wt(B_EKV + 4); ldq(4); ldq(5);
        wt(B_EKV + 5); ldq(6); ldq(7);
        wt(B_EKV + 6); wt(B_EKV + 7); lda(0);
        wt(B_EQ + 0); wt(B_EQ + 1); ldwo(0); lda(1);
        wt(B_EQ + 2); ldwo(1);
        wt(B_EQ + 3); ldwo(2);
        wt(B_EQ + 4); ldwo(3);
        wt(B_EQ + 5); ldwo(4);
        wt(B_EQ + 6); ldwo(5);
        wt(B_EQ + 7); ldwo(6);
        wt(B_XCHG); ldwo(7);
        lda(2); lda(3);
        wt(B_EA + 0); lda(4);
        wt(B_EA + 1); lda(5);
        wt(B_EA + 2); lda(6);
        wt(B_EA + 3); lda(7);
        wt(B_EA + 4); wt(B_EA + 5); ldb(0);
        wt(B_EA + 6); ldb(1);
        wt(B_EA + 7); ldb(2);
        wt(B_EB + 0); ldb(3);
        wt(B_EB + 1); ldb(4);
        wt(B_EB + 2); ldb(5);
        wt(B_EB + 3); ldb(6); ldt(0, H0); ldt(1, H1);
        wt(B_EB + 4); ldb(7);
        wt(B_EB + 5); ldt(2, ring + 65536);
        wt(B_EB + 6); ldt(3, ring);
        wt(B_EB + 7); ldt(4, H0 + 32768); ldt(5, ring + 32768); ldt(6, H1 + 32768);
        wt(B_ET0); ldt(7, H0);
        g_epoch[cta] = g_epoch[cta] + 1;
      }
    } else {
      const int part = warp - 9;
      const uint32_t tag = (__ldcg(&g_epoch[cta]) + 1) & 1;
      mbar_wait(bar + B_PUB * 8);
      PSTAMPW(3, part * 4 + 0);
      if (part == 2) {
        if (lane == 0) l2_prefetch(P.wop + (size_t)cta * 4 * D_, 4 * D_ * 2);
        if (lane == 1) l2_prefetch(P.w1p + (size_t)cta * 4 * F_, 4 * F_ * 2);
        if (lane == 2) l2_prefetch(P.w3p + (size_t)cta * 4 * F_, 4 * F_ * 2);
        if (lane == 3) l2_prefetch(P.w2p + (size_t)cta * 14 * D_, 14 * D_ * 2);
      } else {
        uint32_t v[2][4];
        const uint4* src = g_e0s + g * 128 + part * 64 + lane;
        ll_issue<2>(v, src, 32);
        ll_wait<2>(v, src, 32, tag);
#pragma unroll
        for (int i = 0; i < 2; i++)
          asm volatile("st.shared.v2.u32 [%0], {%1,%2};" ::"r"(sb + OFF_ST + (part * 64 + i * 32 + lane) * 8), "r"(v[i][0]), "r"(v[i][1]) : "memory");
      }
      {
        uint32_t v[8][4];
        const uint4* src = g_e0c + ((j * 3 + part) * 16 + (lane >> 4) * 8) * 16 + (lane & 15);
        ll_issue<8>(v, src, 16);
        ll_wait<8>(v, src, 16, tag);
        uint32_t o[4];
#pragma unroll
        for (int e = 0; e < 4; e++) {
          float s = 0.f;
#pragma unroll
          for (int i = 0; i < 8; i++) s += __uint_as_float(v[i][e]);
          const float t = __shfl_xor_sync(0xffffffffu, s, 16);
          o[e] = __float_as_uint(lane < 16 ? s + t : t + s);
        }
        if (lane < 16) sts128(sb + OFF_CS + (part * 64 + lane * 4) * 4, o);
      }
      __syncwarp();
      if (lane == 0) mbar_arrive(bar + B_READY * 8);
      PSTAMPW(3, part * 4 + 1);
    }
  } else {
    asm volatile("setmaxnreg.inc.sync.aligned.u32 224;");
    const int p = warp >> 2, w = warp & 3;
    const int r = lane >> 2, c = lane & 3;
    const uint32_t Hp = sb + OFF_H + p * 65536;
    const uint32_t ring = sb + OFF_RING;
    const uint32_t tag = (__ldcg(&g_epoch[cta]) + 1) & 1;
    const uint32_t mrow = 16 * w + (lane & 7) + ((lane >> 3) & 1) * 8;
    const uint32_t moff = mrow * 128;
    const uint32_t mhi = lane >> 4, mx = lane & 7;
    const int xw = (g * 2 + p) * 4 + w;
    PSTAMP(0);

    if (p == 1) {
      uint32_t xs[8][4], ws[8][4];
      const int trow = g * 128 + j * 16 + w * 4 + (lane >> 3);
      const __nv_bfloat16* xr = P.xp + (size_t)trow * D_ + (lane & 7) * 8;
#pragma unroll
      for (int i = 0; i < 8; i++) ldg128_nc(xs[i], xr + i * 64);
      if (w < 3) {
        const __nv_bfloat16* wr = P.wqkvp + (size_t)(g * 32 + (lane >> 3) * 8) * (3 * D_) + w * D_ + j * 64 + (lane & 7) * 8;
#pragma unroll
        for (int i = 0; i < 8; i++) ldg128_nc(ws[i], wr + (size_t)i * 3 * D_);
      }
      float s = 0.f;
#pragma unroll
      for (int i = 0; i < 8; i++)
#pragma unroll
        for (int e = 0; e < 4; e++) s += bf_lo(xs[i][e]) + bf_hi(xs[i][e]);
      s += __shfl_xor_sync(0xffffffffu, s, 1); s += __shfl_xor_sync(0xffffffffu, s, 2); s += __shfl_xor_sync(0xffffffffu, s, 4);
      const float mu = s * (1.f / D_);
      float q = 0.f;
#pragma unroll
      for (int i = 0; i < 8; i++)
#pragma unroll
        for (int e = 0; e < 4; e++) {
          const float a = bf_lo(xs[i][e]) - mu, b = bf_hi(xs[i][e]) - mu;
          q = fmaf(a, a, q); q = fmaf(b, b, q);
        }
      q += __shfl_xor_sync(0xffffffffu, q, 1); q += __shfl_xor_sync(0xffffffffu, q, 2); q += __shfl_xor_sync(0xffffffffu, q, 4);
      const float rs = rsqrtf(q * (1.f / D_) + 1e-5f);
      if ((lane & 7) == 0) ll_st(g_e0s + trow, __float_as_uint(mu), __float_as_uint(rs), 0, 0, tag);
      if (w < 3) {
        float cs[8];
#pragma unroll
        for (int e = 0; e < 4; e++) {
          float a = 0.f, b = 0.f;
#pragma unroll
          for (int i = 0; i < 8; i++) { a += bf_lo(ws[i][e]); b += bf_hi(ws[i][e]); }
          cs[2 * e] = a; cs[2 * e + 1] = b;
        }
#pragma unroll
        for (int e = 0; e < 8; e++) { cs[e] += __shfl_xor_sync(0xffffffffu, cs[e], 8); cs[e] += __shfl_xor_sync(0xffffffffu, cs[e], 16); }
        if (lane < 16) {
          const bool up = lane >= 8;
          ll_st(g_e0c + ((j * 3 + w) * 16 + g) * 16 + (lane & 7) * 2 + (lane >> 3),
                __float_as_uint(up ? cs[4] : cs[0]), __float_as_uint(up ? cs[5] : cs[1]),
                __float_as_uint(up ? cs[6] : cs[2]), __float_as_uint(up ? cs[7] : cs[3]), tag);
        }
      }
      __syncwarp();
      if (lane == 0) mbar_arrive(bar + B_PUB * 8);
      PSTAMP(1);
      mbar_wait(bar + B_LAG * 8);
    }

    float akv[64];
#pragma unroll
    for (int kb = 0; kb < 8; kb++) {
      mbar_wait(bar + (B_FX + p * 8 + kb) * 8);
      mbar_wait(bar + (B_FKV + kb) * 8);
      if (kb == 0) PSTAMP(2);
      wg_fence();
#pragma unroll
      for (int k = 0; k < 4; k++)
        wgmma_ss_n128(akv, descA(Hp + kb * 8192 + k * 32), descB(ring + (kb % 6) * 16384 + k * 2048), (kb | k) != 0);
      wg_commit();
      if (kb == LAG_KB - 1 && p == 0 && lane == 0) mbar_arrive(bar + B_LAG * 8);
      if (kb > 0) { wg_wait<1>(); if (lane == 0) mbar_arrive(bar + (B_EKV + kb - 1) * 8); }
    }
    uint32_t xres[4][4];
#pragma unroll
    for (int u = 0; u < 4; u++) ldsm4(xres[u], Hp + j * 8192 + moff + (((2 * u + mhi) ^ mx) << 4));

    float aq[32];
    auto qstep = [&](int kb) {
      mbar_wait(bar + (B_FQ + kb) * 8);
      wg_fence();
#pragma unroll
      for (int k = 0; k < 4; k++)
        wgmma_ss_n64(aq, descA(Hp + kb * 8192 + k * 32), descB(ring + (4 + kb) * 8192 + k * 2048), (kb | k) != 0);
      wg_commit();
      wg_wait<1>();
      if (lane == 0) mbar_arrive(bar + (kb == 0 ? B_EKV + 7 : B_EQ + kb - 1) * 8);
    };
    qstep(0);
    keep(akv);
    PSTAMP(3);
    mbar_wait(bar + B_READY * 8);
    const float2 st0 = lds64(sb + OFF_ST + (2 * (16 * w + r) + p) * 8);
    const float2 st1 = lds64(sb + OFF_ST + (2 * (16 * w + r + 8) + p) * 8);
    uint32_t khi[2][4], vhi[2][4], klo[8], vlo[8];
    {
      const float nm = -st1.x;
#pragma unroll
      for (int b = 0; b < 16; b++) {
        const float2 cs = lds64(sb + OFF_CS + (64 + b * 8 + 2 * c) * 4);
        const uint32_t v = pack2(fmaf(nm, cs.x, akv[4 * b + 2]) * st1.y, fmaf(nm, cs.y, akv[4 * b + 3]) * st1.y);
        if (b < 8) khi[b >> 2][b & 3] = v; else vhi[(b - 8) >> 2][b & 3] = movm(v);
      }
    }
    if (w == 3 && g < 15) {
      uint4* dst = g_e1 + ((g * 8 + j) * 2 + p) * 128 + lane;
      ll_st(dst, khi[0][0], khi[0][1], khi[0][2], khi[0][3], tag);
      ll_st(dst + 32, khi[1][0], khi[1][1], khi[1][2], khi[1][3], tag);
      ll_st(dst + 64, vhi[0][0], vhi[0][1], vhi[0][2], vhi[0][3], tag);
      ll_st(dst + 96, vhi[1][0], vhi[1][1], vhi[1][2], vhi[1][3], tag);
    }
    qstep(1);
    wg_bar(p);
    if (w < 3) {
      const uint32_t a = Hp + w * 2048 + lane * 16;
      sts128(a, khi[0]); sts128(a + 512, khi[1]); sts128(a + 1024, vhi[0]); sts128(a + 1536, vhi[1]);
    }
    qstep(2);
    {
      const float nm = -st0.x;
#pragma unroll
      for (int b = 0; b < 16; b++) {
        const float2 cs = lds64(sb + OFF_CS + (64 + b * 8 + 2 * c) * 4);
        const uint32_t v = pack2(fmaf(nm, cs.x, akv[4 * b]) * st0.y, fmaf(nm, cs.y, akv[4 * b + 1]) * st0.y);
        if (b < 8) klo[b] = v; else vlo[b - 8] = movm(v);
      }
    }
    qstep(3);
    wg_bar(p);
    uint32_t prev[4][4];
    const uint4* halo = g_e1 + (((g - 1) * 8 + j) * 2 + p) * 128 + lane;
    if (w > 0) {
      const uint32_t a = Hp + (w - 1) * 2048 + lane * 16;
      lds128(prev[0], a); lds128(prev[1], a + 512); lds128(prev[2], a + 1024); lds128(prev[3], a + 1536);
    } else if (g > 0) {
      ll_issue<4>(prev, halo, 32);
    } else {
#pragma unroll
      for (int i = 0; i < 4; i++)
#pragma unroll
        for (int e = 0; e < 4; e++) prev[i][e] = 0;
    }
    qstep(4);
    if (p == 1) { fence_async_smem(); __syncwarp(); if (lane == 0) mbar_arrive(bar + B_XCHG * 8); }
    qstep(5);
    qstep(6);
    qstep(7);
    if (w == 0 && g > 0) ll_wait<4>(prev, halo, 32, tag);
    wg_wait<0>();
    keep(aq);
    if (lane == 0) mbar_arrive(bar + (B_EQ + 7) * 8);
    PSTAMP(4);

    uint32_t of[4][4];
    {
      const float sc = 0.25f * 1.4426950408889634f;
      const bool nohalo = (g == 0 && w == 0);
      const bool up0 = 2 * c > r, up1 = 2 * c + 1 > r;
      uint4* dst = g_e2 + (xw * 32 + 4 * j) * 32 + lane;
#pragma unroll
      for (int h = 0; h < 4; h++) {
        uint32_t qf[4];
        {
          const float2 ca = lds64(sb + OFF_CS + (16 * h + 2 * c) * 4), cb = lds64(sb + OFF_CS + (16 * h + 8 + 2 * c) * 4);
          qf[0] = pack2(fmaf(-st0.x, ca.x, aq[8 * h + 0]) * st0.y, fmaf(-st0.x, ca.y, aq[8 * h + 1]) * st0.y);
          qf[1] = pack2(fmaf(-st1.x, ca.x, aq[8 * h + 2]) * st1.y, fmaf(-st1.x, ca.y, aq[8 * h + 3]) * st1.y);
          qf[2] = pack2(fmaf(-st0.x, cb.x, aq[8 * h + 4]) * st0.y, fmaf(-st0.x, cb.y, aq[8 * h + 5]) * st0.y);
          qf[3] = pack2(fmaf(-st1.x, cb.x, aq[8 * h + 6]) * st1.y, fmaf(-st1.x, cb.y, aq[8 * h + 7]) * st1.y);
        }
        float sp[4], sl[4], sh[4];
        mma16816(sp, qf, prev[h >> 1][(2 * h) & 3], prev[h >> 1][(2 * h + 1) & 3]);
        mma16816(sl, qf, klo[2 * h], klo[2 * h + 1]);
        mma16816(sh, qf, khi[h >> 1][(2 * h) & 3], khi[h >> 1][(2 * h + 1) & 3]);
        float a0 = up0 ? (nohalo ? -INFINITY : sp[0]) : sl[0], a1 = up1 ? (nohalo ? -INFINITY : sp[1]) : sl[1];
        float b0 = up0 ? sl[2] : sh[2], b1 = up1 ? sl[3] : sh[3];
        float ma = fmaxf(a0, a1), mb = fmaxf(b0, b1);
        ma = fmaxf(ma, __shfl_xor_sync(0xffffffffu, ma, 1)); mb = fmaxf(mb, __shfl_xor_sync(0xffffffffu, mb, 1));
        ma = fmaxf(ma, __shfl_xor_sync(0xffffffffu, ma, 2)); mb = fmaxf(mb, __shfl_xor_sync(0xffffffffu, mb, 2));
        a0 = ex2((a0 - ma) * sc); a1 = ex2((a1 - ma) * sc); b0 = ex2((b0 - mb) * sc); b1 = ex2((b1 - mb) * sc);
        float sa = a0 + a1, sbb = b0 + b1;
        sa += __shfl_xor_sync(0xffffffffu, sa, 1); sbb += __shfl_xor_sync(0xffffffffu, sbb, 1);
        sa += __shfl_xor_sync(0xffffffffu, sa, 2); sbb += __shfl_xor_sync(0xffffffffu, sbb, 2);
        const float ia = rcp(sa), ib = rcp(sbb);
        const uint32_t pa = pack2(a0 * ia, a1 * ia), pb = pack2(b0 * ib, b1 * ib);
        const uint32_t mup = (up0 ? 0xffffu : 0u) | (up1 ? 0xffff0000u : 0u);
        const uint32_t pf[4] = {pa & mup, 0u, pa & ~mup, pb & mup};
        const uint32_t ph = pb & ~mup;
        float o0[4], o1[4];
        mma16816(o0, pf, prev[2 + (h >> 1)][(2 * h) & 3], vlo[2 * h]);
        mma16816(o1, pf, prev[2 + (h >> 1)][(2 * h + 1) & 3], vlo[2 * h + 1]);
        mma1688_acc(o0, 0u, ph, vhi[h >> 1][(2 * h) & 3]);
        mma1688_acc(o1, 0u, ph, vhi[h >> 1][(2 * h + 1) & 3]);
        of[h][0] = pack2(o0[0], o0[1]); of[h][1] = pack2(o0[2], o0[3]);
        of[h][2] = pack2(o1[0], o1[1]); of[h][3] = pack2(o1[2], o1[3]);
        ll_st(dst + h * 32, of[h][0], of[h][1], of[h][2], of[h][3], tag);
      }
    }
    PSTAMP(5);

    float ah[32];
#pragma unroll
    for (int u = 0; u < 4; u++) {
      ah[8 * u + 0] = bf_lo(xres[u][0]); ah[8 * u + 1] = bf_hi(xres[u][0]);
      ah[8 * u + 2] = bf_lo(xres[u][1]); ah[8 * u + 3] = bf_hi(xres[u][1]);
      ah[8 * u + 4] = bf_lo(xres[u][2]); ah[8 * u + 5] = bf_hi(xres[u][2]);
      ah[8 * u + 6] = bf_lo(xres[u][3]); ah[8 * u + 7] = bf_hi(xres[u][3]);
    }
    {
      const uint32_t H1 = sb + OFF_H + 65536;
      const uint4* src = g_e2 + xw * 32 * 32 + lane;
      uint32_t ob[7][4][4];
      mbar_wait(bar + (B_FWO + 0) * 8);
      keep(ah); keep(of);
      wg_fence();
#pragma unroll
      for (int k = 0; k < 4; k++) wgmma_rs_n64(ah, of[k], descB(H1 + 8192 + k * 2048), 1);
      wg_commit();
#pragma unroll
      for (int i = 1; i < 4; i++) ll_issue<4>(ob[i - 1], src + kb_at(i, j) * 128, 32);
#pragma unroll
      for (int i = 1; i < 8; i++) {
        ll_wait<4>(ob[i - 1], src + kb_at(i, j) * 128, 32, tag);
        if (i == 1) PSTAMP(6);
        if (i + 3 < 8) ll_issue<4>(ob[i + 2], src + kb_at(i + 3, j) * 128, 32);
        mbar_wait(bar + (B_FWO + i) * 8);
        keep(ob[i - 1]);
        wg_fence();
#pragma unroll
        for (int k = 0; k < 4; k++) wgmma_rs_n64(ah, ob[i - 1][k], descB(H1 + ((i + 1) & 7) * 8192 + k * 2048), 1);
        wg_commit();
      }
      wg_wait<0>();
      keep(ah);
      if (lane == 0) mbar_arrive(bar + B_WODONE * 8);
    }
    PSTAMP(7);

    uint32_t hf[4][4];
    float rs0, rs1;
    uint32_t mu0, mu1;
    {
      float s0 = 0.f, q0 = 0.f, s1 = 0.f, q1 = 0.f;
#pragma unroll
      for (int b = 0; b < 8; b++) {
        s0 += ah[4 * b] + ah[4 * b + 1]; s1 += ah[4 * b + 2] + ah[4 * b + 3];
        q0 = fmaf(ah[4 * b], ah[4 * b], q0); q0 = fmaf(ah[4 * b + 1], ah[4 * b + 1], q0);
        q1 = fmaf(ah[4 * b + 2], ah[4 * b + 2], q1); q1 = fmaf(ah[4 * b + 3], ah[4 * b + 3], q1);
      }
#pragma unroll
      for (int o = 1; o <= 2; o <<= 1) {
        s0 += __shfl_xor_sync(0xffffffffu, s0, o); q0 += __shfl_xor_sync(0xffffffffu, q0, o);
        s1 += __shfl_xor_sync(0xffffffffu, s1, o); q1 += __shfl_xor_sync(0xffffffffu, q1, o);
      }
      if (c == 0) ll_st(g_e3s + (xw * 8 + j) * 8 + r, __float_as_uint(s0), __float_as_uint(q0), __float_as_uint(s1), __float_as_uint(q1), tag);
      uint4* dst = g_e3h + (xw * 32 + 4 * j) * 32 + lane;
#pragma unroll
      for (int u = 0; u < 4; u++) {
        hf[u][0] = pack2(ah[8 * u + 0], ah[8 * u + 1]); hf[u][1] = pack2(ah[8 * u + 2], ah[8 * u + 3]);
        hf[u][2] = pack2(ah[8 * u + 4], ah[8 * u + 5]); hf[u][3] = pack2(ah[8 * u + 6], ah[8 * u + 7]);
        ll_st(dst + u * 32, hf[u][0], hf[u][1], hf[u][2], hf[u][3], tag);
      }
      wg_bar(p);
      if (p == 1) mbar_wait(bar + B_WODONE * 8);
      uint32_t sv[2][4];
      const uint4* ssrc = g_e3s + (xw * 8 + 2 * c) * 8 + r;
      ll_issue<2>(sv, ssrc, 8);
      ll_wait<2>(sv, ssrc, 8, tag);
      s0 = __uint_as_float(sv[0][0]) + __uint_as_float(sv[1][0]); q0 = __uint_as_float(sv[0][1]) + __uint_as_float(sv[1][1]);
      s1 = __uint_as_float(sv[0][2]) + __uint_as_float(sv[1][2]); q1 = __uint_as_float(sv[0][3]) + __uint_as_float(sv[1][3]);
#pragma unroll
      for (int o = 1; o <= 2; o <<= 1) {
        s0 += __shfl_xor_sync(0xffffffffu, s0, o); q0 += __shfl_xor_sync(0xffffffffu, q0, o);
        s1 += __shfl_xor_sync(0xffffffffu, s1, o); q1 += __shfl_xor_sync(0xffffffffu, q1, o);
      }
      const float m0 = s0 * (1.f / D_), m1 = s1 * (1.f / D_);
      rs0 = rsqrtf(fmaxf(fmaf(-m0, m0, q0 * (1.f / D_)), 0.f) + 1e-5f);
      rs1 = rsqrtf(fmaxf(fmaf(-m1, m1, q1 * (1.f / D_)), 0.f) + 1e-5f);
      mu0 = pack2(m0, m0); mu1 = pack2(m1, m1);
    }
    PSTAMP(8);

    auto swiglu = [&](float g0, float g1, float u0, float u1, float rs) -> uint32_t {
      const float hr = 0.5f * rs;
      const float x0 = g0 * hr, x1 = g1 * hr;
      const float t0 = tanhf_hw(x0), t1 = tanhf_hw(x1);
      return pack2(fmaf(x0, t0, x0) * (u0 * rs), fmaf(x1, t1, x1) * (u1 * rs));
    };

    uint32_t hA[6][4];
    {
      float a1[64], a2[32];
      const uint4* src = g_e3h + xw * 32 * 32 + lane;
      uint32_t hb[3][4][4];
      ll_issue<4>(hb[1], src + kb_at(1, j) * 128, 32);
      ll_issue<4>(hb[2], src + kb_at(2, j) * 128, 32);
#pragma unroll
      for (int i = 0; i < 8; i++) {
        uint32_t (&a)[4][4] = hb[i % 3];
        if (i == 0) {
#pragma unroll
          for (int u = 0; u < 4; u++)
#pragma unroll
            for (int e = 0; e < 4; e++) a[u][e] = hf[u][e];
        } else {
          ll_wait<4>(a, src + kb_at(i, j) * 128, 32, tag);
        }
#pragma unroll
        for (int u = 0; u < 4; u++) {
          a[u][0] = hsub2(a[u][0], mu0); a[u][1] = hsub2(a[u][1], mu1);
          a[u][2] = hsub2(a[u][2], mu0); a[u][3] = hsub2(a[u][3], mu1);
          stsm4(Hp + i * 8192 + moff + (((2 * u + mhi) ^ mx) << 4), a[u]);
        }
        mbar_wait(bar + (B_FA + i) * 8);
        keep(a);
        wg_fence();
        const uint32_t st = ring + (i & 3) * 24576;
#pragma unroll
        for (int k = 0; k < 4; k++) {
          wgmma_rs_n128(a1, a[k], descB(st + k * 2048), (i | k) != 0);
          wgmma_rs_n64(a2, a[k], descBh(st + 16384 + k * 1024), (i | k) != 0);
        }
        wg_commit();
        if (i > 0) {
          wg_wait<1>();
          if (lane == 0) mbar_arrive(bar + (B_EA + i - 1) * 8);
          if (i + 2 < 8) ll_issue<4>(hb[(i + 2) % 3], src + kb_at(i + 2, j) * 128, 32);
        }
      }
      fence_async_smem();
      wg_wait<0>();
      keep(a1); keep(a2);
      if (lane == 0) mbar_arrive(bar + (B_EA + 7) * 8);
      PSTAMP(9);
#pragma unroll
      for (int u = 0; u < 4; u++) {
        hA[u][0] = swiglu(a1[8 * u + 0], a1[8 * u + 1], a1[32 + 8 * u + 0], a1[32 + 8 * u + 1], rs0);
        hA[u][1] = swiglu(a1[8 * u + 2], a1[8 * u + 3], a1[32 + 8 * u + 2], a1[32 + 8 * u + 3], rs1);
        hA[u][2] = swiglu(a1[8 * u + 4], a1[8 * u + 5], a1[32 + 8 * u + 4], a1[32 + 8 * u + 5], rs0);
        hA[u][3] = swiglu(a1[8 * u + 6], a1[8 * u + 7], a1[32 + 8 * u + 6], a1[32 + 8 * u + 7], rs1);
      }
#pragma unroll
      for (int u = 0; u < 2; u++) {
        hA[4 + u][0] = swiglu(a2[8 * u + 0], a2[8 * u + 1], a2[16 + 8 * u + 0], a2[16 + 8 * u + 1], rs0);
        hA[4 + u][1] = swiglu(a2[8 * u + 2], a2[8 * u + 3], a2[16 + 8 * u + 2], a2[16 + 8 * u + 3], rs1);
        hA[4 + u][2] = swiglu(a2[8 * u + 4], a2[8 * u + 5], a2[16 + 8 * u + 4], a2[16 + 8 * u + 5], rs0);
        hA[4 + u][3] = swiglu(a2[8 * u + 6], a2[8 * u + 7], a2[16 + 8 * u + 6], a2[16 + 8 * u + 7], rs1);
      }
      wg_bar(p);
    }
    PSTAMP(10);

    uint32_t hB[8][4];
    {
      float ab[128];
#pragma unroll
      for (int i = 0; i < 8; i++) {
        mbar_wait(bar + (B_FB + i) * 8);
        wg_fence();
#pragma unroll
        for (int k = 0; k < 4; k++)
          wgmma_ss_n256(ab, descA(Hp + i * 8192 + k * 32), descB(ring + (i % 3) * 32768 + k * 2048), (i | k) != 0);
        wg_commit();
        if (i > 0) { wg_wait<1>(); if (lane == 0) mbar_arrive(bar + (B_EB + i - 1) * 8); }
      }
      wg_wait<0>();
      keep(ab);
      if (lane == 0) mbar_arrive(bar + (B_EB + 7) * 8);
      PSTAMP(11);
#pragma unroll
      for (int u = 0; u < 8; u++) {
        const int o = (u >> 2) * 64 + (u & 3) * 8;
        hB[u][0] = swiglu(ab[o + 0], ab[o + 1], ab[o + 32 + 0], ab[o + 32 + 1], rs0);
        hB[u][1] = swiglu(ab[o + 2], ab[o + 3], ab[o + 32 + 2], ab[o + 32 + 3], rs1);
        hB[u][2] = swiglu(ab[o + 4], ab[o + 5], ab[o + 32 + 4], ab[o + 32 + 5], rs0);
        hB[u][3] = swiglu(ab[o + 6], ab[o + 7], ab[o + 32 + 6], ab[o + 32 + 7], rs1);
      }
    }
    PSTAMP(12);

    {
      float y[2][32], sum[32];
#pragma unroll
      for (int u = 0; u < 4; u++) {
        sum[8 * u + 0] = bf_lo(hf[u][0]); sum[8 * u + 1] = bf_hi(hf[u][0]);
        sum[8 * u + 2] = bf_lo(hf[u][1]); sum[8 * u + 3] = bf_hi(hf[u][1]);
        sum[8 * u + 4] = bf_lo(hf[u][2]); sum[8 * u + 5] = bf_hi(hf[u][2]);
        sum[8 * u + 6] = bf_lo(hf[u][3]); sum[8 * u + 7] = bf_hi(hf[u][3]);
      }
      const uint32_t offA = (j & 1) ? 4096 : 0, offH = (j & 1) ? 0 : 24576;
      const uint32_t H0 = sb + OFF_H, H1 = H0 + 65536;
      uint4* e4 = g_e4 + (size_t)xw * 64 * 128 + lane;
      uint32_t in[4][4];
      keep(hA); keep(hB);
      auto accum = [&](int m) {
        ll_wait<4>(in, e4 + (j * 8 + ((j - 1 - m) & 7)) * 128, 32, tag);
#pragma unroll
        for (int u = 0; u < 4; u++)
#pragma unroll
          for (int e = 0; e < 4; e++) { sum[8 * u + 2 * e] += bf_lo(in[u][e]); sum[8 * u + 2 * e + 1] += bf_hi(in[u][e]); }
      };
#pragma unroll
      for (int m = 0; m < 8; m++) {
        const uint32_t T = m == 0 ? H0 : m == 1 ? H1 : m == 2 ? ring + 65536 : m == 3 ? ring : m == 4 ? H0 + 32768
                         : m == 5 ? ring + 32768 : m == 6 ? H1 + 32768 : H0;
        mbar_wait(bar + (B_FT + m) * 8);
        wg_fence();
#pragma unroll
        for (int k = 0; k < 4; k++) wgmma_rs_n64(y[m & 1], hA[k], descB(T + offA + k * 2048), k != 0);
#pragma unroll
        for (int k = 0; k < 2; k++) wgmma_rs_n64(y[m & 1], hA[4 + k], descB(T + offH + k * 2048), 1);
#pragma unroll
        for (int k = 0; k < 8; k++) wgmma_rs_n64(y[m & 1], hB[k], descB(T + offA + 8192 + k * 2048), 1);
        wg_commit();
        if (m >= 1) {
          wg_wait<1>();
          float (&yy)[32] = y[(m - 1) & 1];
          keep(yy);
          if (m == 1 && lane == 0) mbar_arrive(bar + B_ET0 * 8);
          uint4* dst = e4 + ((((j + m) & 7) * 8 + j) * 128);
#pragma unroll
          for (int u = 0; u < 4; u++)
            ll_st(dst + u * 32, pack2(yy[8 * u], yy[8 * u + 1]), pack2(yy[8 * u + 2], yy[8 * u + 3]),
                  pack2(yy[8 * u + 4], yy[8 * u + 5]), pack2(yy[8 * u + 6], yy[8 * u + 7]), tag);
        }
        if (m >= 3) accum(m - 3);
        if (m >= 2) ll_issue<4>(in, e4 + (j * 8 + ((j - 1 - (m - 2)) & 7)) * 128, 32);
      }
      PSTAMP(13);
      accum(5);
      ll_issue<4>(in, e4 + (j * 8 + ((j - 7) & 7)) * 128, 32);
      wg_wait<0>();
      keep(y[1]);
      PSTAMP(14);
      accum(6);
      const uint32_t stg = Hp + 28672 + (w >> 1) * 32768 + (w & 1) * 2048;
      const uint32_t srow = ((lane & 7) + ((lane >> 3) & 1) * 8) * 128;
#pragma unroll
      for (int u = 0; u < 4; u++) {
        uint32_t o[4];
#pragma unroll
        for (int e = 0; e < 4; e++) o[e] = pack2(sum[8 * u + 2 * e] + y[1][8 * u + 2 * e], sum[8 * u + 2 * e + 1] + y[1][8 * u + 2 * e + 1]);
        stsm4(stg + srow + (((2 * u + mhi) ^ mx) << 4), o);
      }
      fence_async_smem();
      __syncwarp();
      if (elect_one()) {
        tma3d_store(&P.out, stg, 64 * j, p, g * 64 + 16 * w);
        asm volatile("cp.async.bulk.commit_group;" ::: "memory");
        asm volatile("cp.async.bulk.wait_group.read 0;" ::: "memory");
      }
      PSTAMP(15);
    }
  }
}

typedef CUresult (*EncodeFn)(CUtensorMap*, CUtensorMapDataType, cuuint32_t, void*, const cuuint64_t*, const cuuint64_t*,
                             const cuuint32_t*, const cuuint32_t*, CUtensorMapInterleave, CUtensorMapSwizzle,
                             CUtensorMapL2promotion, CUtensorMapFloatOOBfill);

void enc2d(EncodeFn f, CUtensorMap* m, const void* base, uint64_t cols, uint64_t rows, uint32_t bc, uint32_t br, CUtensorMapSwizzle sw) {
  cuuint64_t gd[2] = {cols, rows}, gs[1] = {cols * 2};
  cuuint32_t bd[2] = {bc, br}, es[2] = {1, 1};
  f(m, CU_TENSOR_MAP_DATA_TYPE_BFLOAT16, 2, const_cast<void*>(base), gd, gs, bd, es, CU_TENSOR_MAP_INTERLEAVE_NONE, sw,
    CU_TENSOR_MAP_L2_PROMOTION_L2_128B, CU_TENSOR_MAP_FLOAT_OOB_FILL_NONE);
}
void enc_par(EncodeFn f, CUtensorMap* m, const void* base, uint32_t pairs) {
  cuuint64_t gd[3] = {(cuuint64_t)D_, 2, (cuuint64_t)S_ / 2}, gs[2] = {D_ * 2, D_ * 4};
  cuuint32_t bd[3] = {64, 1, pairs}, es[3] = {1, 1, 1};
  f(m, CU_TENSOR_MAP_DATA_TYPE_BFLOAT16, 3, const_cast<void*>(base), gd, gs, bd, es, CU_TENSOR_MAP_INTERLEAVE_NONE,
    CU_TENSOR_MAP_SWIZZLE_128B, CU_TENSOR_MAP_L2_PROMOTION_L2_128B, CU_TENSOR_MAP_FLOAT_OOB_FILL_NONE);
}

}

extern "C" void kernel_launch(void* const* d_in, const int* in_sizes, int n_in, void* d_out, int out_size) {
  (void)in_sizes; (void)n_in; (void)out_size;
  static EncodeFn enc = nullptr;
  if (!enc) {
    void* fn = nullptr;
    cudaDriverEntryPointQueryResult q;
    cudaGetDriverEntryPoint("cuTensorMapEncodeTiled", &fn, cudaEnableDefault, &q);
    enc = (EncodeFn)fn;
    cudaFuncSetAttribute(fused_block_kernel, cudaFuncAttributeMaxDynamicSharedMemorySize, SMEM_BYTES);
  }
  Params P;
  P.xp = (const __nv_bfloat16*)d_in[0];
  P.wqkvp = (const __nv_bfloat16*)d_in[1];
  P.wop = (const __nv_bfloat16*)d_in[2];
  P.w1p = (const __nv_bfloat16*)d_in[4];
  P.w3p = (const __nv_bfloat16*)d_in[5];
  P.w2p = (const __nv_bfloat16*)d_in[6];
  enc_par(enc, &P.x, P.xp, 64);
  enc_par(enc, &P.out, d_out, 16);
  enc2d(enc, &P.wqkv, P.wqkvp, 3 * D_, D_, 64, 64, CU_TENSOR_MAP_SWIZZLE_128B);
  enc2d(enc, &P.wo, P.wop, D_, D_, 64, 64, CU_TENSOR_MAP_SWIZZLE_128B);
  enc2d(enc, &P.w1, P.w1p, F_, D_, 64, 64, CU_TENSOR_MAP_SWIZZLE_128B);
  enc2d(enc, &P.w3, P.w3p, F_, D_, 64, 64, CU_TENSOR_MAP_SWIZZLE_128B);
  enc2d(enc, &P.w1h, P.w1p, F_, D_, 32, 64, CU_TENSOR_MAP_SWIZZLE_64B);
  enc2d(enc, &P.w3h, P.w3p, F_, D_, 32, 64, CU_TENSOR_MAP_SWIZZLE_64B);
  enc2d(enc, &P.w2, P.w2p, D_, F_, 64, 224, CU_TENSOR_MAP_SWIZZLE_128B);

  cudaLaunchConfig_t cfg = {};
  cfg.gridDim = dim3(128);
  cfg.blockDim = dim3(384);
  cfg.dynamicSmemBytes = SMEM_BYTES;
  cfg.stream = cudaStreamPerThread;
  cudaLaunchAttribute at[1];
  at[0].id = cudaLaunchAttributeCooperative;
  at[0].val.cooperative = 1;
  cfg.attrs = at;
  cfg.numAttrs = 1;
  cudaLaunchKernelEx(&cfg, fused_block_kernel, P);
}
```

```cpp
#include <cuda_runtime.h>
#include <cuda.h>
#include <cuda_bf16.h>
#include <stdint.h>

namespace {

constexpr int S_ = 2048, D_ = 512, F_ = 1792;
#define LAG_KB 3

constexpr uint32_t SPIN_LIMIT = 1u << 18;

__device__ unsigned g_epoch[128];
__device__ uint4 g_e0s[2048];
__device__ uint4 g_e0c[8 * 3 * 16 * 16];
__device__ uint4 g_e1[16 * 8 * 2 * 4 * 32];
__device__ uint4 g_e2[16 * 2 * 4 * 32 * 32];
__device__ uint4 g_e3s[16 * 2 * 4 * 8 * 8];
__device__ uint4 g_e3h[16 * 2 * 4 * 32 * 32];
__device__ uint4 g_e4[16 * 2 * 4 * 8 * 8 * 4 * 32];
#define PSTAMP(i)
#define PSTAMPW(slot, i)

struct alignas(64) Params {
  CUtensorMap x, out, wqkv, wo, w1, w3, w1h, w3h, w2;
  const __nv_bfloat16 *xp, *wqkvp, *wop, *w1p, *w3p, *w2p;
};

constexpr uint32_t SB = 1024;
constexpr uint32_t H0 = SB;
constexpr uint32_t H1 = SB + 65536;
constexpr uint32_t RING = SB + 131072;
constexpr uint32_t BAR = SB + 229376;
constexpr uint32_t CS = BAR + 1024;
constexpr uint32_t ST = CS + 768;
constexpr uint32_t SMEM_BYTES = 232448;
static_assert(ST + 1024 <= SB + SMEM_BYTES, "smem");

enum : int {
  B_FX = 0,
  B_FKV = 16, B_FQ = 24, B_FWO = 32, B_FA = 40, B_FB = 48, B_FT = 56,
  B_EKV = 64, B_EQ = 72, B_XCHG = 80, B_EA = 81, B_EB = 89, B_ET0 = 97,
  B_WODONE = 98, B_READY = 99, B_PUB = 100, B_LAG = 101,
  B_COUNT = 102
};

__device__ __forceinline__ uint32_t smem_u32(const void* p) { return (uint32_t)__cvta_generic_to_shared(p); }
__device__ __forceinline__ void mbar_init(uint32_t b, uint32_t c) { asm volatile("mbarrier.init.shared::cta.b64 [%0], %1;" ::"r"(b), "r"(c) : "memory"); }
__device__ __forceinline__ void mbar_expect_tx(uint32_t b, uint32_t bytes) { asm volatile("mbarrier.arrive.expect_tx.shared::cta.b64 _, [%0], %1;" ::"r"(b), "r"(bytes) : "memory"); }
__device__ __forceinline__ void mbar_arrive(uint32_t b) { asm volatile("mbarrier.arrive.shared::cta.b64 _, [%0];" ::"r"(b) : "memory"); }
__device__ __forceinline__ void mbar_wait(uint32_t b) {
  asm volatile("{\n.reg .pred p;\n.reg .u32 c;\nmov.u32 c, 0;\nLW:\n.pragma \"nounroll\";\n"
               "mbarrier.try_wait.parity.shared::cta.b64 p, [%0], 0;\nadd.u32 c, c, 1;\nsetp.gt.or.u32 p, c, %1, p;\n@!p bra LW;\n}\n"
               ::"r"(b), "n"(SPIN_LIMIT) : "memory");
}
__device__ __forceinline__ bool elect_one() {
  uint32_t p;
  asm volatile("{\n.reg .pred P;\nelect.sync _|P, 0xffffffff;\nselp.u32 %0, 1, 0, P;\n}\n" : "=r"(p));
  return p;
}
__device__ __forceinline__ void tma2d(uint32_t dst, const CUtensorMap* m, int c0, int c1, uint32_t bar) {
  asm volatile("cp.async.bulk.tensor.2d.shared::cluster.global.mbarrier::complete_tx::bytes [%0], [%1, {%3, %4}], [%2];"
               ::"r"(dst), "l"(m), "r"(bar), "r"(c0), "r"(c1) : "memory");
}
__device__ __forceinline__ void tma3d(uint32_t dst, const CUtensorMap* m, int c0, int c1, int c2, uint32_t bar) {
  asm volatile("cp.async.bulk.tensor.3d.shared::cluster.global.mbarrier::complete_tx::bytes [%0], [%1, {%3, %4, %5}], [%2];"
               ::"r"(dst), "l"(m), "r"(bar), "r"(c0), "r"(c1), "r"(c2) : "memory");
}
__device__ __forceinline__ void tma3d_store(const CUtensorMap* m, uint32_t src, int c0, int c1, int c2) {
  asm volatile("cp.async.bulk.tensor.3d.global.shared::cta.bulk_group [%0, {%2, %3, %4}], [%1];"
               ::"l"(m), "r"(src), "r"(c0), "r"(c1), "r"(c2) : "memory");
}
__device__ __forceinline__ void l2_prefetch(const void* p, uint32_t bytes) {
  asm volatile("cp.async.bulk.prefetch.L2.global [%0], %1;" ::"l"(p), "r"(bytes) : "memory");
}
__device__ __forceinline__ void prefetch_map(const CUtensorMap* m) { asm volatile("prefetch.tensormap [%0];" ::"l"(m) : "memory"); }
__device__ __forceinline__ void fence_async_smem() { asm volatile("fence.proxy.async.shared::cta;" ::: "memory"); }
__device__ __forceinline__ void wg_fence() { asm volatile("wgmma.fence.sync.aligned;" ::: "memory"); }
__device__ __forceinline__ void wg_commit() { asm volatile("wgmma.commit_group.sync.aligned;" ::: "memory"); }
template <int N> __device__ __forceinline__ void wg_wait() { asm volatile("wgmma.wait_group.sync.aligned %0;" ::"n"(N) : "memory"); }
__device__ __forceinline__ void wg_bar(int p) {
  if (p == 0) asm volatile("bar.sync 1, 128;" ::: "memory"); else asm volatile("bar.sync 2, 128;" ::: "memory");
}
constexpr uint32_t DESC_HI128 = (1024 >> 4) | (1u << 30);
constexpr uint32_t DESC_HI64 = (512 >> 4) | (2u << 30);
__device__ __forceinline__ constexpr uint32_t descA(uint32_t addr) { return (addr >> 4) | (1u << 16); }
__device__ __forceinline__ constexpr uint32_t descB(uint32_t addr) { return (addr >> 4) | ((8192u >> 4) << 16); }
__device__ __forceinline__ constexpr uint32_t descBh(uint32_t addr) { return (addr >> 4) | ((4096u >> 4) << 16); }

__device__ __forceinline__ void wgmma_ss_n64(float (&d)[32], uint32_t da, uint32_t db, int sc) {
  asm volatile("{\n.reg .pred p;\n.reg .b64 da, db;\nsetp.ne.b32 p, %34, 0;\nmov.b64 da, {%32, %35};\nmov.b64 db, {%33, %35};\n"
    "wgmma.mma_async.sync.aligned.m64n64k16.f32.bf16.bf16 {%0, %1, %2, %3, %4, %5, %6, %7, %8, %9, %10, %11, %12, %13, %14, %15, %16, %17, %18, %19, %20, %21, %22, %23, %24, %25, %26, %27, %28, %29, %30, %31}, da, db, p, 1, 1, 0, 1;\n}\n"
    : "+f"(d[0]), "+f"(d[1]), "+f"(d[2]), "+f"(d[3]), "+f"(d[4]), "+f"(d[5]), "+f"(d[6]), "+f"(d[7]),
      "+f"(d[8]), "+f"(d[9]), "+f"(d[10]), "+f"(d[11]), "+f"(d[12]), "+f"(d[13]), "+f"(d[14]), "+f"(d[15]),
      "+f"(d[16]), "+f"(d[17]), "+f"(d[18]), "+f"(d[19]), "+f"(d[20]), "+f"(d[21]), "+f"(d[22]), "+f"(d[23]),
      "+f"(d[24]), "+f"(d[25]), "+f"(d[26]), "+f"(d[27]), "+f"(d[28]), "+f"(d[29]), "+f"(d[30]), "+f"(d[31])
    : "r"(da), "r"(db), "r"(sc), "n"(DESC_HI128));
}
__device__ __forceinline__ void wgmma_ss_n128(float (&d)[64], uint32_t da, uint32_t db, int sc) {
  asm volatile("{\n.reg .pred p;\n.reg .b64 da, db;\nsetp.ne.b32 p, %66, 0;\nmov.b64 da, {%64, %67};\nmov.b64 db, {%65, %67};\n"
    "wgmma.mma_async.sync.aligned.m64n128k16.f32.bf16.bf16 {%0, %1, %2, %3, %4, %5, %6, %7, %8, %9, %10, %11, %12, %13, %14, %15, %16, %17, %18, %19, %20, %21, %22, %23, %24, %25, %26, %27, %28, %29, %30, %31, %32, %33, %34, %35, %36, %37, %38, %39, %40, %41, %42, %43, %44, %45, %46, %47, %48, %49, %50, %51, %52, %53, %54, %55, %56, %57, %58, %59, %60, %61, %62, %63}, da, db, p, 1, 1, 0, 1;\n}\n"
    : "+f"(d[0]), "+f"(d[1]), "+f"(d[2]), "+f"(d[3]), "+f"(d[4]), "+f"(d[5]), "+f"(d[6]), "+f"(d[7]),
      "+f"(d[8]), "+f"(d[9]), "+f"(d[10]), "+f"(d[11]), "+f"(d[12]), "+f"(d[13]), "+f"(d[14]), "+f"(d[15]),
      "+f"(d[16]), "+f"(d[17]), "+f"(d[18]), "+f"(d[19]), "+f"(d[20]), "+f"(d[21]), "+f"(d[22]), "+f"(d[23]),
      "+f"(d[24]), "+f"(d[25]), "+f"(d[26]), "+f"(d[27]), "+f"(d[28]), "+f"(d[29]), "+f"(d[30]), "+f"(d[31]),
      "+f"(d[32]), "+f"(d[33]), "+f"(d[34]), "+f"(d[35]), "+f"(d[36]), "+f"(d[37]), "+f"(d[38]), "+f"(d[39]),
      "+f"(d[40]), "+f"(d[41]), "+f"(d[42]), "+f"(d[43]), "+f"(d[44]), "+f"(d[45]), "+f"(d[46]), "+f"(d[47]),
      "+f"(d[48]), "+f"(d[49]), "+f"(d[50]), "+f"(d[51]), "+f"(d[52]), "+f"(d[53]), "+f"(d[54]), "+f"(d[55]),
      "+f"(d[56]), "+f"(d[57]), "+f"(d[58]), "+f"(d[59]), "+f"(d[60]), "+f"(d[61]), "+f"(d[62]), "+f"(d[63])
    : "r"(da), "r"(db), "r"(sc), "n"(DESC_HI128));
}
__device__ __forceinline__ void wgmma_ss_n256(float (&d)[128], uint32_t da, uint32_t db, int sc) {
  asm volatile("{\n.reg .pred p;\n.reg .b64 da, db;\nsetp.ne.b32 p, %130, 0;\nmov.b64 da, {%128, %131};\nmov.b64 db, {%129, %131};\n"
    "wgmma.mma_async.sync.aligned.m64n256k16.f32.bf16.bf16 {%0, %1, %2, %3, %4, %5, %6, %7, %8, %9, %10, %11, %12, %13, %14, %15, %16, %17, %18, %19, %20, %21, %22, %23, %24, %25, %26, %27, %28, %29, %30, %31, %32, %33, %34, %35, %36, %37, %38, %39, %40, %41, %42, %43, %44, %45, %46, %47, %48, %49, %50, %51, %52, %53, %54, %55, %56, %57, %58, %59, %60, %61, %62, %63, %64, %65, %66, %67, %68, %69, %70, %71, %72, %73, %74, %75, %76, %77, %78, %79, %80, %81, %82, %83, %84, %85, %86, %87, %88, %89, %90, %91, %92, %93, %94, %95, %96, %97, %98, %99, %100, %101, %102, %103, %104, %105, %106, %107, %108, %109, %110, %111, %112, %113, %114, %115, %116, %117, %118, %119, %120, %121, %122, %123, %124, %125, %126, %127}, da, db, p, 1, 1, 0, 1;\n}\n"
    : "+f"(d[0]), "+f"(d[1]), "+f"(d[2]), "+f"(d[3]), "+f"(d[4]), "+f"(d[5]), "+f"(d[6]), "+f"(d[7]),
      "+f"(d[8]), "+f"(d[9]), "+f"(d[10]), "+f"(d[11]), "+f"(d[12]), "+f"(d[13]), "+f"(d[14]), "+f"(d[15]),
      "+f"(d[16]), "+f"(d[17]), "+f"(d[18]), "+f"(d[19]), "+f"(d[20]), "+f"(d[21]), "+f"(d[22]), "+f"(d[23]),
      "+f"(d[24]), "+f"(d[25]), "+f"(d[26]), "+f"(d[27]), "+f"(d[28]), "+f"(d[29]), "+f"(d[30]), "+f"(d[31]),
      "+f"(d[32]), "+f"(d[33]), "+f"(d[34]), "+f"(d[35]), "+f"(d[36]), "+f"(d[37]), "+f"(d[38]), "+f"(d[39]),
      "+f"(d[40]), "+f"(d[41]), "+f"(d[42]), "+f"(d[43]), "+f"(d[44]), "+f"(d[45]), "+f"(d[46]), "+f"(d[47]),
      "+f"(d[48]), "+f"(d[49]), "+f"(d[50]), "+f"(d[51]), "+f"(d[52]), "+f"(d[53]), "+f"(d[54]), "+f"(d[55]),
      "+f"(d[56]), "+f"(d[57]), "+f"(d[58]), "+f"(d[59]), "+f"(d[60]), "+f"(d[61]), "+f"(d[62]), "+f"(d[63]),
      "+f"(d[64]), "+f"(d[65]), "+f"(d[66]), "+f"(d[67]), "+f"(d[68]), "+f"(d[69]), "+f"(d[70]), "+f"(d[71]),
      "+f"(d[72]), "+f"(d[73]), "+f"(d[74]), "+f"(d[75]), "+f"(d[76]), "+f"(d[77]), "+f"(d[78]), "+f"(d[79]),
      "+f"(d[80]), "+f"(d[81]), "+f"(d[82]), "+f"(d[83]), "+f"(d[84]), "+f"(d[85]), "+f"(d[86]), "+f"(d[87]),
      "+f"(d[88]), "+f"(d[89]), "+f"(d[90]), "+f"(d[91]), "+f"(d[92]), "+f"(d[93]), "+f"(d[94]), "+f"(d[95]),
      "+f"(d[96]), "+f"(d[97]), "+f"(d[98]), "+f"(d[99]), "+f"(d[100]), "+f"(d[101]), "+f"(d[102]), "+f"(d[103]),
      "+f"(d[104]), "+f"(d[105]), "+f"(d[106]), "+f"(d[107]), "+f"(d[108]), "+f"(d[109]), "+f"(d[110]), "+f"(d[111]),
      "+f"(d[112]), "+f"(d[113]), "+f"(d[114]), "+f"(d[115]), "+f"(d[116]), "+f"(d[117]), "+f"(d[118]), "+f"(d[119]),
      "+f"(d[120]), "+f"(d[121]), "+f"(d[122]), "+f"(d[123]), "+f"(d[124]), "+f"(d[125]), "+f"(d[126]), "+f"(d[127])
    : "r"(da), "r"(db), "r"(sc), "n"(DESC_HI128));
}
template <uint32_t HI = DESC_HI128>
__device__ __forceinline__ void wgmma_rs_n64(float (&d)[32], const uint32_t (&a)[4], uint32_t db, int sc) {
  asm volatile("{\n.reg .pred p;\n.reg .b64 db;\nsetp.ne.b32 p, %37, 0;\nmov.b64 db, {%36, %38};\n"
    "wgmma.mma_async.sync.aligned.m64n64k16.f32.bf16.bf16 {%0, %1, %2, %3, %4, %5, %6, %7, %8, %9, %10, %11, %12, %13, %14, %15, %16, %17, %18, %19, %20, %21, %22, %23, %24, %25, %26, %27, %28, %29, %30, %31}, {%32, %33, %34, %35}, db, p, 1, 1, 1;\n}\n"
    : "+f"(d[0]), "+f"(d[1]), "+f"(d[2]), "+f"(d[3]), "+f"(d[4]), "+f"(d[5]), "+f"(d[6]), "+f"(d[7]),
      "+f"(d[8]), "+f"(d[9]), "+f"(d[10]), "+f"(d[11]), "+f"(d[12]), "+f"(d[13]), "+f"(d[14]), "+f"(d[15]),
      "+f"(d[16]), "+f"(d[17]), "+f"(d[18]), "+f"(d[19]), "+f"(d[20]), "+f"(d[21]), "+f"(d[22]), "+f"(d[23]),
      "+f"(d[24]), "+f"(d[25]), "+f"(d[26]), "+f"(d[27]), "+f"(d[28]), "+f"(d[29]), "+f"(d[30]), "+f"(d[31])
    : "r"(a[0]), "r"(a[1]), "r"(a[2]), "r"(a[3]), "r"(db), "r"(sc), "n"(HI));
}
template <uint32_t HI = DESC_HI128>
__device__ __forceinline__ void wgmma_rs_n128(float (&d)[64], const uint32_t (&a)[4], uint32_t db, int sc) {
  asm volatile("{\n.reg .pred p;\n.reg .b64 db;\nsetp.ne.b32 p, %69, 0;\nmov.b64 db, {%68, %70};\n"
    "wgmma.mma_async.sync.aligned.m64n128k16.f32.bf16.bf16 {%0, %1, %2, %3, %4, %5, %6, %7, %8, %9, %10, %11, %12, %13, %14, %15, %16, %17, %18, %19, %20, %21, %22, %23, %24, %25, %26, %27, %28, %29, %30, %31, %32, %33, %34, %35, %36, %37, %38, %39, %40, %41, %42, %43, %44, %45, %46, %47, %48, %49, %50, %51, %52, %53, %54, %55, %56, %57, %58, %59, %60, %61, %62, %63}, {%64, %65, %66, %67}, db, p, 1, 1, 1;\n}\n"
    : "+f"(d[0]), "+f"(d[1]), "+f"(d[2]), "+f"(d[3]), "+f"(d[4]), "+f"(d[5]), "+f"(d[6]), "+f"(d[7]),
      "+f"(d[8]), "+f"(d[9]), "+f"(d[10]), "+f"(d[11]), "+f"(d[12]), "+f"(d[13]), "+f"(d[14]), "+f"(d[15]),
      "+f"(d[16]), "+f"(d[17]), "+f"(d[18]), "+f"(d[19]), "+f"(d[20]), "+f"(d[21]), "+f"(d[22]), "+f"(d[23]),
      "+f"(d[24]), "+f"(d[25]), "+f"(d[26]), "+f"(d[27]), "+f"(d[28]), "+f"(d[29]), "+f"(d[30]), "+f"(d[31]),
      "+f"(d[32]), "+f"(d[33]), "+f"(d[34]), "+f"(d[35]), "+f"(d[36]), "+f"(d[37]), "+f"(d[38]), "+f"(d[39]),
      "+f"(d[40]), "+f"(d[41]), "+f"(d[42]), "+f"(d[43]), "+f"(d[44]), "+f"(d[45]), "+f"(d[46]), "+f"(d[47]),
      "+f"(d[48]), "+f"(d[49]), "+f"(d[50]), "+f"(d[51]), "+f"(d[52]), "+f"(d[53]), "+f"(d[54]), "+f"(d[55]),
      "+f"(d[56]), "+f"(d[57]), "+f"(d[58]), "+f"(d[59]), "+f"(d[60]), "+f"(d[61]), "+f"(d[62]), "+f"(d[63])
    : "r"(a[0]), "r"(a[1]), "r"(a[2]), "r"(a[3]), "r"(db), "r"(sc), "n"(HI));
}

template <int N> __device__ __forceinline__ void keep(float (&d)[N]) {
#pragma unroll
  for (int i = 0; i < N; i++) asm volatile("" : "+f"(d[i])::"memory");
}

template <int N> __device__ __forceinline__ void keep(uint32_t (&d)[N][4]) {
#pragma unroll
  for (int i = 0; i < N; i++) asm volatile("" : "+r"(d[i][0]), "+r"(d[i][1]), "+r"(d[i][2]), "+r"(d[i][3])::"memory");
}

__device__ __forceinline__ uint32_t pack2(float lo, float hi) {
  uint32_t r;
  asm("cvt.rn.bf16x2.f32 %0, %1, %2;" : "=r"(r) : "f"(hi), "f"(lo));
  return r;
}
__device__ __forceinline__ float bf_lo(uint32_t v) { return __uint_as_float(v << 16); }
__device__ __forceinline__ float bf_hi(uint32_t v) { return __uint_as_float(v & 0xffff0000u); }
__device__ __forceinline__ uint32_t hsub2(uint32_t a, uint32_t b) {
  uint32_t r;
  asm("sub.rn.bf16x2 %0, %1, %2;" : "=r"(r) : "r"(a), "r"(b));
  return r;
}
__device__ __forceinline__ uint32_t movm(uint32_t a) {
  uint32_t r;
  asm volatile("movmatrix.sync.aligned.m8n8.trans.b16 %0, %1;" : "=r"(r) : "r"(a));
  return r;
}
__device__ __forceinline__ void ldsm4(uint32_t (&v)[4], uint32_t a) {
  asm volatile("ldmatrix.sync.aligned.m8n8.x4.shared.b16 {%0,%1,%2,%3}, [%4];" : "=r"(v[0]), "=r"(v[1]), "=r"(v[2]), "=r"(v[3]) : "r"(a) : "memory");
}
__device__ __forceinline__ void stsm4(uint32_t a, const uint32_t (&v)[4]) {
  asm volatile("stmatrix.sync.aligned.m8n8.x4.shared.b16 [%0], {%1,%2,%3,%4};" ::"r"(a), "r"(v[0]), "r"(v[1]), "r"(v[2]), "r"(v[3]) : "memory");
}
__device__ __forceinline__ void mma16816(float (&d)[4], const uint32_t (&a)[4], uint32_t b0, uint32_t b1) {
  asm volatile("mma.sync.aligned.m16n8k16.row.col.f32.bf16.bf16.f32 {%0,%1,%2,%3}, {%4,%5,%6,%7}, {%8,%9}, {%10,%10,%10,%10};"
               : "=f"(d[0]), "=f"(d[1]), "=f"(d[2]), "=f"(d[3])
               : "r"(a[0]), "r"(a[1]), "r"(a[2]), "r"(a[3]), "r"(b0), "r"(b1), "f"(0.f));
}
__device__ __forceinline__ void mma1688_acc(float (&d)[4], uint32_t a0, uint32_t a1, uint32_t b0) {
  asm volatile("mma.sync.aligned.m16n8k8.row.col.f32.bf16.bf16.f32 {%0,%1,%2,%3}, {%4,%5}, {%6}, {%0,%1,%2,%3};"
               : "+f"(d[0]), "+f"(d[1]), "+f"(d[2]), "+f"(d[3]) : "r"(a0), "r"(a1), "r"(b0));
}
__device__ __forceinline__ float ex2(float x) { float y; asm("ex2.approx.ftz.f32 %0, %1;" : "=f"(y) : "f"(x)); return y; }
__device__ __forceinline__ float rcp(float x) { float y; asm("rcp.approx.ftz.f32 %0, %1;" : "=f"(y) : "f"(x)); return y; }
__device__ __forceinline__ float tanhf_hw(float x) { float y; asm("tanh.approx.f32 %0, %1;" : "=f"(y) : "f"(x)); return y; }
__device__ __forceinline__ float2 lds64(uint32_t a) { float2 v; asm volatile("ld.shared.v2.f32 {%0,%1}, [%2];" : "=f"(v.x), "=f"(v.y) : "r"(a) : "memory"); return v; }
__device__ __forceinline__ void lds128(uint32_t (&v)[4], uint32_t a) { asm volatile("ld.shared.v4.u32 {%0,%1,%2,%3}, [%4];" : "=r"(v[0]), "=r"(v[1]), "=r"(v[2]), "=r"(v[3]) : "r"(a) : "memory"); }
__device__ __forceinline__ void sts128(uint32_t a, const uint32_t (&v)[4]) { asm volatile("st.shared.v4.u32 [%0], {%1,%2,%3,%4};" ::"r"(a), "r"(v[0]), "r"(v[1]), "r"(v[2]), "r"(v[3]) : "memory"); }
__device__ __forceinline__ void ldg128_nc(uint32_t (&v)[4], const void* p) {
  asm volatile("ld.global.nc.L1::no_allocate.v4.u32 {%0,%1,%2,%3}, [%4];" : "=r"(v[0]), "=r"(v[1]), "=r"(v[2]), "=r"(v[3]) : "l"(p));
}
__device__ __forceinline__ void ll_st(uint4* p, uint32_t a, uint32_t b, uint32_t c, uint32_t d, uint32_t tag) {
  asm volatile("{\n.reg .b128 t;\n.reg .b64 lo, hi;\nmov.b64 lo, {%1, %2};\nmov.b64 hi, {%3, %4};\nmov.b128 t, {lo, hi};\n"
               "st.relaxed.gpu.global.b128 [%0], t;\n}\n" ::"l"(p), "r"((a & ~1u) | tag), "r"(b), "r"(c), "r"(d) : "memory");
}
__device__ __forceinline__ void ll_ld(uint32_t (&v)[4], const uint4* p) {
  asm volatile("{\n.reg .b128 t;\n.reg .b64 lo, hi;\nld.relaxed.gpu.global.b128 t, [%4];\nmov.b128 {lo, hi}, t;\n"
               "mov.b64 {%0, %1}, lo;\nmov.b64 {%2, %3}, hi;\n}\n"
               : "=r"(v[0]), "=r"(v[1]), "=r"(v[2]), "=r"(v[3]) : "l"(p) : "memory");
}
template <int N> __device__ __forceinline__ void ll_issue(uint32_t (&v)[N][4], const uint4* p, int stride) {
#pragma unroll
  for (int i = 0; i < N; i++) ll_ld(v[i], p + i * stride);
}
template <int N> __device__ __forceinline__ void ll_wait(uint32_t (&v)[N][4], const uint4* p, int stride, uint32_t tag) {
  uint32_t it = 0;
#pragma unroll 1
  while (true) {
    uint32_t bad = 0;
#pragma unroll
    for (int i = 0; i < N; i++) bad |= (v[i][0] ^ tag);
    if (!__any_sync(0xffffffffu, bad & 1u)) break;
    if (++it > SPIN_LIMIT) break;
    ll_issue<N>(v, p, stride);
  }
#pragma unroll
  for (int i = 0; i < N; i++) v[i][0] &= ~1u;
}

template <int N> __device__ __forceinline__ void ll_get(uint32_t (&v)[N][4], const uint4* p, int stride, uint32_t tag) {
  uint32_t it = 0;
#pragma unroll 1
  while (true) {
    ll_issue<N>(v, p, stride);
    uint32_t bad = 0;
#pragma unroll
    for (int i = 0; i < N; i++) bad |= (v[i][0] ^ tag);
    if (!__any_sync(0xffffffffu, bad & 1u) || ++it > SPIN_LIMIT) break;
  }
#pragma unroll
  for (int i = 0; i < N; i++) v[i][0] &= ~1u;
}
__device__ __forceinline__ void unpack32(float (&d)[32], const uint32_t (&v)[4][4]) {
#pragma unroll
  for (int u = 0; u < 4; u++)
#pragma unroll
    for (int e = 0; e < 4; e++) { d[8 * u + 2 * e] = bf_lo(v[u][e]); d[8 * u + 2 * e + 1] = bf_hi(v[u][e]); }
}
__device__ __forceinline__ void pack32(uint32_t (&v)[4][4], const float (&d)[32]) {
#pragma unroll
  for (int u = 0; u < 4; u++)
#pragma unroll
    for (int e = 0; e < 4; e++) v[u][e] = pack2(d[8 * u + 2 * e], d[8 * u + 2 * e + 1]);
}
__device__ __forceinline__ uint32_t t_addr(int m) { return SB + ((0x03514620u >> (4 * m)) & 7u) * 32768u; }

__device__ __forceinline__ int kb_at(int i, int j) { return i == 0 ? j : (i - 1 + (i - 1 >= j ? 1 : 0)); }

__global__ void __launch_bounds__(384, 1) fused_block_kernel(const __grid_constant__ Params P) {
  extern __shared__ __align__(1024) uint8_t smem_raw[];
  if (smem_u32(smem_raw) != SB) return;
  const int tid = threadIdx.x;
  const int warp = __shfl_sync(0xffffffffu, tid >> 5, 0);
  const int lane = tid & 31;
  const int cta = blockIdx.x;
  const int j = (cta >> 6) * 4 + (cta & 3);
  const int g = (cta & 63) >> 2;

  if (tid < B_COUNT) {
    uint32_t cnt = 1;
    if (tid >= B_EKV) cnt = 8;
    if (tid == B_XCHG || tid == B_PUB || tid == B_LAG) cnt = 4;
    if (tid == B_READY) cnt = 3;
    mbar_init(BAR + tid * 8, cnt);
    fence_async_smem();
  }
  if (tid == 256) { prefetch_map(&P.x); prefetch_map(&P.wqkv); }
  __syncthreads();

  if (warp >= 8) {
    asm volatile("setmaxnreg.dec.sync.aligned.u32 56;");
    if (warp == 8) {
      PSTAMPW(2, 0);
      if (elect_one()) {
        const int f0 = 224 * j + ((j & 1) ? 32 : 0);
        const int fh = 224 * j + ((j & 1) ? 0 : 192);
        auto ldx = [&](int p, int kb) {
          const uint32_t b = BAR + (B_FX + p * 8 + kb) * 8;
          mbar_expect_tx(b, 8192);
          tma3d(H0 + p * 65536 + kb * 8192, &P.x, kb * 64, p, g * 64, b);
        };
        auto ldkv = [&](int kb, int slot) {
          const uint32_t b = BAR + (B_FKV + kb) * 8, d = RING + slot * 16384;
          mbar_expect_tx(b, 16384);
          tma2d(d, &P.wqkv, 512 + 64 * j, kb * 64, b);
          tma2d(d + 8192, &P.wqkv, 1024 + 64 * j, kb * 64, b);
        };
#pragma unroll 1
        for (int i = 0; i < 10; i++) {
          if (i < 8) ldx(0, i);
          if (i < 6) ldkv(i, i);
          if (i >= 2) ldx(1, i - 2);
        }
        prefetch_map(&P.wo); prefetch_map(&P.w1); prefetch_map(&P.w3); prefetch_map(&P.w1h);
        prefetch_map(&P.w3h); prefetch_map(&P.w2); prefetch_map(&P.out);
#pragma unroll 1
        for (int i = 0; i < 2; i++) { mbar_wait(BAR + (B_EKV + i) * 8); ldkv(6 + i, i); }
#pragma unroll 1
        for (int i = 0; i < 8; i++) {
          const uint32_t b = BAR + (B_FQ + i) * 8;
          mbar_wait(BAR + (B_EKV + 2 + (i >> 1)) * 8);
          mbar_expect_tx(b, 8192);
          tma2d(RING + (4 + i) * 8192, &P.wqkv, 64 * j, i * 64, b);
        }
#pragma unroll 1
        for (int i = 0; i < 8; i++) {
          const uint32_t b = BAR + (B_FWO + i) * 8;
          mbar_wait(BAR + (B_EQ + 1 + i) * 8);
          mbar_expect_tx(b, 8192);
          tma2d(H1 + ((i + 1) & 7) * 8192, &P.wo, 64 * j, kb_at(i, j) * 64, b);
        }
#pragma unroll 1
        for (int i = 0; i < 8; i++) {
          const uint32_t b = BAR + (B_FA + i) * 8, d = RING + (i & 3) * 24576;
          const int k0 = kb_at(i, j) * 64;
          if (i >= 4) mbar_wait(BAR + (B_EA + i - 4) * 8);
          mbar_expect_tx(b, 24576);
          tma2d(d, &P.w1, f0, k0, b);
          tma2d(d + 8192, &P.w3, f0, k0, b);
          tma2d(d + 16384, &P.w1h, fh, k0, b);
          tma2d(d + 20480, &P.w3h, fh, k0, b);
        }
        uint32_t d = RING;
#pragma unroll 1
        for (int i = 0; i < 8; i++) {
          const uint32_t b = BAR + (B_FB + i) * 8;
          const int k0 = kb_at(i, j) * 64;
          mbar_wait(BAR + (B_EA + 5 + i) * 8);
          mbar_expect_tx(b, 32768);
          tma2d(d, &P.w1, f0 + 64, k0, b);
          tma2d(d + 8192, &P.w3, f0 + 64, k0, b);
          tma2d(d + 16384, &P.w1, f0 + 128, k0, b);
          tma2d(d + 24576, &P.w3, f0 + 128, k0, b);
          d = d == RING + 65536 ? RING : d + 32768;
        }
#pragma unroll 1
        for (int m = 0; m < 8; m++) {
          const uint32_t b = BAR + (B_FT + m) * 8;
          mbar_wait(BAR + (B_EB + (m == 7 ? 8 : min(m + 3, 7))) * 8);
          mbar_expect_tx(b, 28672);
          tma2d(t_addr(m), &P.w2, 64 * ((j + 1 + m) & 7), 224 * j, b);
        }
        g_epoch[cta] = g_epoch[cta] + 1;
      }
    } else {
      const int part = warp - 9;
      const uint32_t tag = (__ldcg(&g_epoch[cta]) + 1) & 1;
      mbar_wait(BAR + B_PUB * 8);
      PSTAMPW(3, part * 4 + 0);
      if (part == 2) {
        if (lane == 0) l2_prefetch(P.wop + (size_t)cta * 4 * D_, 4 * D_ * 2);
        if (lane == 1) l2_prefetch(P.w1p + (size_t)cta * 4 * F_, 4 * F_ * 2);
        if (lane == 2) l2_prefetch(P.w3p + (size_t)cta * 4 * F_, 4 * F_ * 2);
        if (lane == 3) l2_prefetch(P.w2p + (size_t)cta * 14 * D_, 14 * D_ * 2);
      } else {
        uint32_t v[2][4];
        ll_get<2>(v, g_e0s + g * 128 + part * 64 + lane, 32, tag);
#pragma unroll
        for (int i = 0; i < 2; i++)
          asm volatile("st.shared.v2.u32 [%0], {%1,%2};" ::"r"(ST + (part * 64 + i * 32 + lane) * 8), "r"(v[i][0]), "r"(v[i][1]) : "memory");
      }
      {
        uint32_t v[8][4];
        ll_get<8>(v, g_e0c + ((j * 3 + part) * 16 + (lane >> 4) * 8) * 16 + (lane & 15), 16, tag);
        uint32_t o[4];
#pragma unroll
        for (int e = 0; e < 4; e++) {
          float s = 0.f;
#pragma unroll
          for (int i = 0; i < 8; i++) s += __uint_as_float(v[i][e]);
          o[e] = __float_as_uint(s + __shfl_xor_sync(0xffffffffu, s, 16));
        }
        if (lane < 16) sts128(CS + (part * 64 + lane * 4) * 4, o);
      }
      __syncwarp();
      if (lane == 0) mbar_arrive(BAR + B_READY * 8);
      PSTAMPW(3, part * 4 + 1);
    }
  } else {
    asm volatile("setmaxnreg.inc.sync.aligned.u32 224;");
    const int p = warp >> 2, w = warp & 3;
    const int r = lane >> 2, c = lane & 3;
    const uint32_t Hp = H0 + p * 65536;
    const uint32_t dAp = descA(H0) + p * 4096;
    const uint32_t tag = (__ldcg(&g_epoch[cta]) + 1) & 1;
    const uint32_t moff = ((lane & 7) + ((lane >> 3) & 1) * 8) * 128 + (((lane >> 4) ^ (lane & 7)) << 4);
    const uint32_t Hw = Hp + w * 2048;
    const int xw = (g * 2 + p) * 4 + w;
    PSTAMP(0);

    if (p == 1) {
      uint32_t xs[8][4], ws[8][4];
      const int trow = g * 128 + j * 16 + w * 4 + (lane >> 3);
      const int wp = w < 3 ? w : 0;
      const __nv_bfloat16* xr = P.xp + (size_t)trow * D_ + (lane & 7) * 8;
      const __nv_bfloat16* wr = P.wqkvp + (size_t)(g * 32 + (lane >> 3) * 8) * (3 * D_) + wp * D_ + j * 64 + (lane & 7) * 8;
#pragma unroll
      for (int i = 0; i < 8; i++) ldg128_nc(xs[i], xr + i * 64);
#pragma unroll
      for (int i = 0; i < 8; i++) ldg128_nc(ws[i], wr + (size_t)i * 3 * D_);
      float s = 0.f, q = 0.f;
      const float piv = __shfl_sync(0xffffffffu, bf_lo(xs[0][0]), lane & 24);
#pragma unroll
      for (int i = 0; i < 8; i++)
#pragma unroll
        for (int e = 0; e < 4; e++) {
          const float a = bf_lo(xs[i][e]) - piv, b = bf_hi(xs[i][e]) - piv;
          s += a + b; q = fmaf(a, a, q); q = fmaf(b, b, q);
        }
#pragma unroll
      for (int o = 1; o <= 4; o <<= 1) { s += __shfl_xor_sync(0xffffffffu, s, o); q += __shfl_xor_sync(0xffffffffu, q, o); }
      const float dm = s * (1.f / D_);
      const float rs = rsqrtf(fmaxf(fmaf(-dm, dm, q * (1.f / D_)), 0.f) + 1e-5f);
      if ((lane & 7) == 0) ll_st(g_e0s + trow, __float_as_uint(piv + dm), __float_as_uint(rs), 0, 0, tag);
      float cs[8];
#pragma unroll
      for (int e = 0; e < 4; e++) {
        float a = 0.f, b = 0.f;
#pragma unroll
        for (int i = 0; i < 8; i++) { a += bf_lo(ws[i][e]); b += bf_hi(ws[i][e]); }
        cs[2 * e] = a; cs[2 * e + 1] = b;
      }
      const bool up = lane & 8;
#pragma unroll
      for (int e = 0; e < 4; e++) {
        const float keepv = up ? cs[4 + e] : cs[e], give = up ? cs[e] : cs[4 + e];
        cs[e] = keepv + __shfl_xor_sync(0xffffffffu, give, 8);
        cs[e] += __shfl_xor_sync(0xffffffffu, cs[e], 16);
      }
      if (lane < 16 && w < 3)
        ll_st(g_e0c + ((j * 3 + w) * 16 + g) * 16 + (lane & 7) * 2 + (lane >> 3), __float_as_uint(cs[0]), __float_as_uint(cs[1]),
              __float_as_uint(cs[2]), __float_as_uint(cs[3]), tag);
      __syncwarp();
      if (lane == 0) mbar_arrive(BAR + B_PUB * 8);
      PSTAMP(1);
      mbar_wait(BAR + B_LAG * 8);
    }

    float akv[64];
#pragma unroll 1
    for (int kb = 0; kb < 8; kb++) {
      mbar_wait(BAR + (B_FX + p * 8 + kb) * 8);
      mbar_wait(BAR + (B_FKV + kb) * 8);
      if (kb == 0) PSTAMP(2);
      const uint32_t da = dAp + kb * 512, db = descB(RING) + (kb < 6 ? kb : kb - 6) * 1024;
      wg_fence();
      wgmma_ss_n128(akv, da, db, kb);
#pragma unroll
      for (int k = 1; k < 4; k++) wgmma_ss_n128(akv, da + k * 2, db + k * 128, 1);
      wg_commit();
      if (kb == LAG_KB - 1 && p == 0 && lane == 0) mbar_arrive(BAR + B_LAG * 8);
      wg_wait<1>();
      if (kb > 0 && lane == 0) mbar_arrive(BAR + (B_EKV + kb - 1) * 8);
    }
    uint32_t xres[4][4];
#pragma unroll
    for (int u = 0; u < 4; u++) ldsm4(xres[u], Hw + j * 8192 + (moff ^ (u << 5)));

    float aq[32];
    auto qstep = [&](int kb) {
      mbar_wait(BAR + (B_FQ + kb) * 8);
      const uint32_t da = dAp + kb * 512, db = descB(RING + 32768) + kb * 512;
      wg_fence();
      wgmma_ss_n64(aq, da, db, kb);
#pragma unroll
      for (int k = 1; k < 4; k++) wgmma_ss_n64(aq, da + k * 2, db + k * 128, 1);
      wg_commit();
      wg_wait<1>();
      if (lane == 0) mbar_arrive(BAR + (B_EQ + kb - 1) * 8);
    };
    qstep(0);
    keep(akv);
    PSTAMP(3);
    mbar_wait(BAR + B_READY * 8);
    const float2 st0 = lds64(ST + (2 * (16 * w + r) + p) * 8);
    const float2 st1 = lds64(ST + (2 * (16 * w + r + 8) + p) * 8);
    uint32_t hi[4][4], klo[8], vlo[8];
#pragma unroll
    for (int b = 0; b < 16; b++) {
      const float2 cs = lds64(CS + (64 + b * 8 + 2 * c) * 4);
      const uint32_t v = pack2(fmaf(-st1.x, cs.x, akv[4 * b + 2]) * st1.y, fmaf(-st1.x, cs.y, akv[4 * b + 3]) * st1.y);
      hi[b >> 2][b & 3] = b < 8 ? v : movm(v);
    }
    if (w == 3 && g < 15) {
      uint4* dst = g_e1 + ((g * 8 + j) * 2 + p) * 128 + lane;
#pragma unroll
      for (int i = 0; i < 4; i++) ll_st(dst + i * 32, hi[i][0], hi[i][1], hi[i][2], hi[i][3], tag);
    }
    qstep(1);
    wg_bar(p);
#pragma unroll
    for (int i = 0; i < 4; i++) sts128(Hw + lane * 16 + i * 512, hi[i]);
    qstep(2);
#pragma unroll
    for (int b = 0; b < 16; b++) {
      const float2 cs = lds64(CS + (64 + b * 8 + 2 * c) * 4);
      const uint32_t v = pack2(fmaf(-st0.x, cs.x, akv[4 * b]) * st0.y, fmaf(-st0.x, cs.y, akv[4 * b + 1]) * st0.y);
      if (b < 8) klo[b] = v; else vlo[b - 8] = movm(v);
    }
    wg_bar(p);
    uint32_t prev[4][4];
    if (w > 0) {
#pragma unroll
      for (int i = 0; i < 4; i++) lds128(prev[i], Hw - 2048 + lane * 16 + i * 512);
    }
    fence_async_smem();
    __syncwarp();
    if (p == 1 && lane == 0) mbar_arrive(BAR + B_XCHG * 8);
#pragma unroll 1
    for (int kb = 3; kb < 8; kb++) qstep(kb);
    if (w == 0) {
      if (g > 0) {
        ll_get<4>(prev, g_e1 + (((g - 1) * 8 + j) * 2 + p) * 128 + lane, 32, tag);
      } else {
#pragma unroll
        for (int i = 0; i < 4; i++)
#pragma unroll
          for (int e = 0; e < 4; e++) prev[i][e] = 0;
      }
    }
    wg_wait<0>();
    keep(aq);
    if (lane == 0) mbar_arrive(BAR + (B_EQ + 7) * 8);
    PSTAMP(4);

    uint32_t of[4][4];
    {
      const float sc = 0.25f * 1.4426950408889634f;
      const float nohalo = (g == 0 && w == 0) ? -INFINITY : 0.f;
      const bool up0 = 2 * c > r, up1 = 2 * c + 1 > r;
      const uint32_t mup = (up0 ? 0xffffu : 0u) | (up1 ? 0xffff0000u : 0u);
      uint4* dst = g_e2 + (xw * 32 + 4 * j) * 32 + lane;
#pragma unroll
      for (int h = 0; h < 4; h++) {
        uint32_t qf[4];
        {
          const float2 ca = lds64(CS + (16 * h + 2 * c) * 4), cb = lds64(CS + (16 * h + 8 + 2 * c) * 4);
          qf[0] = pack2(fmaf(-st0.x, ca.x, aq[8 * h + 0]) * st0.y, fmaf(-st0.x, ca.y, aq[8 * h + 1]) * st0.y);
          qf[1] = pack2(fmaf(-st1.x, ca.x, aq[8 * h + 2]) * st1.y, fmaf(-st1.x, ca.y, aq[8 * h + 3]) * st1.y);
          qf[2] = pack2(fmaf(-st0.x, cb.x, aq[8 * h + 4]) * st0.y, fmaf(-st0.x, cb.y, aq[8 * h + 5]) * st0.y);
          qf[3] = pack2(fmaf(-st1.x, cb.x, aq[8 * h + 6]) * st1.y, fmaf(-st1.x, cb.y, aq[8 * h + 7]) * st1.y);
        }
        float sp[4], sl[4], sh[4];
        mma16816(sp, qf, prev[h >> 1][(2 * h) & 3], prev[h >> 1][(2 * h + 1) & 3]);
        mma16816(sl, qf, klo[2 * h], klo[2 * h + 1]);
        mma16816(sh, qf, hi[h >> 1][(2 * h) & 3], hi[h >> 1][(2 * h + 1) & 3]);
        float a0 = up0 ? sp[0] + nohalo : sl[0], a1 = up1 ? sp[1] + nohalo : sl[1];
        float b0 = up0 ? sl[2] : sh[2], b1 = up1 ? sl[3] : sh[3];
        float ma = fmaxf(a0, a1), mb = fmaxf(b0, b1);
        ma = fmaxf(ma, __shfl_xor_sync(0xffffffffu, ma, 1)); mb = fmaxf(mb, __shfl_xor_sync(0xffffffffu, mb, 1));
        ma = fmaxf(ma, __shfl_xor_sync(0xffffffffu, ma, 2)); mb = fmaxf(mb, __shfl_xor_sync(0xffffffffu, mb, 2));
        a0 = ex2((a0 - ma) * sc); a1 = ex2((a1 - ma) * sc); b0 = ex2((b0 - mb) * sc); b1 = ex2((b1 - mb) * sc);
        float sa = a0 + a1, sbb = b0 + b1;
        sa += __shfl_xor_sync(0xffffffffu, sa, 1); sbb += __shfl_xor_sync(0xffffffffu, sbb, 1);
        sa += __shfl_xor_sync(0xffffffffu, sa, 2); sbb += __shfl_xor_sync(0xffffffffu, sbb, 2);
        const float ia = rcp(sa), ib = rcp(sbb);
        const uint32_t pa = pack2(a0 * ia, a1 * ia), pb = pack2(b0 * ib, b1 * ib);
        const uint32_t pf[4] = {pa & mup, 0u, pa & ~mup, pb & mup};
        const uint32_t ph = pb & ~mup;
        float o0[4], o1[4];
        mma16816(o0, pf, prev[2 + (h >> 1)][(2 * h) & 3], vlo[2 * h]);
        mma16816(o1, pf, prev[2 + (h >> 1)][(2 * h + 1) & 3], vlo[2 * h + 1]);
        mma1688_acc(o0, 0u, ph, hi[2 + (h >> 1)][(2 * h) & 3]);
        mma1688_acc(o1, 0u, ph, hi[2 + (h >> 1)][(2 * h + 1) & 3]);
        of[h][0] = pack2(o0[0], o0[1]); of[h][1] = pack2(o0[2], o0[3]);
        of[h][2] = pack2(o1[0], o1[1]); of[h][3] = pack2(o1[2], o1[3]);
        ll_st(dst + h * 32, of[h][0], of[h][1], of[h][2], of[h][3], tag);
      }
    }
    PSTAMP(5);

    float ah[32];
    unpack32(ah, xres);
    {
      const uint4* src = g_e2 + xw * 32 * 32 + lane;
      uint32_t ob[4][4], oc[4][4];
      auto step = [&](uint32_t (&a)[4][4], int i) {
        mbar_wait(BAR + (B_FWO + i) * 8);
        const uint32_t db = descB(H1) + ((i + 1) & 7) * 512;
        keep(a);
        wg_fence();
#pragma unroll
        for (int k = 0; k < 4; k++) wgmma_rs_n64(ah, a[k], db + k * 128, 1);
        wg_commit();
      };
      keep(ah);
      step(of, 0);
      ll_issue<4>(ob, src + kb_at(1, j) * 128, 32);
      ll_issue<4>(oc, src + kb_at(2, j) * 128, 32);
      wg_wait<0>();
#pragma unroll 1
      for (int i = 1; i < 8; i += 3) {
        if (i < 6) ll_issue<4>(of, src + kb_at(i + 2, j) * 128, 32);
        ll_wait<4>(ob, src + kb_at(i, j) * 128, 32, tag);
        if (i == 1) PSTAMP(6);
        step(ob, i);
        if (i == 7) break;
        ll_wait<4>(oc, src + kb_at(i + 1, j) * 128, 32, tag);
        step(oc, i + 1);
        wg_wait<1>();
        ll_issue<4>(ob, src + kb_at(i + 3, j) * 128, 32);
        ll_wait<4>(of, src + kb_at(i + 2, j) * 128, 32, tag);
        step(of, i + 2);
        wg_wait<1>();
        if (i < 4) ll_issue<4>(oc, src + kb_at(i + 4, j) * 128, 32);
        wg_wait<0>();
      }
      wg_wait<0>();
      keep(ah);
      if (lane == 0) mbar_arrive(BAR + B_WODONE * 8);
    }
    PSTAMP(7);

    uint32_t hf[4][4];
    float rs0, rs1;
    uint32_t mu0, mu1;
    {
      float s0 = 0.f, q0 = 0.f, s1 = 0.f, q1 = 0.f;
#pragma unroll
      for (int b = 0; b < 8; b++) {
        s0 += ah[4 * b] + ah[4 * b + 1]; s1 += ah[4 * b + 2] + ah[4 * b + 3];
        q0 = fmaf(ah[4 * b], ah[4 * b], q0); q0 = fmaf(ah[4 * b + 1], ah[4 * b + 1], q0);
        q1 = fmaf(ah[4 * b + 2], ah[4 * b + 2], q1); q1 = fmaf(ah[4 * b + 3], ah[4 * b + 3], q1);
      }
#pragma unroll
      for (int o = 1; o <= 2; o <<= 1) {
        s0 += __shfl_xor_sync(0xffffffffu, s0, o); q0 += __shfl_xor_sync(0xffffffffu, q0, o);
        s1 += __shfl_xor_sync(0xffffffffu, s1, o); q1 += __shfl_xor_sync(0xffffffffu, q1, o);
      }
      if (c == 0) ll_st(g_e3s + (xw * 8 + j) * 8 + r, __float_as_uint(s0), __float_as_uint(q0), __float_as_uint(s1), __float_as_uint(q1), tag);
      uint4* dst = g_e3h + (xw * 32 + 4 * j) * 32 + lane;
#pragma unroll
      for (int u = 0; u < 4; u++) {
#pragma unroll
        for (int e = 0; e < 4; e++) hf[u][e] = pack2(ah[8 * u + 2 * e], ah[8 * u + 2 * e + 1]);
        ll_st(dst + u * 32, hf[u][0], hf[u][1], hf[u][2], hf[u][3], tag);
      }
      wg_bar(p);
      if (p == 1) mbar_wait(BAR + B_WODONE * 8);
      uint32_t sv[2][4];
      ll_get<2>(sv, g_e3s + (xw * 8 + 2 * c) * 8 + r, 8, tag);
      s0 = __uint_as_float(sv[0][0]) + __uint_as_float(sv[1][0]); q0 = __uint_as_float(sv[0][1]) + __uint_as_float(sv[1][1]);
      s1 = __uint_as_float(sv[0][2]) + __uint_as_float(sv[1][2]); q1 = __uint_as_float(sv[0][3]) + __uint_as_float(sv[1][3]);
#pragma unroll
      for (int o = 1; o <= 2; o <<= 1) {
        s0 += __shfl_xor_sync(0xffffffffu, s0, o); q0 += __shfl_xor_sync(0xffffffffu, q0, o);
        s1 += __shfl_xor_sync(0xffffffffu, s1, o); q1 += __shfl_xor_sync(0xffffffffu, q1, o);
      }
      const float m0 = s0 * (1.f / D_), m1 = s1 * (1.f / D_);
      rs0 = rsqrtf(fmaxf(fmaf(-m0, m0, q0 * (1.f / D_)), 0.f) + 1e-5f);
      rs1 = rsqrtf(fmaxf(fmaf(-m1, m1, q1 * (1.f / D_)), 0.f) + 1e-5f);
      mu0 = pack2(m0, m0); mu1 = pack2(m1, m1);
    }
    PSTAMP(8);

    auto swiglu = [&](float g0, float g1, float u0, float u1, float rs) -> uint32_t {
      const float hr = 0.5f * rs;
      const float x0 = g0 * hr, x1 = g1 * hr;
      const float t0 = tanhf_hw(x0), t1 = tanhf_hw(x1);
      return pack2(fmaf(x0, t0, x0) * (u0 * rs), fmaf(x1, t1, x1) * (u1 * rs));
    };

    uint32_t hA[6][4];
    {
      float a1[64], a2[32];
      const uint4* src = g_e3h + xw * 32 * 32 + lane;
      uint32_t ra[4][4], rb[4][4], oa[4][4], ob[4][4];
#pragma unroll
      for (int u = 0; u < 4; u++) { ra[u][0] = (hf[u][0] & ~1u) | tag; ra[u][1] = hf[u][1]; ra[u][2] = hf[u][2]; ra[u][3] = hf[u][3]; }
      ll_issue<4>(rb, src + kb_at(1, j) * 128, 32);
      auto step = [&](uint32_t (&raw)[4][4], uint32_t (&a)[4][4], int i) {
        ll_wait<4>(raw, src + kb_at(i, j) * 128, 32, tag);
#pragma unroll
        for (int u = 0; u < 4; u++) {
          a[u][0] = hsub2(raw[u][0], mu0); a[u][1] = hsub2(raw[u][1], mu1);
          a[u][2] = hsub2(raw[u][2], mu0); a[u][3] = hsub2(raw[u][3], mu1);
        }
        keep(a);
        if (i < 6) ll_issue<4>(raw, src + kb_at(i + 2, j) * 128, 32);
        mbar_wait(BAR + (B_FA + i) * 8);
        const uint32_t db = descB(RING) + (i & 3) * 1536, dh = descBh(RING + 16384) + (i & 3) * 1536;
        wg_fence();
        wgmma_rs_n128(a1, a[0], db, i);
        wgmma_rs_n64<DESC_HI64>(a2, a[0], dh, i);
#pragma unroll
        for (int k = 1; k < 4; k++) {
          wgmma_rs_n128(a1, a[k], db + k * 128, 1);
          wgmma_rs_n64<DESC_HI64>(a2, a[k], dh + k * 64, 1);
        }
        wg_commit();
#pragma unroll
        for (int u = 0; u < 4; u++) stsm4(Hw + i * 8192 + (moff ^ (u << 5)), a[u]);
        wg_wait<1>();
        if (i > 0 && lane == 0) mbar_arrive(BAR + (B_EA + i - 1) * 8);
      };
#pragma unroll 1
      for (int i = 0; i < 8; i += 2) { step(ra, oa, i); step(rb, ob, i + 1); }
      fence_async_smem();
      wg_wait<0>();
      keep(a1); keep(a2);
      if (lane == 0) mbar_arrive(BAR + (B_EA + 7) * 8);
      wg_bar(p);
      PSTAMP(9);
#pragma unroll
      for (int u = 0; u < 4; u++)
#pragma unroll
        for (int e = 0; e < 4; e++)
          hA[u][e] = swiglu(a1[8 * u + 2 * e], a1[8 * u + 2 * e + 1], a1[32 + 8 * u + 2 * e], a1[33 + 8 * u + 2 * e], (e & 1) ? rs1 : rs0);
#pragma unroll
      for (int u = 0; u < 2; u++)
#pragma unroll
        for (int e = 0; e < 4; e++)
          hA[4 + u][e] = swiglu(a2[8 * u + 2 * e], a2[8 * u + 2 * e + 1], a2[16 + 8 * u + 2 * e], a2[17 + 8 * u + 2 * e], (e & 1) ? rs1 : rs0);
      keep(hA);
    }
    PSTAMP(10);

    uint32_t hB[8][4];
    {
      float ab[128];
      uint32_t db = descB(RING);
#pragma unroll 1
      for (int i = 0; i < 8; i++) {
        mbar_wait(BAR + (B_FB + i) * 8);
        const uint32_t da = dAp + i * 512;
        wg_fence();
        wgmma_ss_n256(ab, da, db, i);
#pragma unroll
        for (int k = 1; k < 4; k++) wgmma_ss_n256(ab, da + k * 2, db + k * 128, 1);
        wg_commit();
        wg_wait<1>();
        if (i > 0 && lane == 0) mbar_arrive(BAR + (B_EB + i - 1) * 8);
        db = db == descB(RING + 65536) ? descB(RING) : db + 2048;
      }
      wg_wait<0>();
      keep(ab);
      if (lane == 0) mbar_arrive(BAR + (B_EB + 7) * 8);
      PSTAMP(11);
#pragma unroll
      for (int u = 0; u < 8; u++) {
        const int o = (u >> 2) * 64 + (u & 3) * 8;
#pragma unroll
        for (int e = 0; e < 4; e++)
          hB[u][e] = swiglu(ab[o + 2 * e], ab[o + 2 * e + 1], ab[o + 32 + 2 * e], ab[o + 33 + 2 * e], (e & 1) ? rs1 : rs0);
      }
      keep(hB);
    }
    PSTAMP(12);

    {
      float ya[32], yb[32], sum[32];
      unpack32(sum, hf);
      const uint32_t offA = (j & 1) ? 256 : 0, offH = (j & 1) ? 0 : 1536;
      uint4* e4 = g_e4 + (size_t)xw * 64 * 128 + lane;
      uint32_t in[4][4];
      auto accum = [&](int m) {
        ll_wait<4>(in, e4 + (j * 8 + ((j - 1 - m) & 7)) * 128, 32, tag);
#pragma unroll
        for (int u = 0; u < 4; u++)
#pragma unroll
          for (int e = 0; e < 4; e++) { sum[8 * u + 2 * e] += bf_lo(in[u][e]); sum[8 * u + 2 * e + 1] += bf_hi(in[u][e]); }
      };
      auto pass = [&](float (&y)[32], int m) {
        mbar_wait(BAR + (B_FT + m) * 8);
        const uint32_t T = descB(0) + (t_addr(m) >> 4);
        wg_fence();
#pragma unroll
        for (int k = 0; k < 4; k++) wgmma_rs_n64(y, hA[k], T + offA + k * 128, k);
#pragma unroll
        for (int k = 0; k < 2; k++) wgmma_rs_n64(y, hA[4 + k], T + offH + k * 128, 1);
#pragma unroll
        for (int k = 0; k < 8; k++) wgmma_rs_n64(y, hB[k], T + offA + 512 + k * 128, 1);
        wg_commit();
      };
      auto publish = [&](const uint32_t (&v)[4][4], int m) {
        uint4* dst = e4 + ((((j + 1 + m) & 7) * 8 + j) * 128);
#pragma unroll
        for (int u = 0; u < 4; u++) ll_st(dst + u * 32, v[u][0], v[u][1], v[u][2], v[u][3], tag);
      };
      auto fetch = [&](int m) { ll_issue<4>(in, e4 + (j * 8 + ((j - 1 - m) & 7)) * 128, 32); };
      uint32_t pk[4][4];
#pragma unroll 1
      for (int m = 0; m < 8; m += 2) {
        pass(ya, m);
        if (m > 0) {
          publish(pk, m - 1);
          if (m > 2) accum(m - 3);
          fetch(m - 2);
        }
        pass(yb, m + 1);
        wg_wait<1>();
        keep(ya);
        if (m == 0 && lane == 0) mbar_arrive(BAR + B_ET0 * 8);
        pack32(pk, ya);
        publish(pk, m);
        if (m > 0) {
#pragma unroll 1
          for (int q = m - 2; ; q++) {
            accum(q);
            if (q == 6) break;
            fetch(q + 1);
            if (m < 6) break;
          }
        }
        if (m == 6) PSTAMP(13);
        wg_wait<0>();
        keep(yb);
        pack32(pk, yb);
      }
      PSTAMP(14);
      const uint32_t stg = Hp + 28672 + (w >> 1) * 32768 + (w & 1) * 2048;
#pragma unroll
      for (int u = 0; u < 4; u++) {
        uint32_t o[4];
#pragma unroll
        for (int e = 0; e < 4; e++) o[e] = pack2(sum[8 * u + 2 * e] + yb[8 * u + 2 * e], sum[8 * u + 2 * e + 1] + yb[8 * u + 2 * e + 1]);
        stsm4(stg + (moff ^ (u << 5)), o);
      }
      fence_async_smem();
      __syncwarp();
      if (elect_one()) {
        tma3d_store(&P.out, stg, 64 * j, p, g * 64 + 16 * w);
        asm volatile("cp.async.bulk.commit_group;" ::: "memory");
        asm volatile("cp.async.bulk.wait_group.read 0;" ::: "memory");
      }
      PSTAMP(15);
    }
  }
}

typedef CUresult (*EncodeFn)(CUtensorMap*, CUtensorMapDataType, cuuint32_t, void*, const cuuint64_t*, const cuuint64_t*,
                             const cuuint32_t*, const cuuint32_t*, CUtensorMapInterleave, CUtensorMapSwizzle,
                             CUtensorMapL2promotion, CUtensorMapFloatOOBfill);

void enc2d(EncodeFn f, CUtensorMap* m, const void* base, uint64_t cols, uint64_t rows, uint32_t bc, uint32_t br, CUtensorMapSwizzle sw) {
  cuuint64_t gd[2] = {cols, rows}, gs[1] = {cols * 2};
  cuuint32_t bd[2] = {bc, br}, es[2] = {1, 1};
  f(m, CU_TENSOR_MAP_DATA_TYPE_BFLOAT16, 2, const_cast<void*>(base), gd, gs, bd, es, CU_TENSOR_MAP_INTERLEAVE_NONE, sw,
    CU_TENSOR_MAP_L2_PROMOTION_L2_128B, CU_TENSOR_MAP_FLOAT_OOB_FILL_NONE);
}
void enc_par(EncodeFn f, CUtensorMap* m, const void* base, uint32_t pairs) {
  cuuint64_t gd[3] = {(cuuint64_t)D_, 2, (cuuint64_t)S_ / 2}, gs[2] = {D_ * 2, D_ * 4};
  cuuint32_t bd[3] = {64, 1, pairs}, es[3] = {1, 1, 1};
  f(m, CU_TENSOR_MAP_DATA_TYPE_BFLOAT16, 3, const_cast<void*>(base), gd, gs, bd, es, CU_TENSOR_MAP_INTERLEAVE_NONE,
    CU_TENSOR_MAP_SWIZZLE_128B, CU_TENSOR_MAP_L2_PROMOTION_L2_128B, CU_TENSOR_MAP_FLOAT_OOB_FILL_NONE);
}

}

extern "C" void kernel_launch(void* const* d_in, const int* in_sizes, int n_in, void* d_out, int out_size) {
  (void)in_sizes; (void)n_in; (void)out_size;
  static EncodeFn enc = nullptr;
  if (!enc) {
    void* fn = nullptr;
    cudaDriverEntryPointQueryResult q;
    cudaGetDriverEntryPoint("cuTensorMapEncodeTiled", &fn, cudaEnableDefault, &q);
    enc = (EncodeFn)fn;
    cudaFuncSetAttribute(fused_block_kernel, cudaFuncAttributeMaxDynamicSharedMemorySize, SMEM_BYTES);
  }
  Params P;
  P.xp = (const __nv_bfloat16*)d_in[0];
  P.wqkvp = (const __nv_bfloat16*)d_in[1];
  P.wop = (const __nv_bfloat16*)d_in[2];
  P.w1p = (const __nv_bfloat16*)d_in[4];
  P.w3p = (const __nv_bfloat16*)d_in[5];
  P.w2p = (const __nv_bfloat16*)d_in[6];
  enc_par(enc, &P.x, P.xp, 64);
  enc_par(enc, &P.out, d_out, 16);
  enc2d(enc, &P.wqkv, P.wqkvp, 3 * D_, D_, 64, 64, CU_TENSOR_MAP_SWIZZLE_128B);
  enc2d(enc, &P.wo, P.wop, D_, D_, 64, 64, CU_TENSOR_MAP_SWIZZLE_128B);
  enc2d(enc, &P.w1, P.w1p, F_, D_, 64, 64, CU_TENSOR_MAP_SWIZZLE_128B);
  enc2d(enc, &P.w3, P.w3p, F_, D_, 64, 64, CU_TENSOR_MAP_SWIZZLE_128B);
  enc2d(enc, &P.w1h, P.w1p, F_, D_, 32, 64, CU_TENSOR_MAP_SWIZZLE_64B);
  enc2d(enc, &P.w3h, P.w3p, F_, D_, 32, 64, CU_TENSOR_MAP_SWIZZLE_64B);
  enc2d(enc, &P.w2, P.w2p, D_, F_, 64, 224, CU_TENSOR_MAP_SWIZZLE_128B);

  cudaLaunchConfig_t cfg = {};
  cfg.gridDim = dim3(128);
  cfg.blockDim = dim3(384);
  cfg.dynamicSmemBytes = SMEM_BYTES;
  cfg.stream = cudaStreamPerThread;
  cudaLaunchAttribute at[1];
  at[0].id = cudaLaunchAttributeCooperative;
  at[0].val.cooperative = 1;
  cfg.attrs = at;
  cfg.numAttrs = 1;
  cudaLaunchKernelEx(&cfg, fused_block_kernel, P);
}
```

```cpp
#include <cuda_runtime.h>
#include <cuda.h>
#include <cuda_bf16.h>
#include <stdint.h>

namespace {

constexpr int S_ = 2048, D_ = 512, F_ = 1792;
#define LAG_KB 3
#define XO_DELAY 2

constexpr uint32_t SPIN_LIMIT = 1u << 18;

__device__ unsigned g_epoch[128];
__device__ uint4 g_e0s[2048];
__device__ uint4 g_e0c[8 * 3 * 16 * 16];
__device__ uint4 g_e1[16 * 8 * 2 * 4 * 32];
__device__ uint4 g_e0w[8 * 64];
__device__ uint4 g_e2[16 * 2 * 4 * 32 * 32];
__device__ uint4 g_e2s[16 * 2 * 4 * 8 * 8];
__device__ uint4 g_e3s[16 * 2 * 4 * 8 * 8];
__device__ uint4 g_e3h[16 * 2 * 4 * 32 * 32];
__device__ uint4 g_e4[16 * 2 * 4 * 8 * 8 * 4 * 32];
#define PSTAMP(i)
#define PSTAMPW(slot, i)

struct alignas(64) Params {
  CUtensorMap x, out, wqkv, wo, w1, w3, w1h, w3h, w2;
  const __nv_bfloat16 *xp, *wqkvp, *wop, *w1p, *w3p, *w2p;
};

constexpr uint32_t SB = 1024;
constexpr uint32_t H0 = SB;
constexpr uint32_t H1 = SB + 65536;
constexpr uint32_t RING = SB + 131072;
constexpr uint32_t BAR = SB + 229376;
constexpr uint32_t CS = BAR + 1024;
constexpr uint32_t ST = CS + 768;
constexpr uint32_t WB = ST + 1024;
constexpr uint32_t SMEM_BYTES = 232448;
static_assert(WB + 256 <= SB + SMEM_BYTES, "smem");

enum : int {
  B_FX = 0,
  B_FKV = 16, B_FQ = 24, B_FWO = 32, B_FA = 40, B_FB = 48, B_FT = 56,
  B_EKV = 64, B_EQ = 72, B_EA = 80, B_EB = 88, B_ET0 = 96,
  B_WODONE = 97, B_PUB = 98,
  B_EX = 104,
  B_LAG = 112, B_READY = 113
};

__device__ __forceinline__ uint32_t smem_u32(const void* p) { return (uint32_t)__cvta_generic_to_shared(p); }
__device__ __forceinline__ void mbar_init(uint32_t b, uint32_t c) { asm volatile("mbarrier.init.shared::cta.b64 [%0], %1;" ::"r"(b), "r"(c) : "memory"); }
__device__ __forceinline__ void mbar_expect_tx(uint32_t b, uint32_t bytes) { asm volatile("mbarrier.arrive.expect_tx.shared::cta.b64 _, [%0], %1;" ::"r"(b), "r"(bytes) : "memory"); }
__device__ __forceinline__ void mbar_arrive(uint32_t b) { asm volatile("mbarrier.arrive.shared::cta.b64 _, [%0];" ::"r"(b) : "memory"); }
__device__ __forceinline__ void mbar_wait(uint32_t b) {
  asm volatile("{\n.reg .pred p;\n.reg .u32 c;\nmov.u32 c, 0;\nLW:\n.pragma \"nounroll\";\n"
               "mbarrier.try_wait.parity.shared::cta.b64 p, [%0], 0;\nadd.u32 c, c, 1;\nsetp.gt.or.u32 p, c, %1, p;\n@!p bra LW;\n}\n"
               ::"r"(b), "n"(SPIN_LIMIT) : "memory");
}
__device__ __forceinline__ bool elect_one() {
  uint32_t p;
  asm volatile("{\n.reg .pred P;\nelect.sync _|P, 0xffffffff;\nselp.u32 %0, 1, 0, P;\n}\n" : "=r"(p));
  return p;
}
__device__ __forceinline__ void tma2d(uint32_t dst, const CUtensorMap* m, int c0, int c1, uint32_t bar) {
  asm volatile("cp.async.bulk.tensor.2d.shared::cluster.global.mbarrier::complete_tx::bytes [%0], [%1, {%3, %4}], [%2];"
               ::"r"(dst), "l"(m), "r"(bar), "r"(c0), "r"(c1) : "memory");
}
__device__ __forceinline__ void tma3d(uint32_t dst, const CUtensorMap* m, int c0, int c1, int c2, uint32_t bar) {
  asm volatile("cp.async.bulk.tensor.3d.shared::cluster.global.mbarrier::complete_tx::bytes [%0], [%1, {%3, %4, %5}], [%2];"
               ::"r"(dst), "l"(m), "r"(bar), "r"(c0), "r"(c1), "r"(c2) : "memory");
}
__device__ __forceinline__ void tma3d_store(const CUtensorMap* m, uint32_t src, int c0, int c1, int c2) {
  asm volatile("cp.async.bulk.tensor.3d.global.shared::cta.bulk_group [%0, {%2, %3, %4}], [%1];"
               ::"l"(m), "r"(src), "r"(c0), "r"(c1), "r"(c2) : "memory");
}
__device__ __forceinline__ void l2_prefetch(const void* p, uint32_t bytes) {
  asm volatile("cp.async.bulk.prefetch.L2.global [%0], %1;" ::"l"(p), "r"(bytes) : "memory");
}
__device__ __forceinline__ void prefetch_map(const CUtensorMap* m) { asm volatile("prefetch.tensormap [%0];" ::"l"(m) : "memory"); }
__device__ __forceinline__ void fence_async_smem() { asm volatile("fence.proxy.async.shared::cta;" ::: "memory"); }
__device__ __forceinline__ void wg_fence() { asm volatile("wgmma.fence.sync.aligned;" ::: "memory"); }
__device__ __forceinline__ void wg_commit() { asm volatile("wgmma.commit_group.sync.aligned;" ::: "memory"); }
template <int N> __device__ __forceinline__ void wg_wait() { asm volatile("wgmma.wait_group.sync.aligned %0;" ::"n"(N) : "memory"); }
__device__ __forceinline__ void wg_bar(int p) {
  if (p == 0) asm volatile("bar.sync 1, 128;" ::: "memory"); else asm volatile("bar.sync 2, 128;" ::: "memory");
}
constexpr uint32_t DESC_HI128 = (1024 >> 4) | (1u << 30);
constexpr uint32_t DESC_HI64 = (512 >> 4) | (2u << 30);
__device__ __forceinline__ constexpr uint32_t descA(uint32_t addr) { return (addr >> 4) | (1u << 16); }
__device__ __forceinline__ constexpr uint32_t descB(uint32_t addr) { return (addr >> 4) | ((8192u >> 4) << 16); }
__device__ __forceinline__ constexpr uint32_t descBh(uint32_t addr) { return (addr >> 4) | ((4096u >> 4) << 16); }

__device__ __forceinline__ void wgmma_ss_n64(float (&d)[32], uint32_t da, uint32_t db, int sc) {
  asm volatile("{\n.reg .pred p;\n.reg .b64 da, db;\nsetp.ne.b32 p, %34, 0;\nmov.b64 da, {%32, %35};\nmov.b64 db, {%33, %35};\n"
    "wgmma.mma_async.sync.aligned.m64n64k16.f32.bf16.bf16 {%0, %1, %2, %3, %4, %5, %6, %7, %8, %9, %10, %11, %12, %13, %14, %15, %16, %17, %18, %19, %20, %21, %22, %23, %24, %25, %26, %27, %28, %29, %30, %31}, da, db, p, 1, 1, 0, 1;\n}\n"
    : "+f"(d[0]), "+f"(d[1]), "+f"(d[2]), "+f"(d[3]), "+f"(d[4]), "+f"(d[5]), "+f"(d[6]), "+f"(d[7]),
      "+f"(d[8]), "+f"(d[9]), "+f"(d[10]), "+f"(d[11]), "+f"(d[12]), "+f"(d[13]), "+f"(d[14]), "+f"(d[15]),
      "+f"(d[16]), "+f"(d[17]), "+f"(d[18]), "+f"(d[19]), "+f"(d[20]), "+f"(d[21]), "+f"(d[22]), "+f"(d[23]),
      "+f"(d[24]), "+f"(d[25]), "+f"(d[26]), "+f"(d[27]), "+f"(d[28]), "+f"(d[29]), "+f"(d[30]), "+f"(d[31])
    : "r"(da), "r"(db), "r"(sc), "n"(DESC_HI128));
}
__device__ __forceinline__ void wgmma_ss_n128(float (&d)[64], uint32_t da, uint32_t db, int sc) {
  asm volatile("{\n.reg .pred p;\n.reg .b64 da, db;\nsetp.ne.b32 p, %66, 0;\nmov.b64 da, {%64, %67};\nmov.b64 db, {%65, %67};\n"
    "wgmma.mma_async.sync.aligned.m64n128k16.f32.bf16.bf16 {%0, %1, %2, %3, %4, %5, %6, %7, %8, %9, %10, %11, %12, %13, %14, %15, %16, %17, %18, %19, %20, %21, %22, %23, %24, %25, %26, %27, %28, %29, %30, %31, %32, %33, %34, %35, %36, %37, %38, %39, %40, %41, %42, %43, %44, %45, %46, %47, %48, %49, %50, %51, %52, %53, %54, %55, %56, %57, %58, %59, %60, %61, %62, %63}, da, db, p, 1, 1, 0, 1;\n}\n"
    : "+f"(d[0]), "+f"(d[1]), "+f"(d[2]), "+f"(d[3]), "+f"(d[4]), "+f"(d[5]), "+f"(d[6]), "+f"(d[7]),
      "+f"(d[8]), "+f"(d[9]), "+f"(d[10]), "+f"(d[11]), "+f"(d[12]), "+f"(d[13]), "+f"(d[14]), "+f"(d[15]),
      "+f"(d[16]), "+f"(d[17]), "+f"(d[18]), "+f"(d[19]), "+f"(d[20]), "+f"(d[21]), "+f"(d[22]), "+f"(d[23]),
      "+f"(d[24]), "+f"(d[25]), "+f"(d[26]), "+f"(d[27]), "+f"(d[28]), "+f"(d[29]), "+f"(d[30]), "+f"(d[31]),
      "+f"(d[32]), "+f"(d[33]), "+f"(d[34]), "+f"(d[35]), "+f"(d[36]), "+f"(d[37]), "+f"(d[38]), "+f"(d[39]),
      "+f"(d[40]), "+f"(d[41]), "+f"(d[42]), "+f"(d[43]), "+f"(d[44]), "+f"(d[45]), "+f"(d[46]), "+f"(d[47]),
      "+f"(d[48]), "+f"(d[49]), "+f"(d[50]), "+f"(d[51]), "+f"(d[52]), "+f"(d[53]), "+f"(d[54]), "+f"(d[55]),
      "+f"(d[56]), "+f"(d[57]), "+f"(d[58]), "+f"(d[59]), "+f"(d[60]), "+f"(d[61]), "+f"(d[62]), "+f"(d[63])
    : "r"(da), "r"(db), "r"(sc), "n"(DESC_HI128));
}
__device__ __forceinline__ void wgmma_ss_n256(float (&d)[128], uint32_t da, uint32_t db, int sc) {
  asm volatile("{\n.reg .pred p;\n.reg .b64 da, db;\nsetp.ne.b32 p, %130, 0;\nmov.b64 da, {%128, %131};\nmov.b64 db, {%129, %131};\n"
    "wgmma.mma_async.sync.aligned.m64n256k16.f32.bf16.bf16 {%0, %1, %2, %3, %4, %5, %6, %7, %8, %9, %10, %11, %12, %13, %14, %15, %16, %17, %18, %19, %20, %21, %22, %23, %24, %25, %26, %27, %28, %29, %30, %31, %32, %33, %34, %35, %36, %37, %38, %39, %40, %41, %42, %43, %44, %45, %46, %47, %48, %49, %50, %51, %52, %53, %54, %55, %56, %57, %58, %59, %60, %61, %62, %63, %64, %65, %66, %67, %68, %69, %70, %71, %72, %73, %74, %75, %76, %77, %78, %79, %80, %81, %82, %83, %84, %85, %86, %87, %88, %89, %90, %91, %92, %93, %94, %95, %96, %97, %98, %99, %100, %101, %102, %103, %104, %105, %106, %107, %108, %109, %110, %111, %112, %113, %114, %115, %116, %117, %118, %119, %120, %121, %122, %123, %124, %125, %126, %127}, da, db, p, 1, 1, 0, 1;\n}\n"
    : "+f"(d[0]), "+f"(d[1]), "+f"(d[2]), "+f"(d[3]), "+f"(d[4]), "+f"(d[5]), "+f"(d[6]), "+f"(d[7]),
      "+f"(d[8]), "+f"(d[9]), "+f"(d[10]), "+f"(d[11]), "+f"(d[12]), "+f"(d[13]), "+f"(d[14]), "+f"(d[15]),
      "+f"(d[16]), "+f"(d[17]), "+f"(d[18]), "+f"(d[19]), "+f"(d[20]), "+f"(d[21]), "+f"(d[22]), "+f"(d[23]),
      "+f"(d[24]), "+f"(d[25]), "+f"(d[26]), "+f"(d[27]), "+f"(d[28]), "+f"(d[29]), "+f"(d[30]), "+f"(d[31]),
      "+f"(d[32]), "+f"(d[33]), "+f"(d[34]), "+f"(d[35]), "+f"(d[36]), "+f"(d[37]), "+f"(d[38]), "+f"(d[39]),
      "+f"(d[40]), "+f"(d[41]), "+f"(d[42]), "+f"(d[43]), "+f"(d[44]), "+f"(d[45]), "+f"(d[46]), "+f"(d[47]),
      "+f"(d[48]), "+f"(d[49]), "+f"(d[50]), "+f"(d[51]), "+f"(d[52]), "+f"(d[53]), "+f"(d[54]), "+f"(d[55]),
      "+f"(d[56]), "+f"(d[57]), "+f"(d[58]), "+f"(d[59]), "+f"(d[60]), "+f"(d[61]), "+f"(d[62]), "+f"(d[63]),
      "+f"(d[64]), "+f"(d[65]), "+f"(d[66]), "+f"(d[67]), "+f"(d[68]), "+f"(d[69]), "+f"(d[70]), "+f"(d[71]),
      "+f"(d[72]), "+f"(d[73]), "+f"(d[74]), "+f"(d[75]), "+f"(d[76]), "+f"(d[77]), "+f"(d[78]), "+f"(d[79]),
      "+f"(d[80]), "+f"(d[81]), "+f"(d[82]), "+f"(d[83]), "+f"(d[84]), "+f"(d[85]), "+f"(d[86]), "+f"(d[87]),
      "+f"(d[88]), "+f"(d[89]), "+f"(d[90]), "+f"(d[91]), "+f"(d[92]), "+f"(d[93]), "+f"(d[94]), "+f"(d[95]),
      "+f"(d[96]), "+f"(d[97]), "+f"(d[98]), "+f"(d[99]), "+f"(d[100]), "+f"(d[101]), "+f"(d[102]), "+f"(d[103]),
      "+f"(d[104]), "+f"(d[105]), "+f"(d[106]), "+f"(d[107]), "+f"(d[108]), "+f"(d[109]), "+f"(d[110]), "+f"(d[111]),
      "+f"(d[112]), "+f"(d[113]), "+f"(d[114]), "+f"(d[115]), "+f"(d[116]), "+f"(d[117]), "+f"(d[118]), "+f"(d[119]),
      "+f"(d[120]), "+f"(d[121]), "+f"(d[122]), "+f"(d[123]), "+f"(d[124]), "+f"(d[125]), "+f"(d[126]), "+f"(d[127])
    : "r"(da), "r"(db), "r"(sc), "n"(DESC_HI128));
}
template <uint32_t HI = DESC_HI128>
__device__ __forceinline__ void wgmma_rs_n64(float (&d)[32], const uint32_t (&a)[4], uint32_t db, int sc) {
  asm volatile("{\n.reg .pred p;\n.reg .b64 db;\nsetp.ne.b32 p, %37, 0;\nmov.b64 db, {%36, %38};\n"
    "wgmma.mma_async.sync.aligned.m64n64k16.f32.bf16.bf16 {%0, %1, %2, %3, %4, %5, %6, %7, %8, %9, %10, %11, %12, %13, %14, %15, %16, %17, %18, %19, %20, %21, %22, %23, %24, %25, %26, %27, %28, %29, %30, %31}, {%32, %33, %34, %35}, db, p, 1, 1, 1;\n}\n"
    : "+f"(d[0]), "+f"(d[1]), "+f"(d[2]), "+f"(d[3]), "+f"(d[4]), "+f"(d[5]), "+f"(d[6]), "+f"(d[7]),
      "+f"(d[8]), "+f"(d[9]), "+f"(d[10]), "+f"(d[11]), "+f"(d[12]), "+f"(d[13]), "+f"(d[14]), "+f"(d[15]),
      "+f"(d[16]), "+f"(d[17]), "+f"(d[18]), "+f"(d[19]), "+f"(d[20]), "+f"(d[21]), "+f"(d[22]), "+f"(d[23]),
      "+f"(d[24]), "+f"(d[25]), "+f"(d[26]), "+f"(d[27]), "+f"(d[28]), "+f"(d[29]), "+f"(d[30]), "+f"(d[31])
    : "r"(a[0]), "r"(a[1]), "r"(a[2]), "r"(a[3]), "r"(db), "r"(sc), "n"(HI));
}
template <uint32_t HI = DESC_HI128>
__device__ __forceinline__ void wgmma_rs_n128(float (&d)[64], const uint32_t (&a)[4], uint32_t db, int sc) {
  asm volatile("{\n.reg .pred p;\n.reg .b64 db;\nsetp.ne.b32 p, %69, 0;\nmov.b64 db, {%68, %70};\n"
    "wgmma.mma_async.sync.aligned.m64n128k16.f32.bf16.bf16 {%0, %1, %2, %3, %4, %5, %6, %7, %8, %9, %10, %11, %12, %13, %14, %15, %16, %17, %18, %19, %20, %21, %22, %23, %24, %25, %26, %27, %28, %29, %30, %31, %32, %33, %34, %35, %36, %37, %38, %39, %40, %41, %42, %43, %44, %45, %46, %47, %48, %49, %50, %51, %52, %53, %54, %55, %56, %57, %58, %59, %60, %61, %62, %63}, {%64, %65, %66, %67}, db, p, 1, 1, 1;\n}\n"
    : "+f"(d[0]), "+f"(d[1]), "+f"(d[2]), "+f"(d[3]), "+f"(d[4]), "+f"(d[5]), "+f"(d[6]), "+f"(d[7]),
      "+f"(d[8]), "+f"(d[9]), "+f"(d[10]), "+f"(d[11]), "+f"(d[12]), "+f"(d[13]), "+f"(d[14]), "+f"(d[15]),
      "+f"(d[16]), "+f"(d[17]), "+f"(d[18]), "+f"(d[19]), "+f"(d[20]), "+f"(d[21]), "+f"(d[22]), "+f"(d[23]),
      "+f"(d[24]), "+f"(d[25]), "+f"(d[26]), "+f"(d[27]), "+f"(d[28]), "+f"(d[29]), "+f"(d[30]), "+f"(d[31]),
      "+f"(d[32]), "+f"(d[33]), "+f"(d[34]), "+f"(d[35]), "+f"(d[36]), "+f"(d[37]), "+f"(d[38]), "+f"(d[39]),
      "+f"(d[40]), "+f"(d[41]), "+f"(d[42]), "+f"(d[43]), "+f"(d[44]), "+f"(d[45]), "+f"(d[46]), "+f"(d[47]),
      "+f"(d[48]), "+f"(d[49]), "+f"(d[50]), "+f"(d[51]), "+f"(d[52]), "+f"(d[53]), "+f"(d[54]), "+f"(d[55]),
      "+f"(d[56]), "+f"(d[57]), "+f"(d[58]), "+f"(d[59]), "+f"(d[60]), "+f"(d[61]), "+f"(d[62]), "+f"(d[63])
    : "r"(a[0]), "r"(a[1]), "r"(a[2]), "r"(a[3]), "r"(db), "r"(sc), "n"(HI));
}

template <int N> __device__ __forceinline__ void keep(float (&d)[N]) {
#pragma unroll
  for (int i = 0; i < N; i++) asm volatile("" : "+f"(d[i])::"memory");
}

__device__ __forceinline__ void keep(uint32_t (&d)[4]) { asm volatile("" : "+r"(d[0]), "+r"(d[1]), "+r"(d[2]), "+r"(d[3])::"memory"); }
template <int N> __device__ __forceinline__ void keep(uint32_t (&d)[N][4]) {
#pragma unroll
  for (int i = 0; i < N; i++) asm volatile("" : "+r"(d[i][0]), "+r"(d[i][1]), "+r"(d[i][2]), "+r"(d[i][3])::"memory");
}

__device__ __forceinline__ uint32_t pack2(float lo, float hi) {
  uint32_t r;
  asm("cvt.rn.bf16x2.f32 %0, %1, %2;" : "=r"(r) : "f"(hi), "f"(lo));
  return r;
}
__device__ __forceinline__ float bf_lo(uint32_t v) { return __uint_as_float(v << 16); }
__device__ __forceinline__ float bf_hi(uint32_t v) { return __uint_as_float(v & 0xffff0000u); }
__device__ __forceinline__ uint32_t hsub2(uint32_t a, uint32_t b) {
  uint32_t r;
  asm("sub.rn.bf16x2 %0, %1, %2;" : "=r"(r) : "r"(a), "r"(b));
  return r;
}
__device__ __forceinline__ uint32_t movm(uint32_t a) {
  uint32_t r;
  asm volatile("movmatrix.sync.aligned.m8n8.trans.b16 %0, %1;" : "=r"(r) : "r"(a));
  return r;
}
__device__ __forceinline__ void ldsm4(uint32_t (&v)[4], uint32_t a) {
  asm volatile("ldmatrix.sync.aligned.m8n8.x4.shared.b16 {%0,%1,%2,%3}, [%4];" : "=r"(v[0]), "=r"(v[1]), "=r"(v[2]), "=r"(v[3]) : "r"(a) : "memory");
}
__device__ __forceinline__ void stsm4(uint32_t a, const uint32_t (&v)[4]) {
  asm volatile("stmatrix.sync.aligned.m8n8.x4.shared.b16 [%0], {%1,%2,%3,%4};" ::"r"(a), "r"(v[0]), "r"(v[1]), "r"(v[2]), "r"(v[3]) : "memory");
}
__device__ __forceinline__ void mma16816(float (&d)[4], const uint32_t (&a)[4], uint32_t b0, uint32_t b1) {
  asm volatile("mma.sync.aligned.m16n8k16.row.col.f32.bf16.bf16.f32 {%0,%1,%2,%3}, {%4,%5,%6,%7}, {%8,%9}, {%10,%10,%10,%10};"
               : "=f"(d[0]), "=f"(d[1]), "=f"(d[2]), "=f"(d[3])
               : "r"(a[0]), "r"(a[1]), "r"(a[2]), "r"(a[3]), "r"(b0), "r"(b1), "f"(0.f));
}
__device__ __forceinline__ void mma1688_acc(float (&d)[4], uint32_t a0, uint32_t a1, uint32_t b0) {
  asm volatile("mma.sync.aligned.m16n8k8.row.col.f32.bf16.bf16.f32 {%0,%1,%2,%3}, {%4,%5}, {%6}, {%0,%1,%2,%3};"
               : "+f"(d[0]), "+f"(d[1]), "+f"(d[2]), "+f"(d[3]) : "r"(a0), "r"(a1), "r"(b0));
}
__device__ __forceinline__ float ex2(float x) { float y; asm("ex2.approx.ftz.f32 %0, %1;" : "=f"(y) : "f"(x)); return y; }
__device__ __forceinline__ float rcp(float x) { float y; asm("rcp.approx.ftz.f32 %0, %1;" : "=f"(y) : "f"(x)); return y; }
__device__ __forceinline__ float tanhf_hw(float x) { float y; asm("tanh.approx.f32 %0, %1;" : "=f"(y) : "f"(x)); return y; }
__device__ __forceinline__ float2 lds64(uint32_t a) { float2 v; asm volatile("ld.shared.v2.f32 {%0,%1}, [%2];" : "=f"(v.x), "=f"(v.y) : "r"(a) : "memory"); return v; }
__device__ __forceinline__ void lds128(uint32_t (&v)[4], uint32_t a) { asm volatile("ld.shared.v4.u32 {%0,%1,%2,%3}, [%4];" : "=r"(v[0]), "=r"(v[1]), "=r"(v[2]), "=r"(v[3]) : "r"(a) : "memory"); }
__device__ __forceinline__ void sts128(uint32_t a, const uint32_t (&v)[4]) { asm volatile("st.shared.v4.u32 [%0], {%1,%2,%3,%4};" ::"r"(a), "r"(v[0]), "r"(v[1]), "r"(v[2]), "r"(v[3]) : "memory"); }
__device__ __forceinline__ void ldg128_nc(uint32_t (&v)[4], const void* p) {
  asm volatile("ld.global.nc.L1::no_allocate.v4.u32 {%0,%1,%2,%3}, [%4];" : "=r"(v[0]), "=r"(v[1]), "=r"(v[2]), "=r"(v[3]) : "l"(p));
}
__device__ __forceinline__ void ll_st(uint4* p, uint32_t a, uint32_t b, uint32_t c, uint32_t d, uint32_t tag) {
  asm volatile("{\n.reg .b128 t;\n.reg .b64 lo, hi;\nmov.b64 lo, {%1, %2};\nmov.b64 hi, {%3, %4};\nmov.b128 t, {lo, hi};\n"
               "st.relaxed.gpu.global.b128 [%0], t;\n}\n" ::"l"(p), "r"((a & ~1u) | tag), "r"(b), "r"(c), "r"(d) : "memory");
}
__device__ __forceinline__ void ll_ld(uint32_t (&v)[4], const uint4* p) {
  asm volatile("{\n.reg .b128 t;\n.reg .b64 lo, hi;\nld.relaxed.gpu.global.b128 t, [%4];\nmov.b128 {lo, hi}, t;\n"
               "mov.b64 {%0, %1}, lo;\nmov.b64 {%2, %3}, hi;\n}\n"
               : "=r"(v[0]), "=r"(v[1]), "=r"(v[2]), "=r"(v[3]) : "l"(p) : "memory");
}
template <int N> __device__ __forceinline__ void ll_issue(uint32_t (&v)[N][4], const uint4* p, int stride) {
#pragma unroll
  for (int i = 0; i < N; i++) ll_ld(v[i], p + i * stride);
}
template <int N> __device__ __forceinline__ bool ll_bad(const uint32_t (&v)[N][4], uint32_t tag) {
  uint32_t bad = v[0][0] ^ tag;
#pragma unroll
  for (int i = 1; i < N; i++) bad |= (v[i][0] ^ tag);
  return __any_sync(0xffffffffu, bad & 1u);
}
template <int N> __device__ __forceinline__ void ll_clear(uint32_t (&v)[N][4]) {
#pragma unroll
  for (int i = 0; i < N; i++) v[i][0] &= ~1u;
}
template <int N> __device__ __forceinline__ void ll_spin(uint32_t (&v)[N][4], const uint4* p, int stride, uint32_t tag) {
  uint32_t it = 0;
#pragma unroll 1
  do { ll_issue<N>(v, p, stride); } while (ll_bad<N>(v, tag) && ++it < SPIN_LIMIT);
}
template <int N> __device__ __forceinline__ void ll_get(uint32_t (&v)[N][4], const uint4* p, int stride, uint32_t tag) {
  ll_spin<N>(v, p, stride, tag);
  ll_clear<N>(v);
}
template <int N> __device__ __forceinline__ void ll_wait(uint32_t (&v)[N][4], const uint4* p, int stride, uint32_t tag) {
  if (__builtin_expect(ll_bad<N>(v, tag), 0)) ll_spin<N>(v, p, stride, tag);
  ll_clear<N>(v);
}
__device__ __forceinline__ void unpack32(float (&d)[32], const uint32_t (&v)[4][4]) {
#pragma unroll
  for (int u = 0; u < 4; u++)
#pragma unroll
    for (int e = 0; e < 4; e++) { d[8 * u + 2 * e] = bf_lo(v[u][e]); d[8 * u + 2 * e + 1] = bf_hi(v[u][e]); }
}
__device__ __forceinline__ void pack32(uint32_t (&v)[4][4], const float (&d)[32]) {
#pragma unroll
  for (int u = 0; u < 4; u++)
#pragma unroll
    for (int e = 0; e < 4; e++) v[u][e] = pack2(d[8 * u + 2 * e], d[8 * u + 2 * e + 1]);
}
__device__ __forceinline__ uint32_t t_addr(int m) { return SB + ((0x03514620u >> (4 * m)) & 7u) * 32768u; }

__device__ __forceinline__ int kb_at(int i, int j) { return i == 0 ? j : (i - 1 + (i - 1 >= j ? 1 : 0)); }

__device__ __forceinline__ void init_bars(int set) {
  if (elect_one()) {
    const uint32_t cnt = set < 5 ? 1 : set < 10 ? 8 : 4;
#pragma unroll
    for (int i = 0; i < 8; i++) mbar_init(BAR + (24 + 8 * set + i) * 8, cnt);
    if (set == 10) { mbar_init(BAR + B_LAG * 8, 4); mbar_init(BAR + B_READY * 8, 3); }
    fence_async_smem();
  }
  __syncwarp();
  asm volatile("bar.arrive 4, 384;" ::: "memory");
  asm volatile("bar.sync 3, 384;" ::: "memory");
}

__global__ void __launch_bounds__(384, 1) fused_block_kernel(const __grid_constant__ Params P) {
  extern __shared__ __align__(1024) uint8_t smem_raw[];
  if (smem_u32(smem_raw) != SB) return;
  const int tid = threadIdx.x;
  const int warp = __shfl_sync(0xffffffffu, tid >> 5, 0);
  const int lane = tid & 31;
  const int cta = blockIdx.x;
  const int j = (cta >> 6) * 4 + (cta & 3);
  const int g = (cta & 63) >> 2;

  if (warp >= 8) {
    if (warp == 8) {
      PSTAMPW(2, 0);
      const bool leader = elect_one();
      if (leader) {
        prefetch_map(&P.x); prefetch_map(&P.wqkv);
#pragma unroll
        for (int i = 0; i < 24; i++) mbar_init(BAR + i * 8, 1);
        fence_async_smem();
      }
      __syncwarp();
      asm volatile("bar.arrive 3, 384;" ::: "memory");
      asm volatile("setmaxnreg.dec.sync.aligned.u32 56;");
      auto ldx = [&](int p, int kb) {
        const uint32_t b = BAR + (B_FX + p * 8 + kb) * 8;
        mbar_expect_tx(b, 8192);
        tma3d(H0 + p * 65536 + kb * 8192, &P.x, kb * 64, p, g * 64, b);
      };
      auto ldkv = [&](int kb, int slot) {
        const uint32_t b = BAR + (B_FKV + kb) * 8, d = RING + slot * 16384;
        mbar_expect_tx(b, 16384);
        tma2d(d, &P.wqkv, 512 + 64 * j, kb * 64, b);
        tma2d(d + 8192, &P.wqkv, 1024 + 64 * j, kb * 64, b);
      };
      if (leader) {
#pragma unroll 1
        for (int i = 0; i < 8 + XO_DELAY; i++) {
          if (i < 8) ldx(0, i);
          if (i < 6) ldkv(i, i);
          if (i >= XO_DELAY) ldx(1, i - XO_DELAY);
        }
        PSTAMPW(2, 2);
      }
      __syncwarp();
      asm volatile("bar.sync 4, 384;" ::: "memory");
      if (leader) {
        const int f0 = 224 * j + ((j & 1) ? 32 : 0);
        const int fh = 224 * j + ((j & 1) ? 0 : 192);
        prefetch_map(&P.wo); prefetch_map(&P.w1); prefetch_map(&P.w3); prefetch_map(&P.w1h);
        prefetch_map(&P.w3h); prefetch_map(&P.w2); prefetch_map(&P.out);
#pragma unroll 1
        for (int i = 0; i < 2; i++) { mbar_wait(BAR + (B_EKV + i) * 8); ldkv(6 + i, i); }
#pragma unroll 1
        for (int i = 0; i < 8; i++) {
          const uint32_t b = BAR + (B_FQ + i) * 8;
          mbar_wait(BAR + (B_EKV + 2 + (i >> 1)) * 8);
          mbar_expect_tx(b, 8192);
          tma2d(RING + (4 + i) * 8192, &P.wqkv, 64 * j, i * 64, b);
        }
        mbar_expect_tx(BAR + B_FWO * 8, 65536);
#pragma unroll 1
        for (int i = 0; i < 8; i++) {
          const int kb = (i + 1) & 7;
          mbar_wait(BAR + (B_EX + i) * 8);
          tma2d(H0 + kb * 8192, &P.wo, 64 * j, kb * 64, BAR + B_FWO * 8);
          PSTAMPW(2, 4 + i);
        }
#pragma unroll 1
        for (int i = 0; i < 8; i++) {
          const uint32_t b = BAR + (B_FA + i) * 8, d = RING + (i & 3) * 24576;
          const int k0 = kb_at(i, j) * 64;
          mbar_wait(BAR + (B_EKV + 7 + ((0xCBA98520u >> (4 * i)) & 15)) * 8);
          mbar_expect_tx(b, 24576);
          tma2d(d, &P.w1, f0, k0, b);
          tma2d(d + 8192, &P.w3, f0, k0, b);
          tma2d(d + 16384, &P.w1h, fh, k0, b);
          tma2d(d + 20480, &P.w3h, fh, k0, b);
          PSTAMPW(2, 12 + i);
        }
        uint32_t d = RING;
#pragma unroll 1
        for (int i = 0; i < 8; i++) {
          const uint32_t b = BAR + (B_FB + i) * 8;
          const int k0 = kb_at(i, j) * 64;
          mbar_wait(BAR + (B_EA + 5 + i) * 8);
          mbar_expect_tx(b, 32768);
          tma2d(d, &P.w1, f0 + 64, k0, b);
          tma2d(d + 8192, &P.w3, f0 + 64, k0, b);
          tma2d(d + 16384, &P.w1, f0 + 128, k0, b);
          tma2d(d + 24576, &P.w3, f0 + 128, k0, b);
          d = d == RING + 65536 ? RING : d + 32768;
        }
#pragma unroll 1
        for (int m = 0; m < 8; m++) {
          const uint32_t b = BAR + (B_FT + m) * 8;
          mbar_wait(BAR + (B_EB + (m == 7 ? 8 : min(m + 3, 7))) * 8);
          mbar_expect_tx(b, 28672);
          tma2d(t_addr(m), &P.w2, 64 * ((j + 1 + m) & 7), 224 * j, b);
        }
        g_epoch[cta] = g_epoch[cta] + 1;
      }
    } else {
      asm volatile("setmaxnreg.dec.sync.aligned.u32 56;");
      const int part = warp - 9;
      uint32_t v[8][4];
      {
        const __nv_bfloat16* wr = P.wqkvp + (size_t)(g * 32 + (lane >> 3) * 8) * (3 * D_) + part * D_ + j * 64 + (lane & 7) * 8;
#pragma unroll
        for (int i = 0; i < 8; i++) ldg128_nc(v[i], wr + (size_t)i * 3 * D_);
      }
      const uint32_t tag = (__ldcg(&g_epoch[cta]) + 1) & 1;
      init_bars(warp - 1);
      {
        float cs[8];
#pragma unroll
        for (int e = 0; e < 4; e++) {
          float a = 0.f, b = 0.f;
#pragma unroll
          for (int i = 0; i < 8; i++) { a += bf_lo(v[i][e]); b += bf_hi(v[i][e]); }
          cs[2 * e] = a; cs[2 * e + 1] = b;
        }
        const bool up = lane & 8;
#pragma unroll
        for (int e = 0; e < 4; e++) {
          const float keepv = up ? cs[4 + e] : cs[e], give = up ? cs[e] : cs[4 + e];
          cs[e] = keepv + __shfl_xor_sync(0xffffffffu, give, 8);
          cs[e] += __shfl_xor_sync(0xffffffffu, cs[e], 16);
        }
        if (lane < 16)
          ll_st(g_e0c + ((j * 3 + part) * 16 + g) * 16 + (lane & 7) * 2 + (lane >> 3), __float_as_uint(cs[0]), __float_as_uint(cs[1]),
                __float_as_uint(cs[2]), __float_as_uint(cs[3]), tag);
      }
      mbar_wait(BAR + B_PUB * 8);
      PSTAMPW(3, part * 4 + 0);
      if (lane == 0) l2_prefetch(part == 0 ? P.w1p + (size_t)cta * 4 * F_ : part == 1 ? P.w3p + (size_t)cta * 4 * F_ : P.w2p + (size_t)cta * 14 * D_, 14336);
      {
        uint32_t u[2][4];
        ll_get<2>(u, (part == 2 ? g_e0w + j * 64 : g_e0s + g * 128 + part * 64) + lane, 32, tag);
#pragma unroll
        for (int i = 0; i < 2; i++) {
          if (part == 2) asm volatile("st.shared.u32 [%0], %1;" ::"r"(WB + (i * 32 + lane) * 4), "r"(u[i][0]) : "memory");
          else asm volatile("st.shared.v2.u32 [%0], {%1,%2};" ::"r"(ST + (part * 64 + i * 32 + lane) * 8), "r"(u[i][0]), "r"(u[i][1]) : "memory");
        }
      }
      ll_get<8>(v, g_e0c + ((j * 3 + part) * 16 + (lane >> 4) * 8) * 16 + (lane & 15), 16, tag);
      uint32_t o[4];
#pragma unroll
      for (int e = 0; e < 4; e++) {
        float s = 0.f;
#pragma unroll
        for (int i = 0; i < 8; i++) s += __uint_as_float(v[i][e]);
        o[e] = __float_as_uint(s + __shfl_xor_sync(0xffffffffu, s, 16));
      }
      if (lane < 16) sts128(CS + (part * 64 + lane * 4) * 4, o);
      __syncwarp();
      if (lane == 0) mbar_arrive(BAR + B_READY * 8);
      PSTAMPW(3, part * 4 + 1);
    }
  } else {
    const int p = warp >> 2, w = warp & 3;
    const int r = lane >> 2, c = lane & 3;
    uint32_t tag;
    {
      uint32_t xs[4][4], ws[4];
      const int trow = g * 128 + j * 16 + warp * 2 + (lane >> 4);
      const __nv_bfloat16* xr = P.xp + (size_t)trow * D_ + (lane & 15) * 8;
#pragma unroll
      for (int i = 0; i < 4; i++) ldg128_nc(xs[i], xr + i * 128);
      ldg128_nc(ws, P.wop + (size_t)(j * 64 + g * 4 + w) * D_ + p * 256 + lane * 8);
      tag = (__ldcg(&g_epoch[cta]) + 1) & 1;
      asm volatile("setmaxnreg.inc.sync.aligned.u32 224;");
      init_bars(warp);
      PSTAMP(0);
      float s = 0.f, q = 0.f;
      const float piv = __shfl_sync(0xffffffffu, bf_lo(xs[0][0]), lane & 16);
#pragma unroll
      for (int i = 0; i < 4; i++)
#pragma unroll
        for (int e = 0; e < 4; e++) {
          const float a = bf_lo(xs[i][e]) - piv, b = bf_hi(xs[i][e]) - piv;
          s += a + b; q = fmaf(a, a, q); q = fmaf(b, b, q);
        }
      float t = 0.f;
#pragma unroll
      for (int e = 0; e < 4; e++) t += bf_lo(ws[e]) + bf_hi(ws[e]);
#pragma unroll
      for (int o = 1; o <= 8; o <<= 1) {
        s += __shfl_xor_sync(0xffffffffu, s, o); q += __shfl_xor_sync(0xffffffffu, q, o); t += __shfl_xor_sync(0xffffffffu, t, o);
      }
      t += __shfl_xor_sync(0xffffffffu, t, 16);
      const float dm = s * (1.f / D_);
      const float rs = rsqrtf(fmaxf(fmaf(-dm, dm, q * (1.f / D_)), 0.f) + 1e-5f);
      if ((lane & 15) == 0) ll_st(g_e0s + trow, __float_as_uint(piv + dm), __float_as_uint(rs), 0, 0, tag);
      if (p == 1 && lane == 0) asm volatile("st.shared.f32 [%0], %1;" ::"r"(CS + w * 4), "f"(t) : "memory");
      asm volatile("bar.sync 5, 256;" ::: "memory");
      if (p == 0 && lane == 0) {
        float t2;
        asm volatile("ld.shared.f32 %0, [%1];" : "=f"(t2) : "r"(CS + w * 4) : "memory");
        ll_st(g_e0w + j * 64 + g * 4 + w, __float_as_uint((t + t2) * (1.f / D_)), 0, 0, 0, tag);
      }
      __syncwarp();
      if (lane == 0) mbar_arrive(BAR + B_PUB * 8);
      PSTAMP(1);
    }
    const uint32_t dAx = descA(H0) + p * 4096;
    const uint32_t Hn = H1 - p * 65536;
    const uint32_t moff = ((lane & 7) + ((lane >> 3) & 1) * 8) * 128 + (((lane >> 4) ^ (lane & 7)) << 4);
    const uint32_t Xw = H0 + p * 65536 + w * 2048;
    const int xw = (g * 2 + p) * 4 + w;
    if (p == 1) mbar_wait(BAR + B_LAG * 8);

    float akv[64];
#pragma unroll 1
    for (int kb = 0; kb < 8; kb++) {
      mbar_wait(BAR + (B_FX + p * 8 + kb) * 8);
      mbar_wait(BAR + (B_FKV + kb) * 8);
      if (kb == 0) PSTAMP(2);
      const uint32_t da = dAx + kb * 512, db = descB(RING) + (kb < 6 ? kb : kb - 6) * 1024;
      wg_fence();
      wgmma_ss_n128(akv, da, db, kb);
#pragma unroll
      for (int k = 1; k < 4; k++) wgmma_ss_n128(akv, da + k * 2, db + k * 128, 1);
      wg_commit();
      if (kb == LAG_KB - 1 && p == 0 && lane == 0) mbar_arrive(BAR + B_LAG * 8);
      wg_wait<1>();
      if (kb > 0 && lane == 0) mbar_arrive(BAR + (B_EKV + kb - 1) * 8);
    }
    uint32_t xres[4][4];
#pragma unroll
    for (int u = 0; u < 4; u++) ldsm4(xres[u], Xw + j * 8192 + (moff ^ (u << 5)));

    float aq[32];
    auto qstep = [&](int kb) {
      mbar_wait(BAR + (B_FQ + kb) * 8);
      const uint32_t da = dAx + kb * 512, db = descB(RING + 32768) + kb * 512;
      wg_fence();
      wgmma_ss_n64(aq, da, db, kb);
#pragma unroll
      for (int k = 1; k < 4; k++) wgmma_ss_n64(aq, da + k * 2, db + k * 128, 1);
      wg_commit();
      wg_wait<1>();
      if (lane == 0) {
        mbar_arrive(BAR + (B_EQ + kb - 1) * 8);
        if (p == 0 && kb >= 2) mbar_arrive(BAR + (B_EX + kb - 2) * 8);
      }
    };
    qstep(0);
    keep(akv);
    PSTAMP(3);
    mbar_wait(BAR + B_READY * 8);
    const float2 st0 = lds64(ST + (2 * (16 * w + r) + p) * 8);
    const float2 st1 = lds64(ST + (2 * (16 * w + r + 8) + p) * 8);
    uint32_t hi[4][4], lo[4][4];
    {
      float2 cs[16];
      auto cvt = [&](uint32_t (&d)[4][4], int b0, int ofs, const float2& st) {
#pragma unroll
        for (int b = b0; b < b0 + 8; b++) {
          if (ofs == 2) cs[b] = lds64(CS + (64 + b * 8 + 2 * c) * 4);
          const uint32_t v = pack2(fmaf(-st.x, cs[b].x, akv[4 * b + ofs]) * st.y, fmaf(-st.x, cs[b].y, akv[4 * b + ofs + 1]) * st.y);
          d[b >> 2][b & 3] = b < 8 ? v : movm(v);
        }
      };
      cvt(hi, 0, 2, st1);
      keep(hi[0]); keep(hi[1]);
      qstep(1);
      cvt(hi, 8, 2, st1);
      if (w == 3 && g < 15) {
        uint4* dst = g_e1 + ((g * 8 + j) * 2 + p) * 128 + lane;
#pragma unroll
        for (int i = 0; i < 4; i++) ll_st(dst + i * 32, hi[i][0], hi[i][1], hi[i][2], hi[i][3], tag);
      }
      wg_bar(p);
#pragma unroll
      for (int i = 0; i < 4; i++) sts128(Xw + lane * 16 + i * 512, hi[i]);
      qstep(2);
      cvt(lo, 0, 0, st0);
      keep(lo[0]); keep(lo[1]);
      qstep(3);
      cvt(lo, 8, 0, st0);
    }
    wg_bar(p);
    uint32_t prev[4][4];
    if (w > 0) {
#pragma unroll
      for (int i = 0; i < 4; i++) lds128(prev[i], Xw - 2048 + lane * 16 + i * 512);
    }
    if (p == 0) {
      asm volatile("fence.proxy.async.shared::cta;" ::: "memory");
      __syncwarp();
      if (lane == 0) mbar_arrive(BAR + (B_EX + 7) * 8);
    }
#pragma unroll 1
    for (int kb = 4; kb < 8; kb++) qstep(kb);
    if (w == 0) {
      if (g > 0) {
        ll_get<4>(prev, g_e1 + (((g - 1) * 8 + j) * 2 + p) * 128 + lane, 32, tag);
      } else {
#pragma unroll
        for (int i = 0; i < 4; i++)
#pragma unroll
          for (int e = 0; e < 4; e++) prev[i][e] = 0;
      }
    }
    wg_wait<0>();
    keep(aq);
    if (lane == 0) { mbar_arrive(BAR + (B_EQ + 7) * 8); if (p == 0) mbar_arrive(BAR + (B_EX + 6) * 8); }
    PSTAMP(4);

    uint32_t of[4][4];
    uint32_t og[4][7][4];
    const uint4* osrc[7];
#pragma unroll
    for (int i = 0; i < 7; i++) osrc[i] = g_e2 + (xw * 32 + 4 * kb_at(i + 1, j)) * 32 + lane;
    auto oissue = [&](int h) {
#pragma unroll
      for (int i = 0; i < 7; i++) ll_ld(og[h][i], osrc[i] + h * 32);
    };
    {
      const float sc = 0.25f * 1.4426950408889634f;
      const float nohalo = (g == 0 && w == 0) ? -INFINITY : 0.f;
      const bool up0 = 2 * c > r, up1 = 2 * c + 1 > r;
      const uint32_t mup = (up0 ? 0xffffu : 0u) | (up1 ? 0xffff0000u : 0u);
      uint4* dst = g_e2 + (xw * 32 + 4 * j) * 32 + lane;
      float d0 = 0.f, d1 = 0.f;
#pragma unroll
      for (int h = 0; h < 4; h++) {
        uint32_t qf[4];
        {
          const float2 ca = lds64(CS + (16 * h + 2 * c) * 4), cb = lds64(CS + (16 * h + 8 + 2 * c) * 4);
          qf[0] = pack2(fmaf(-st0.x, ca.x, aq[8 * h + 0]) * st0.y, fmaf(-st0.x, ca.y, aq[8 * h + 1]) * st0.y);
          qf[1] = pack2(fmaf(-st1.x, ca.x, aq[8 * h + 2]) * st1.y, fmaf(-st1.x, ca.y, aq[8 * h + 3]) * st1.y);
          qf[2] = pack2(fmaf(-st0.x, cb.x, aq[8 * h + 4]) * st0.y, fmaf(-st0.x, cb.y, aq[8 * h + 5]) * st0.y);
          qf[3] = pack2(fmaf(-st1.x, cb.x, aq[8 * h + 6]) * st1.y, fmaf(-st1.x, cb.y, aq[8 * h + 7]) * st1.y);
        }
        const int i0 = h >> 1, e0 = (2 * h) & 3;
        float sp[4], sl[4], sh[4];
        mma16816(sp, qf, prev[i0][e0], prev[i0][e0 + 1]);
        mma16816(sl, qf, lo[i0][e0], lo[i0][e0 + 1]);
        mma16816(sh, qf, hi[i0][e0], hi[i0][e0 + 1]);
        float a0 = up0 ? sp[0] + nohalo : sl[0], a1 = up1 ? sp[1] + nohalo : sl[1];
        float b0 = up0 ? sl[2] : sh[2], b1 = up1 ? sl[3] : sh[3];
        float ma = fmaxf(a0, a1), mb = fmaxf(b0, b1);
        ma = fmaxf(ma, __shfl_xor_sync(0xffffffffu, ma, 1)); mb = fmaxf(mb, __shfl_xor_sync(0xffffffffu, mb, 1));
        ma = fmaxf(ma, __shfl_xor_sync(0xffffffffu, ma, 2)); mb = fmaxf(mb, __shfl_xor_sync(0xffffffffu, mb, 2));
        a0 = ex2((a0 - ma) * sc); a1 = ex2((a1 - ma) * sc); b0 = ex2((b0 - mb) * sc); b1 = ex2((b1 - mb) * sc);
        float sa = a0 + a1, sbb = b0 + b1;
        sa += __shfl_xor_sync(0xffffffffu, sa, 1); sbb += __shfl_xor_sync(0xffffffffu, sbb, 1);
        sa += __shfl_xor_sync(0xffffffffu, sa, 2); sbb += __shfl_xor_sync(0xffffffffu, sbb, 2);
        const float ia = rcp(sa), ib = rcp(sbb);
        const uint32_t pa = pack2(a0 * ia, a1 * ia), pb = pack2(b0 * ib, b1 * ib);
        const uint32_t pf[4] = {pa & mup, 0u, pa & ~mup, pb & mup};
        const uint32_t ph = pb & ~mup;
        float o0[4], o1[4];
        mma16816(o0, pf, prev[2 + i0][e0], lo[2 + i0][e0]);
        mma16816(o1, pf, prev[2 + i0][e0 + 1], lo[2 + i0][e0 + 1]);
        mma1688_acc(o0, 0u, ph, hi[2 + i0][e0]);
        mma1688_acc(o1, 0u, ph, hi[2 + i0][e0 + 1]);
        of[h][0] = pack2(o0[0], o0[1]); of[h][1] = pack2(o0[2], o0[3]);
        of[h][2] = pack2(o1[0], o1[1]); of[h][3] = pack2(o1[2], o1[3]);
        ll_st(dst + h * 32, of[h][0], of[h][1], of[h][2], of[h][3], tag);
        const float2 wa = lds64(WB + (16 * h + 2 * c) * 4), wb = lds64(WB + (16 * h + 8 + 2 * c) * 4);
        d0 = fmaf(o0[0], wa.x, d0); d0 = fmaf(o0[1], wa.y, d0); d0 = fmaf(o1[0], wb.x, d0); d0 = fmaf(o1[1], wb.y, d0);
        d1 = fmaf(o0[2], wa.x, d1); d1 = fmaf(o0[3], wa.y, d1); d1 = fmaf(o1[2], wb.x, d1); d1 = fmaf(o1[3], wb.y, d1);
        if (h == 2) oissue(0);
      }
#pragma unroll
      for (int o = 1; o <= 2; o <<= 1) { d0 += __shfl_xor_sync(0xffffffffu, d0, o); d1 += __shfl_xor_sync(0xffffffffu, d1, o); }
      if (c == 0) ll_st(g_e2s + (xw * 8 + j) * 8 + r, __float_as_uint(d0), __float_as_uint(d1), 0, 0, tag);
      oissue(1);
    }
    PSTAMP(5);

    float ah[32];
    uint32_t sv[2][4];
    unpack32(ah, xres);
    {
      mbar_wait(BAR + B_FWO * 8);
      keep(ah); keep(of);
      wg_fence();
#pragma unroll
      for (int k = 0; k < 4; k++) wgmma_rs_n64(ah, of[k], descB(H0) + j * 512 + k * 128, 1);
      wg_commit();
      oissue(2);
#pragma unroll
      for (int h = 0; h < 4; h++) {
        if (__builtin_expect(ll_bad<7>(og[h], tag), 0)) {
          uint32_t it = 0;
#pragma unroll 1
          do { oissue(h); } while (ll_bad<7>(og[h], tag) && ++it < SPIN_LIMIT);
        }
        ll_clear<7>(og[h]);
        keep(og[h]);
        if (h == 0) PSTAMP(6);
        if (h == 3) PSTAMP(16);
        wg_fence();
#pragma unroll
        for (int i = 0; i < 7; i++) wgmma_rs_n64(ah, og[h][i], descB(H0) + kb_at(i + 1, j) * 512 + h * 128, 1);
        wg_commit();
        if (h == 0) oissue(3);
        if (h == 1) ll_issue<2>(sv, g_e2s + (xw * 8 + 2 * c) * 8 + r, 8);
      }
      ll_wait<2>(sv, g_e2s + (xw * 8 + 2 * c) * 8 + r, 8, tag);
    }
    float m0 = __uint_as_float(sv[0][0]) + __uint_as_float(sv[1][0]), m1 = __uint_as_float(sv[0][1]) + __uint_as_float(sv[1][1]);
#pragma unroll
    for (int o = 1; o <= 2; o <<= 1) { m0 += __shfl_xor_sync(0xffffffffu, m0, o); m1 += __shfl_xor_sync(0xffffffffu, m1, o); }
    const uint32_t mu0 = pack2(m0 + st0.x, m0 + st0.x), mu1 = pack2(m1 + st1.x, m1 + st1.x);
    wg_wait<0>();
    keep(ah);
    if (lane == 0) mbar_arrive(BAR + B_WODONE * 8);
    PSTAMP(7);

    uint32_t hf[4][4], ra[4][4];
    pack32(hf, ah);
    {
      uint4* dst = g_e3h + (xw * 32 + 4 * j) * 32 + lane;
#pragma unroll
      for (int u = 0; u < 4; u++) {
        ra[u][0] = (hsub2(hf[u][0], mu0) & ~1u) | tag; ra[u][1] = hsub2(hf[u][1], mu1);
        ra[u][2] = hsub2(hf[u][2], mu0); ra[u][3] = hsub2(hf[u][3], mu1);
        ll_st(dst + u * 32, ra[u][0], ra[u][1], ra[u][2], ra[u][3], tag);
      }
      float s0 = 0.f, q0 = 0.f, s1 = 0.f, q1 = 0.f;
#pragma unroll
      for (int b = 0; b < 8; b++) {
        s0 += ah[4 * b] + ah[4 * b + 1]; s1 += ah[4 * b + 2] + ah[4 * b + 3];
        q0 = fmaf(ah[4 * b], ah[4 * b], q0); q0 = fmaf(ah[4 * b + 1], ah[4 * b + 1], q0);
        q1 = fmaf(ah[4 * b + 2], ah[4 * b + 2], q1); q1 = fmaf(ah[4 * b + 3], ah[4 * b + 3], q1);
      }
#pragma unroll
      for (int o = 1; o <= 2; o <<= 1) {
        s0 += __shfl_xor_sync(0xffffffffu, s0, o); q0 += __shfl_xor_sync(0xffffffffu, q0, o);
        s1 += __shfl_xor_sync(0xffffffffu, s1, o); q1 += __shfl_xor_sync(0xffffffffu, q1, o);
      }
      if (c == 0) ll_st(g_e3s + (xw * 8 + j) * 8 + r, __float_as_uint(s0), __float_as_uint(q0), __float_as_uint(s1), __float_as_uint(q1), tag);
      mbar_wait(BAR + (p == 0 ? B_EQ + 7 : B_WODONE) * 8);
    }
    PSTAMP(8);

    float rs0, rs1;
    auto swiglu = [&](float g0, float g1, float u0, float u1, float rs) -> uint32_t {
      const float hr = 0.5f * rs;
      const float x0 = g0 * hr, x1 = g1 * hr;
      const float t0 = tanhf_hw(x0), t1 = tanhf_hw(x1);
      return pack2(fmaf(x0, t0, x0) * (u0 * rs), fmaf(x1, t1, x1) * (u1 * rs));
    };
    uint32_t hA[6][4];
    {
      float a1[64], a2[32];
      const uint4* src = g_e3h + xw * 32 * 32 + lane;
      uint32_t rb[4][4], oa[4][4], ob[4][4];
      auto prep = [&](uint32_t (&raw)[4][4], uint32_t (&a)[4][4], int i) {
        if (__builtin_expect(ll_bad<4>(raw, tag), 0)) ll_spin<4>(raw, src + kb_at(i, j) * 128, 32, tag);
#pragma unroll
        for (int u = 0; u < 4; u++) { a[u][0] = raw[u][0] & ~1u; a[u][1] = raw[u][1]; a[u][2] = raw[u][2]; a[u][3] = raw[u][3]; }
        keep(a);
        if (i < 6) ll_issue<4>(raw, src + kb_at(i + 2, j) * 128, 32);
      };
      auto step = [&](uint32_t (&a)[4][4], uint32_t (&rawn)[4][4], uint32_t (&an)[4][4], int i) {
        mbar_wait(BAR + (B_FA + i) * 8);
        const uint32_t db = descB(RING) + (i & 3) * 1536, dh = descBh(RING + 16384) + (i & 3) * 1536;
        wg_fence();
        wgmma_rs_n64<DESC_HI64>(a2, a[0], dh, i);
        wgmma_rs_n128(a1, a[0], db, i);
        wg_commit();
#pragma unroll
        for (int u = 0; u < 4; u++) stsm4(Hn + w * 2048 + i * 8192 + (moff ^ (u << 5)), a[u]);
        wg_wait<1>();
        if (i > 0 && lane == 0) mbar_arrive(BAR + (B_EA + i - 1) * 8);
        wg_fence();
        wgmma_rs_n64<DESC_HI64>(a2, a[1], dh + 64, 1);
        wgmma_rs_n128(a1, a[1], db + 128, 1);
        wgmma_rs_n64<DESC_HI64>(a2, a[2], dh + 128, 1);
        wgmma_rs_n128(a1, a[2], db + 256, 1);
        wg_commit();
        if (i < 7) prep(rawn, an, i + 1);
        wg_fence();
        wgmma_rs_n64<DESC_HI64>(a2, a[3], dh + 192, 1);
        wgmma_rs_n128(a1, a[3], db + 384, 1);
        wg_commit();
      };
      ll_issue<4>(rb, src + kb_at(1, j) * 128, 32);
      prep(ra, oa, 0);
#pragma unroll 1
      for (int i = 0; i < 8; i += 2) {
        step(oa, rb, ob, i);
        if (i == 0) PSTAMP(17);
        if (i == 4) ll_issue<2>(sv, g_e3s + (xw * 8 + 2 * c) * 8 + r, 8);
        step(ob, ra, oa, i + 1);
      }
      fence_async_smem();
      ll_wait<2>(sv, g_e3s + (xw * 8 + 2 * c) * 8 + r, 8, tag);
      float s0 = __uint_as_float(sv[0][0]) + __uint_as_float(sv[1][0]), q0 = __uint_as_float(sv[0][1]) + __uint_as_float(sv[1][1]);
      float s1 = __uint_as_float(sv[0][2]) + __uint_as_float(sv[1][2]), q1 = __uint_as_float(sv[0][3]) + __uint_as_float(sv[1][3]);
#pragma unroll
      for (int o = 1; o <= 2; o <<= 1) {
        s0 += __shfl_xor_sync(0xffffffffu, s0, o); q0 += __shfl_xor_sync(0xffffffffu, q0, o);
        s1 += __shfl_xor_sync(0xffffffffu, s1, o); q1 += __shfl_xor_sync(0xffffffffu, q1, o);
      }
      s0 *= 1.f / D_; s1 *= 1.f / D_;
      rs0 = rsqrtf(fmaxf(fmaf(-s0, s0, q0 * (1.f / D_)), 0.f) + 1e-5f);
      rs1 = rsqrtf(fmaxf(fmaf(-s1, s1, q1 * (1.f / D_)), 0.f) + 1e-5f);
      wg_wait<0>();
      keep(a1); keep(a2);
      if (lane == 0) mbar_arrive(BAR + (B_EA + 7) * 8);
      PSTAMP(9);
#pragma unroll
      for (int u = 0; u < 4; u++)
#pragma unroll
        for (int e = 0; e < 4; e++)
          hA[u][e] = swiglu(a1[8 * u + 2 * e], a1[8 * u + 2 * e + 1], a1[32 + 8 * u + 2 * e], a1[33 + 8 * u + 2 * e], (e & 1) ? rs1 : rs0);
#pragma unroll
      for (int u = 0; u < 2; u++)
#pragma unroll
        for (int e = 0; e < 4; e++)
          hA[4 + u][e] = swiglu(a2[8 * u + 2 * e], a2[8 * u + 2 * e + 1], a2[16 + 8 * u + 2 * e], a2[17 + 8 * u + 2 * e], (e & 1) ? rs1 : rs0);
      keep(hA);
      wg_bar(p);
    }
    PSTAMP(10);

    uint32_t hB[8][4];
    {
      float ab[128];
      uint32_t db = descB(RING);
      const uint32_t dAn = descA(H1) - p * 4096;
#pragma unroll 1
      for (int i = 0; i < 8; i++) {
        mbar_wait(BAR + (B_FB + i) * 8);
        const uint32_t da = dAn + i * 512;
        wg_fence();
        wgmma_ss_n256(ab, da, db, i);
#pragma unroll
        for (int k = 1; k < 4; k++) wgmma_ss_n256(ab, da + k * 2, db + k * 128, 1);
        wg_commit();
        wg_wait<1>();
        if (i > 0 && lane == 0) mbar_arrive(BAR + (B_EB + i - 1) * 8);
        db = db == descB(RING + 65536) ? descB(RING) : db + 2048;
      }
      wg_wait<0>();
      keep(ab);
      if (lane == 0) mbar_arrive(BAR + (B_EB + 7) * 8);
      PSTAMP(11);
#pragma unroll
      for (int u = 0; u < 8; u++) {
        const int o = (u >> 2) * 64 + (u & 3) * 8;
#pragma unroll
        for (int e = 0; e < 4; e++)
          hB[u][e] = swiglu(ab[o + 2 * e], ab[o + 2 * e + 1], ab[o + 32 + 2 * e], ab[o + 33 + 2 * e], (e & 1) ? rs1 : rs0);
      }
      keep(hB);
    }
    PSTAMP(12);

    {
      float ya[32], yb[32], sum[32];
      unpack32(sum, hf);
      const uint32_t offA = (j & 1) ? 256 : 0, offH = (j & 1) ? 0 : 1536;
      uint4* e4 = g_e4 + (size_t)xw * 64 * 128 + lane;
      uint32_t in[4][4], pk[4][4];
#pragma unroll
      for (int u = 0; u < 4; u++) {
        in[u][0] = tag; in[u][1] = 0; in[u][2] = 0; in[u][3] = 0;
        pk[u][0] = 0; pk[u][1] = 0; pk[u][2] = 0; pk[u][3] = 0;
      }
      uint32_t T;
      auto mm = [&](float (&y)[32], int k) {
        if (k < 4) wgmma_rs_n64(y, hA[k], T + offA + k * 128, k);
        else if (k < 6) wgmma_rs_n64(y, hA[k], T + offH + (k - 4) * 128, 1);
        else wgmma_rs_n64(y, hB[k - 6], T + offA + 512 + (k - 6) * 128, 1);
      };
      auto acc = [&](int u) {
        sum[8 * u] += bf_lo(in[u][0] & ~1u); sum[8 * u + 1] += bf_hi(in[u][0]);
#pragma unroll
        for (int e = 1; e < 4; e++) { sum[8 * u + 2 * e] += bf_lo(in[u][e]); sum[8 * u + 2 * e + 1] += bf_hi(in[u][e]); }
        asm volatile("" : "+f"(sum[8 * u]), "+f"(sum[8 * u + 1]), "+f"(sum[8 * u + 2]), "+f"(sum[8 * u + 3]),
                          "+f"(sum[8 * u + 4]), "+f"(sum[8 * u + 5]), "+f"(sum[8 * u + 6]), "+f"(sum[8 * u + 7]));
      };
      auto insrc = [&](int q) { return e4 + (j * 8 + ((j - 1 - q) & 7)) * 128; };
      auto tail = [&](float (&y)[32], int m) {
        wg_commit();
        if (__builtin_expect(ll_bad<4>(in, tag), 0)) ll_spin<4>(in, insrc(m - 3), 32, tag);
        wg_fence();
        mm(y, 9); acc(0); mm(y, 10); acc(1); mm(y, 11); acc(2); mm(y, 12); acc(3);
        if (m >= 2) ll_issue<4>(in, insrc(m - 2), 32);
        mm(y, 13);
        wg_commit();
      };
#pragma unroll 1
      for (int m = 0; m < 8; m += 2) {
        {
          mbar_wait(BAR + (B_FT + m) * 8);
          T = descB(0) + (t_addr(m) >> 4);
          uint4* dst = e4 + (((j + m) & 7) * 8 + j) * 128;
          wg_fence();
          mm(ya, 0);
#pragma unroll
          for (int u = 0; u < 4; u++) {
            ll_st(dst + u * 32, pk[u][0], pk[u][1], pk[u][2], pk[u][3], tag);
            mm(ya, 1 + 2 * u); mm(ya, 2 + 2 * u);
          }
          tail(ya, m);
        }
        {
          mbar_wait(BAR + (B_FT + m + 1) * 8);
          T = descB(0) + (t_addr(m + 1) >> 4);
          uint4* dst = e4 + (((j + m + 1) & 7) * 8 + j) * 128;
          wg_fence();
          mm(yb, 0);
          wg_commit();
          wg_wait<1>();
          keep(ya);
          if (m == 0 && lane == 0) mbar_arrive(BAR + B_ET0 * 8);
          wg_fence();
#pragma unroll
          for (int u = 0; u < 4; u++) {
            mm(yb, 1 + 2 * u);
            ll_st(dst + u * 32, pack2(ya[8 * u], ya[8 * u + 1]), pack2(ya[8 * u + 2], ya[8 * u + 3]),
                  pack2(ya[8 * u + 4], ya[8 * u + 5]), pack2(ya[8 * u + 6], ya[8 * u + 7]), tag);
            mm(yb, 2 + 2 * u);
          }
          tail(yb, m + 1);
        }
        if (m == 6) {
          PSTAMP(13);
#pragma unroll 1
          for (int q = 5; q < 7; q++) {
            if (q == 6 || ll_bad<4>(in, tag)) ll_spin<4>(in, insrc(q), 32, tag);
            acc(0); acc(1); acc(2); acc(3);
          }
        }
        wg_wait<0>();
        keep(yb);
        pack32(pk, yb);
        if (m == 0) PSTAMP(27);
        if (m == 2) PSTAMP(26);
        if (m == 4) PSTAMP(28);
      }
      PSTAMP(14);
      const uint32_t stg = H0 + p * 65536 + 28672 + (w >> 1) * 32768 + (w & 1) * 2048;
#pragma unroll
      for (int u = 0; u < 4; u++) {
        uint32_t o[4];
#pragma unroll
        for (int e = 0; e < 4; e++) o[e] = pack2(sum[8 * u + 2 * e] + yb[8 * u + 2 * e], sum[8 * u + 2 * e + 1] + yb[8 * u + 2 * e + 1]);
        stsm4(stg + (moff ^ (u << 5)), o);
      }
      fence_async_smem();
      __syncwarp();
      if (elect_one()) {
        tma3d_store(&P.out, stg, 64 * j, p, g * 64 + 16 * w);
        asm volatile("cp.async.bulk.commit_group;" ::: "memory");
        asm volatile("cp.async.bulk.wait_group.read 0;" ::: "memory");
      }
      PSTAMP(15);
    }
  }
}

typedef CUresult (*EncodeFn)(CUtensorMap*, CUtensorMapDataType, cuuint32_t, void*, const cuuint64_t*, const cuuint64_t*,
                             const cuuint32_t*, const cuuint32_t*, CUtensorMapInterleave, CUtensorMapSwizzle,
                             CUtensorMapL2promotion, CUtensorMapFloatOOBfill);

void enc2d(EncodeFn f, CUtensorMap* m, const void* base, uint64_t cols, uint64_t rows, uint32_t bc, uint32_t br, CUtensorMapSwizzle sw) {
  cuuint64_t gd[2] = {cols, rows}, gs[1] = {cols * 2};
  cuuint32_t bd[2] = {bc, br}, es[2] = {1, 1};
  f(m, CU_TENSOR_MAP_DATA_TYPE_BFLOAT16, 2, const_cast<void*>(base), gd, gs, bd, es, CU_TENSOR_MAP_INTERLEAVE_NONE, sw,
    CU_TENSOR_MAP_L2_PROMOTION_L2_128B, CU_TENSOR_MAP_FLOAT_OOB_FILL_NONE);
}
void enc_par(EncodeFn f, CUtensorMap* m, const void* base, uint32_t pairs) {
  cuuint64_t gd[3] = {(cuuint64_t)D_, 2, (cuuint64_t)S_ / 2}, gs[2] = {D_ * 2, D_ * 4};
  cuuint32_t bd[3] = {64, 1, pairs}, es[3] = {1, 1, 1};
  f(m, CU_TENSOR_MAP_DATA_TYPE_BFLOAT16, 3, const_cast<void*>(base), gd, gs, bd, es, CU_TENSOR_MAP_INTERLEAVE_NONE,
    CU_TENSOR_MAP_SWIZZLE_128B, CU_TENSOR_MAP_L2_PROMOTION_L2_128B, CU_TENSOR_MAP_FLOAT_OOB_FILL_NONE);
}

}

extern "C" void kernel_launch(void* const* d_in, const int* in_sizes, int n_in, void* d_out, int out_size) {
  (void)in_sizes; (void)n_in; (void)out_size;
  static EncodeFn enc = nullptr;
  if (!enc) {
    void* fn = nullptr;
    cudaDriverEntryPointQueryResult q;
    cudaGetDriverEntryPoint("cuTensorMapEncodeTiled", &fn, cudaEnableDefault, &q);
    enc = (EncodeFn)fn;
    cudaFuncSetAttribute(fused_block_kernel, cudaFuncAttributeMaxDynamicSharedMemorySize, SMEM_BYTES);
  }
  Params P;
  P.xp = (const __nv_bfloat16*)d_in[0];
  P.wqkvp = (const __nv_bfloat16*)d_in[1];
  P.wop = (const __nv_bfloat16*)d_in[2];
  P.w1p = (const __nv_bfloat16*)d_in[4];
  P.w3p = (const __nv_bfloat16*)d_in[5];
  P.w2p = (const __nv_bfloat16*)d_in[6];
  enc_par(enc, &P.x, P.xp, 64);
  enc_par(enc, &P.out, d_out, 16);
  enc2d(enc, &P.wqkv, P.wqkvp, 3 * D_, D_, 64, 64, CU_TENSOR_MAP_SWIZZLE_128B);
  enc2d(enc, &P.wo, P.wop, D_, D_, 64, 64, CU_TENSOR_MAP_SWIZZLE_128B);
  enc2d(enc, &P.w1, P.w1p, F_, D_, 64, 64, CU_TENSOR_MAP_SWIZZLE_128B);
  enc2d(enc, &P.w3, P.w3p, F_, D_, 64, 64, CU_TENSOR_MAP_SWIZZLE_128B);
  enc2d(enc, &P.w1h, P.w1p, F_, D_, 32, 64, CU_TENSOR_MAP_SWIZZLE_64B);
  enc2d(enc, &P.w3h, P.w3p, F_, D_, 32, 64, CU_TENSOR_MAP_SWIZZLE_64B);
  enc2d(enc, &P.w2, P.w2p, D_, F_, 64, 224, CU_TENSOR_MAP_SWIZZLE_128B);

  cudaLaunchConfig_t cfg = {};
  cfg.gridDim = dim3(128);
  cfg.blockDim = dim3(384);
  cfg.dynamicSmemBytes = SMEM_BYTES;
  cfg.stream = cudaStreamPerThread;
  cudaLaunchAttribute at[1];
  at[0].id = cudaLaunchAttributeCooperative;
  at[0].val.cooperative = 1;
  cfg.attrs = at;
  cfg.numAttrs = 1;
  cudaLaunchKernelEx(&cfg, fused_block_kernel, P);
}
```

```cpp
#include <cuda_runtime.h>
#include <cuda.h>
#include <cuda_bf16.h>
#include <stdint.h>

namespace {

constexpr int S_ = 2048, D_ = 512, F_ = 1792;
#define LAG_KB 3
#define E4_FIRST 0
#define PP_AHEAD 1
#define XO_DELAY 2

constexpr uint32_t SPIN_LIMIT = 1u << 18;

struct Scratch {
  uint4 e4[16 * 2 * 4 * 8 * 8 * 4 * 32];
  uint4 e2[16 * 2 * 4 * 32 * 32];
  uint4 e3h[16 * 2 * 4 * 32 * 32];
  uint4 e1[16 * 8 * 2 * 4 * 32];
  uint4 e2s[16 * 2 * 4 * 8 * 8];
  uint4 e3s[16 * 2 * 4 * 8 * 8];
  uint4 e0c[8 * 3 * 16 * 16];
  uint4 e0s[2048];
  uint4 e0w[8 * 64];
  unsigned epoch[128];
};
__device__ Scratch g_scratch;
#define PSTAMP(i)
#define PSTAMPW(slot, i)

struct alignas(64) Params {
  CUtensorMap x, out, wqkv, wo, w1, w3, w1h, w3h, w2;
  const __nv_bfloat16 *w1p, *w3p, *w2p;
};

constexpr uint32_t SB = 1024;
constexpr uint32_t H0 = SB;
constexpr uint32_t H1 = SB + 65536;
constexpr uint32_t RING = SB + 131072;
constexpr uint32_t BAR = SB + 229376;
constexpr uint32_t CS = BAR + 1024;
constexpr uint32_t ST = CS + 768;
constexpr uint32_t WB = ST + 1024;
constexpr uint32_t SMEM_BYTES = 232448;
static_assert(WB + 256 <= SB + SMEM_BYTES, "smem");

enum : int {
  B_FX = 0,
  B_FKV = 16, B_FQ = 24, B_FWO = 32, B_FA = 40, B_FB = 48, B_FT = 56,
  B_EKV = 64, B_EQ = 72, B_EA = 80, B_EB = 88, B_ET0 = 96,
  B_WODONE = 97,
  B_EX = 104,
  B_LAG = 112, B_READY = 113, B_PUB = 114, B_CLR = 115
};

__device__ __forceinline__ uint32_t smem_u32(const void* p) { return (uint32_t)__cvta_generic_to_shared(p); }
__device__ __forceinline__ void mbar_init(uint32_t b, uint32_t c) { asm volatile("mbarrier.init.shared::cta.b64 [%0], %1;" ::"r"(b), "r"(c) : "memory"); }
__device__ __forceinline__ void mbar_expect_tx(uint32_t b, uint32_t bytes) { asm volatile("mbarrier.arrive.expect_tx.shared::cta.b64 _, [%0], %1;" ::"r"(b), "r"(bytes) : "memory"); }
__device__ __forceinline__ void mbar_arrive(uint32_t b) { asm volatile("mbarrier.arrive.shared::cta.b64 _, [%0];" ::"r"(b) : "memory"); }
__device__ __forceinline__ void mbar_wait(uint32_t b) {
  asm volatile("{\n.reg .pred p;\n.reg .u32 c;\nmov.u32 c, 0;\nLW:\n.pragma \"nounroll\";\n"
               "mbarrier.try_wait.parity.shared::cta.b64 p, [%0], 0;\nadd.u32 c, c, 1;\nsetp.gt.or.u32 p, c, %1, p;\n@!p bra LW;\n}\n"
               ::"r"(b), "n"(SPIN_LIMIT) : "memory");
}
__device__ __forceinline__ bool elect_one() {
  uint32_t p;
  asm volatile("{\n.reg .pred P;\nelect.sync _|P, 0xffffffff;\nselp.u32 %0, 1, 0, P;\n}\n" : "=r"(p));
  return p;
}
__device__ __forceinline__ void tma2d(uint32_t dst, const CUtensorMap* m, int c0, int c1, uint32_t bar) {
  asm volatile("cp.async.bulk.tensor.2d.shared::cluster.global.mbarrier::complete_tx::bytes [%0], [%1, {%3, %4}], [%2];"
               ::"r"(dst), "l"(m), "r"(bar), "r"(c0), "r"(c1) : "memory");
}
__device__ __forceinline__ void tma3d(uint32_t dst, const CUtensorMap* m, int c0, int c1, int c2, uint32_t bar) {
  asm volatile("cp.async.bulk.tensor.3d.shared::cluster.global.mbarrier::complete_tx::bytes [%0], [%1, {%3, %4, %5}], [%2];"
               ::"r"(dst), "l"(m), "r"(bar), "r"(c0), "r"(c1), "r"(c2) : "memory");
}
__device__ __forceinline__ void tma3d_store(const CUtensorMap* m, uint32_t src, int c0, int c1, int c2) {
  asm volatile("cp.async.bulk.tensor.3d.global.shared::cta.bulk_group [%0, {%2, %3, %4}], [%1];"
               ::"l"(m), "r"(src), "r"(c0), "r"(c1), "r"(c2) : "memory");
}
__device__ __forceinline__ void l2_prefetch(const void* p, uint32_t bytes) {
  asm volatile("cp.async.bulk.prefetch.L2.global [%0], %1;" ::"l"(p), "r"(bytes) : "memory");
}
__device__ __forceinline__ void prefetch_map(const CUtensorMap* m) { asm volatile("prefetch.tensormap [%0];" ::"l"(m) : "memory"); }
__device__ __forceinline__ void fence_async_smem() { asm volatile("fence.proxy.async.shared::cta;" ::: "memory"); }
__device__ __forceinline__ void wg_fence() { asm volatile("wgmma.fence.sync.aligned;" ::: "memory"); }
__device__ __forceinline__ void wg_commit() { asm volatile("wgmma.commit_group.sync.aligned;" ::: "memory"); }
template <int N> __device__ __forceinline__ void wg_wait() { asm volatile("wgmma.wait_group.sync.aligned %0;" ::"n"(N) : "memory"); }
__device__ __forceinline__ void wg_bar(int p) {
  if (p == 0) asm volatile("bar.sync 1, 128;" ::: "memory"); else asm volatile("bar.sync 2, 128;" ::: "memory");
}
constexpr uint32_t DESC_HI128 = (1024 >> 4) | (1u << 30);
constexpr uint32_t DESC_HI64 = (512 >> 4) | (2u << 30);
__device__ __forceinline__ constexpr uint32_t descA(uint32_t addr) { return (addr >> 4) | (1u << 16); }
__device__ __forceinline__ constexpr uint32_t descB(uint32_t addr) { return (addr >> 4) | ((8192u >> 4) << 16); }
__device__ __forceinline__ constexpr uint32_t descBh(uint32_t addr) { return (addr >> 4) | ((4096u >> 4) << 16); }

__device__ __forceinline__ void wgmma_ss_n64(float (&d)[32], uint32_t da, uint32_t db, int sc) {
  asm volatile("{\n.reg .pred p;\n.reg .b64 da, db;\nsetp.ne.b32 p, %34, 0;\nmov.b64 da, {%32, %35};\nmov.b64 db, {%33, %35};\n"
    "wgmma.mma_async.sync.aligned.m64n64k16.f32.bf16.bf16 {%0, %1, %2, %3, %4, %5, %6, %7, %8, %9, %10, %11, %12, %13, %14, %15, %16, %17, %18, %19, %20, %21, %22, %23, %24, %25, %26, %27, %28, %29, %30, %31}, da, db, p, 1, 1, 0, 1;\n}\n"
    : "+f"(d[0]), "+f"(d[1]), "+f"(d[2]), "+f"(d[3]), "+f"(d[4]), "+f"(d[5]), "+f"(d[6]), "+f"(d[7]),
      "+f"(d[8]), "+f"(d[9]), "+f"(d[10]), "+f"(d[11]), "+f"(d[12]), "+f"(d[13]), "+f"(d[14]), "+f"(d[15]),
      "+f"(d[16]), "+f"(d[17]), "+f"(d[18]), "+f"(d[19]), "+f"(d[20]), "+f"(d[21]), "+f"(d[22]), "+f"(d[23]),
      "+f"(d[24]), "+f"(d[25]), "+f"(d[26]), "+f"(d[27]), "+f"(d[28]), "+f"(d[29]), "+f"(d[30]), "+f"(d[31])
    : "r"(da), "r"(db), "r"(sc), "n"(DESC_HI128));
}
__device__ __forceinline__ void wgmma_ss_n128(float (&d)[64], uint32_t da, uint32_t db, int sc) {
  asm volatile("{\n.reg .pred p;\n.reg .b64 da, db;\nsetp.ne.b32 p, %66, 0;\nmov.b64 da, {%64, %67};\nmov.b64 db, {%65, %67};\n"
    "wgmma.mma_async.sync.aligned.m64n128k16.f32.bf16.bf16 {%0, %1, %2, %3, %4, %5, %6, %7, %8, %9, %10, %11, %12, %13, %14, %15, %16, %17, %18, %19, %20, %21, %22, %23, %24, %25, %26, %27, %28, %29, %30, %31, %32, %33, %34, %35, %36, %37, %38, %39, %40, %41, %42, %43, %44, %45, %46, %47, %48, %49, %50, %51, %52, %53, %54, %55, %56, %57, %58, %59, %60, %61, %62, %63}, da, db, p, 1, 1, 0, 1;\n}\n"
    : "+f"(d[0]), "+f"(d[1]), "+f"(d[2]), "+f"(d[3]), "+f"(d[4]), "+f"(d[5]), "+f"(d[6]), "+f"(d[7]),
      "+f"(d[8]), "+f"(d[9]), "+f"(d[10]), "+f"(d[11]), "+f"(d[12]), "+f"(d[13]), "+f"(d[14]), "+f"(d[15]),
      "+f"(d[16]), "+f"(d[17]), "+f"(d[18]), "+f"(d[19]), "+f"(d[20]), "+f"(d[21]), "+f"(d[22]), "+f"(d[23]),
      "+f"(d[24]), "+f"(d[25]), "+f"(d[26]), "+f"(d[27]), "+f"(d[28]), "+f"(d[29]), "+f"(d[30]), "+f"(d[31]),
      "+f"(d[32]), "+f"(d[33]), "+f"(d[34]), "+f"(d[35]), "+f"(d[36]), "+f"(d[37]), "+f"(d[38]), "+f"(d[39]),
      "+f"(d[40]), "+f"(d[41]), "+f"(d[42]), "+f"(d[43]), "+f"(d[44]), "+f"(d[45]), "+f"(d[46]), "+f"(d[47]),
      "+f"(d[48]), "+f"(d[49]), "+f"(d[50]), "+f"(d[51]), "+f"(d[52]), "+f"(d[53]), "+f"(d[54]), "+f"(d[55]),
      "+f"(d[56]), "+f"(d[57]), "+f"(d[58]), "+f"(d[59]), "+f"(d[60]), "+f"(d[61]), "+f"(d[62]), "+f"(d[63])
    : "r"(da), "r"(db), "r"(sc), "n"(DESC_HI128));
}
__device__ __forceinline__ void wgmma_ss_n256(float (&d)[128], uint32_t da, uint32_t db, int sc) {
  asm volatile("{\n.reg .pred p;\n.reg .b64 da, db;\nsetp.ne.b32 p, %130, 0;\nmov.b64 da, {%128, %131};\nmov.b64 db, {%129, %131};\n"
    "wgmma.mma_async.sync.aligned.m64n256k16.f32.bf16.bf16 {%0, %1, %2, %3, %4, %5, %6, %7, %8, %9, %10, %11, %12, %13, %14, %15, %16, %17, %18, %19, %20, %21, %22, %23, %24, %25, %26, %27, %28, %29, %30, %31, %32, %33, %34, %35, %36, %37, %38, %39, %40, %41, %42, %43, %44, %45, %46, %47, %48, %49, %50, %51, %52, %53, %54, %55, %56, %57, %58, %59, %60, %61, %62, %63, %64, %65, %66, %67, %68, %69, %70, %71, %72, %73, %74, %75, %76, %77, %78, %79, %80, %81, %82, %83, %84, %85, %86, %87, %88, %89, %90, %91, %92, %93, %94, %95, %96, %97, %98, %99, %100, %101, %102, %103, %104, %105, %106, %107, %108, %109, %110, %111, %112, %113, %114, %115, %116, %117, %118, %119, %120, %121, %122, %123, %124, %125, %126, %127}, da, db, p, 1, 1, 0, 1;\n}\n"
    : "+f"(d[0]), "+f"(d[1]), "+f"(d[2]), "+f"(d[3]), "+f"(d[4]), "+f"(d[5]), "+f"(d[6]), "+f"(d[7]),
      "+f"(d[8]), "+f"(d[9]), "+f"(d[10]), "+f"(d[11]), "+f"(d[12]), "+f"(d[13]), "+f"(d[14]), "+f"(d[15]),
      "+f"(d[16]), "+f"(d[17]), "+f"(d[18]), "+f"(d[19]), "+f"(d[20]), "+f"(d[21]), "+f"(d[22]), "+f"(d[23]),
      "+f"(d[24]), "+f"(d[25]), "+f"(d[26]), "+f"(d[27]), "+f"(d[28]), "+f"(d[29]), "+f"(d[30]), "+f"(d[31]),
      "+f"(d[32]), "+f"(d[33]), "+f"(d[34]), "+f"(d[35]), "+f"(d[36]), "+f"(d[37]), "+f"(d[38]), "+f"(d[39]),
      "+f"(d[40]), "+f"(d[41]), "+f"(d[42]), "+f"(d[43]), "+f"(d[44]), "+f"(d[45]), "+f"(d[46]), "+f"(d[47]),
      "+f"(d[48]), "+f"(d[49]), "+f"(d[50]), "+f"(d[51]), "+f"(d[52]), "+f"(d[53]), "+f"(d[54]), "+f"(d[55]),
      "+f"(d[56]), "+f"(d[57]), "+f"(d[58]), "+f"(d[59]), "+f"(d[60]), "+f"(d[61]), "+f"(d[62]), "+f"(d[63]),
      "+f"(d[64]), "+f"(d[65]), "+f"(d[66]), "+f"(d[67]), "+f"(d[68]), "+f"(d[69]), "+f"(d[70]), "+f"(d[71]),
      "+f"(d[72]), "+f"(d[73]), "+f"(d[74]), "+f"(d[75]), "+f"(d[76]), "+f"(d[77]), "+f"(d[78]), "+f"(d[79]),
      "+f"(d[80]), "+f"(d[81]), "+f"(d[82]), "+f"(d[83]), "+f"(d[84]), "+f"(d[85]), "+f"(d[86]), "+f"(d[87]),
      "+f"(d[88]), "+f"(d[89]), "+f"(d[90]), "+f"(d[91]), "+f"(d[92]), "+f"(d[93]), "+f"(d[94]), "+f"(d[95]),
      "+f"(d[96]), "+f"(d[97]), "+f"(d[98]), "+f"(d[99]), "+f"(d[100]), "+f"(d[101]), "+f"(d[102]), "+f"(d[103]),
      "+f"(d[104]), "+f"(d[105]), "+f"(d[106]), "+f"(d[107]), "+f"(d[108]), "+f"(d[109]), "+f"(d[110]), "+f"(d[111]),
      "+f"(d[112]), "+f"(d[113]), "+f"(d[114]), "+f"(d[115]), "+f"(d[116]), "+f"(d[117]), "+f"(d[118]), "+f"(d[119]),
      "+f"(d[120]), "+f"(d[121]), "+f"(d[122]), "+f"(d[123]), "+f"(d[124]), "+f"(d[125]), "+f"(d[126]), "+f"(d[127])
    : "r"(da), "r"(db), "r"(sc), "n"(DESC_HI128));
}
template <uint32_t HI = DESC_HI128>
__device__ __forceinline__ void wgmma_rs_n64(float (&d)[32], const uint32_t (&a)[4], uint32_t db, int sc) {
  asm volatile("{\n.reg .pred p;\n.reg .b64 db;\nsetp.ne.b32 p, %37, 0;\nmov.b64 db, {%36, %38};\n"
    "wgmma.mma_async.sync.aligned.m64n64k16.f32.bf16.bf16 {%0, %1, %2, %3, %4, %5, %6, %7, %8, %9, %10, %11, %12, %13, %14, %15, %16, %17, %18, %19, %20, %21, %22, %23, %24, %25, %26, %27, %28, %29, %30, %31}, {%32, %33, %34, %35}, db, p, 1, 1, 1;\n}\n"
    : "+f"(d[0]), "+f"(d[1]), "+f"(d[2]), "+f"(d[3]), "+f"(d[4]), "+f"(d[5]), "+f"(d[6]), "+f"(d[7]),
      "+f"(d[8]), "+f"(d[9]), "+f"(d[10]), "+f"(d[11]), "+f"(d[12]), "+f"(d[13]), "+f"(d[14]), "+f"(d[15]),
      "+f"(d[16]), "+f"(d[17]), "+f"(d[18]), "+f"(d[19]), "+f"(d[20]), "+f"(d[21]), "+f"(d[22]), "+f"(d[23]),
      "+f"(d[24]), "+f"(d[25]), "+f"(d[26]), "+f"(d[27]), "+f"(d[28]), "+f"(d[29]), "+f"(d[30]), "+f"(d[31])
    : "r"(a[0]), "r"(a[1]), "r"(a[2]), "r"(a[3]), "r"(db), "r"(sc), "n"(HI));
}
template <uint32_t HI = DESC_HI128>
__device__ __forceinline__ void wgmma_rs_n128(float (&d)[64], const uint32_t (&a)[4], uint32_t db, int sc) {
  asm volatile("{\n.reg .pred p;\n.reg .b64 db;\nsetp.ne.b32 p, %69, 0;\nmov.b64 db, {%68, %70};\n"
    "wgmma.mma_async.sync.aligned.m64n128k16.f32.bf16.bf16 {%0, %1, %2, %3, %4, %5, %6, %7, %8, %9, %10, %11, %12, %13, %14, %15, %16, %17, %18, %19, %20, %21, %22, %23, %24, %25, %26, %27, %28, %29, %30, %31, %32, %33, %34, %35, %36, %37, %38, %39, %40, %41, %42, %43, %44, %45, %46, %47, %48, %49, %50, %51, %52, %53, %54, %55, %56, %57, %58, %59, %60, %61, %62, %63}, {%64, %65, %66, %67}, db, p, 1, 1, 1;\n}\n"
    : "+f"(d[0]), "+f"(d[1]), "+f"(d[2]), "+f"(d[3]), "+f"(d[4]), "+f"(d[5]), "+f"(d[6]), "+f"(d[7]),
      "+f"(d[8]), "+f"(d[9]), "+f"(d[10]), "+f"(d[11]), "+f"(d[12]), "+f"(d[13]), "+f"(d[14]), "+f"(d[15]),
      "+f"(d[16]), "+f"(d[17]), "+f"(d[18]), "+f"(d[19]), "+f"(d[20]), "+f"(d[21]), "+f"(d[22]), "+f"(d[23]),
      "+f"(d[24]), "+f"(d[25]), "+f"(d[26]), "+f"(d[27]), "+f"(d[28]), "+f"(d[29]), "+f"(d[30]), "+f"(d[31]),
      "+f"(d[32]), "+f"(d[33]), "+f"(d[34]), "+f"(d[35]), "+f"(d[36]), "+f"(d[37]), "+f"(d[38]), "+f"(d[39]),
      "+f"(d[40]), "+f"(d[41]), "+f"(d[42]), "+f"(d[43]), "+f"(d[44]), "+f"(d[45]), "+f"(d[46]), "+f"(d[47]),
      "+f"(d[48]), "+f"(d[49]), "+f"(d[50]), "+f"(d[51]), "+f"(d[52]), "+f"(d[53]), "+f"(d[54]), "+f"(d[55]),
      "+f"(d[56]), "+f"(d[57]), "+f"(d[58]), "+f"(d[59]), "+f"(d[60]), "+f"(d[61]), "+f"(d[62]), "+f"(d[63])
    : "r"(a[0]), "r"(a[1]), "r"(a[2]), "r"(a[3]), "r"(db), "r"(sc), "n"(HI));
}

template <int N> __device__ __forceinline__ void keep(float (&d)[N]) {
#pragma unroll
  for (int i = 0; i < N; i++) asm volatile("" : "+f"(d[i])::"memory");
}

__device__ __forceinline__ void keep(uint32_t (&d)[4]) { asm volatile("" : "+r"(d[0]), "+r"(d[1]), "+r"(d[2]), "+r"(d[3])::"memory"); }
template <int N> __device__ __forceinline__ void keep(uint32_t (&d)[N][4]) {
#pragma unroll
  for (int i = 0; i < N; i++) asm volatile("" : "+r"(d[i][0]), "+r"(d[i][1]), "+r"(d[i][2]), "+r"(d[i][3])::"memory");
}

__device__ __forceinline__ uint32_t pack2(float lo, float hi) {
  uint32_t r;
  asm("cvt.rn.bf16x2.f32 %0, %1, %2;" : "=r"(r) : "f"(hi), "f"(lo));
  return r;
}
__device__ __forceinline__ float bf_lo(uint32_t v) { return __uint_as_float(v << 16); }
__device__ __forceinline__ float bf_hi(uint32_t v) { return __uint_as_float(v & 0xffff0000u); }
__device__ __forceinline__ uint32_t hsub2(uint32_t a, uint32_t b) {
  uint32_t r;
  asm("sub.rn.bf16x2 %0, %1, %2;" : "=r"(r) : "r"(a), "r"(b));
  return r;
}
__device__ __forceinline__ uint32_t movm(uint32_t a) {
  uint32_t r;
  asm volatile("movmatrix.sync.aligned.m8n8.trans.b16 %0, %1;" : "=r"(r) : "r"(a));
  return r;
}
__device__ __forceinline__ void ldsm4(uint32_t (&v)[4], uint32_t a) {
  asm volatile("ldmatrix.sync.aligned.m8n8.x4.shared.b16 {%0,%1,%2,%3}, [%4];" : "=r"(v[0]), "=r"(v[1]), "=r"(v[2]), "=r"(v[3]) : "r"(a) : "memory");
}
__device__ __forceinline__ void stsm4(uint32_t a, const uint32_t (&v)[4]) {
  asm volatile("stmatrix.sync.aligned.m8n8.x4.shared.b16 [%0], {%1,%2,%3,%4};" ::"r"(a), "r"(v[0]), "r"(v[1]), "r"(v[2]), "r"(v[3]) : "memory");
}
__device__ __forceinline__ void mma16816(float (&d)[4], const uint32_t (&a)[4], uint32_t b0, uint32_t b1) {
  asm volatile("mma.sync.aligned.m16n8k16.row.col.f32.bf16.bf16.f32 {%0,%1,%2,%3}, {%4,%5,%6,%7}, {%8,%9}, {%10,%10,%10,%10};"
               : "=f"(d[0]), "=f"(d[1]), "=f"(d[2]), "=f"(d[3])
               : "r"(a[0]), "r"(a[1]), "r"(a[2]), "r"(a[3]), "r"(b0), "r"(b1), "f"(0.f));
}
__device__ __forceinline__ void mma1688_acc(float (&d)[4], uint32_t a0, uint32_t a1, uint32_t b0) {
  asm volatile("mma.sync.aligned.m16n8k8.row.col.f32.bf16.bf16.f32 {%0,%1,%2,%3}, {%4,%5}, {%6}, {%0,%1,%2,%3};"
               : "+f"(d[0]), "+f"(d[1]), "+f"(d[2]), "+f"(d[3]) : "r"(a0), "r"(a1), "r"(b0));
}
__device__ __forceinline__ float ex2(float x) { float y; asm("ex2.approx.ftz.f32 %0, %1;" : "=f"(y) : "f"(x)); return y; }
__device__ __forceinline__ float rcp(float x) { float y; asm("rcp.approx.ftz.f32 %0, %1;" : "=f"(y) : "f"(x)); return y; }
__device__ __forceinline__ float tanhf_hw(float x) { float y; asm("tanh.approx.f32 %0, %1;" : "=f"(y) : "f"(x)); return y; }
__device__ __forceinline__ float2 lds64(uint32_t a) { float2 v; asm volatile("ld.shared.v2.f32 {%0,%1}, [%2];" : "=f"(v.x), "=f"(v.y) : "r"(a) : "memory"); return v; }
__device__ __forceinline__ void lds128(uint32_t (&v)[4], uint32_t a) { asm volatile("ld.shared.v4.u32 {%0,%1,%2,%3}, [%4];" : "=r"(v[0]), "=r"(v[1]), "=r"(v[2]), "=r"(v[3]) : "r"(a) : "memory"); }
__device__ __forceinline__ void sts128(uint32_t a, const uint32_t (&v)[4]) { asm volatile("st.shared.v4.u32 [%0], {%1,%2,%3,%4};" ::"r"(a), "r"(v[0]), "r"(v[1]), "r"(v[2]), "r"(v[3]) : "memory"); }
__device__ __forceinline__ void ldg128_nc(uint32_t (&v)[4], const void* p) {
  asm volatile("ld.global.nc.L1::no_allocate.v4.u32 {%0,%1,%2,%3}, [%4];" : "=r"(v[0]), "=r"(v[1]), "=r"(v[2]), "=r"(v[3]) : "l"(p));
}
__device__ __forceinline__ void pin(uint32_t zero) {
  asm volatile("{\n.reg .pred p;\n.reg .u32 c;\nmov.u32 c, %0;\nLP:\n.pragma \"nounroll\";\nsetp.eq.u32 p, c, 0;\n@p bra LD;\n"
               "nanosleep.u32 c;\nsub.u32 c, c, 1;\nbra LP;\nLD:\n}\n" ::"r"(zero) : "memory");
}
__device__ __forceinline__ uint32_t ld_epoch(const unsigned* p) {
  uint32_t v;
  asm volatile("ld.relaxed.gpu.global.u32 %0, [%1];" : "=r"(v) : "l"(p) : "memory");
  return v;
}
__device__ __forceinline__ void ll_st(uint4* p, uint32_t a, uint32_t b, uint32_t c, uint32_t d, uint32_t tag) {
  asm volatile("{\n.reg .b128 t;\n.reg .b64 lo, hi;\nmov.b64 lo, {%1, %2};\nmov.b64 hi, {%3, %4};\nmov.b128 t, {lo, hi};\n"
               "st.relaxed.gpu.global.b128 [%0], t;\n}\n" ::"l"(p), "r"((a & ~1u) | tag), "r"(b), "r"(c), "r"(d) : "memory");
}
__device__ __forceinline__ void ll_ld(uint32_t (&v)[4], const uint4* p) {
  asm volatile("{\n.reg .b128 t;\n.reg .b64 lo, hi;\nld.relaxed.gpu.global.b128 t, [%4];\nmov.b128 {lo, hi}, t;\n"
               "mov.b64 {%0, %1}, lo;\nmov.b64 {%2, %3}, hi;\n}\n"
               : "=r"(v[0]), "=r"(v[1]), "=r"(v[2]), "=r"(v[3]) : "l"(p) : "memory");
}
template <int N> __device__ __forceinline__ void ll_issue(uint32_t (&v)[N][4], const uint4* p, int stride) {
#pragma unroll
  for (int i = 0; i < N; i++) ll_ld(v[i], p + i * stride);
}
template <int N> __device__ __forceinline__ bool ll_bad(const uint32_t (&v)[N][4], uint32_t tag) {
  uint32_t bad = v[0][0] ^ tag;
#pragma unroll
  for (int i = 1; i < N; i++) bad |= (v[i][0] ^ tag);
  return __any_sync(0xffffffffu, bad & 1u);
}
template <int N> __device__ __forceinline__ void ll_clear(uint32_t (&v)[N][4]) {
#pragma unroll
  for (int i = 0; i < N; i++) v[i][0] &= ~1u;
}
template <int N> __device__ __forceinline__ void ll_spin(uint32_t (&v)[N][4], const uint4* p, int stride, uint32_t tag) {
  uint32_t it = 0;
#pragma unroll 1
  do { ll_issue<N>(v, p, stride); } while (ll_bad<N>(v, tag) && ++it < SPIN_LIMIT);
}
template <int N> __device__ __forceinline__ void ll_get(uint32_t (&v)[N][4], const uint4* p, int stride, uint32_t tag) {
  ll_spin<N>(v, p, stride, tag);
  ll_clear<N>(v);
}
template <int N> __device__ __forceinline__ void ll_wait(uint32_t (&v)[N][4], const uint4* p, int stride, uint32_t tag) {
  if (__builtin_expect(ll_bad<N>(v, tag), 0)) ll_spin<N>(v, p, stride, tag);
  ll_clear<N>(v);
}
__device__ __forceinline__ void unpack32(float (&d)[32], const uint32_t (&v)[4][4]) {
#pragma unroll
  for (int u = 0; u < 4; u++)
#pragma unroll
    for (int e = 0; e < 4; e++) { d[8 * u + 2 * e] = bf_lo(v[u][e]); d[8 * u + 2 * e + 1] = bf_hi(v[u][e]); }
}
__device__ __forceinline__ void pack32(uint32_t (&v)[4][4], const float (&d)[32]) {
#pragma unroll
  for (int u = 0; u < 4; u++)
#pragma unroll
    for (int e = 0; e < 4; e++) v[u][e] = pack2(d[8 * u + 2 * e], d[8 * u + 2 * e + 1]);
}
__device__ __forceinline__ uint32_t t_addr(int m) { return SB + ((0x03514620u >> (4 * m)) & 7u) * 32768u; }

__device__ __forceinline__ int kb_at(int i, int j) { return i == 0 ? j : (i - 1 + (i - 1 >= j ? 1 : 0)); }

__device__ __forceinline__ void init_bars(int set) {
  if (elect_one()) {
    const uint32_t cnt = set < 5 ? 1 : set < 10 ? 8 : 4;
#pragma unroll
    for (int i = 0; i < 8; i++) mbar_init(BAR + (24 + 8 * set + i) * 8, cnt);
    if (set == 10) { mbar_init(BAR + B_LAG * 8, 4); mbar_init(BAR + B_READY * 8, 3); mbar_init(BAR + B_PUB * 8, 4); mbar_init(BAR + B_CLR * 8, 3); }
    asm volatile("fence.mbarrier_init.release.cluster;" ::: "memory");
  }
  __syncwarp();
  asm volatile("bar.arrive 4, 384;" ::: "memory");
  asm volatile("bar.sync 3, 384;" ::: "memory");
}

__global__ void __launch_bounds__(384, 1) fused_block_kernel(Scratch* __restrict__ X, const __nv_bfloat16* __restrict__ xp,
                                                             const __nv_bfloat16* __restrict__ wqkvp, const __nv_bfloat16* __restrict__ wop, const uint32_t zero,
                                                             const __grid_constant__ Params P) {
  extern __shared__ __align__(1024) uint8_t smem_raw[];
  if (smem_u32(smem_raw) != SB) return;
  const int tid = threadIdx.x;
  const int warp = __shfl_sync(0xffffffffu, tid >> 5, 0);
  const int lane = tid & 31;
  const int cta = blockIdx.x;
  const int j = (cta >> 6) * 4 + (cta & 3);
  const int g = (cta & 63) >> 2;

  if (warp >= 8) {
    asm volatile("setmaxnreg.dec.sync.aligned.u32 56;");
    if (warp == 8) {
      PSTAMPW(2, 0);
      const bool leader = elect_one();
      if (leader) {
        prefetch_map(&P.x); prefetch_map(&P.wqkv);
#pragma unroll
        for (int i = 0; i < 24; i++) mbar_init(BAR + i * 8, 1);
        asm volatile("fence.mbarrier_init.release.cluster;" ::: "memory");
      }
      __syncwarp();
      asm volatile("bar.arrive 3, 384;" ::: "memory");
      PSTAMPW(2, 20);
      auto ldx = [&](int p, int kb) {
        const uint32_t b = BAR + (B_FX + p * 8 + kb) * 8;
        mbar_expect_tx(b, 8192);
        tma3d(H0 + p * 65536 + kb * 8192, &P.x, kb * 64, p, g * 64, b);
      };
      auto ldkv = [&](int kb, int slot) {
        const uint32_t b = BAR + (B_FKV + kb) * 8, d = RING + slot * 16384;
        mbar_expect_tx(b, 16384);
        tma2d(d, &P.wqkv, 512 + 64 * j, kb * 64, b);
        tma2d(d + 8192, &P.wqkv, 1024 + 64 * j, kb * 64, b);
      };
      if (leader) {
#pragma unroll 1
        for (int i = 0; i < 8 + XO_DELAY; i++) {
          if (i < 8) ldx(0, i);
          if (i < 6) ldkv(i, i);
          if (i >= XO_DELAY) ldx(1, i - XO_DELAY);
          if (i == 0) PSTAMPW(2, 21);
        }
        PSTAMPW(2, 2);
      }
      __syncwarp();
      asm volatile("bar.sync 4, 384;" ::: "memory");
      if (leader) {
        const int f0 = 224 * j + ((j & 1) ? 32 : 0);
        const int fh = 224 * j + ((j & 1) ? 0 : 192);
        prefetch_map(&P.wo); prefetch_map(&P.w1); prefetch_map(&P.w3); prefetch_map(&P.w1h);
        prefetch_map(&P.w3h); prefetch_map(&P.w2); prefetch_map(&P.out);
#pragma unroll 1
        for (int i = 0; i < 2; i++) { mbar_wait(BAR + (B_EKV + i) * 8); ldkv(6 + i, i); }
#pragma unroll 1
        for (int i = 0; i < 8; i++) {
          const uint32_t b = BAR + (B_FQ + i) * 8;
          mbar_wait(BAR + (B_EKV + 2 + (i >> 1)) * 8);
          mbar_expect_tx(b, 8192);
          tma2d(RING + (4 + i) * 8192, &P.wqkv, 64 * j, i * 64, b);
        }
        mbar_expect_tx(BAR + B_FWO * 8, 65536);
#pragma unroll 1
        for (int i = 0; i < 8; i++) {
          const int kb = (i + 1) & 7;
          mbar_wait(BAR + (B_EX + i) * 8);
          tma2d(H0 + kb * 8192, &P.wo, 64 * j, kb * 64, BAR + B_FWO * 8);
          PSTAMPW(2, 4 + i);
        }
#pragma unroll 1
        for (int i = 0; i < 8; i++) {
          const uint32_t b = BAR + (B_FA + i) * 8, d = RING + (i & 3) * 24576;
          const int k0 = kb_at(i, j) * 64;
          mbar_wait(BAR + (B_EKV + 7 + ((0xCBA98520u >> (4 * i)) & 15)) * 8);
          mbar_expect_tx(b, 24576);
          tma2d(d, &P.w1, f0, k0, b);
          tma2d(d + 8192, &P.w3, f0, k0, b);
          tma2d(d + 16384, &P.w1h, fh, k0, b);
          tma2d(d + 20480, &P.w3h, fh, k0, b);
          PSTAMPW(2, 12 + i);
        }
        uint32_t d = RING;
#pragma unroll 1
        for (int i = 0; i < 8; i++) {
          const uint32_t b = BAR + (B_FB + i) * 8;
          const int k0 = kb_at(i, j) * 64;
          mbar_wait(BAR + (B_EA + 5 + i) * 8);
          mbar_expect_tx(b, 32768);
          tma2d(d, &P.w1, f0 + 64, k0, b);
          tma2d(d + 8192, &P.w3, f0 + 64, k0, b);
          tma2d(d + 16384, &P.w1, f0 + 128, k0, b);
          tma2d(d + 24576, &P.w3, f0 + 128, k0, b);
          d = d == RING + 65536 ? RING : d + 32768;
        }
#pragma unroll 1
        for (int m = 0; m < 8; m++) {
          const uint32_t b = BAR + (B_FT + m) * 8;
          mbar_wait(BAR + (B_EB + (m == 7 ? 8 : min(m + 3, 7))) * 8);
          mbar_expect_tx(b, 28672);
          tma2d(t_addr(m), &P.w2, 64 * ((j + 1 + m) & 7), 224 * j, b);
        }
        X->epoch[cta] = X->epoch[cta] + 1;
      }
    } else {
      const int part = warp - 9;
      init_bars(warp - 1);
      const uint32_t tag = (ld_epoch(X->epoch + cta) + 1) & 1;
      const int xw0 = g * 8;
      auto clear = [&](uint4* p, int n, int stride) {
#pragma unroll 1
        for (int i = part; i < n; i += 3) ll_st(p + i * stride + lane, 0, 0, 0, 0, tag ^ 1);
      };
      clear(X->e1 + (g * 8 + j) * 256, 8, 32);
      if (lane < 8) { clear(X->e2s + (xw0 * 8 + j) * 8, 8, 64); clear(X->e3s + (xw0 * 8 + j) * 8, 8, 64); }
#pragma unroll 1
      for (int u = 0; u < 4; u++) clear(X->e2 + (xw0 * 32 + 4 * j + u) * 32, 8, 1024);
      uint32_t v[8][4];
      mbar_wait(BAR + (B_FKV + 1) * 8);
      {
        const __nv_bfloat16* wr = wqkvp + (size_t)(g * 32 + (lane >> 3) * 8) * (3 * D_) + part * D_ + j * 64 + (lane & 7) * 8;
#pragma unroll
        for (int i = 0; i < 8; i++) ldg128_nc(v[i], wr + (size_t)i * 3 * D_);
      }
#pragma unroll 1
      for (int u = 0; u < 4; u++) clear(X->e3h + (xw0 * 32 + 4 * j + u) * 32, 8, 1024);
      {
        float cs[8];
#pragma unroll
        for (int e = 0; e < 4; e++) {
          float a = 0.f, b = 0.f;
#pragma unroll
          for (int i = 0; i < 8; i++) { a += bf_lo(v[i][e]); b += bf_hi(v[i][e]); }
          cs[2 * e] = a; cs[2 * e + 1] = b;
        }
        const bool up = lane & 8;
#pragma unroll
        for (int e = 0; e < 4; e++) {
          const float keepv = up ? cs[4 + e] : cs[e], give = up ? cs[e] : cs[4 + e];
          cs[e] = keepv + __shfl_xor_sync(0xffffffffu, give, 8);
          cs[e] += __shfl_xor_sync(0xffffffffu, cs[e], 16);
        }
        if (lane < 16)
          ll_st(X->e0c + ((j * 3 + part) * 16 + g) * 16 + (lane & 7) * 2 + (lane >> 3), __float_as_uint(cs[0]), __float_as_uint(cs[1]),
                __float_as_uint(cs[2]), __float_as_uint(cs[3]), tag);
      }
      PSTAMPW(3, part * 4 + 2);
      mbar_wait(BAR + B_PUB * 8);
      PSTAMPW(3, part * 4 + 0);
      {
        uint32_t u[2][4];
        const uint4* us = (part == 2 ? X->e0w + j * 64 : X->e0s + g * 128 + part * 64) + lane;
        const uint4* vs = X->e0c + ((j * 3 + part) * 16 + (lane >> 4) * 8) * 16 + (lane & 15);
        uint32_t it = 0;
#pragma unroll 1
        do { ll_issue<2>(u, us, 32); ll_issue<8>(v, vs, 16); } while ((ll_bad<2>(u, tag) || ll_bad<8>(v, tag)) && ++it < SPIN_LIMIT);
        ll_clear<2>(u); ll_clear<8>(v);
#pragma unroll
        for (int i = 0; i < 2; i++) {
          if (part == 2) asm volatile("st.shared.u32 [%0], %1;" ::"r"(WB + (i * 32 + lane) * 4), "r"(u[i][0]) : "memory");
          else asm volatile("st.shared.v2.u32 [%0], {%1,%2};" ::"r"(ST + (part * 64 + i * 32 + lane) * 8), "r"(u[i][0]), "r"(u[i][1]) : "memory");
        }
      }
      uint32_t o[4];
#pragma unroll
      for (int e = 0; e < 4; e++) {
        float s = 0.f;
#pragma unroll
        for (int i = 0; i < 8; i++) s += __uint_as_float(v[i][e]);
        o[e] = __float_as_uint(s + __shfl_xor_sync(0xffffffffu, s, 16));
      }
      if (lane < 16) sts128(CS + (part * 64 + lane * 4) * 4, o);
      __syncwarp();
      if (lane == 0) mbar_arrive(BAR + B_READY * 8);
      PSTAMPW(3, part * 4 + 1);
      if (lane == 0) l2_prefetch(part == 0 ? P.w1p + (size_t)cta * 4 * F_ : part == 1 ? P.w3p + (size_t)cta * 4 * F_ : P.w2p + (size_t)cta * 14 * D_, 14336);
      mbar_wait(BAR + (B_EA + 1) * 8);
#pragma unroll 1
      for (int m = E4_FIRST; m < 7; m++)
#pragma unroll 1
        for (int u = 0; u < 4; u++) clear(X->e4 + ((size_t)xw0 * 64 + ((j + 1 + m) & 7) * 8 + j) * 128 + u * 32, 8, 8192);
      __syncwarp();
      if (lane == 0) mbar_arrive(BAR + B_CLR * 8);
      PSTAMPW(3, part * 4 + 3);
    }
  } else {
    const int p = warp >> 2, w = warp & 3;
    const int r = lane >> 2, c = lane & 3;
    init_bars(warp);
    uint32_t tag = ld_epoch(X->epoch + cta);
    asm volatile("setmaxnreg.inc.sync.aligned.u32 224;");
    PSTAMP(0);
    const uint32_t dAx = descA(H0) + p * 4096;
    const uint32_t Hn = H1 - p * 65536;
    const uint32_t moff = ((lane & 7) + ((lane >> 3) & 1) * 8) * 128 + (((lane >> 4) ^ (lane & 7)) << 4);
    const uint32_t Xw = H0 + p * 65536 + w * 2048;
    const int xw = (g * 2 + p) * 4 + w;
    uint32_t xs[8][4], ws[2][4];
    const int trow = g * 128 + j * 16 + w * 4 + (lane >> 3);
    if (p == 1) {
      mbar_wait(BAR + B_LAG * 8);
      const __nv_bfloat16* xr = xp + (size_t)trow * D_ + (lane & 7) * 8;
#pragma unroll
      for (int i = 0; i < 8; i++) ldg128_nc(xs[i], xr + i * 64);
#pragma unroll
      for (int i = 0; i < 2; i++) ldg128_nc(ws[i], wop + (size_t)(j * 64 + g * 4 + w) * D_ + i * 256 + lane * 8);
    }

    float akv[64];
#pragma unroll 1
    for (int kb = 0; kb < 8; kb++) {
      mbar_wait(BAR + (B_FX + p * 8 + kb) * 8);
      mbar_wait(BAR + (B_FKV + kb) * 8);
      if (kb == 0) PSTAMP(2);
      const uint32_t da = dAx + kb * 512, db = descB(RING) + (kb < 6 ? kb : kb - 6) * 1024;
      wg_fence();
      wgmma_ss_n128(akv, da, db, kb);
#pragma unroll
      for (int k = 1; k < 4; k++) wgmma_ss_n128(akv, da + k * 2, db + k * 128, 1);
      wg_commit();
      if (kb == LAG_KB - 1 && p == 0 && lane == 0) mbar_arrive(BAR + B_LAG * 8);
      wg_wait<1>();
      if (kb > 0 && lane == 0) mbar_arrive(BAR + (B_EKV + kb - 1) * 8);
      if (kb == 1 && p == 1) {
        PSTAMP(18);
        float s = 0.f, q = 0.f, t = 0.f;
        const float piv = __shfl_sync(0xffffffffu, bf_lo(xs[0][0]), lane & 24);
#pragma unroll
        for (int i = 0; i < 8; i++)
#pragma unroll
          for (int e = 0; e < 4; e++) {
            const float a = bf_lo(xs[i][e]) - piv, b = bf_hi(xs[i][e]) - piv;
            s += a + b; q = fmaf(a, a, q); q = fmaf(b, b, q);
          }
#pragma unroll
        for (int e = 0; e < 8; e++) t += bf_lo(ws[e >> 2][e & 3]) + bf_hi(ws[e >> 2][e & 3]);
#pragma unroll
        for (int o = 1; o <= 4; o <<= 1) { s += __shfl_xor_sync(0xffffffffu, s, o); q += __shfl_xor_sync(0xffffffffu, q, o); }
#pragma unroll
        for (int o = 1; o <= 16; o <<= 1) t += __shfl_xor_sync(0xffffffffu, t, o);
        const float dm = s * (1.f / D_);
        const float rs = rsqrtf(fmaxf(fmaf(-dm, dm, q * (1.f / D_)), 0.f) + 1e-5f);
        const uint32_t tg = (tag + 1) & 1;
        if ((lane & 7) == 0) ll_st(X->e0s + trow, __float_as_uint(piv + dm), __float_as_uint(rs), 0, 0, tg);
        if (lane == 0) {
          ll_st(X->e0w + j * 64 + g * 4 + w, __float_as_uint(t * (1.f / D_)), 0, 0, 0, tg);
          mbar_arrive(BAR + B_PUB * 8);
        }
        PSTAMP(1);
      }
    }
    asm volatile("" : "+r"(tag));
    tag = (tag + 1) & 1;
    uint32_t xres[4][4];
#pragma unroll
    for (int u = 0; u < 4; u++) ldsm4(xres[u], Xw + j * 8192 + (moff ^ (u << 5)));

    float aq[32];
    auto qstep = [&](int kb) {
      mbar_wait(BAR + (B_FQ + kb) * 8);
      const uint32_t da = dAx + kb * 512, db = descB(RING + 32768) + kb * 512;
      wg_fence();
      wgmma_ss_n64(aq, da, db, kb);
#pragma unroll
      for (int k = 1; k < 4; k++) wgmma_ss_n64(aq, da + k * 2, db + k * 128, 1);
      wg_commit();
      wg_wait<1>();
      if (lane == 0) {
        mbar_arrive(BAR + (B_EQ + kb - 1) * 8);
        if (p == 0 && kb >= 2) mbar_arrive(BAR + (B_EX + kb - 2) * 8);
      }
    };
    qstep(0);
    keep(akv);
    PSTAMP(3);
    qstep(1);
    mbar_wait(BAR + B_READY * 8);
    PSTAMP(19);
    const float2 st0 = lds64(ST + (2 * (16 * w + r) + p) * 8);
    const float2 st1 = lds64(ST + (2 * (16 * w + r + 8) + p) * 8);
    uint32_t hi[4][4], lo[4][4];
    {
      float2 cs[16];
      auto cvt = [&](uint32_t (&d)[4][4], int b0, int ofs, const float2& st) {
#pragma unroll
        for (int b = b0; b < b0 + 8; b++) {
          if (ofs == 2) cs[b] = lds64(CS + (64 + b * 8 + 2 * c) * 4);
          const uint32_t v = pack2(fmaf(-st.x, cs[b].x, akv[4 * b + ofs]) * st.y, fmaf(-st.x, cs[b].y, akv[4 * b + ofs + 1]) * st.y);
          d[b >> 2][b & 3] = b < 8 ? v : movm(v);
        }
      };
      cvt(hi, 0, 2, st1);
      keep(hi[0]); keep(hi[1]);
      qstep(2);
      cvt(hi, 8, 2, st1);
      if (w == 3 && g < 15) {
        uint4* dst = X->e1 + ((g * 8 + j) * 2 + p) * 128 + lane;
#pragma unroll
        for (int i = 0; i < 4; i++) ll_st(dst + i * 32, hi[i][0], hi[i][1], hi[i][2], hi[i][3], tag);
      }
      wg_bar(p);
#pragma unroll
      for (int i = 0; i < 4; i++) sts128(Xw + lane * 16 + i * 512, hi[i]);
      qstep(3);
      cvt(lo, 0, 0, st0);
      keep(lo[0]); keep(lo[1]);
      qstep(4);
      cvt(lo, 8, 0, st0);
    }
    wg_bar(p);
    uint32_t prev[4][4];
    if (w > 0) {
#pragma unroll
      for (int i = 0; i < 4; i++) lds128(prev[i], Xw - 2048 + lane * 16 + i * 512);
    }
    if (p == 0) {
      asm volatile("fence.proxy.async.shared::cta;" ::: "memory");
      __syncwarp();
      if (lane == 0) mbar_arrive(BAR + (B_EX + 7) * 8);
    }
#pragma unroll 1
    for (int kb = 5; kb < 8; kb++) qstep(kb);
    if (w == 0) {
      if (g > 0) {
        ll_get<4>(prev, X->e1 + (((g - 1) * 8 + j) * 2 + p) * 128 + lane, 32, tag);
      } else {
#pragma unroll
        for (int i = 0; i < 4; i++)
#pragma unroll
          for (int e = 0; e < 4; e++) prev[i][e] = 0;
      }
    }
    wg_wait<0>();
    keep(aq);
    if (lane == 0) { mbar_arrive(BAR + (B_EQ + 7) * 8); if (p == 0) mbar_arrive(BAR + (B_EX + 6) * 8); }
    PSTAMP(4);

    uint32_t of[4][4];
    {
      const float sc = 0.25f * 1.4426950408889634f;
      const float nohalo = (g == 0 && w == 0) ? -INFINITY : 0.f;
      const bool up0 = 2 * c > r, up1 = 2 * c + 1 > r;
      const uint32_t mup = (up0 ? 0xffffu : 0u) | (up1 ? 0xffff0000u : 0u);
      uint4* dst = X->e2 + (xw * 32 + 4 * j) * 32 + lane;
      float d0 = 0.f, d1 = 0.f;
#pragma unroll 1
      for (int hp = 0; hp < 2; hp++) {
#pragma unroll
        for (int e = 0; e < 4; e++) { of[0][e] = of[2][e]; of[1][e] = of[3][e]; }
#pragma unroll
        for (int h = 0; h < 2; h++) {
          uint32_t qf[4];
          const uint32_t co = (32 * hp + 16 * h + 2 * c) * 4;
          {
            const float2 ca = lds64(CS + co), cb = lds64(CS + co + 32);
            qf[0] = pack2(fmaf(-st0.x, ca.x, aq[8 * h + 0]) * st0.y, fmaf(-st0.x, ca.y, aq[8 * h + 1]) * st0.y);
            qf[1] = pack2(fmaf(-st1.x, ca.x, aq[8 * h + 2]) * st1.y, fmaf(-st1.x, ca.y, aq[8 * h + 3]) * st1.y);
            qf[2] = pack2(fmaf(-st0.x, cb.x, aq[8 * h + 4]) * st0.y, fmaf(-st0.x, cb.y, aq[8 * h + 5]) * st0.y);
            qf[3] = pack2(fmaf(-st1.x, cb.x, aq[8 * h + 6]) * st1.y, fmaf(-st1.x, cb.y, aq[8 * h + 7]) * st1.y);
          }
          const int e0 = 2 * h;
          float sp[4], sl[4], sh[4];
          mma16816(sp, qf, prev[0][e0], prev[0][e0 + 1]);
          mma16816(sl, qf, lo[0][e0], lo[0][e0 + 1]);
          mma16816(sh, qf, hi[0][e0], hi[0][e0 + 1]);
          float a0 = up0 ? sp[0] + nohalo : sl[0], a1 = up1 ? sp[1] + nohalo : sl[1];
          float b0 = up0 ? sl[2] : sh[2], b1 = up1 ? sl[3] : sh[3];
          float ma = fmaxf(a0, a1), mb = fmaxf(b0, b1);
          ma = fmaxf(ma, __shfl_xor_sync(0xffffffffu, ma, 1)); mb = fmaxf(mb, __shfl_xor_sync(0xffffffffu, mb, 1));
          ma = fmaxf(ma, __shfl_xor_sync(0xffffffffu, ma, 2)); mb = fmaxf(mb, __shfl_xor_sync(0xffffffffu, mb, 2));
          a0 = ex2((a0 - ma) * sc); a1 = ex2((a1 - ma) * sc); b0 = ex2((b0 - mb) * sc); b1 = ex2((b1 - mb) * sc);
          float sa = a0 + a1, sbb = b0 + b1;
          sa += __shfl_xor_sync(0xffffffffu, sa, 1); sbb += __shfl_xor_sync(0xffffffffu, sbb, 1);
          sa += __shfl_xor_sync(0xffffffffu, sa, 2); sbb += __shfl_xor_sync(0xffffffffu, sbb, 2);
          const float ia = rcp(sa), ib = rcp(sbb);
          const uint32_t pa = pack2(a0 * ia, a1 * ia), pb = pack2(b0 * ib, b1 * ib);
          const uint32_t pf[4] = {pa & mup, 0u, pa & ~mup, pb & mup};
          const uint32_t ph = pb & ~mup;
          float o0[4], o1[4];
          mma16816(o0, pf, prev[2][e0], lo[2][e0]);
          mma16816(o1, pf, prev[2][e0 + 1], lo[2][e0 + 1]);
          mma1688_acc(o0, 0u, ph, hi[2][e0]);
          mma1688_acc(o1, 0u, ph, hi[2][e0 + 1]);
          of[2 + h][0] = pack2(o0[0], o0[1]); of[2 + h][1] = pack2(o0[2], o0[3]);
          of[2 + h][2] = pack2(o1[0], o1[1]); of[2 + h][3] = pack2(o1[2], o1[3]);
          ll_st(dst + (2 * hp + h) * 32, of[2 + h][0], of[2 + h][1], of[2 + h][2], of[2 + h][3], tag);
          const float2 wa = lds64(WB + co), wb = lds64(WB + co + 32);
          d0 = fmaf(o0[0], wa.x, d0); d0 = fmaf(o0[1], wa.y, d0); d0 = fmaf(o1[0], wb.x, d0); d0 = fmaf(o1[1], wb.y, d0);
          d1 = fmaf(o0[2], wa.x, d1); d1 = fmaf(o0[3], wa.y, d1); d1 = fmaf(o1[2], wb.x, d1); d1 = fmaf(o1[3], wb.y, d1);
        }
#pragma unroll
        for (int e = 0; e < 16; e++) aq[e] = aq[16 + e];
#pragma unroll
        for (int e = 0; e < 4; e++) {
          prev[0][e] = prev[1][e]; prev[2][e] = prev[3][e];
          lo[0][e] = lo[1][e]; lo[2][e] = lo[3][e];
          hi[0][e] = hi[1][e]; hi[2][e] = hi[3][e];
        }
      }
#pragma unroll
      for (int o = 1; o <= 2; o <<= 1) { d0 += __shfl_xor_sync(0xffffffffu, d0, o); d1 += __shfl_xor_sync(0xffffffffu, d1, o); }
      if (c == 0) ll_st(X->e2s + (xw * 8 + j) * 8 + r, __float_as_uint(d0), __float_as_uint(d1), 0, 0, tag);
    }
    PSTAMP(5);

    float ah[32];
    uint32_t sv[2][4];
    unpack32(ah, xres);
    {
      uint32_t og[2][14][4];
      const uint4* osrc[7];
#pragma unroll
      for (int i = 0; i < 7; i++) osrc[i] = X->e2 + (xw * 32 + 4 * kb_at(i + 1, j)) * 32 + lane;
      const uint4* ssrc = X->e2s + (xw * 8 + 2 * c) * 8 + r;
      auto oissue = [&](int hp) {
#pragma unroll
        for (int i = 0; i < 14; i++) ll_ld(og[hp][i], osrc[i >> 1] + (2 * hp + (i & 1)) * 32);
        if (hp == 1) ll_issue<2>(sv, ssrc, 8);
      };
      auto omma = [&](int hp) {
        ll_clear<14>(og[hp]);
        keep(og[hp]);
        wg_fence();
#pragma unroll
        for (int i = 0; i < 14; i++) wgmma_rs_n64(ah, og[hp][i], descB(H0) + kb_at((i >> 1) + 1, j) * 512 + (2 * hp + (i & 1)) * 128, 1);
        wg_commit();
      };
      mbar_wait(BAR + B_FWO * 8);
      keep(ah); keep(of);
      wg_fence();
#pragma unroll
      for (int k = 0; k < 4; k++) wgmma_rs_n64(ah, of[k], descB(H0) + j * 512 + k * 128, 1);
      wg_commit();
      uint32_t it = 0;
#pragma unroll 1
      do { oissue(0); } while (ll_bad<14>(og[0], tag) && ++it < SPIN_LIMIT);
      PSTAMP(6);
      oissue(1);
      omma(0);
      pin(zero);
      if (__builtin_expect(ll_bad<14>(og[1], tag) || ll_bad<2>(sv, tag), 0)) {
#pragma unroll 1
        do { oissue(1); } while ((ll_bad<14>(og[1], tag) || ll_bad<2>(sv, tag)) && ++it < SPIN_LIMIT);
      }
      PSTAMP(16);
      omma(1);
      ll_clear<2>(sv);
    }
    float m0 = __uint_as_float(sv[0][0]) + __uint_as_float(sv[1][0]), m1 = __uint_as_float(sv[0][1]) + __uint_as_float(sv[1][1]);
#pragma unroll
    for (int o = 1; o <= 2; o <<= 1) { m0 += __shfl_xor_sync(0xffffffffu, m0, o); m1 += __shfl_xor_sync(0xffffffffu, m1, o); }
    const uint32_t mu0 = pack2(m0 + st0.x, m0 + st0.x), mu1 = pack2(m1 + st1.x, m1 + st1.x);
    wg_wait<0>();
    keep(ah);
    if (lane == 0) mbar_arrive(BAR + B_WODONE * 8);
    PSTAMP(7);

    uint32_t hf[4][4], ra[4][4];
    pack32(hf, ah);
    {
      uint4* dst = X->e3h + (xw * 32 + 4 * j) * 32 + lane;
#pragma unroll
      for (int u = 0; u < 4; u++) {
        ra[u][0] = hsub2(hf[u][0], mu0); ra[u][1] = hsub2(hf[u][1], mu1);
        ra[u][2] = hsub2(hf[u][2], mu0); ra[u][3] = hsub2(hf[u][3], mu1);
        ll_st(dst + u * 32, ra[u][0], ra[u][1], ra[u][2], ra[u][3], tag);
      }
      float s0 = 0.f, q0 = 0.f, s1 = 0.f, q1 = 0.f;
#pragma unroll
      for (int b = 0; b < 8; b++) {
        s0 += ah[4 * b] + ah[4 * b + 1]; s1 += ah[4 * b + 2] + ah[4 * b + 3];
        q0 = fmaf(ah[4 * b], ah[4 * b], q0); q0 = fmaf(ah[4 * b + 1], ah[4 * b + 1], q0);
        q1 = fmaf(ah[4 * b + 2], ah[4 * b + 2], q1); q1 = fmaf(ah[4 * b + 3], ah[4 * b + 3], q1);
      }
#pragma unroll
      for (int o = 1; o <= 2; o <<= 1) {
        s0 += __shfl_xor_sync(0xffffffffu, s0, o); q0 += __shfl_xor_sync(0xffffffffu, q0, o);
        s1 += __shfl_xor_sync(0xffffffffu, s1, o); q1 += __shfl_xor_sync(0xffffffffu, q1, o);
      }
      if (c == 0) ll_st(X->e3s + (xw * 8 + j) * 8 + r, __float_as_uint(s0), __float_as_uint(q0), __float_as_uint(s1), __float_as_uint(q1), tag);
      mbar_wait(BAR + (p == 0 ? B_EQ + 7 : B_WODONE) * 8);
    }
    PSTAMP(8);

    float rs0, rs1;
    auto swiglu = [&](float g0, float g1, float u0, float u1, float rs) -> uint32_t {
      const float hr = 0.5f * rs;
      const float x0 = g0 * hr, x1 = g1 * hr;
      const float t0 = tanhf_hw(x0), t1 = tanhf_hw(x1);
      return pack2(fmaf(x0, t0, x0) * (u0 * rs), fmaf(x1, t1, x1) * (u1 * rs));
    };
    uint32_t hA[6][4];
    {
      float a1[64], a2[32];
      const uint4* src = X->e3h + xw * 32 * 32 + lane;
      uint32_t rb[4][4], rc[4][4], rd[4][4];
      auto fetch = [&](uint32_t (&a)[4][4], int i) { ll_issue<4>(a, src + kb_at(i, j) * 128, 32); };
      auto check = [&](uint32_t (&a)[4][4], uint32_t (&b)[4][4], int i) {
        if (__builtin_expect(ll_bad<4>(a, tag) || ll_bad<4>(b, tag), 0)) {
          uint32_t it = 0;
#pragma unroll 1
          do { fetch(a, i); fetch(b, i + 1); } while ((ll_bad<4>(a, tag) || ll_bad<4>(b, tag)) && ++it < SPIN_LIMIT);
        }
        ll_clear<4>(a); ll_clear<4>(b);
        keep(a); keep(b);
      };
      auto head = [&](uint32_t (&a)[4][4], int i) {
        mbar_wait(BAR + (B_FA + i) * 8);
        wg_fence();
        wgmma_rs_n64<DESC_HI64>(a2, a[0], descBh(RING + 16384) + (i & 3) * 1536, i);
        wgmma_rs_n128(a1, a[0], descB(RING) + (i & 3) * 1536, i);
        wg_commit();
#pragma unroll
        for (int u = 0; u < 4; u++) stsm4(Hn + w * 2048 + i * 8192 + (moff ^ (u << 5)), a[u]);
        wg_wait<1>();
        if (i > 0 && lane == 0) mbar_arrive(BAR + (B_EA + i - 1) * 8);
      };
      auto rest = [&](uint32_t (&a)[4][4], int i) {
        wg_fence();
#pragma unroll
        for (int k = 1; k < 4; k++) {
          wgmma_rs_n64<DESC_HI64>(a2, a[k], descBh(RING + 16384) + (i & 3) * 1536 + k * 64, 1);
          wgmma_rs_n128(a1, a[k], descB(RING) + (i & 3) * 1536 + k * 128, 1);
        }
        wg_commit();
      };
      ll_clear<4>(ra);
      keep(ra);
      head(ra, 0); rest(ra, 0);
      ll_get<4>(rb, src + kb_at(1, j) * 128, 32, tag);
      keep(rb);
      PSTAMP(17);
      fetch(rc, 2); fetch(rd, 3);
#pragma unroll 1
      for (int i = 0; i < 8; i += 4) {
        if (i) { head(ra, i); fetch(rc, i + 2); fetch(rd, i + 3); rest(ra, i); }
        head(rb, i + 1); rest(rb, i + 1);
        pin(zero);
        check(rc, rd, i + 2);
        head(rc, i + 2);
        if (i == 0) { fetch(ra, 4); fetch(rb, 5); } else ll_issue<2>(sv, X->e3s + (xw * 8 + 2 * c) * 8 + r, 8);
        rest(rc, i + 2);
        head(rd, i + 3); rest(rd, i + 3);
        pin(zero);
        if (i == 0) check(ra, rb, 4);
      }
      fence_async_smem();
      ll_wait<2>(sv, X->e3s + (xw * 8 + 2 * c) * 8 + r, 8, tag);
      float s0 = __uint_as_float(sv[0][0]) + __uint_as_float(sv[1][0]), q0 = __uint_as_float(sv[0][1]) + __uint_as_float(sv[1][1]);
      float s1 = __uint_as_float(sv[0][2]) + __uint_as_float(sv[1][2]), q1 = __uint_as_float(sv[0][3]) + __uint_as_float(sv[1][3]);
#pragma unroll
      for (int o = 1; o <= 2; o <<= 1) {
        s0 += __shfl_xor_sync(0xffffffffu, s0, o); q0 += __shfl_xor_sync(0xffffffffu, q0, o);
        s1 += __shfl_xor_sync(0xffffffffu, s1, o); q1 += __shfl_xor_sync(0xffffffffu, q1, o);
      }
      s0 *= 1.f / D_; s1 *= 1.f / D_;
      rs0 = rsqrtf(fmaxf(fmaf(-s0, s0, q0 * (1.f / D_)), 0.f) + 1e-5f);
      rs1 = rsqrtf(fmaxf(fmaf(-s1, s1, q1 * (1.f / D_)), 0.f) + 1e-5f);
      wg_wait<0>();
      keep(a1); keep(a2);
      if (lane == 0) mbar_arrive(BAR + (B_EA + 7) * 8);
      PSTAMP(9);
#pragma unroll
      for (int u = 0; u < 4; u++)
#pragma unroll
        for (int e = 0; e < 4; e++)
          hA[u][e] = swiglu(a1[8 * u + 2 * e], a1[8 * u + 2 * e + 1], a1[32 + 8 * u + 2 * e], a1[33 + 8 * u + 2 * e], (e & 1) ? rs1 : rs0);
#pragma unroll
      for (int u = 0; u < 2; u++)
#pragma unroll
        for (int e = 0; e < 4; e++)
          hA[4 + u][e] = swiglu(a2[8 * u + 2 * e], a2[8 * u + 2 * e + 1], a2[16 + 8 * u + 2 * e], a2[17 + 8 * u + 2 * e], (e & 1) ? rs1 : rs0);
      keep(hA);
      wg_bar(p);
    }
    PSTAMP(10);

    uint32_t hB[8][4];
    {
      float ab[128];
      uint32_t db = descB(RING);
      const uint32_t dAn = descA(H1) - p * 4096;
#pragma unroll 1
      for (int i = 0; i < 8; i++) {
        mbar_wait(BAR + (B_FB + i) * 8);
        const uint32_t da = dAn + i * 512;
        wg_fence();
        wgmma_ss_n256(ab, da, db, i);
#pragma unroll
        for (int k = 1; k < 4; k++) wgmma_ss_n256(ab, da + k * 2, db + k * 128, 1);
        wg_commit();
        wg_wait<1>();
        if (i > 0 && lane == 0) mbar_arrive(BAR + (B_EB + i - 1) * 8);
        db = db == descB(RING + 65536) ? descB(RING) : db + 2048;
      }
      wg_wait<0>();
      keep(ab);
      if (lane == 0) mbar_arrive(BAR + (B_EB + 7) * 8);
      PSTAMP(11);
#pragma unroll
      for (int u = 0; u < 8; u++) {
        const int o = (u >> 2) * 64 + (u & 3) * 8;
#pragma unroll
        for (int e = 0; e < 4; e++)
          hB[u][e] = swiglu(ab[o + 2 * e], ab[o + 2 * e + 1], ab[o + 32 + 2 * e], ab[o + 33 + 2 * e], (e & 1) ? rs1 : rs0);
      }
      keep(hB);
    }
    PSTAMP(12);

    {
      float y[32], sum[32];
      unpack32(sum, hf);
      const uint32_t offA = (j & 1) ? 256 : 0, offH = (j & 1) ? 0 : 1536;
      uint4* e4 = X->e4 + (size_t)xw * 64 * 128 + lane;
      uint32_t in[4][4];
#pragma unroll
      for (int u = 0; u < 4; u++) { in[u][0] = tag; in[u][1] = 0; in[u][2] = 0; in[u][3] = 0; }
      auto insrc = [&](int q) { return e4 + (j * 8 + ((j - 1 - q) & 7)) * 128; };
      mbar_wait(BAR + B_CLR * 8);
#pragma unroll 1
      for (int m = 0; m < 9; m++) {
        if (m < 8) {
          mbar_wait(BAR + (B_FT + m) * 8);
          const uint32_t T = descB(0) + (t_addr(m) >> 4);
          if (p == 0) { if (m > PP_AHEAD) asm volatile("bar.sync 6, 256;" ::: "memory"); }
          else if (m + PP_AHEAD < 8) asm volatile("bar.sync 7, 256;" ::: "memory");
          wg_fence();
#pragma unroll
          for (int k = 0; k < 4; k++) wgmma_rs_n64(y, hA[k], T + offA + k * 128, k);
#pragma unroll
          for (int k = 0; k < 2; k++) wgmma_rs_n64(y, hA[4 + k], T + offH + k * 128, 1);
#pragma unroll
          for (int k = 0; k < 8; k++) wgmma_rs_n64(y, hB[k], T + offA + 512 + k * 128, 1);
          wg_commit();
          if (p == 0) { if (m >= PP_AHEAD) asm volatile("bar.arrive 7, 256;" ::: "memory"); }
          else if (m + PP_AHEAD < 7) asm volatile("bar.arrive 6, 256;" ::: "memory");
          wg_wait<0>();
          keep(y);
          if (m == 0 && lane == 0) mbar_arrive(BAR + B_ET0 * 8);
          if (m < 7) {
            uint4* dst = e4 + (((j + 1 + m) & 7) * 8 + j) * 128;
            uint32_t pk[4][4];
            pack32(pk, y);
#pragma unroll
            for (int u = 0; u < 4; u++) ll_st(dst + u * 32, pk[u][0], pk[u][1], pk[u][2], pk[u][3], tag);
          }
        }
        if (m == 7) PSTAMP(13);
        if (m == 1) PSTAMP(27);
        if (m == 3) PSTAMP(26);
        if (m == 5) PSTAMP(28);
        if (__builtin_expect(ll_bad<4>(in, tag), 0)) ll_spin<4>(in, insrc(m - 2), 32, tag);
#pragma unroll
        for (int u = 0; u < 4; u++) {
          sum[8 * u] += bf_lo(in[u][0] & ~1u); sum[8 * u + 1] += bf_hi(in[u][0]);
#pragma unroll
          for (int e = 1; e < 4; e++) { sum[8 * u + 2 * e] += bf_lo(in[u][e]); sum[8 * u + 2 * e + 1] += bf_hi(in[u][e]); }
        }
        keep(sum);
        if (m >= 1 && m < 8) ll_issue<4>(in, insrc(m - 1), 32);
      }
      PSTAMP(14);
      const uint32_t stg = H0 + p * 65536 + 28672 + (w >> 1) * 32768 + (w & 1) * 2048;
#pragma unroll
      for (int u = 0; u < 4; u++) {
        uint32_t o[4];
#pragma unroll
        for (int e = 0; e < 4; e++) o[e] = pack2(sum[8 * u + 2 * e] + y[8 * u + 2 * e], sum[8 * u + 2 * e + 1] + y[8 * u + 2 * e + 1]);
        stsm4(stg + (moff ^ (u << 5)), o);
      }
      fence_async_smem();
      __syncwarp();
      if (elect_one()) {
        tma3d_store(&P.out, stg, 64 * j, p, g * 64 + 16 * w);
        asm volatile("cp.async.bulk.commit_group;" ::: "memory");
        asm volatile("cp.async.bulk.wait_group.read 0;" ::: "memory");
      }
      PSTAMP(15);
    }
  }
}

typedef CUresult (*EncodeFn)(CUtensorMap*, CUtensorMapDataType, cuuint32_t, void*, const cuuint64_t*, const cuuint64_t*,
                             const cuuint32_t*, const cuuint32_t*, CUtensorMapInterleave, CUtensorMapSwizzle,
                             CUtensorMapL2promotion, CUtensorMapFloatOOBfill);

void enc2d(EncodeFn f, CUtensorMap* m, const void* base, uint64_t cols, uint64_t rows, uint32_t bc, uint32_t br, CUtensorMapSwizzle sw) {
  cuuint64_t gd[2] = {cols, rows}, gs[1] = {cols * 2};
  cuuint32_t bd[2] = {bc, br}, es[2] = {1, 1};
  f(m, CU_TENSOR_MAP_DATA_TYPE_BFLOAT16, 2, const_cast<void*>(base), gd, gs, bd, es, CU_TENSOR_MAP_INTERLEAVE_NONE, sw,
    CU_TENSOR_MAP_L2_PROMOTION_L2_128B, CU_TENSOR_MAP_FLOAT_OOB_FILL_NONE);
}
void enc_par(EncodeFn f, CUtensorMap* m, const void* base, uint32_t pairs) {
  cuuint64_t gd[3] = {(cuuint64_t)D_, 2, (cuuint64_t)S_ / 2}, gs[2] = {D_ * 2, D_ * 4};
  cuuint32_t bd[3] = {64, 1, pairs}, es[3] = {1, 1, 1};
  f(m, CU_TENSOR_MAP_DATA_TYPE_BFLOAT16, 3, const_cast<void*>(base), gd, gs, bd, es, CU_TENSOR_MAP_INTERLEAVE_NONE,
    CU_TENSOR_MAP_SWIZZLE_128B, CU_TENSOR_MAP_L2_PROMOTION_L2_128B, CU_TENSOR_MAP_FLOAT_OOB_FILL_NONE);
}

}

extern "C" void kernel_launch(void* const* d_in, const int* in_sizes, int n_in, void* d_out, int out_size) {
  (void)in_sizes; (void)n_in; (void)out_size;
  static EncodeFn enc = nullptr;
  static Scratch* scratch = nullptr;
  if (!enc) {
    void* fn = nullptr;
    cudaDriverEntryPointQueryResult q;
    cudaGetDriverEntryPoint("cuTensorMapEncodeTiled", &fn, cudaEnableDefault, &q);
    enc = (EncodeFn)fn;
    cudaGetSymbolAddress((void**)&scratch, g_scratch);
    cudaFuncSetAttribute(fused_block_kernel, cudaFuncAttributeMaxDynamicSharedMemorySize, SMEM_BYTES);
  }
  Params P;
  const __nv_bfloat16* xp = (const __nv_bfloat16*)d_in[0];
  const __nv_bfloat16* wqkvp = (const __nv_bfloat16*)d_in[1];
  const __nv_bfloat16* wop = (const __nv_bfloat16*)d_in[2];
  P.w1p = (const __nv_bfloat16*)d_in[4];
  P.w3p = (const __nv_bfloat16*)d_in[5];
  P.w2p = (const __nv_bfloat16*)d_in[6];
  enc_par(enc, &P.x, xp, 64);
  enc_par(enc, &P.out, d_out, 16);
  enc2d(enc, &P.wqkv, wqkvp, 3 * D_, D_, 64, 64, CU_TENSOR_MAP_SWIZZLE_128B);
  enc2d(enc, &P.wo, wop, D_, D_, 64, 64, CU_TENSOR_MAP_SWIZZLE_128B);
  enc2d(enc, &P.w1, P.w1p, F_, D_, 64, 64, CU_TENSOR_MAP_SWIZZLE_128B);
  enc2d(enc, &P.w3, P.w3p, F_, D_, 64, 64, CU_TENSOR_MAP_SWIZZLE_128B);
  enc2d(enc, &P.w1h, P.w1p, F_, D_, 32, 64, CU_TENSOR_MAP_SWIZZLE_64B);
  enc2d(enc, &P.w3h, P.w3p, F_, D_, 32, 64, CU_TENSOR_MAP_SWIZZLE_64B);
  enc2d(enc, &P.w2, P.w2p, D_, F_, 64, 224, CU_TENSOR_MAP_SWIZZLE_128B);

  cudaLaunchConfig_t cfg = {};
  cfg.gridDim = dim3(128);
  cfg.blockDim = dim3(384);
  cfg.dynamicSmemBytes = SMEM_BYTES;
  cfg.stream = cudaStreamPerThread;
  cudaLaunchAttribute at[1];
  at[0].id = cudaLaunchAttributeCooperative;
  at[0].val.cooperative = 1;
  cfg.attrs = at;
  cfg.numAttrs = 1;
  cudaLaunchKernelEx(&cfg, fused_block_kernel, scratch, xp, wqkvp, wop, 0u, P);
}
```

```cpp
#include <cuda_runtime.h>
#include <cuda.h>
#include <cuda_bf16.h>
#include <stdint.h>

namespace {

constexpr int S_ = 2048, D_ = 512, F_ = 1792;
#define LAG_KB 3
#define E4_FIRST 0
#define PP_AHEAD 1
#define SIDE_KB 1
#define XO_DELAY 2

constexpr uint32_t SPIN_LIMIT = 1u << 18;

struct Scratch {
  uint4 e4[16 * 2 * 4 * 8 * 8 * 4 * 32];
  uint4 e2[16 * 2 * 4 * 32 * 32];
  uint4 e3h[16 * 2 * 4 * 32 * 32];
  uint4 e1[16 * 8 * 2 * 4 * 32];
  uint4 e2s[16 * 2 * 4 * 8 * 8];
  uint4 e3s[16 * 2 * 4 * 8 * 8];
  uint4 e0c[8 * 3 * 16 * 16];
  uint4 e0s[2048];
  uint4 e0w[8 * 64];
  unsigned epoch[128];
};
__device__ Scratch g_scratch;
#define PSTAMP(i)
#define PSTAMPW(slot, i)

struct alignas(64) Params {
  CUtensorMap x, out, wqkv, wo, w1, w3, w1h, w3h, w2;
  const __nv_bfloat16 *w1p, *w3p, *w2p;
};

constexpr uint32_t SB = 1024;
constexpr uint32_t H0 = SB;
constexpr uint32_t H1 = SB + 65536;
constexpr uint32_t RING = SB + 131072;
constexpr uint32_t BAR = SB + 229376;
constexpr uint32_t TAGS = BAR + 1016;
constexpr uint32_t CS = BAR + 1024;
constexpr uint32_t ST = CS + 768;
constexpr uint32_t WB = ST + 1024;
constexpr uint32_t SMEM_BYTES = 232448;
static_assert(WB + 256 <= SB + SMEM_BYTES, "smem");

enum : int {
  B_FX = 0,
  B_FKV = 16, B_FQ = 24, B_FWO = 32, B_FA = 40, B_FB = 48, B_FT = 56,
  B_EKV = 64, B_EQ = 72, B_EA = 80, B_EB = 88, B_ET0 = 96,
  B_WODONE = 97,
  B_EX = 104,
  B_LAG = 112, B_READY = 113, B_PUB = 114, B_CLR = 115, B_TAG = 116
};

__device__ __forceinline__ uint32_t smem_u32(const void* p) { return (uint32_t)__cvta_generic_to_shared(p); }
__device__ __forceinline__ void mbar_init(uint32_t b, uint32_t c) { asm volatile("mbarrier.init.shared::cta.b64 [%0], %1;" ::"r"(b), "r"(c) : "memory"); }
__device__ __forceinline__ void mbar_expect_tx(uint32_t b, uint32_t bytes) { asm volatile("mbarrier.arrive.expect_tx.shared::cta.b64 _, [%0], %1;" ::"r"(b), "r"(bytes) : "memory"); }
__device__ __forceinline__ void mbar_arrive(uint32_t b) { asm volatile("mbarrier.arrive.shared::cta.b64 _, [%0];" ::"r"(b) : "memory"); }
__device__ __forceinline__ void mbar_wait(uint32_t b) {
  asm volatile("{\n.reg .pred p;\n.reg .u32 c;\nmov.u32 c, 0;\nLW:\n.pragma \"nounroll\";\n"
               "mbarrier.try_wait.parity.shared::cta.b64 p, [%0], 0;\nadd.u32 c, c, 1;\nsetp.gt.or.u32 p, c, %1, p;\n@!p bra LW;\n}\n"
               ::"r"(b), "n"(SPIN_LIMIT) : "memory");
}
__device__ __forceinline__ bool elect_one() {
  uint32_t p;
  asm volatile("{\n.reg .pred P;\nelect.sync _|P, 0xffffffff;\nselp.u32 %0, 1, 0, P;\n}\n" : "=r"(p));
  return p;
}
__device__ __forceinline__ void tma2d(uint32_t dst, const CUtensorMap* m, int c0, int c1, uint32_t bar) {
  asm volatile("cp.async.bulk.tensor.2d.shared::cluster.global.mbarrier::complete_tx::bytes [%0], [%1, {%3, %4}], [%2];"
               ::"r"(dst), "l"(m), "r"(bar), "r"(c0), "r"(c1) : "memory");
}
__device__ __forceinline__ void tma3d(uint32_t dst, const CUtensorMap* m, int c0, int c1, int c2, uint32_t bar) {
  asm volatile("cp.async.bulk.tensor.3d.shared::cluster.global.mbarrier::complete_tx::bytes [%0], [%1, {%3, %4, %5}], [%2];"
               ::"r"(dst), "l"(m), "r"(bar), "r"(c0), "r"(c1), "r"(c2) : "memory");
}
__device__ __forceinline__ void tma3d_store(const CUtensorMap* m, uint32_t src, int c0, int c1, int c2) {
  asm volatile("cp.async.bulk.tensor.3d.global.shared::cta.bulk_group [%0, {%2, %3, %4}], [%1];"
               ::"l"(m), "r"(src), "r"(c0), "r"(c1), "r"(c2) : "memory");
}
__device__ __forceinline__ void l2_prefetch(const void* p, uint32_t bytes) {
  asm volatile("cp.async.bulk.prefetch.L2.global [%0], %1;" ::"l"(p), "r"(bytes) : "memory");
}
__device__ __forceinline__ void prefetch_map(const CUtensorMap* m) { asm volatile("prefetch.tensormap [%0];" ::"l"(m) : "memory"); }
__device__ __forceinline__ void fence_async_smem() { asm volatile("fence.proxy.async.shared::cta;" ::: "memory"); }
__device__ __forceinline__ void wg_fence() { asm volatile("wgmma.fence.sync.aligned;" ::: "memory"); }
__device__ __forceinline__ void wg_commit() { asm volatile("wgmma.commit_group.sync.aligned;" ::: "memory"); }
template <int N> __device__ __forceinline__ void wg_wait() { asm volatile("wgmma.wait_group.sync.aligned %0;" ::"n"(N) : "memory"); }
__device__ __forceinline__ void wg_bar(int p) {
  if (p == 0) asm volatile("bar.sync 1, 128;" ::: "memory"); else asm volatile("bar.sync 2, 128;" ::: "memory");
}
constexpr uint32_t DESC_HI128 = (1024 >> 4) | (1u << 30);
constexpr uint32_t DESC_HI64 = (512 >> 4) | (2u << 30);
__device__ __forceinline__ constexpr uint32_t descA(uint32_t addr) { return (addr >> 4) | (1u << 16); }
__device__ __forceinline__ constexpr uint32_t descB(uint32_t addr) { return (addr >> 4) | ((8192u >> 4) << 16); }
__device__ __forceinline__ constexpr uint32_t descBh(uint32_t addr) { return (addr >> 4) | ((4096u >> 4) << 16); }

__device__ __forceinline__ void wgmma_ss_n64(float (&d)[32], uint32_t da, uint32_t db, int sc) {
  asm volatile("{\n.reg .pred p;\n.reg .b64 da, db;\nsetp.ne.b32 p, %34, 0;\nmov.b64 da, {%32, %35};\nmov.b64 db, {%33, %35};\n"
    "wgmma.mma_async.sync.aligned.m64n64k16.f32.bf16.bf16 {%0, %1, %2, %3, %4, %5, %6, %7, %8, %9, %10, %11, %12, %13, %14, %15, %16, %17, %18, %19, %20, %21, %22, %23, %24, %25, %26, %27, %28, %29, %30, %31}, da, db, p, 1, 1, 0, 1;\n}\n"
    : "+f"(d[0]), "+f"(d[1]), "+f"(d[2]), "+f"(d[3]), "+f"(d[4]), "+f"(d[5]), "+f"(d[6]), "+f"(d[7]),
      "+f"(d[8]), "+f"(d[9]), "+f"(d[10]), "+f"(d[11]), "+f"(d[12]), "+f"(d[13]), "+f"(d[14]), "+f"(d[15]),
      "+f"(d[16]), "+f"(d[17]), "+f"(d[18]), "+f"(d[19]), "+f"(d[20]), "+f"(d[21]), "+f"(d[22]), "+f"(d[23]),
      "+f"(d[24]), "+f"(d[25]), "+f"(d[26]), "+f"(d[27]), "+f"(d[28]), "+f"(d[29]), "+f"(d[30]), "+f"(d[31])
    : "r"(da), "r"(db), "r"(sc), "n"(DESC_HI128));
}
__device__ __forceinline__ void wgmma_ss_n128(float (&d)[64], uint32_t da, uint32_t db, int sc) {
  asm volatile("{\n.reg .pred p;\n.reg .b64 da, db;\nsetp.ne.b32 p, %66, 0;\nmov.b64 da, {%64, %67};\nmov.b64 db, {%65, %67};\n"
    "wgmma.mma_async.sync.aligned.m64n128k16.f32.bf16.bf16 {%0, %1, %2, %3, %4, %5, %6, %7, %8, %9, %10, %11, %12, %13, %14, %15, %16, %17, %18, %19, %20, %21, %22, %23, %24, %25, %26, %27, %28, %29, %30, %31, %32, %33, %34, %35, %36, %37, %38, %39, %40, %41, %42, %43, %44, %45, %46, %47, %48, %49, %50, %51, %52, %53, %54, %55, %56, %57, %58, %59, %60, %61, %62, %63}, da, db, p, 1, 1, 0, 1;\n}\n"
    : "+f"(d[0]), "+f"(d[1]), "+f"(d[2]), "+f"(d[3]), "+f"(d[4]), "+f"(d[5]), "+f"(d[6]), "+f"(d[7]),
      "+f"(d[8]), "+f"(d[9]), "+f"(d[10]), "+f"(d[11]), "+f"(d[12]), "+f"(d[13]), "+f"(d[14]), "+f"(d[15]),
      "+f"(d[16]), "+f"(d[17]), "+f"(d[18]), "+f"(d[19]), "+f"(d[20]), "+f"(d[21]), "+f"(d[22]), "+f"(d[23]),
      "+f"(d[24]), "+f"(d[25]), "+f"(d[26]), "+f"(d[27]), "+f"(d[28]), "+f"(d[29]), "+f"(d[30]), "+f"(d[31]),
      "+f"(d[32]), "+f"(d[33]), "+f"(d[34]), "+f"(d[35]), "+f"(d[36]), "+f"(d[37]), "+f"(d[38]), "+f"(d[39]),
      "+f"(d[40]), "+f"(d[41]), "+f"(d[42]), "+f"(d[43]), "+f"(d[44]), "+f"(d[45]), "+f"(d[46]), "+f"(d[47]),
      "+f"(d[48]), "+f"(d[49]), "+f"(d[50]), "+f"(d[51]), "+f"(d[52]), "+f"(d[53]), "+f"(d[54]), "+f"(d[55]),
      "+f"(d[56]), "+f"(d[57]), "+f"(d[58]), "+f"(d[59]), "+f"(d[60]), "+f"(d[61]), "+f"(d[62]), "+f"(d[63])
    : "r"(da), "r"(db), "r"(sc), "n"(DESC_HI128));
}
__device__ __forceinline__ void wgmma_ss_n256(float (&d)[128], uint32_t da, uint32_t db, int sc) {
  asm volatile("{\n.reg .pred p;\n.reg .b64 da, db;\nsetp.ne.b32 p, %130, 0;\nmov.b64 da, {%128, %131};\nmov.b64 db, {%129, %131};\n"
    "wgmma.mma_async.sync.aligned.m64n256k16.f32.bf16.bf16 {%0, %1, %2, %3, %4, %5, %6, %7, %8, %9, %10, %11, %12, %13, %14, %15, %16, %17, %18, %19, %20, %21, %22, %23, %24, %25, %26, %27, %28, %29, %30, %31, %32, %33, %34, %35, %36, %37, %38, %39, %40, %41, %42, %43, %44, %45, %46, %47, %48, %49, %50, %51, %52, %53, %54, %55, %56, %57, %58, %59, %60, %61, %62, %63, %64, %65, %66, %67, %68, %69, %70, %71, %72, %73, %74, %75, %76, %77, %78, %79, %80, %81, %82, %83, %84, %85, %86, %87, %88, %89, %90, %91, %92, %93, %94, %95, %96, %97, %98, %99, %100, %101, %102, %103, %104, %105, %106, %107, %108, %109, %110, %111, %112, %113, %114, %115, %116, %117, %118, %119, %120, %121, %122, %123, %124, %125, %126, %127}, da, db, p, 1, 1, 0, 1;\n}\n"
    : "+f"(d[0]), "+f"(d[1]), "+f"(d[2]), "+f"(d[3]), "+f"(d[4]), "+f"(d[5]), "+f"(d[6]), "+f"(d[7]),
      "+f"(d[8]), "+f"(d[9]), "+f"(d[10]), "+f"(d[11]), "+f"(d[12]), "+f"(d[13]), "+f"(d[14]), "+f"(d[15]),
      "+f"(d[16]), "+f"(d[17]), "+f"(d[18]), "+f"(d[19]), "+f"(d[20]), "+f"(d[21]), "+f"(d[22]), "+f"(d[23]),
      "+f"(d[24]), "+f"(d[25]), "+f"(d[26]), "+f"(d[27]), "+f"(d[28]), "+f"(d[29]), "+f"(d[30]), "+f"(d[31]),
      "+f"(d[32]), "+f"(d[33]), "+f"(d[34]), "+f"(d[35]), "+f"(d[36]), "+f"(d[37]), "+f"(d[38]), "+f"(d[39]),
      "+f"(d[40]), "+f"(d[41]), "+f"(d[42]), "+f"(d[43]), "+f"(d[44]), "+f"(d[45]), "+f"(d[46]), "+f"(d[47]),
      "+f"(d[48]), "+f"(d[49]), "+f"(d[50]), "+f"(d[51]), "+f"(d[52]), "+f"(d[53]), "+f"(d[54]), "+f"(d[55]),
      "+f"(d[56]), "+f"(d[57]), "+f"(d[58]), "+f"(d[59]), "+f"(d[60]), "+f"(d[61]), "+f"(d[62]), "+f"(d[63]),
      "+f"(d[64]), "+f"(d[65]), "+f"(d[66]), "+f"(d[67]), "+f"(d[68]), "+f"(d[69]), "+f"(d[70]), "+f"(d[71]),
      "+f"(d[72]), "+f"(d[73]), "+f"(d[74]), "+f"(d[75]), "+f"(d[76]), "+f"(d[77]), "+f"(d[78]), "+f"(d[79]),
      "+f"(d[80]), "+f"(d[81]), "+f"(d[82]), "+f"(d[83]), "+f"(d[84]), "+f"(d[85]), "+f"(d[86]), "+f"(d[87]),
      "+f"(d[88]), "+f"(d[89]), "+f"(d[90]), "+f"(d[91]), "+f"(d[92]), "+f"(d[93]), "+f"(d[94]), "+f"(d[95]),
      "+f"(d[96]), "+f"(d[97]), "+f"(d[98]), "+f"(d[99]), "+f"(d[100]), "+f"(d[101]), "+f"(d[102]), "+f"(d[103]),
      "+f"(d[104]), "+f"(d[105]), "+f"(d[106]), "+f"(d[107]), "+f"(d[108]), "+f"(d[109]), "+f"(d[110]), "+f"(d[111]),
      "+f"(d[112]), "+f"(d[113]), "+f"(d[114]), "+f"(d[115]), "+f"(d[116]), "+f"(d[117]), "+f"(d[118]), "+f"(d[119]),
      "+f"(d[120]), "+f"(d[121]), "+f"(d[122]), "+f"(d[123]), "+f"(d[124]), "+f"(d[125]), "+f"(d[126]), "+f"(d[127])
    : "r"(da), "r"(db), "r"(sc), "n"(DESC_HI128));
}
template <uint32_t HI = DESC_HI128>
__device__ __forceinline__ void wgmma_rs_n64(float (&d)[32], const uint32_t (&a)[4], uint32_t db, int sc) {
  asm volatile("{\n.reg .pred p;\n.reg .b64 db;\nsetp.ne.b32 p, %37, 0;\nmov.b64 db, {%36, %38};\n"
    "wgmma.mma_async.sync.aligned.m64n64k16.f32.bf16.bf16 {%0, %1, %2, %3, %4, %5, %6, %7, %8, %9, %10, %11, %12, %13, %14, %15, %16, %17, %18, %19, %20, %21, %22, %23, %24, %25, %26, %27, %28, %29, %30, %31}, {%32, %33, %34, %35}, db, p, 1, 1, 1;\n}\n"
    : "+f"(d[0]), "+f"(d[1]), "+f"(d[2]), "+f"(d[3]), "+f"(d[4]), "+f"(d[5]), "+f"(d[6]), "+f"(d[7]),
      "+f"(d[8]), "+f"(d[9]), "+f"(d[10]), "+f"(d[11]), "+f"(d[12]), "+f"(d[13]), "+f"(d[14]), "+f"(d[15]),
      "+f"(d[16]), "+f"(d[17]), "+f"(d[18]), "+f"(d[19]), "+f"(d[20]), "+f"(d[21]), "+f"(d[22]), "+f"(d[23]),
      "+f"(d[24]), "+f"(d[25]), "+f"(d[26]), "+f"(d[27]), "+f"(d[28]), "+f"(d[29]), "+f"(d[30]), "+f"(d[31])
    : "r"(a[0]), "r"(a[1]), "r"(a[2]), "r"(a[3]), "r"(db), "r"(sc), "n"(HI));
}
template <uint32_t HI = DESC_HI128>
__device__ __forceinline__ void wgmma_rs_n128(float (&d)[64], const uint32_t (&a)[4], uint32_t db, int sc) {
  asm volatile("{\n.reg .pred p;\n.reg .b64 db;\nsetp.ne.b32 p, %69, 0;\nmov.b64 db, {%68, %70};\n"
    "wgmma.mma_async.sync.aligned.m64n128k16.f32.bf16.bf16 {%0, %1, %2, %3, %4, %5, %6, %7, %8, %9, %10, %11, %12, %13, %14, %15, %16, %17, %18, %19, %20, %21, %22, %23, %24, %25, %26, %27, %28, %29, %30, %31, %32, %33, %34, %35, %36, %37, %38, %39, %40, %41, %42, %43, %44, %45, %46, %47, %48, %49, %50, %51, %52, %53, %54, %55, %56, %57, %58, %59, %60, %61, %62, %63}, {%64, %65, %66, %67}, db, p, 1, 1, 1;\n}\n"
    : "+f"(d[0]), "+f"(d[1]), "+f"(d[2]), "+f"(d[3]), "+f"(d[4]), "+f"(d[5]), "+f"(d[6]), "+f"(d[7]),
      "+f"(d[8]), "+f"(d[9]), "+f"(d[10]), "+f"(d[11]), "+f"(d[12]), "+f"(d[13]), "+f"(d[14]), "+f"(d[15]),
      "+f"(d[16]), "+f"(d[17]), "+f"(d[18]), "+f"(d[19]), "+f"(d[20]), "+f"(d[21]), "+f"(d[22]), "+f"(d[23]),
      "+f"(d[24]), "+f"(d[25]), "+f"(d[26]), "+f"(d[27]), "+f"(d[28]), "+f"(d[29]), "+f"(d[30]), "+f"(d[31]),
      "+f"(d[32]), "+f"(d[33]), "+f"(d[34]), "+f"(d[35]), "+f"(d[36]), "+f"(d[37]), "+f"(d[38]), "+f"(d[39]),
      "+f"(d[40]), "+f"(d[41]), "+f"(d[42]), "+f"(d[43]), "+f"(d[44]), "+f"(d[45]), "+f"(d[46]), "+f"(d[47]),
      "+f"(d[48]), "+f"(d[49]), "+f"(d[50]), "+f"(d[51]), "+f"(d[52]), "+f"(d[53]), "+f"(d[54]), "+f"(d[55]),
      "+f"(d[56]), "+f"(d[57]), "+f"(d[58]), "+f"(d[59]), "+f"(d[60]), "+f"(d[61]), "+f"(d[62]), "+f"(d[63])
    : "r"(a[0]), "r"(a[1]), "r"(a[2]), "r"(a[3]), "r"(db), "r"(sc), "n"(HI));
}

template <int N> __device__ __forceinline__ void keep(float (&d)[N]) {
#pragma unroll
  for (int i = 0; i < N; i++) asm volatile("" : "+f"(d[i])::"memory");
}

__device__ __forceinline__ void keep(uint32_t (&d)[4]) { asm volatile("" : "+r"(d[0]), "+r"(d[1]), "+r"(d[2]), "+r"(d[3])::"memory"); }
template <int N> __device__ __forceinline__ void keep(uint32_t (&d)[N][4]) {
#pragma unroll
  for (int i = 0; i < N; i++) asm volatile("" : "+r"(d[i][0]), "+r"(d[i][1]), "+r"(d[i][2]), "+r"(d[i][3])::"memory");
}

__device__ __forceinline__ uint32_t pack2(float lo, float hi) {
  uint32_t r;
  asm("cvt.rn.bf16x2.f32 %0, %1, %2;" : "=r"(r) : "f"(hi), "f"(lo));
  return r;
}
__device__ __forceinline__ float bf_lo(uint32_t v) { return __uint_as_float(v << 16); }
__device__ __forceinline__ float bf_hi(uint32_t v) { return __uint_as_float(v & 0xffff0000u); }
__device__ __forceinline__ uint32_t hsub2(uint32_t a, uint32_t b) {
  uint32_t r;
  asm("sub.rn.bf16x2 %0, %1, %2;" : "=r"(r) : "r"(a), "r"(b));
  return r;
}
__device__ __forceinline__ uint32_t movm(uint32_t a) {
  uint32_t r;
  asm volatile("movmatrix.sync.aligned.m8n8.trans.b16 %0, %1;" : "=r"(r) : "r"(a));
  return r;
}
__device__ __forceinline__ void ldsm4(uint32_t (&v)[4], uint32_t a) {
  asm volatile("ldmatrix.sync.aligned.m8n8.x4.shared.b16 {%0,%1,%2,%3}, [%4];" : "=r"(v[0]), "=r"(v[1]), "=r"(v[2]), "=r"(v[3]) : "r"(a) : "memory");
}
__device__ __forceinline__ void stsm4(uint32_t a, const uint32_t (&v)[4]) {
  asm volatile("stmatrix.sync.aligned.m8n8.x4.shared.b16 [%0], {%1,%2,%3,%4};" ::"r"(a), "r"(v[0]), "r"(v[1]), "r"(v[2]), "r"(v[3]) : "memory");
}
__device__ __forceinline__ void mma16816(float (&d)[4], const uint32_t (&a)[4], uint32_t b0, uint32_t b1) {
  asm volatile("mma.sync.aligned.m16n8k16.row.col.f32.bf16.bf16.f32 {%0,%1,%2,%3}, {%4,%5,%6,%7}, {%8,%9}, {%10,%10,%10,%10};"
               : "=f"(d[0]), "=f"(d[1]), "=f"(d[2]), "=f"(d[3])
               : "r"(a[0]), "r"(a[1]), "r"(a[2]), "r"(a[3]), "r"(b0), "r"(b1), "f"(0.f));
}
__device__ __forceinline__ void mma1688_acc(float (&d)[4], uint32_t a0, uint32_t a1, uint32_t b0) {
  asm volatile("mma.sync.aligned.m16n8k8.row.col.f32.bf16.bf16.f32 {%0,%1,%2,%3}, {%4,%5}, {%6}, {%0,%1,%2,%3};"
               : "+f"(d[0]), "+f"(d[1]), "+f"(d[2]), "+f"(d[3]) : "r"(a0), "r"(a1), "r"(b0));
}
__device__ __forceinline__ float ex2(float x) { float y; asm("ex2.approx.ftz.f32 %0, %1;" : "=f"(y) : "f"(x)); return y; }
__device__ __forceinline__ float rcp(float x) { float y; asm("rcp.approx.ftz.f32 %0, %1;" : "=f"(y) : "f"(x)); return y; }
__device__ __forceinline__ float tanhf_hw(float x) { float y; asm("tanh.approx.f32 %0, %1;" : "=f"(y) : "f"(x)); return y; }
__device__ __forceinline__ uint32_t lds32(uint32_t a) { uint32_t v; asm volatile("ld.shared.u32 %0, [%1];" : "=r"(v) : "r"(a) : "memory"); return v; }
__device__ __forceinline__ float2 lds64(uint32_t a) { float2 v; asm volatile("ld.shared.v2.f32 {%0,%1}, [%2];" : "=f"(v.x), "=f"(v.y) : "r"(a) : "memory"); return v; }
__device__ __forceinline__ void lds128(uint32_t (&v)[4], uint32_t a) { asm volatile("ld.shared.v4.u32 {%0,%1,%2,%3}, [%4];" : "=r"(v[0]), "=r"(v[1]), "=r"(v[2]), "=r"(v[3]) : "r"(a) : "memory"); }
__device__ __forceinline__ void sts128(uint32_t a, const uint32_t (&v)[4]) { asm volatile("st.shared.v4.u32 [%0], {%1,%2,%3,%4};" ::"r"(a), "r"(v[0]), "r"(v[1]), "r"(v[2]), "r"(v[3]) : "memory"); }
__device__ __forceinline__ void ldg128_nc(uint32_t (&v)[4], const void* p) {
  asm volatile("ld.global.nc.L1::no_allocate.v4.u32 {%0,%1,%2,%3}, [%4];" : "=r"(v[0]), "=r"(v[1]), "=r"(v[2]), "=r"(v[3]) : "l"(p));
}
__device__ __forceinline__ uint32_t pin(uint32_t v, uint32_t zero) {
  asm volatile("{\n.reg .pred p;\n.reg .u32 c;\nmov.u32 c, %1;\nLP:\n.pragma \"nounroll\";\nsetp.eq.u32 p, c, 0;\n@p bra LD;\n"
               "nanosleep.u32 c;\nadd.u32 %0, %0, c;\nsub.u32 c, c, 1;\nbra LP;\nLD:\n}\n" : "+r"(v) : "r"(zero) : "memory");
  return v;
}
__device__ __forceinline__ void mbar_arrive_if(uint32_t b, bool cond) {
  asm volatile("{\n.reg .pred p;\nsetp.ne.u32 p, %1, 0;\n@p mbarrier.arrive.shared::cta.b64 _, [%0];\n}\n" ::"r"(b), "r"((uint32_t)cond) : "memory");
}
__device__ __forceinline__ uint32_t ld_epoch(const unsigned* p) {
  uint32_t v;
  asm volatile("ld.relaxed.gpu.global.u32 %0, [%1];" : "=r"(v) : "l"(p) : "memory");
  return v;
}
__device__ __forceinline__ void ll_st(uint4* p, uint32_t a, uint32_t b, uint32_t c, uint32_t d, uint32_t tag) {
  asm volatile("{\n.reg .b128 t;\n.reg .b64 lo, hi;\nmov.b64 lo, {%1, %2};\nmov.b64 hi, {%3, %4};\nmov.b128 t, {lo, hi};\n"
               "st.relaxed.gpu.global.b128 [%0], t;\n}\n" ::"l"(p), "r"((a & ~1u) | tag), "r"(b), "r"(c), "r"(d) : "memory");
}
__device__ __forceinline__ void ll_ld(uint32_t (&v)[4], const uint4* p) {
  asm volatile("{\n.reg .b128 t;\n.reg .b64 lo, hi;\nld.relaxed.gpu.global.b128 t, [%4];\nmov.b128 {lo, hi}, t;\n"
               "mov.b64 {%0, %1}, lo;\nmov.b64 {%2, %3}, hi;\n}\n"
               : "=r"(v[0]), "=r"(v[1]), "=r"(v[2]), "=r"(v[3]) : "l"(p) : "memory");
}
template <int N> __device__ __forceinline__ void ll_issue(uint32_t (&v)[N][4], const uint4* p, int stride) {
#pragma unroll
  for (int i = 0; i < N; i++) ll_ld(v[i], p + i * stride);
}
template <int N> __device__ __forceinline__ uint32_t ll_acc(const uint32_t (&v)[N][4], uint32_t tag, uint32_t acc = 0) {
#pragma unroll
  for (int i = 0; i < N; i++) asm("lop3.b32 %0, %1, %2, %0, 0xBE;" : "+r"(acc) : "r"(v[i][0]), "r"(tag));
  return acc;
}
__device__ __forceinline__ bool ll_any(uint32_t acc) { return __any_sync(0xffffffffu, acc & 1u); }
template <int N> __device__ __forceinline__ bool ll_bad(const uint32_t (&v)[N][4], uint32_t tag) { return ll_any(ll_acc<N>(v, tag)); }
template <int N> __device__ __forceinline__ void ll_clear(uint32_t (&v)[N][4]) {
#pragma unroll
  for (int i = 0; i < N; i++) v[i][0] &= ~1u;
}
template <int N> __device__ __forceinline__ void ll_spin(uint32_t (&v)[N][4], const uint4* p, int stride, uint32_t tag) {
  uint32_t it = 0;
#pragma unroll 1
  do { ll_issue<N>(v, p, stride); } while (ll_bad<N>(v, tag) && ++it < SPIN_LIMIT);
}
template <int N> __device__ __forceinline__ void ll_get(uint32_t (&v)[N][4], const uint4* p, int stride, uint32_t tag) {
  ll_spin<N>(v, p, stride, tag);
  ll_clear<N>(v);
}
template <int N> __device__ __forceinline__ void ll_wait(uint32_t (&v)[N][4], const uint4* p, int stride, uint32_t tag) {
  if (__builtin_expect(ll_bad<N>(v, tag), 0)) ll_spin<N>(v, p, stride, tag);
  ll_clear<N>(v);
}
__device__ __forceinline__ void unpack32(float (&d)[32], const uint32_t (&v)[4][4]) {
#pragma unroll
  for (int u = 0; u < 4; u++)
#pragma unroll
    for (int e = 0; e < 4; e++) { d[8 * u + 2 * e] = bf_lo(v[u][e]); d[8 * u + 2 * e + 1] = bf_hi(v[u][e]); }
}
__device__ __forceinline__ void pack32(uint32_t (&v)[4][4], const float (&d)[32]) {
#pragma unroll
  for (int u = 0; u < 4; u++)
#pragma unroll
    for (int e = 0; e < 4; e++) v[u][e] = pack2(d[8 * u + 2 * e], d[8 * u + 2 * e + 1]);
}
__device__ __forceinline__ uint32_t t_addr(int m) { return SB + ((0x03514620u >> (4 * m)) & 7u) * 32768u; }

__device__ __forceinline__ int kb_at(int i, int j) { return i == 0 ? j : (i - 1 + (i - 1 >= j ? 1 : 0)); }

__device__ __forceinline__ void init_bars(int set) {
  if (set >= 0 && elect_one()) {
    const uint32_t cnt = set < 5 ? 1 : 8;
#pragma unroll
    for (int i = 0; i < 8; i++) mbar_init(BAR + (24 + 8 * set + i) * 8, cnt);
    if (set == 9) {
#pragma unroll
      for (int i = 0; i < 9; i++) mbar_init(BAR + (B_EX + i) * 8, 4);
#pragma unroll
      for (int i = 0; i < 3; i++) mbar_init(BAR + (B_READY + i) * 8, 3);
      mbar_init(BAR + B_TAG * 8, 1);
    }
    asm volatile("fence.mbarrier_init.release.cluster;" ::: "memory");
  }
  __syncwarp();
  asm volatile("bar.arrive 4, 384;" ::: "memory");
  asm volatile("bar.sync 3, 384;" ::: "memory");
}

__global__ void __launch_bounds__(384, 1) fused_block_kernel(Scratch* __restrict__ X, const __nv_bfloat16* __restrict__ xp,
                                                             const __nv_bfloat16* __restrict__ wqkvp, const __nv_bfloat16* __restrict__ wop, const uint32_t zero,
                                                             const __grid_constant__ Params P) {
  extern __shared__ __align__(1024) uint8_t smem_raw[];
  if (smem_u32(smem_raw) != SB) return;
  const int tid = threadIdx.x;
  const int warp = __shfl_sync(0xffffffffu, tid >> 5, 0);
  const int lane = tid & 31;
  const int cta = blockIdx.x;
  const int j = (cta >> 6) * 4 + (cta & 3);
  const int g = (cta & 63) >> 2;

  if (warp >= 8) {
    asm volatile("setmaxnreg.dec.sync.aligned.u32 56;");
    if (warp == 8) {
      PSTAMPW(2, 0);
      const bool leader = elect_one();
      if (leader) {
        prefetch_map(&P.x); prefetch_map(&P.wqkv);
#pragma unroll
        for (int i = 0; i < 24; i++) mbar_init(BAR + i * 8, 1);
        asm volatile("fence.mbarrier_init.release.cluster;" ::: "memory");
      }
      __syncwarp();
      asm volatile("bar.arrive 3, 384;" ::: "memory");
      PSTAMPW(2, 20);
      auto ldx = [&](int p, int kb) {
        const uint32_t b = BAR + (B_FX + p * 8 + kb) * 8;
        mbar_expect_tx(b, 8192);
        tma3d(H0 + p * 65536 + kb * 8192, &P.x, kb * 64, p, g * 64, b);
      };
      auto ldkv = [&](int kb, int slot) {
        const uint32_t b = BAR + (B_FKV + kb) * 8, d = RING + slot * 16384;
        mbar_expect_tx(b, 16384);
        tma2d(d, &P.wqkv, 512 + 64 * j, kb * 64, b);
        tma2d(d + 8192, &P.wqkv, 1024 + 64 * j, kb * 64, b);
      };
      if (leader) {
#pragma unroll 1
        for (int i = 0; i < 8 + XO_DELAY; i++) {
          if (i < 8) ldx(0, i);
          if (i < 6) ldkv(i, i);
          if (i >= XO_DELAY) ldx(1, i - XO_DELAY);
          if (i == 0) PSTAMPW(2, 21);
        }
        PSTAMPW(2, 2);
      }
      __syncwarp();
      asm volatile("bar.sync 4, 384;" ::: "memory");
      if (leader) {
        const int f0 = 224 * j + ((j & 1) ? 32 : 0);
        const int fh = 224 * j + ((j & 1) ? 0 : 192);
        prefetch_map(&P.wo); prefetch_map(&P.w1); prefetch_map(&P.w3); prefetch_map(&P.w1h);
        prefetch_map(&P.w3h); prefetch_map(&P.w2); prefetch_map(&P.out);
#pragma unroll 1
        for (int i = 0; i < 2; i++) { mbar_wait(BAR + (B_EKV + i) * 8); ldkv(6 + i, i); }
#pragma unroll 1
        for (int i = 0; i < 8; i++) {
          const uint32_t b = BAR + (B_FQ + i) * 8;
          mbar_wait(BAR + (B_EKV + 2 + (i >> 1)) * 8);
          mbar_expect_tx(b, 8192);
          tma2d(RING + (4 + i) * 8192, &P.wqkv, 64 * j, i * 64, b);
        }
        mbar_expect_tx(BAR + B_FWO * 8, 65536);
#pragma unroll 1
        for (int i = 0; i < 8; i++) {
          const int kb = (i + 1) & 7;
          mbar_wait(BAR + (B_EX + i) * 8);
          tma2d(H0 + kb * 8192, &P.wo, 64 * j, kb * 64, BAR + B_FWO * 8);
          PSTAMPW(2, 4 + i);
        }
#pragma unroll 1
        for (int i = 0; i < 8; i++) {
          const uint32_t b = BAR + (B_FA + i) * 8, d = RING + (i & 3) * 24576;
          const int k0 = kb_at(i, j) * 64;
          mbar_wait(BAR + (B_EKV + 7 + ((0xCBA98520u >> (4 * i)) & 15)) * 8);
          mbar_expect_tx(b, 24576);
          tma2d(d, &P.w1, f0, k0, b);
          tma2d(d + 8192, &P.w3, f0, k0, b);
          tma2d(d + 16384, &P.w1h, fh, k0, b);
          tma2d(d + 20480, &P.w3h, fh, k0, b);
          PSTAMPW(2, 12 + i);
        }
        uint32_t d = RING;
#pragma unroll 1
        for (int i = 0; i < 8; i++) {
          const uint32_t b = BAR + (B_FB + i) * 8;
          const int k0 = kb_at(i, j) * 64;
          mbar_wait(BAR + (B_EA + 5 + i) * 8);
          mbar_expect_tx(b, 32768);
          tma2d(d, &P.w1, f0 + 64, k0, b);
          tma2d(d + 8192, &P.w3, f0 + 64, k0, b);
          tma2d(d + 16384, &P.w1, f0 + 128, k0, b);
          tma2d(d + 24576, &P.w3, f0 + 128, k0, b);
          d = d == RING + 65536 ? RING : d + 32768;
        }
#pragma unroll 1
        for (int m = 0; m < 8; m++) {
          const uint32_t b = BAR + (B_FT + m) * 8;
          mbar_wait(BAR + (B_EB + (m == 7 ? 8 : min(m + 3, 7))) * 8);
          mbar_expect_tx(b, 28672);
          tma2d(t_addr(m), &P.w2, 64 * ((j + 1 + m) & 7), 224 * j, b);
        }
        X->epoch[cta] = X->epoch[cta] + 1;
      }
    } else {
      const int part = warp - 9;
      uint32_t tag;
      if (part == 2) {
        tag = ld_epoch(X->epoch + cta);
        init_bars(-1);
        tag = (tag + 1) & 1;
        if (lane == 0) {
          asm volatile("st.shared.u32 [%0], %1;" ::"r"(TAGS), "r"(tag) : "memory");
          mbar_arrive(BAR + B_TAG * 8);
        }
      } else {
        init_bars(warp - 1);
        mbar_wait(BAR + B_TAG * 8);
        tag = lds32(TAGS);
      }
      PSTAMPW(3, 16 + part);
      const int xw0 = g * 8;
      auto clear = [&](uint4* p, int n, int stride) {
#pragma unroll 1
        for (int i = part; i < n; i += 3) ll_st(p + i * stride + lane, 0, 0, 0, 0, tag ^ 1);
      };
      clear(X->e1 + (g * 8 + j) * 256, 8, 32);
      if (lane < 8) { clear(X->e2s + (xw0 * 8 + j) * 8, 8, 64); clear(X->e3s + (xw0 * 8 + j) * 8, 8, 64); }
#pragma unroll 1
      for (int u = 0; u < 8; u++) clear((u < 4 ? X->e2 : X->e3h) + (xw0 * 32 + 4 * j + (u & 3)) * 32, 8, 1024);
      PSTAMPW(3, 20 + part);
      uint32_t v[8][4];
      mbar_wait(BAR + (B_FKV + SIDE_KB) * 8);
      if (part == 2 && lane == 0) l2_prefetch(wop + (size_t)(j * 64 + g * 4) * D_, 4096);
      {
        const __nv_bfloat16* wr = wqkvp + (size_t)(g * 32 + (lane >> 3) * 8) * (3 * D_) + ((part + 1) % 3) * D_ + j * 64 + (lane & 7) * 8;
#pragma unroll
        for (int i = 0; i < 8; i++) ldg128_nc(v[i], wr + (size_t)i * 3 * D_);
        float cs[8];
#pragma unroll
        for (int e = 0; e < 4; e++) {
          float a = 0.f, b = 0.f;
#pragma unroll
          for (int i = 0; i < 8; i++) { a += bf_lo(v[i][e]); b += bf_hi(v[i][e]); }
          cs[2 * e] = a; cs[2 * e + 1] = b;
        }
        const bool up = lane & 8;
#pragma unroll
        for (int e = 0; e < 4; e++) {
          const float keepv = up ? cs[4 + e] : cs[e], give = up ? cs[e] : cs[4 + e];
          cs[e] = keepv + __shfl_xor_sync(0xffffffffu, give, 8);
          cs[e] += __shfl_xor_sync(0xffffffffu, cs[e], 16);
        }
        if (lane < 16)
          ll_st(X->e0c + ((j * 3 + part) * 16 + g) * 16 + (lane & 7) * 2 + (lane >> 3), __float_as_uint(cs[0]), __float_as_uint(cs[1]),
                __float_as_uint(cs[2]), __float_as_uint(cs[3]), tag);
      }
      PSTAMPW(3, 24 + part);
      {
        float s = 0.f, q = 0.f, piv = 0.f;
        const uint32_t xa = H0 + part * 65536 + (8 * j + (lane >> 2)) * 128 + (lane & 3) * 16 + (lane & 4) * 16;
        const __nv_bfloat16* wr = wop + (size_t)(j * 64 + g * 4 + (lane >> 3)) * D_ + (lane & 7) * 8;
#pragma unroll 1
        for (int kb = 0; kb < 8; kb++) {
          uint32_t t[2][4];
          if (part < 2) {
            mbar_wait(BAR + (B_FX + part * 8 + kb) * 8);
            lds128(t[0], xa + kb * 8192); lds128(t[1], (xa + kb * 8192) ^ 64);
            if (kb == 0) piv = __shfl_sync(0xffffffffu, bf_lo(t[0][0]), lane & 28);
          } else {
            if (kb >= 4) break;
            ldg128_nc(t[0], wr + kb * 128); ldg128_nc(t[1], wr + kb * 128 + 64);
          }
#pragma unroll
          for (int e = 0; e < 8; e++) {
            const float a = bf_lo(t[e >> 2][e & 3]) - piv, b = bf_hi(t[e >> 2][e & 3]) - piv;
            s += a + b; q = fmaf(a, a, q); q = fmaf(b, b, q);
          }
        }
#pragma unroll
        for (int o = 1; o <= 2; o <<= 1) { s += __shfl_xor_sync(0xffffffffu, s, o); q += __shfl_xor_sync(0xffffffffu, q, o); }
        const float s8 = s + __shfl_xor_sync(0xffffffffu, s, 4);
        const float dm = (part < 2 ? s : s8) * (1.f / D_);
        const float rs = rsqrtf(fmaxf(fmaf(-dm, dm, q * (1.f / D_)), 0.f) + 1e-5f);
        uint4* dst = part < 2 ? X->e0s + g * 128 + 2 * (8 * j + (lane >> 2)) + part : X->e0w + j * 64 + g * 4 + (lane >> 3);
        if ((lane & (part < 2 ? 3 : 7)) == 0) ll_st(dst, __float_as_uint(piv + dm), __float_as_uint(rs), 0, 0, tag);
        __syncwarp();
        if (lane == 0) mbar_arrive(BAR + B_PUB * 8);
      }
      PSTAMPW(3, part * 4 + 2);
      mbar_wait(BAR + B_PUB * 8);
      PSTAMPW(3, part * 4 + 0);
      {
        uint32_t u[2][4];
        const uint4* us = (part == 2 ? X->e0w + j * 64 : X->e0s + g * 128 + part * 64) + lane;
        const uint4* vs = X->e0c + ((j * 3 + part) * 16 + (lane >> 4) * 8) * 16 + (lane & 15);
        uint32_t it = 0;
#pragma unroll 1
        do { ll_issue<2>(u, us, 32); ll_issue<8>(v, vs, 16); } while (ll_any(ll_acc<8>(v, tag, ll_acc<2>(u, tag))) && ++it < SPIN_LIMIT);
        ll_clear<2>(u); ll_clear<8>(v);
#pragma unroll
        for (int i = 0; i < 2; i++) {
          if (part == 2) asm volatile("st.shared.u32 [%0], %1;" ::"r"(WB + (i * 32 + lane) * 4), "r"(u[i][0]) : "memory");
          else asm volatile("st.shared.v2.u32 [%0], {%1,%2};" ::"r"(ST + (part * 64 + i * 32 + lane) * 8), "r"(u[i][0]), "r"(u[i][1]) : "memory");
        }
      }
      uint32_t o[4];
#pragma unroll
      for (int e = 0; e < 4; e++) {
        float s = 0.f;
#pragma unroll
        for (int i = 0; i < 8; i++) s += __uint_as_float(v[i][e]);
        o[e] = __float_as_uint(s + __shfl_xor_sync(0xffffffffu, s, 16));
      }
      if (lane < 16) sts128(CS + (((part + 1) % 3) * 64 + lane * 4) * 4, o);
      __syncwarp();
      if (lane == 0) mbar_arrive(BAR + B_READY * 8);
      PSTAMPW(3, part * 4 + 1);
      if (lane == 0) l2_prefetch(part == 0 ? P.w1p + (size_t)cta * 4 * F_ : part == 1 ? P.w3p + (size_t)cta * 4 * F_ : P.w2p + (size_t)cta * 14 * D_, 14336);
      mbar_wait(BAR + (B_EA + 1) * 8);
#pragma unroll 1
      for (int m = E4_FIRST; m < 7; m++)
#pragma unroll 1
        for (int u = 0; u < 4; u++) clear(X->e4 + ((size_t)xw0 * 64 + ((j + 1 + m) & 7) * 8 + j) * 128 + u * 32, 8, 8192);
      __syncwarp();
      if (lane == 0) mbar_arrive(BAR + B_CLR * 8);
      PSTAMPW(3, part * 4 + 3);
    }
  } else {
    const int p = warp >> 2, w = warp & 3;
    const int r = lane >> 2, c = lane & 3;
    init_bars(warp);
    asm volatile("setmaxnreg.inc.sync.aligned.u32 224;");
    PSTAMP(0);
    const uint32_t dAx = descA(H0) + p * 4096;
    const uint32_t Hn = H1 - p * 65536;
    const uint32_t moff = ((lane & 7) + ((lane >> 3) & 1) * 8) * 128 + (((lane >> 4) ^ (lane & 7)) << 4);
    const uint32_t Xw = H0 + p * 65536 + w * 2048;
    const int xw = (g * 2 + p) * 4 + w;
    if (p == 1) mbar_wait(BAR + B_LAG * 8);

    float akv[64];
#pragma unroll 1
    for (int kb = 0; kb < 8; kb++) {
      mbar_wait(BAR + (B_FX + p * 8 + kb) * 8);
      mbar_wait(BAR + (B_FKV + kb) * 8);
      if (kb == 0) PSTAMP(2);
      const uint32_t da = dAx + kb * 512, db = descB(RING) + (kb < 6 ? kb : kb - 6) * 1024;
      wg_fence();
      wgmma_ss_n128(akv, da, db, kb);
#pragma unroll
      for (int k = 1; k < 4; k++) wgmma_ss_n128(akv, da + k * 2, db + k * 128, 1);
      wg_commit();
      mbar_arrive_if(BAR + B_LAG * 8, kb == LAG_KB - 1 && p == 0 && lane == 0);
      wg_wait<1>();
      mbar_arrive_if(BAR + (B_EKV + kb - 1) * 8, kb > 0 && lane == 0);
    }
    uint32_t xres[4][4];
#pragma unroll
    for (int u = 0; u < 4; u++) ldsm4(xres[u], Xw + j * 8192 + (moff ^ (u << 5)));

    float aq[32];
    auto qstep = [&](int kb) {
      mbar_wait(BAR + (B_FQ + kb) * 8);
      const uint32_t da = dAx + kb * 512, db = descB(RING + 32768) + kb * 512;
      wg_fence();
      wgmma_ss_n64(aq, da, db, kb);
#pragma unroll
      for (int k = 1; k < 4; k++) wgmma_ss_n64(aq, da + k * 2, db + k * 128, 1);
      wg_commit();
      wg_wait<1>();
      mbar_arrive_if(BAR + (B_EQ + kb - 1) * 8, lane == 0);
      mbar_arrive_if(BAR + (B_EX + kb - 2) * 8, lane == 0 && p == 0 && kb >= 2);
    };
    qstep(0);
    keep(akv);
    PSTAMP(3);
    qstep(1);
    mbar_wait(BAR + B_READY * 8);
    PSTAMP(19);
    const uint32_t tag = lds32(TAGS);
    const float2 st0 = lds64(ST + (2 * (16 * w + r) + p) * 8);
    const float2 st1 = lds64(ST + (2 * (16 * w + r + 8) + p) * 8);
    uint32_t hi[4][4], lo[4][4];
    {
      float2 cs[16];
      auto cvt = [&](uint32_t (&d)[4][4], int b0, int ofs, const float2& st) {
#pragma unroll
        for (int b = b0; b < b0 + 8; b++) {
          if (ofs == 2) cs[b] = lds64(CS + (64 + b * 8 + 2 * c) * 4);
          const uint32_t v = pack2(fmaf(-st.x, cs[b].x, akv[4 * b + ofs]) * st.y, fmaf(-st.x, cs[b].y, akv[4 * b + ofs + 1]) * st.y);
          d[b >> 2][b & 3] = b < 8 ? v : movm(v);
        }
      };
      cvt(hi, 0, 2, st1);
      keep(hi[0]); keep(hi[1]);
      qstep(2);
      cvt(hi, 8, 2, st1);
      if (w == 3 && g < 15) {
        uint4* dst = X->e1 + ((g * 8 + j) * 2 + p) * 128 + lane;
#pragma unroll
        for (int i = 0; i < 4; i++) ll_st(dst + i * 32, hi[i][0], hi[i][1], hi[i][2], hi[i][3], tag);
      }
      PSTAMP(20);
      wg_bar(p);
#pragma unroll
      for (int i = 0; i < 4; i++) sts128(Xw + lane * 16 + i * 512, hi[i]);
      qstep(3);
      cvt(lo, 0, 0, st0);
      keep(lo[0]); keep(lo[1]);
      qstep(4);
      cvt(lo, 8, 0, st0);
    }
    PSTAMP(21);
    wg_bar(p);
    uint32_t prev[4][4];
    if (w > 0) {
#pragma unroll
      for (int i = 0; i < 4; i++) lds128(prev[i], Xw - 2048 + lane * 16 + i * 512);
    }
    if (p == 0) {
      asm volatile("fence.proxy.async.shared::cta;" ::: "memory");
      __syncwarp();
      if (lane == 0) mbar_arrive(BAR + (B_EX + 7) * 8);
    }
    PSTAMP(22);
#pragma unroll 1
    for (int kb = 5; kb < 8; kb++) qstep(kb);
    PSTAMP(23);
    if (w == 0) {
      if (g > 0) {
        ll_get<4>(prev, X->e1 + (((g - 1) * 8 + j) * 2 + p) * 128 + lane, 32, tag);
      } else {
#pragma unroll
        for (int i = 0; i < 4; i++)
#pragma unroll
          for (int e = 0; e < 4; e++) prev[i][e] = 0;
      }
    }
    wg_wait<0>();
    keep(aq);
    mbar_arrive_if(BAR + (B_EQ + 7) * 8, lane == 0);
    mbar_arrive_if(BAR + (B_EX + 6) * 8, lane == 0 && p == 0);
    PSTAMP(4);

    uint32_t of[4][4];
    {
      const float sc = 0.25f * 1.4426950408889634f;
      const float nohalo = (g == 0 && w == 0) ? -INFINITY : 0.f;
      const bool up0 = 2 * c > r, up1 = 2 * c + 1 > r;
      const uint32_t mup = (up0 ? 0xffffu : 0u) | (up1 ? 0xffff0000u : 0u);
      uint4* dst = X->e2 + (xw * 32 + 4 * j) * 32 + lane;
      float d0 = 0.f, d1 = 0.f;
#pragma unroll 1
      for (int hp = 0; hp < 2; hp++) {
#pragma unroll
        for (int e = 0; e < 4; e++) { of[0][e] = of[2][e]; of[1][e] = of[3][e]; }
#pragma unroll
        for (int h = 0; h < 2; h++) {
          uint32_t qf[4];
          const uint32_t co = (32 * hp + 16 * h + 2 * c) * 4;
          {
            const float2 ca = lds64(CS + co), cb = lds64(CS + co + 32);
            qf[0] = pack2(fmaf(-st0.x, ca.x, aq[8 * h + 0]) * st0.y, fmaf(-st0.x, ca.y, aq[8 * h + 1]) * st0.y);
            qf[1] = pack2(fmaf(-st1.x, ca.x, aq[8 * h + 2]) * st1.y, fmaf(-st1.x, ca.y, aq[8 * h + 3]) * st1.y);
            qf[2] = pack2(fmaf(-st0.x, cb.x, aq[8 * h + 4]) * st0.y, fmaf(-st0.x, cb.y, aq[8 * h + 5]) * st0.y);
            qf[3] = pack2(fmaf(-st1.x, cb.x, aq[8 * h + 6]) * st1.y, fmaf(-st1.x, cb.y, aq[8 * h + 7]) * st1.y);
          }
          const int e0 = 2 * h;
          float sp[4], sl[4], sh[4];
          mma16816(sp, qf, prev[0][e0], prev[0][e0 + 1]);
          mma16816(sl, qf, lo[0][e0], lo[0][e0 + 1]);
          mma16816(sh, qf, hi[0][e0], hi[0][e0 + 1]);
          float a0 = up0 ? sp[0] + nohalo : sl[0], a1 = up1 ? sp[1] + nohalo : sl[1];
          float b0 = up0 ? sl[2] : sh[2], b1 = up1 ? sl[3] : sh[3];
          float ma = fmaxf(a0, a1), mb = fmaxf(b0, b1);
          ma = fmaxf(ma, __shfl_xor_sync(0xffffffffu, ma, 1)); mb = fmaxf(mb, __shfl_xor_sync(0xffffffffu, mb, 1));
          ma = fmaxf(ma, __shfl_xor_sync(0xffffffffu, ma, 2)); mb = fmaxf(mb, __shfl_xor_sync(0xffffffffu, mb, 2));
          a0 = ex2((a0 - ma) * sc); a1 = ex2((a1 - ma) * sc); b0 = ex2((b0 - mb) * sc); b1 = ex2((b1 - mb) * sc);
          float sa = a0 + a1, sbb = b0 + b1;
          sa += __shfl_xor_sync(0xffffffffu, sa, 1); sbb += __shfl_xor_sync(0xffffffffu, sbb, 1);
          sa += __shfl_xor_sync(0xffffffffu, sa, 2); sbb += __shfl_xor_sync(0xffffffffu, sbb, 2);
          const float ia = rcp(sa), ib = rcp(sbb);
          const uint32_t pa = pack2(a0 * ia, a1 * ia), pb = pack2(b0 * ib, b1 * ib);
          const uint32_t pf[4] = {pa & mup, 0u, pa & ~mup, pb & mup};
          const uint32_t ph = pb & ~mup;
          float o0[4], o1[4];
          mma16816(o0, pf, prev[2][e0], lo[2][e0]);
          mma16816(o1, pf, prev[2][e0 + 1], lo[2][e0 + 1]);
          mma1688_acc(o0, 0u, ph, hi[2][e0]);
          mma1688_acc(o1, 0u, ph, hi[2][e0 + 1]);
          of[2 + h][0] = pack2(o0[0], o0[1]); of[2 + h][1] = pack2(o0[2], o0[3]);
          of[2 + h][2] = pack2(o1[0], o1[1]); of[2 + h][3] = pack2(o1[2], o1[3]);
          ll_st(dst + (2 * hp + h) * 32, of[2 + h][0], of[2 + h][1], of[2 + h][2], of[2 + h][3], tag);
          const float2 wa = lds64(WB + co), wb = lds64(WB + co + 32);
          d0 = fmaf(o0[0], wa.x, d0); d0 = fmaf(o0[1], wa.y, d0); d0 = fmaf(o1[0], wb.x, d0); d0 = fmaf(o1[1], wb.y, d0);
          d1 = fmaf(o0[2], wa.x, d1); d1 = fmaf(o0[3], wa.y, d1); d1 = fmaf(o1[2], wb.x, d1); d1 = fmaf(o1[3], wb.y, d1);
        }
#pragma unroll
        for (int e = 0; e < 16; e++) aq[e] = aq[16 + e];
#pragma unroll
        for (int e = 0; e < 4; e++) {
          prev[0][e] = prev[1][e]; prev[2][e] = prev[3][e];
          lo[0][e] = lo[1][e]; lo[2][e] = lo[3][e];
          hi[0][e] = hi[1][e]; hi[2][e] = hi[3][e];
        }
      }
#pragma unroll
      for (int o = 1; o <= 2; o <<= 1) { d0 += __shfl_xor_sync(0xffffffffu, d0, o); d1 += __shfl_xor_sync(0xffffffffu, d1, o); }
      if (c == 0) ll_st(X->e2s + (xw * 8 + j) * 8 + r, __float_as_uint(d0), __float_as_uint(d1), 0, 0, tag);
    }
    PSTAMP(5);

    float ah[32];
    uint32_t sv[2][4];
    unpack32(ah, xres);
    {
      uint32_t og[2][14][4];
      const uint4* osrc[7];
#pragma unroll
      for (int i = 0; i < 7; i++) osrc[i] = X->e2 + (xw * 32 + 4 * kb_at(i + 1, j)) * 32 + lane;
      const uint4* ssrc = X->e2s + (xw * 8 + 2 * c) * 8 + r;
      auto oissue = [&](int hp) {
#pragma unroll
        for (int i = 0; i < 14; i++) ll_ld(og[hp][i], osrc[i >> 1] + (2 * hp + (i & 1)) * 32);
        if (hp == 1) ll_issue<2>(sv, ssrc, 8);
      };
      auto omma = [&](int hp) {
        ll_clear<14>(og[hp]);
        keep(og[hp]);
        wg_fence();
#pragma unroll
        for (int i = 0; i < 14; i++) wgmma_rs_n64(ah, og[hp][i], descB(H0) + kb_at((i >> 1) + 1, j) * 512 + (2 * hp + (i & 1)) * 128, 1);
        wg_commit();
      };
      mbar_wait(BAR + B_FWO * 8);
      keep(ah); keep(of);
      wg_fence();
#pragma unroll
      for (int k = 0; k < 4; k++) wgmma_rs_n64(ah, of[k], descB(H0) + j * 512 + k * 128, 1);
      wg_commit();
      uint32_t it = 0;
#pragma unroll 1
      do { oissue(0); } while (ll_bad<14>(og[0], tag) && ++it < SPIN_LIMIT);
      PSTAMP(6);
      oissue(1);
      omma(0);
      const uint32_t tg = pin(tag, zero);
      if (__builtin_expect(ll_any(ll_acc<14>(og[1], tg, ll_acc<2>(sv, tg))), 0)) {
#pragma unroll 1
        do { oissue(1); } while (ll_any(ll_acc<14>(og[1], tag, ll_acc<2>(sv, tag))) && ++it < SPIN_LIMIT);
      }
      PSTAMP(16);
      omma(1);
      ll_clear<2>(sv);
    }
    float m0 = __uint_as_float(sv[0][0]) + __uint_as_float(sv[1][0]), m1 = __uint_as_float(sv[0][1]) + __uint_as_float(sv[1][1]);
#pragma unroll
    for (int o = 1; o <= 2; o <<= 1) { m0 += __shfl_xor_sync(0xffffffffu, m0, o); m1 += __shfl_xor_sync(0xffffffffu, m1, o); }
    const uint32_t mu0 = pack2(m0 + st0.x, m0 + st0.x), mu1 = pack2(m1 + st1.x, m1 + st1.x);
    wg_wait<0>();
    keep(ah);
    if (lane == 0) mbar_arrive(BAR + B_WODONE * 8);
    PSTAMP(7);

    uint32_t hf[4][4], ra[4][4];
    pack32(hf, ah);
    {
      uint4* dst = X->e3h + (xw * 32 + 4 * j) * 32 + lane;
#pragma unroll
      for (int u = 0; u < 4; u++) {
        ra[u][0] = hsub2(hf[u][0], mu0); ra[u][1] = hsub2(hf[u][1], mu1);
        ra[u][2] = hsub2(hf[u][2], mu0); ra[u][3] = hsub2(hf[u][3], mu1);
        ll_st(dst + u * 32, ra[u][0], ra[u][1], ra[u][2], ra[u][3], tag);
      }
      float s0 = 0.f, q0 = 0.f, s1 = 0.f, q1 = 0.f;
#pragma unroll
      for (int b = 0; b < 8; b++) {
        s0 += ah[4 * b] + ah[4 * b + 1]; s1 += ah[4 * b + 2] + ah[4 * b + 3];
        q0 = fmaf(ah[4 * b], ah[4 * b], q0); q0 = fmaf(ah[4 * b + 1], ah[4 * b + 1], q0);
        q1 = fmaf(ah[4 * b + 2], ah[4 * b + 2], q1); q1 = fmaf(ah[4 * b + 3], ah[4 * b + 3], q1);
      }
#pragma unroll
      for (int o = 1; o <= 2; o <<= 1) {
        s0 += __shfl_xor_sync(0xffffffffu, s0, o); q0 += __shfl_xor_sync(0xffffffffu, q0, o);
        s1 += __shfl_xor_sync(0xffffffffu, s1, o); q1 += __shfl_xor_sync(0xffffffffu, q1, o);
      }
      if (c == 0) ll_st(X->e3s + (xw * 8 + j) * 8 + r, __float_as_uint(s0), __float_as_uint(q0), __float_as_uint(s1), __float_as_uint(q1), tag);
      mbar_wait(BAR + (p == 0 ? B_EQ + 7 : B_WODONE) * 8);
    }
    PSTAMP(8);

    float rs0, rs1;
    auto swiglu = [&](float g0, float g1, float u0, float u1, float rs) -> uint32_t {
      const float hr = 0.5f * rs;
      const float x0 = g0 * hr, x1 = g1 * hr;
      const float t0 = tanhf_hw(x0), t1 = tanhf_hw(x1);
      return pack2(fmaf(x0, t0, x0) * (u0 * rs), fmaf(x1, t1, x1) * (u1 * rs));
    };
    uint32_t hA[6][4];
    {
      float a1[64], a2[32];
      const uint4* src = X->e3h + xw * 32 * 32 + lane;
      uint32_t rb[4][4], rc[4][4], rd[4][4];
      auto fetch = [&](uint32_t (&a)[4][4], int i) { ll_issue<4>(a, src + kb_at(i, j) * 128, 32); };
      auto check = [&](uint32_t (&a)[4][4], uint32_t (&b)[4][4], int i) {
        const uint32_t tg = pin(tag, zero);
        if (__builtin_expect(ll_any(ll_acc<4>(a, tg, ll_acc<4>(b, tg))), 0)) {
          uint32_t it = 0;
#pragma unroll 1
          do { fetch(a, i); fetch(b, i + 1); } while (ll_any(ll_acc<4>(a, tag, ll_acc<4>(b, tag))) && ++it < SPIN_LIMIT);
        }
        ll_clear<4>(a); ll_clear<4>(b);
        keep(a); keep(b);
      };
      auto head = [&](uint32_t (&a)[4][4], int i) {
        mbar_wait(BAR + (B_FA + i) * 8);
        wg_fence();
        wgmma_rs_n64<DESC_HI64>(a2, a[0], descBh(RING + 16384) + (i & 3) * 1536, i);
        wgmma_rs_n128(a1, a[0], descB(RING) + (i & 3) * 1536, i);
        wg_commit();
#pragma unroll
        for (int u = 0; u < 4; u++) stsm4(Hn + w * 2048 + i * 8192 + (moff ^ (u << 5)), a[u]);
        wg_wait<1>();
        if (i > 0) mbar_arrive_if(BAR + (B_EA + i - 1) * 8, lane == 0);
      };
      auto rest = [&](uint32_t (&a)[4][4], int i) {
        wg_fence();
#pragma unroll
        for (int k = 1; k < 4; k++) {
          wgmma_rs_n64<DESC_HI64>(a2, a[k], descBh(RING + 16384) + (i & 3) * 1536 + k * 64, 1);
          wgmma_rs_n128(a1, a[k], descB(RING) + (i & 3) * 1536 + k * 128, 1);
        }
        wg_commit();
      };
      ll_clear<4>(ra);
      keep(ra);
      head(ra, 0); rest(ra, 0);
      ll_get<4>(rb, src + kb_at(1, j) * 128, 32, tag);
      keep(rb);
      PSTAMP(17);
      fetch(rc, 2); fetch(rd, 3);
      head(rb, 1); rest(rb, 1);
      check(rc, rd, 2);
      head(rc, 2); fetch(ra, 4); fetch(rb, 5); rest(rc, 2);
      head(rd, 3); rest(rd, 3);
      check(ra, rb, 4);
      head(ra, 4); fetch(rc, 6); fetch(rd, 7); ll_issue<2>(sv, X->e3s + (xw * 8 + 2 * c) * 8 + r, 8); rest(ra, 4);
      head(rb, 5); rest(rb, 5);
      check(rc, rd, 6);
      head(rc, 6); rest(rc, 6);
      head(rd, 7); rest(rd, 7);
      fence_async_smem();
      ll_wait<2>(sv, X->e3s + (xw * 8 + 2 * c) * 8 + r, 8, tag);
      float s0 = __uint_as_float(sv[0][0]) + __uint_as_float(sv[1][0]), q0 = __uint_as_float(sv[0][1]) + __uint_as_float(sv[1][1]);
      float s1 = __uint_as_float(sv[0][2]) + __uint_as_float(sv[1][2]), q1 = __uint_as_float(sv[0][3]) + __uint_as_float(sv[1][3]);
#pragma unroll
      for (int o = 1; o <= 2; o <<= 1) {
        s0 += __shfl_xor_sync(0xffffffffu, s0, o); q0 += __shfl_xor_sync(0xffffffffu, q0, o);
        s1 += __shfl_xor_sync(0xffffffffu, s1, o); q1 += __shfl_xor_sync(0xffffffffu, q1, o);
      }
      s0 *= 1.f / D_; s1 *= 1.f / D_;
      rs0 = rsqrtf(fmaxf(fmaf(-s0, s0, q0 * (1.f / D_)), 0.f) + 1e-5f);
      rs1 = rsqrtf(fmaxf(fmaf(-s1, s1, q1 * (1.f / D_)), 0.f) + 1e-5f);
      wg_wait<0>();
      keep(a1); keep(a2);
      if (lane == 0) mbar_arrive(BAR + (B_EA + 7) * 8);
      PSTAMP(9);
#pragma unroll
      for (int u = 0; u < 4; u++)
#pragma unroll
        for (int e = 0; e < 4; e++)
          hA[u][e] = swiglu(a1[8 * u + 2 * e], a1[8 * u + 2 * e + 1], a1[32 + 8 * u + 2 * e], a1[33 + 8 * u + 2 * e], (e & 1) ? rs1 : rs0);
#pragma unroll
      for (int u = 0; u < 2; u++)
#pragma unroll
        for (int e = 0; e < 4; e++)
          hA[4 + u][e] = swiglu(a2[8 * u + 2 * e], a2[8 * u + 2 * e + 1], a2[16 + 8 * u + 2 * e], a2[17 + 8 * u + 2 * e], (e & 1) ? rs1 : rs0);
      keep(hA);
      wg_bar(p);
    }
    PSTAMP(10);

    uint32_t hB[8][4];
    {
      float ab[128];
      uint32_t db = descB(RING);
      const uint32_t dAn = descA(H1) - p * 4096;
#pragma unroll 1
      for (int i = 0; i < 8; i++) {
        mbar_wait(BAR + (B_FB + i) * 8);
        const uint32_t da = dAn + i * 512;
        wg_fence();
        wgmma_ss_n256(ab, da, db, i);
#pragma unroll
        for (int k = 1; k < 4; k++) wgmma_ss_n256(ab, da + k * 2, db + k * 128, 1);
        wg_commit();
        wg_wait<1>();
        mbar_arrive_if(BAR + (B_EB + i - 1) * 8, i > 0 && lane == 0);
        db = db == descB(RING + 65536) ? descB(RING) : db + 2048;
      }
      wg_wait<0>();
      keep(ab);
      if (lane == 0) mbar_arrive(BAR + (B_EB + 7) * 8);
      PSTAMP(11);
#pragma unroll
      for (int u = 0; u < 8; u++) {
        const int o = (u >> 2) * 64 + (u & 3) * 8;
#pragma unroll
        for (int e = 0; e < 4; e++)
          hB[u][e] = swiglu(ab[o + 2 * e], ab[o + 2 * e + 1], ab[o + 32 + 2 * e], ab[o + 33 + 2 * e], (e & 1) ? rs1 : rs0);
      }
      keep(hB);
    }
    PSTAMP(12);

    {
      float y[32], sum[32];
      unpack32(sum, hf);
      const uint32_t offA = (j & 1) ? 256 : 0, offH = (j & 1) ? 0 : 1536;
      uint4* e4 = X->e4 + (size_t)xw * 64 * 128 + lane;
      uint32_t in[4][4];
#pragma unroll
      for (int u = 0; u < 4; u++) { in[u][0] = tag; in[u][1] = 0; in[u][2] = 0; in[u][3] = 0; }
      auto insrc = [&](int q) { return e4 + (j * 8 + ((j - 1 - q) & 7)) * 128; };
      mbar_wait(BAR + B_CLR * 8);
      auto acc = [&]() {
#pragma unroll
        for (int u = 0; u < 4; u++) {
          sum[8 * u] += bf_lo(in[u][0] & ~1u); sum[8 * u + 1] += bf_hi(in[u][0]);
#pragma unroll
          for (int e = 1; e < 4; e++) { sum[8 * u + 2 * e] += bf_lo(in[u][e]); sum[8 * u + 2 * e + 1] += bf_hi(in[u][e]); }
        }
      };
#pragma unroll 1
      for (int m = 0; m < 8; m++) {
        if (m >= 2) ll_issue<4>(in, insrc(m - 2), 32);
        mbar_wait(BAR + (B_FT + m) * 8);
        const uint32_t T = descB(0) + (t_addr(m) >> 4);
        asm volatile("{\n.reg .pred p;\nsetp.ne.u32 p, %1, 0;\n@p bar.sync %0, 256;\n}\n"
                     ::"r"(6 + p), "r"((uint32_t)(p == 0 ? m > PP_AHEAD : m + PP_AHEAD < 8)) : "memory");
        wg_fence();
#pragma unroll
        for (int k = 0; k < 4; k++) wgmma_rs_n64(y, hA[k], T + offA + k * 128, k);
#pragma unroll
        for (int k = 0; k < 2; k++) wgmma_rs_n64(y, hA[4 + k], T + offH + k * 128, 1);
#pragma unroll
        for (int k = 0; k < 8; k++) wgmma_rs_n64(y, hB[k], T + offA + 512 + k * 128, 1);
        wg_commit();
        asm volatile("{\n.reg .pred p;\nsetp.ne.u32 p, %1, 0;\n@p bar.arrive %0, 256;\n}\n"
                     ::"r"(7 - p), "r"((uint32_t)(p == 0 ? m >= PP_AHEAD : m + PP_AHEAD < 7)) : "memory");
        wg_wait<0>();
        keep(y);
        mbar_arrive_if(BAR + B_ET0 * 8, m == 0 && lane == 0);
        uint4* dst = e4 + (((j + 1 + m) & 7) * 8 + j) * 128;
        uint32_t pk[4][4];
        pack32(pk, y);
#pragma unroll
        for (int u = 0; u < 4; u++) ll_st(dst + u * 32, pk[u][0], pk[u][1], pk[u][2], pk[u][3], tag);
        if (m == 7) PSTAMP(13);
        if (m == 1) PSTAMP(27);
        if (m == 3) PSTAMP(26);
        if (m == 5) PSTAMP(28);
        if (__builtin_expect(ll_bad<4>(in, pin(tag, zero)), 0)) ll_spin<4>(in, insrc(m - 2), 32, tag);
        acc();
      }
      ll_spin<4>(in, insrc(6), 32, tag);
      acc();
      PSTAMP(14);
      const uint32_t stg = H0 + p * 65536 + 28672 + (w >> 1) * 32768 + (w & 1) * 2048;
#pragma unroll
      for (int u = 0; u < 4; u++) {
        uint32_t o[4];
#pragma unroll
        for (int e = 0; e < 4; e++) o[e] = pack2(sum[8 * u + 2 * e] + y[8 * u + 2 * e], sum[8 * u + 2 * e + 1] + y[8 * u + 2 * e + 1]);
        stsm4(stg + (moff ^ (u << 5)), o);
      }
      fence_async_smem();
      __syncwarp();
      if (elect_one()) {
        tma3d_store(&P.out, stg, 64 * j, p, g * 64 + 16 * w);
        asm volatile("cp.async.bulk.commit_group;" ::: "memory");
        asm volatile("cp.async.bulk.wait_group.read 0;" ::: "memory");
      }
      PSTAMP(15);
    }
  }
}

typedef CUresult (*EncodeFn)(CUtensorMap*, CUtensorMapDataType, cuuint32_t, void*, const cuuint64_t*, const cuuint64_t*,
                             const cuuint32_t*, const cuuint32_t*, CUtensorMapInterleave, CUtensorMapSwizzle,
                             CUtensorMapL2promotion, CUtensorMapFloatOOBfill);

void enc2d(EncodeFn f, CUtensorMap* m, const void* base, uint64_t cols, uint64_t rows, uint32_t bc, uint32_t br, CUtensorMapSwizzle sw) {
  cuuint64_t gd[2] = {cols, rows}, gs[1] = {cols * 2};
  cuuint32_t bd[2] = {bc, br}, es[2] = {1, 1};
  f(m, CU_TENSOR_MAP_DATA_TYPE_BFLOAT16, 2, const_cast<void*>(base), gd, gs, bd, es, CU_TENSOR_MAP_INTERLEAVE_NONE, sw,
    CU_TENSOR_MAP_L2_PROMOTION_L2_128B, CU_TENSOR_MAP_FLOAT_OOB_FILL_NONE);
}
void enc_par(EncodeFn f, CUtensorMap* m, const void* base, uint32_t pairs) {
  cuuint64_t gd[3] = {(cuuint64_t)D_, 2, (cuuint64_t)S_ / 2}, gs[2] = {D_ * 2, D_ * 4};
  cuuint32_t bd[3] = {64, 1, pairs}, es[3] = {1, 1, 1};
  f(m, CU_TENSOR_MAP_DATA_TYPE_BFLOAT16, 3, const_cast<void*>(base), gd, gs, bd, es, CU_TENSOR_MAP_INTERLEAVE_NONE,
    CU_TENSOR_MAP_SWIZZLE_128B, CU_TENSOR_MAP_L2_PROMOTION_L2_128B, CU_TENSOR_MAP_FLOAT_OOB_FILL_NONE);
}

}

extern "C" void kernel_launch(void* const* d_in, const int* in_sizes, int n_in, void* d_out, int out_size) {
  (void)in_sizes; (void)n_in; (void)out_size;
  static EncodeFn enc = nullptr;
  static Scratch* scratch = nullptr;
  if (!enc) {
    void* fn = nullptr;
    cudaDriverEntryPointQueryResult q;
    cudaGetDriverEntryPoint("cuTensorMapEncodeTiled", &fn, cudaEnableDefault, &q);
    enc = (EncodeFn)fn;
    cudaGetSymbolAddress((void**)&scratch, g_scratch);
    cudaFuncSetAttribute(fused_block_kernel, cudaFuncAttributeMaxDynamicSharedMemorySize, SMEM_BYTES);
  }
  Params P;
  const __nv_bfloat16* xp = (const __nv_bfloat16*)d_in[0];
  const __nv_bfloat16* wqkvp = (const __nv_bfloat16*)d_in[1];
  const __nv_bfloat16* wop = (const __nv_bfloat16*)d_in[2];
  P.w1p = (const __nv_bfloat16*)d_in[4];
  P.w3p = (const __nv_bfloat16*)d_in[5];
  P.w2p = (const __nv_bfloat16*)d_in[6];
  enc_par(enc, &P.x, xp, 64);
  enc_par(enc, &P.out, d_out, 16);
  enc2d(enc, &P.wqkv, wqkvp, 3 * D_, D_, 64, 64, CU_TENSOR_MAP_SWIZZLE_128B);
  enc2d(enc, &P.wo, wop, D_, D_, 64, 64, CU_TENSOR_MAP_SWIZZLE_128B);
  enc2d(enc, &P.w1, P.w1p, F_, D_, 64, 64, CU_TENSOR_MAP_SWIZZLE_128B);
  enc2d(enc, &P.w3, P.w3p, F_, D_, 64, 64, CU_TENSOR_MAP_SWIZZLE_128B);
  enc2d(enc, &P.w1h, P.w1p, F_, D_, 32, 64, CU_TENSOR_MAP_SWIZZLE_64B);
  enc2d(enc, &P.w3h, P.w3p, F_, D_, 32, 64, CU_TENSOR_MAP_SWIZZLE_64B);
  enc2d(enc, &P.w2, P.w2p, D_, F_, 64, 224, CU_TENSOR_MAP_SWIZZLE_128B);

  cudaLaunchConfig_t cfg = {};
  cfg.gridDim = dim3(128);
  cfg.blockDim = dim3(384);
  cfg.dynamicSmemBytes = SMEM_BYTES;
  cfg.stream = cudaStreamPerThread;
  cudaLaunchAttribute at[1];
  at[0].id = cudaLaunchAttributeCooperative;
  at[0].val.cooperative = 1;
  cfg.attrs = at;
  cfg.numAttrs = 1;
  cudaLaunchKernelEx(&cfg, fused_block_kernel, scratch, xp, wqkvp, wop, 0u, P);
}
```

```cpp
#include <cuda_runtime.h>
#include <cuda.h>
#include <cuda_bf16.h>
#include <stdint.h>

namespace {

constexpr int S_ = 2048, D_ = 512, F_ = 1792;
#define LAG_KB 3
#define E4_FIRST 0
#define PP_AHEAD 1
#define SIDE_KB 0
#define XO_DELAY 2

constexpr uint32_t SPIN_LIMIT = 1u << 18;

struct Scratch {
  uint4 e4[16 * 2 * 4 * 8 * 8 * 4 * 32];
  uint4 e2[16 * 2 * 4 * 32 * 32];
  uint4 e3h[16 * 2 * 4 * 32 * 32];
  uint4 e1[16 * 8 * 2 * 4 * 32];
  uint4 e2s[16 * 2 * 4 * 8 * 8];
  uint4 e3s[16 * 2 * 4 * 8 * 8];
  uint4 e0c[8 * 3 * 16 * 16];
  uint4 e0s[2048];
  uint4 e0w[8 * 64];
  unsigned epoch[128];
};
__device__ Scratch g_scratch;
#define PSTAMP(i)
#define PSTAMPW(slot, i)

struct alignas(64) Params {
  CUtensorMap x, out, wqkv, wo, w1, w3, w1h, w3h, w2;
  const __nv_bfloat16 *w1p, *w3p, *w2p;
};

constexpr uint32_t SB = 1024;
constexpr uint32_t H0 = SB;
constexpr uint32_t H1 = SB + 65536;
constexpr uint32_t RING = SB + 131072;
constexpr uint32_t BAR = SB + 229376;
constexpr uint32_t TAGS = BAR + 1016;
constexpr uint32_t CS = BAR + 1024;
constexpr uint32_t ST = CS + 768;
constexpr uint32_t WB = ST + 1024;
constexpr uint32_t SMEM_BYTES = 232448;
static_assert(WB + 256 <= SB + SMEM_BYTES, "smem");

enum : int {
  B_FX = 0,
  B_FKV = 16, B_FQ = 24, B_FWO = 32, B_FA = 40, B_FB = 48, B_FT = 56,
  B_EKV = 64, B_EQ = 72, B_EA = 80, B_EB = 88, B_ET0 = 96,
  B_WODONE = 97,
  B_EX = 104,
  B_LAG = 112, B_READY = 113, B_PUB = 114, B_CLR = 115, B_TAG = 116
};

__device__ __forceinline__ uint32_t smem_u32(const void* p) { return (uint32_t)__cvta_generic_to_shared(p); }
__device__ __forceinline__ void mbar_init(uint32_t b, uint32_t c) { asm volatile("mbarrier.init.shared::cta.b64 [%0], %1;" ::"r"(b), "r"(c) : "memory"); }
__device__ __forceinline__ void mbar_expect_tx(uint32_t b, uint32_t bytes) { asm volatile("mbarrier.arrive.expect_tx.shared::cta.b64 _, [%0], %1;" ::"r"(b), "r"(bytes) : "memory"); }
__device__ __forceinline__ void mbar_arrive(uint32_t b) { asm volatile("mbarrier.arrive.shared::cta.b64 _, [%0];" ::"r"(b) : "memory"); }
__device__ __forceinline__ void mbar_wait(uint32_t b) {
  asm volatile("{\n.reg .pred p;\n.reg .u32 c;\nmov.u32 c, 0;\nLW:\n.pragma \"nounroll\";\n"
               "mbarrier.try_wait.parity.shared::cta.b64 p, [%0], 0;\nadd.u32 c, c, 1;\nsetp.gt.or.u32 p, c, %1, p;\n@!p bra LW;\n}\n"
               ::"r"(b), "n"(SPIN_LIMIT) : "memory");
}
__device__ __forceinline__ bool elect_one() {
  uint32_t p;
  asm volatile("{\n.reg .pred P;\nelect.sync _|P, 0xffffffff;\nselp.u32 %0, 1, 0, P;\n}\n" : "=r"(p));
  return p;
}
__device__ __forceinline__ void tma2d(uint32_t dst, const CUtensorMap* m, int c0, int c1, uint32_t bar) {
  asm volatile("cp.async.bulk.tensor.2d.shared::cluster.global.mbarrier::complete_tx::bytes [%0], [%1, {%3, %4}], [%2];"
               ::"r"(dst), "l"(m), "r"(bar), "r"(c0), "r"(c1) : "memory");
}
__device__ __forceinline__ void tma3d(uint32_t dst, const CUtensorMap* m, int c0, int c1, int c2, uint32_t bar) {
  asm volatile("cp.async.bulk.tensor.3d.shared::cluster.global.mbarrier::complete_tx::bytes [%0], [%1, {%3, %4, %5}], [%2];"
               ::"r"(dst), "l"(m), "r"(bar), "r"(c0), "r"(c1), "r"(c2) : "memory");
}
__device__ __forceinline__ void tma3d_store(const CUtensorMap* m, uint32_t src, int c0, int c1, int c2) {
  asm volatile("cp.async.bulk.tensor.3d.global.shared::cta.bulk_group [%0, {%2, %3, %4}], [%1];"
               ::"l"(m), "r"(src), "r"(c0), "r"(c1), "r"(c2) : "memory");
}
__device__ __forceinline__ void l2_prefetch(const void* p, uint32_t bytes) {
  asm volatile("cp.async.bulk.prefetch.L2.global [%0], %1;" ::"l"(p), "r"(bytes) : "memory");
}
__device__ __forceinline__ void prefetch_map(const CUtensorMap* m) { asm volatile("prefetch.tensormap [%0];" ::"l"(m) : "memory"); }
__device__ __forceinline__ void fence_async_smem() { asm volatile("fence.proxy.async.shared::cta;" ::: "memory"); }
__device__ __forceinline__ void wg_fence() { asm volatile("wgmma.fence.sync.aligned;" ::: "memory"); }
__device__ __forceinline__ void wg_commit() { asm volatile("wgmma.commit_group.sync.aligned;" ::: "memory"); }
template <int N> __device__ __forceinline__ void wg_wait() { asm volatile("wgmma.wait_group.sync.aligned %0;" ::"n"(N) : "memory"); }
__device__ __forceinline__ void wg_bar(int p) {
  if (p == 0) asm volatile("bar.sync 1, 128;" ::: "memory"); else asm volatile("bar.sync 2, 128;" ::: "memory");
}
constexpr uint32_t DESC_HI128 = (1024 >> 4) | (1u << 30);
constexpr uint32_t DESC_HI64 = (512 >> 4) | (2u << 30);
__device__ __forceinline__ constexpr uint32_t descA(uint32_t addr) { return (addr >> 4) | (1u << 16); }
__device__ __forceinline__ constexpr uint32_t descB(uint32_t addr) { return (addr >> 4) | ((8192u >> 4) << 16); }
__device__ __forceinline__ constexpr uint32_t descBh(uint32_t addr) { return (addr >> 4) | ((4096u >> 4) << 16); }

__device__ __forceinline__ void wgmma_ss_n64(float (&d)[32], uint32_t da, uint32_t db, int sc) {
  asm volatile("{\n.reg .pred p;\n.reg .b64 da, db;\nsetp.ne.b32 p, %34, 0;\nmov.b64 da, {%32, %35};\nmov.b64 db, {%33, %35};\n"
    "wgmma.mma_async.sync.aligned.m64n64k16.f32.bf16.bf16 {%0, %1, %2, %3, %4, %5, %6, %7, %8, %9, %10, %11, %12, %13, %14, %15, %16, %17, %18, %19, %20, %21, %22, %23, %24, %25, %26, %27, %28, %29, %30, %31}, da, db, p, 1, 1, 0, 1;\n}\n"
    : "+f"(d[0]), "+f"(d[1]), "+f"(d[2]), "+f"(d[3]), "+f"(d[4]), "+f"(d[5]), "+f"(d[6]), "+f"(d[7]),
      "+f"(d[8]), "+f"(d[9]), "+f"(d[10]), "+f"(d[11]), "+f"(d[12]), "+f"(d[13]), "+f"(d[14]), "+f"(d[15]),
      "+f"(d[16]), "+f"(d[17]), "+f"(d[18]), "+f"(d[19]), "+f"(d[20]), "+f"(d[21]), "+f"(d[22]), "+f"(d[23]),
      "+f"(d[24]), "+f"(d[25]), "+f"(d[26]), "+f"(d[27]), "+f"(d[28]), "+f"(d[29]), "+f"(d[30]), "+f"(d[31])
    : "r"(da), "r"(db), "r"(sc), "n"(DESC_HI128));
}
__device__ __forceinline__ void wgmma_ss_n128(float (&d)[64], uint32_t da, uint32_t db, int sc) {
  asm volatile("{\n.reg .pred p;\n.reg .b64 da, db;\nsetp.ne.b32 p, %66, 0;\nmov.b64 da, {%64, %67};\nmov.b64 db, {%65, %67};\n"
    "wgmma.mma_async.sync.aligned.m64n128k16.f32.bf16.bf16 {%0, %1, %2, %3, %4, %5, %6, %7, %8, %9, %10, %11, %12, %13, %14, %15, %16, %17, %18, %19, %20, %21, %22, %23, %24, %25, %26, %27, %28, %29, %30, %31, %32, %33, %34, %35, %36, %37, %38, %39, %40, %41, %42, %43, %44, %45, %46, %47, %48, %49, %50, %51, %52, %53, %54, %55, %56, %57, %58, %59, %60, %61, %62, %63}, da, db, p, 1, 1, 0, 1;\n}\n"
    : "+f"(d[0]), "+f"(d[1]), "+f"(d[2]), "+f"(d[3]), "+f"(d[4]), "+f"(d[5]), "+f"(d[6]), "+f"(d[7]),
      "+f"(d[8]), "+f"(d[9]), "+f"(d[10]), "+f"(d[11]), "+f"(d[12]), "+f"(d[13]), "+f"(d[14]), "+f"(d[15]),
      "+f"(d[16]), "+f"(d[17]), "+f"(d[18]), "+f"(d[19]), "+f"(d[20]), "+f"(d[21]), "+f"(d[22]), "+f"(d[23]),
      "+f"(d[24]), "+f"(d[25]), "+f"(d[26]), "+f"(d[27]), "+f"(d[28]), "+f"(d[29]), "+f"(d[30]), "+f"(d[31]),
      "+f"(d[32]), "+f"(d[33]), "+f"(d[34]), "+f"(d[35]), "+f"(d[36]), "+f"(d[37]), "+f"(d[38]), "+f"(d[39]),
      "+f"(d[40]), "+f"(d[41]), "+f"(d[42]), "+f"(d[43]), "+f"(d[44]), "+f"(d[45]), "+f"(d[46]), "+f"(d[47]),
      "+f"(d[48]), "+f"(d[49]), "+f"(d[50]), "+f"(d[51]), "+f"(d[52]), "+f"(d[53]), "+f"(d[54]), "+f"(d[55]),
      "+f"(d[56]), "+f"(d[57]), "+f"(d[58]), "+f"(d[59]), "+f"(d[60]), "+f"(d[61]), "+f"(d[62]), "+f"(d[63])
    : "r"(da), "r"(db), "r"(sc), "n"(DESC_HI128));
}
__device__ __forceinline__ void wgmma_ss_n256(float (&d)[128], uint32_t da, uint32_t db, int sc) {
  asm volatile("{\n.reg .pred p;\n.reg .b64 da, db;\nsetp.ne.b32 p, %130, 0;\nmov.b64 da, {%128, %131};\nmov.b64 db, {%129, %131};\n"
    "wgmma.mma_async.sync.aligned.m64n256k16.f32.bf16.bf16 {%0, %1, %2, %3, %4, %5, %6, %7, %8, %9, %10, %11, %12, %13, %14, %15, %16, %17, %18, %19, %20, %21, %22, %23, %24, %25, %26, %27, %28, %29, %30, %31, %32, %33, %34, %35, %36, %37, %38, %39, %40, %41, %42, %43, %44, %45, %46, %47, %48, %49, %50, %51, %52, %53, %54, %55, %56, %57, %58, %59, %60, %61, %62, %63, %64, %65, %66, %67, %68, %69, %70, %71, %72, %73, %74, %75, %76, %77, %78, %79, %80, %81, %82, %83, %84, %85, %86, %87, %88, %89, %90, %91, %92, %93, %94, %95, %96, %97, %98, %99, %100, %101, %102, %103, %104, %105, %106, %107, %108, %109, %110, %111, %112, %113, %114, %115, %116, %117, %118, %119, %120, %121, %122, %123, %124, %125, %126, %127}, da, db, p, 1, 1, 0, 1;\n}\n"
    : "+f"(d[0]), "+f"(d[1]), "+f"(d[2]), "+f"(d[3]), "+f"(d[4]), "+f"(d[5]), "+f"(d[6]), "+f"(d[7]),
      "+f"(d[8]), "+f"(d[9]), "+f"(d[10]), "+f"(d[11]), "+f"(d[12]), "+f"(d[13]), "+f"(d[14]), "+f"(d[15]),
      "+f"(d[16]), "+f"(d[17]), "+f"(d[18]), "+f"(d[19]), "+f"(d[20]), "+f"(d[21]), "+f"(d[22]), "+f"(d[23]),
      "+f"(d[24]), "+f"(d[25]), "+f"(d[26]), "+f"(d[27]), "+f"(d[28]), "+f"(d[29]), "+f"(d[30]), "+f"(d[31]),
      "+f"(d[32]), "+f"(d[33]), "+f"(d[34]), "+f"(d[35]), "+f"(d[36]), "+f"(d[37]), "+f"(d[38]), "+f"(d[39]),
      "+f"(d[40]), "+f"(d[41]), "+f"(d[42]), "+f"(d[43]), "+f"(d[44]), "+f"(d[45]), "+f"(d[46]), "+f"(d[47]),
      "+f"(d[48]), "+f"(d[49]), "+f"(d[50]), "+f"(d[51]), "+f"(d[52]), "+f"(d[53]), "+f"(d[54]), "+f"(d[55]),
      "+f"(d[56]), "+f"(d[57]), "+f"(d[58]), "+f"(d[59]), "+f"(d[60]), "+f"(d[61]), "+f"(d[62]), "+f"(d[63]),
      "+f"(d[64]), "+f"(d[65]), "+f"(d[66]), "+f"(d[67]), "+f"(d[68]), "+f"(d[69]), "+f"(d[70]), "+f"(d[71]),
      "+f"(d[72]), "+f"(d[73]), "+f"(d[74]), "+f"(d[75]), "+f"(d[76]), "+f"(d[77]), "+f"(d[78]), "+f"(d[79]),
      "+f"(d[80]), "+f"(d[81]), "+f"(d[82]), "+f"(d[83]), "+f"(d[84]), "+f"(d[85]), "+f"(d[86]), "+f"(d[87]),
      "+f"(d[88]), "+f"(d[89]), "+f"(d[90]), "+f"(d[91]), "+f"(d[92]), "+f"(d[93]), "+f"(d[94]), "+f"(d[95]),
      "+f"(d[96]), "+f"(d[97]), "+f"(d[98]), "+f"(d[99]), "+f"(d[100]), "+f"(d[101]), "+f"(d[102]), "+f"(d[103]),
      "+f"(d[104]), "+f"(d[105]), "+f"(d[106]), "+f"(d[107]), "+f"(d[108]), "+f"(d[109]), "+f"(d[110]), "+f"(d[111]),
      "+f"(d[112]), "+f"(d[113]), "+f"(d[114]), "+f"(d[115]), "+f"(d[116]), "+f"(d[117]), "+f"(d[118]), "+f"(d[119]),
      "+f"(d[120]), "+f"(d[121]), "+f"(d[122]), "+f"(d[123]), "+f"(d[124]), "+f"(d[125]), "+f"(d[126]), "+f"(d[127])
    : "r"(da), "r"(db), "r"(sc), "n"(DESC_HI128));
}
template <uint32_t HI = DESC_HI128>
__device__ __forceinline__ void wgmma_rs_n64(float (&d)[32], const uint32_t (&a)[4], uint32_t db, int sc) {
  asm volatile("{\n.reg .pred p;\n.reg .b64 db;\nsetp.ne.b32 p, %37, 0;\nmov.b64 db, {%36, %38};\n"
    "wgmma.mma_async.sync.aligned.m64n64k16.f32.bf16.bf16 {%0, %1, %2, %3, %4, %5, %6, %7, %8, %9, %10, %11, %12, %13, %14, %15, %16, %17, %18, %19, %20, %21, %22, %23, %24, %25, %26, %27, %28, %29, %30, %31}, {%32, %33, %34, %35}, db, p, 1, 1, 1;\n}\n"
    : "+f"(d[0]), "+f"(d[1]), "+f"(d[2]), "+f"(d[3]), "+f"(d[4]), "+f"(d[5]), "+f"(d[6]), "+f"(d[7]),
      "+f"(d[8]), "+f"(d[9]), "+f"(d[10]), "+f"(d[11]), "+f"(d[12]), "+f"(d[13]), "+f"(d[14]), "+f"(d[15]),
      "+f"(d[16]), "+f"(d[17]), "+f"(d[18]), "+f"(d[19]), "+f"(d[20]), "+f"(d[21]), "+f"(d[22]), "+f"(d[23]),
      "+f"(d[24]), "+f"(d[25]), "+f"(d[26]), "+f"(d[27]), "+f"(d[28]), "+f"(d[29]), "+f"(d[30]), "+f"(d[31])
    : "r"(a[0]), "r"(a[1]), "r"(a[2]), "r"(a[3]), "r"(db), "r"(sc), "n"(HI));
}
template <uint32_t HI = DESC_HI128>
__device__ __forceinline__ void wgmma_rs_n128(float (&d)[64], const uint32_t (&a)[4], uint32_t db, int sc) {
  asm volatile("{\n.reg .pred p;\n.reg .b64 db;\nsetp.ne.b32 p, %69, 0;\nmov.b64 db, {%68, %70};\n"
    "wgmma.mma_async.sync.aligned.m64n128k16.f32.bf16.bf16 {%0, %1, %2, %3, %4, %5, %6, %7, %8, %9, %10, %11, %12, %13, %14, %15, %16, %17, %18, %19, %20, %21, %22, %23, %24, %25, %26, %27, %28, %29, %30, %31, %32, %33, %34, %35, %36, %37, %38, %39, %40, %41, %42, %43, %44, %45, %46, %47, %48, %49, %50, %51, %52, %53, %54, %55, %56, %57, %58, %59, %60, %61, %62, %63}, {%64, %65, %66, %67}, db, p, 1, 1, 1;\n}\n"
    : "+f"(d[0]), "+f"(d[1]), "+f"(d[2]), "+f"(d[3]), "+f"(d[4]), "+f"(d[5]), "+f"(d[6]), "+f"(d[7]),
      "+f"(d[8]), "+f"(d[9]), "+f"(d[10]), "+f"(d[11]), "+f"(d[12]), "+f"(d[13]), "+f"(d[14]), "+f"(d[15]),
      "+f"(d[16]), "+f"(d[17]), "+f"(d[18]), "+f"(d[19]), "+f"(d[20]), "+f"(d[21]), "+f"(d[22]), "+f"(d[23]),
      "+f"(d[24]), "+f"(d[25]), "+f"(d[26]), "+f"(d[27]), "+f"(d[28]), "+f"(d[29]), "+f"(d[30]), "+f"(d[31]),
      "+f"(d[32]), "+f"(d[33]), "+f"(d[34]), "+f"(d[35]), "+f"(d[36]), "+f"(d[37]), "+f"(d[38]), "+f"(d[39]),
      "+f"(d[40]), "+f"(d[41]), "+f"(d[42]), "+f"(d[43]), "+f"(d[44]), "+f"(d[45]), "+f"(d[46]), "+f"(d[47]),
      "+f"(d[48]), "+f"(d[49]), "+f"(d[50]), "+f"(d[51]), "+f"(d[52]), "+f"(d[53]), "+f"(d[54]), "+f"(d[55]),
      "+f"(d[56]), "+f"(d[57]), "+f"(d[58]), "+f"(d[59]), "+f"(d[60]), "+f"(d[61]), "+f"(d[62]), "+f"(d[63])
    : "r"(a[0]), "r"(a[1]), "r"(a[2]), "r"(a[3]), "r"(db), "r"(sc), "n"(HI));
}

template <int N> __device__ __forceinline__ void keep(float (&d)[N]) {
#pragma unroll
  for (int i = 0; i < N; i++) asm volatile("" : "+f"(d[i])::"memory");
}

__device__ __forceinline__ void keep(uint32_t (&d)[4]) { asm volatile("" : "+r"(d[0]), "+r"(d[1]), "+r"(d[2]), "+r"(d[3])::"memory"); }
template <int N> __device__ __forceinline__ void keep(uint32_t (&d)[N][4]) {
#pragma unroll
  for (int i = 0; i < N; i++) asm volatile("" : "+r"(d[i][0]), "+r"(d[i][1]), "+r"(d[i][2]), "+r"(d[i][3])::"memory");
}

__device__ __forceinline__ uint32_t pack2(float lo, float hi) {
  uint32_t r;
  asm("cvt.rn.bf16x2.f32 %0, %1, %2;" : "=r"(r) : "f"(hi), "f"(lo));
  return r;
}
__device__ __forceinline__ float bf_lo(uint32_t v) { return __uint_as_float(v << 16); }
__device__ __forceinline__ float bf_hi(uint32_t v) { return __uint_as_float(v & 0xffff0000u); }
__device__ __forceinline__ uint32_t hsub2(uint32_t a, uint32_t b) {
  uint32_t r;
  asm("sub.rn.bf16x2 %0, %1, %2;" : "=r"(r) : "r"(a), "r"(b));
  return r;
}
__device__ __forceinline__ uint32_t movm(uint32_t a) {
  uint32_t r;
  asm volatile("movmatrix.sync.aligned.m8n8.trans.b16 %0, %1;" : "=r"(r) : "r"(a));
  return r;
}
__device__ __forceinline__ void ldsm4(uint32_t (&v)[4], uint32_t a) {
  asm volatile("ldmatrix.sync.aligned.m8n8.x4.shared.b16 {%0,%1,%2,%3}, [%4];" : "=r"(v[0]), "=r"(v[1]), "=r"(v[2]), "=r"(v[3]) : "r"(a) : "memory");
}
__device__ __forceinline__ void stsm4(uint32_t a, const uint32_t (&v)[4]) {
  asm volatile("stmatrix.sync.aligned.m8n8.x4.shared.b16 [%0], {%1,%2,%3,%4};" ::"r"(a), "r"(v[0]), "r"(v[1]), "r"(v[2]), "r"(v[3]) : "memory");
}
__device__ __forceinline__ void mma16816(float (&d)[4], const uint32_t (&a)[4], uint32_t b0, uint32_t b1) {
  asm volatile("mma.sync.aligned.m16n8k16.row.col.f32.bf16.bf16.f32 {%0,%1,%2,%3}, {%4,%5,%6,%7}, {%8,%9}, {%10,%10,%10,%10};"
               : "=f"(d[0]), "=f"(d[1]), "=f"(d[2]), "=f"(d[3])
               : "r"(a[0]), "r"(a[1]), "r"(a[2]), "r"(a[3]), "r"(b0), "r"(b1), "f"(0.f));
}
__device__ __forceinline__ void mma1688_acc(float (&d)[4], uint32_t a0, uint32_t a1, uint32_t b0) {
  asm volatile("mma.sync.aligned.m16n8k8.row.col.f32.bf16.bf16.f32 {%0,%1,%2,%3}, {%4,%5}, {%6}, {%0,%1,%2,%3};"
               : "+f"(d[0]), "+f"(d[1]), "+f"(d[2]), "+f"(d[3]) : "r"(a0), "r"(a1), "r"(b0));
}
__device__ __forceinline__ float ex2(float x) { float y; asm("ex2.approx.ftz.f32 %0, %1;" : "=f"(y) : "f"(x)); return y; }
__device__ __forceinline__ float rcp(float x) { float y; asm("rcp.approx.ftz.f32 %0, %1;" : "=f"(y) : "f"(x)); return y; }
__device__ __forceinline__ float tanhf_hw(float x) { float y; asm("tanh.approx.f32 %0, %1;" : "=f"(y) : "f"(x)); return y; }
__device__ __forceinline__ uint32_t lds32(uint32_t a) { uint32_t v; asm volatile("ld.shared.u32 %0, [%1];" : "=r"(v) : "r"(a) : "memory"); return v; }
__device__ __forceinline__ float2 lds64(uint32_t a) { float2 v; asm volatile("ld.shared.v2.f32 {%0,%1}, [%2];" : "=f"(v.x), "=f"(v.y) : "r"(a) : "memory"); return v; }
__device__ __forceinline__ void lds128(uint32_t (&v)[4], uint32_t a) { asm volatile("ld.shared.v4.u32 {%0,%1,%2,%3}, [%4];" : "=r"(v[0]), "=r"(v[1]), "=r"(v[2]), "=r"(v[3]) : "r"(a) : "memory"); }
__device__ __forceinline__ void sts128(uint32_t a, const uint32_t (&v)[4]) { asm volatile("st.shared.v4.u32 [%0], {%1,%2,%3,%4};" ::"r"(a), "r"(v[0]), "r"(v[1]), "r"(v[2]), "r"(v[3]) : "memory"); }
__device__ __forceinline__ void ldg128_nc(uint32_t (&v)[4], const void* p) {
  asm volatile("ld.global.nc.L1::no_allocate.v4.u32 {%0,%1,%2,%3}, [%4];" : "=r"(v[0]), "=r"(v[1]), "=r"(v[2]), "=r"(v[3]) : "l"(p));
}
__device__ __forceinline__ uint32_t pin(uint32_t v, uint32_t zero) {
  asm volatile("{\n.reg .pred p;\n.reg .u32 c;\nmov.u32 c, %1;\nLP:\n.pragma \"nounroll\";\nsetp.eq.u32 p, c, 0;\n@p bra LD;\n"
               "nanosleep.u32 c;\nadd.u32 %0, %0, c;\nsub.u32 c, c, 1;\nbra LP;\nLD:\n}\n" : "+r"(v) : "r"(zero) : "memory");
  return v;
}
__device__ __forceinline__ void mbar_arrive_if(uint32_t b, bool cond) {
  asm volatile("{\n.reg .pred p;\nsetp.ne.u32 p, %1, 0;\n@p mbarrier.arrive.shared::cta.b64 _, [%0];\n}\n" ::"r"(b), "r"((uint32_t)cond) : "memory");
}
__device__ __forceinline__ uint32_t ld_epoch(const unsigned* p) {
  uint32_t v;
  asm volatile("ld.relaxed.gpu.global.u32 %0, [%1];" : "=r"(v) : "l"(p) : "memory");
  return v;
}
__device__ __forceinline__ void ll_st(uint4* p, uint32_t a, uint32_t b, uint32_t c, uint32_t d, uint32_t tag) {
  asm volatile("{\n.reg .b128 t;\n.reg .b64 lo, hi;\nmov.b64 lo, {%1, %2};\nmov.b64 hi, {%3, %4};\nmov.b128 t, {lo, hi};\n"
               "st.relaxed.gpu.global.b128 [%0], t;\n}\n" ::"l"(p), "r"((a & ~1u) | tag), "r"(b), "r"(c), "r"(d) : "memory");
}
__device__ __forceinline__ void ll_ld(uint32_t (&v)[4], const uint4* p) {
  asm volatile("{\n.reg .b128 t;\n.reg .b64 lo, hi;\nld.relaxed.gpu.global.b128 t, [%4];\nmov.b128 {lo, hi}, t;\n"
               "mov.b64 {%0, %1}, lo;\nmov.b64 {%2, %3}, hi;\n}\n"
               : "=r"(v[0]), "=r"(v[1]), "=r"(v[2]), "=r"(v[3]) : "l"(p) : "memory");
}
template <int N> __device__ __forceinline__ void ll_issue(uint32_t (&v)[N][4], const uint4* p, int stride) {
#pragma unroll
  for (int i = 0; i < N; i++) ll_ld(v[i], p + i * stride);
}
template <int N> __device__ __forceinline__ uint32_t ll_acc(const uint32_t (&v)[N][4], uint32_t tag, uint32_t acc = 0) {
#pragma unroll
  for (int i = 0; i < N; i++) asm("lop3.b32 %0, %1, %2, %0, 0xBE;" : "+r"(acc) : "r"(v[i][0]), "r"(tag));
  return acc;
}
__device__ __forceinline__ bool ll_any(uint32_t acc) { return __any_sync(0xffffffffu, acc & 1u); }
template <int N> __device__ __forceinline__ bool ll_bad(const uint32_t (&v)[N][4], uint32_t tag) { return ll_any(ll_acc<N>(v, tag)); }
template <int N> __device__ __forceinline__ void ll_clear(uint32_t (&v)[N][4]) {
#pragma unroll
  for (int i = 0; i < N; i++) v[i][0] &= ~1u;
}
template <int N> __device__ __forceinline__ void ll_spin(uint32_t (&v)[N][4], const uint4* p, int stride, uint32_t tag) {
  uint32_t it = 0;
#pragma unroll 1
  do { ll_issue<N>(v, p, stride); } while (ll_bad<N>(v, tag) && ++it < SPIN_LIMIT);
}
template <int N> __device__ __forceinline__ void ll_get(uint32_t (&v)[N][4], const uint4* p, int stride, uint32_t tag) {
  ll_spin<N>(v, p, stride, tag);
  ll_clear<N>(v);
}
template <int N> __device__ __forceinline__ void ll_wait(uint32_t (&v)[N][4], const uint4* p, int stride, uint32_t tag) {
  if (__builtin_expect(ll_bad<N>(v, tag), 0)) ll_spin<N>(v, p, stride, tag);
  ll_clear<N>(v);
}
__device__ __forceinline__ void unpack32(float (&d)[32], const uint32_t (&v)[4][4]) {
#pragma unroll
  for (int u = 0; u < 4; u++)
#pragma unroll
    for (int e = 0; e < 4; e++) { d[8 * u + 2 * e] = bf_lo(v[u][e]); d[8 * u + 2 * e + 1] = bf_hi(v[u][e]); }
}
__device__ __forceinline__ void pack32(uint32_t (&v)[4][4], const float (&d)[32]) {
#pragma unroll
  for (int u = 0; u < 4; u++)
#pragma unroll
    for (int e = 0; e < 4; e++) v[u][e] = pack2(d[8 * u + 2 * e], d[8 * u + 2 * e + 1]);
}
__device__ __forceinline__ uint32_t t_addr(int m) { return SB + ((0x03514620u >> (4 * m)) & 7u) * 32768u; }

__device__ __forceinline__ int kb_at(int i, int j) { return i == 0 ? j : (i - 1 + (i - 1 >= j ? 1 : 0)); }

__device__ __forceinline__ void init_bars(int set) {
  if (set >= 0 && elect_one()) {
    const uint32_t cnt = set < 5 ? 1 : 8;
#pragma unroll
    for (int i = 0; i < 8; i++) mbar_init(BAR + (24 + 8 * set + i) * 8, cnt);
    if (set == 9) {
#pragma unroll
      for (int i = 0; i < 9; i++) mbar_init(BAR + (B_EX + i) * 8, 4);
#pragma unroll
      for (int i = 0; i < 3; i++) mbar_init(BAR + (B_READY + i) * 8, i == 1 ? 7 : 3);
      mbar_init(BAR + B_TAG * 8, 1);
    }
    asm volatile("fence.mbarrier_init.release.cluster;" ::: "memory");
  }
  __syncwarp();
  asm volatile("bar.arrive 4, 384;" ::: "memory");
  asm volatile("bar.sync 3, 384;" ::: "memory");
}

__global__ void __launch_bounds__(384, 1) fused_block_kernel(Scratch* __restrict__ X, const __nv_bfloat16* __restrict__ xp,
                                                             const __nv_bfloat16* __restrict__ wqkvp, const __nv_bfloat16* __restrict__ wop, const uint32_t zero,
                                                             const __grid_constant__ Params P) {
  extern __shared__ __align__(1024) uint8_t smem_raw[];
  if (smem_u32(smem_raw) != SB) return;
  const int tid = threadIdx.x;
  const int warp = __shfl_sync(0xffffffffu, tid >> 5, 0);
  const int lane = tid & 31;
  const int cta = blockIdx.x;
  const int j = (cta >> 6) * 4 + (cta & 3);
  const int g = (cta & 63) >> 2;

  if (warp >= 8) {
    asm volatile("setmaxnreg.dec.sync.aligned.u32 56;");
    if (warp == 8) {
      PSTAMPW(2, 0);
      const bool leader = elect_one();
      if (leader) {
        prefetch_map(&P.x); prefetch_map(&P.wqkv);
#pragma unroll
        for (int i = 0; i < 24; i++) mbar_init(BAR + i * 8, 1);
        asm volatile("fence.mbarrier_init.release.cluster;" ::: "memory");
      }
      __syncwarp();
      asm volatile("bar.arrive 3, 384;" ::: "memory");
      PSTAMPW(2, 20);
      auto ldx = [&](int p, int kb) {
        const uint32_t b = BAR + (B_FX + p * 8 + kb) * 8;
        mbar_expect_tx(b, 8192);
        tma3d(H0 + p * 65536 + kb * 8192, &P.x, kb * 64, p, g * 64, b);
      };
      auto ldkv = [&](int kb, int slot) {
        const uint32_t b = BAR + (B_FKV + kb) * 8, d = RING + slot * 16384;
        mbar_expect_tx(b, 16384);
        tma2d(d, &P.wqkv, 512 + 64 * j, kb * 64, b);
        tma2d(d + 8192, &P.wqkv, 1024 + 64 * j, kb * 64, b);
      };
      if (leader) {
#pragma unroll 1
        for (int i = 0; i < 8 + XO_DELAY; i++) {
          if (i < 8) ldx(0, i);
          if (i < 6) ldkv(i, i);
          if (i >= XO_DELAY) ldx(1, i - XO_DELAY);
          if (i == 0) PSTAMPW(2, 21);
        }
        PSTAMPW(2, 2);
      }
      __syncwarp();
      asm volatile("bar.sync 4, 384;" ::: "memory");
      if (leader) {
        const int f0 = 224 * j + ((j & 1) ? 32 : 0);
        const int fh = 224 * j + ((j & 1) ? 0 : 192);
        prefetch_map(&P.wo); prefetch_map(&P.w1); prefetch_map(&P.w3); prefetch_map(&P.w1h);
        prefetch_map(&P.w3h); prefetch_map(&P.w2); prefetch_map(&P.out);
#pragma unroll 1
        for (int i = 0; i < 2; i++) { mbar_wait(BAR + (B_EKV + i) * 8); ldkv(6 + i, i); }
#pragma unroll 1
        for (int i = 0; i < 8; i++) {
          const uint32_t b = BAR + (B_FQ + i) * 8;
          mbar_wait(BAR + (B_EKV + 2 + (i >> 1)) * 8);
          mbar_expect_tx(b, 8192);
          tma2d(RING + (4 + i) * 8192, &P.wqkv, 64 * j, i * 64, b);
        }
        mbar_expect_tx(BAR + B_FWO * 8, 65536);
#pragma unroll 1
        for (int i = 0; i < 8; i++) {
          const int kb = (i + 1) & 7;
          mbar_wait(BAR + (B_EX + i) * 8);
          tma2d(H0 + kb * 8192, &P.wo, 64 * j, kb * 64, BAR + B_FWO * 8);
          PSTAMPW(2, 4 + i);
        }
#pragma unroll 1
        for (int i = 0; i < 8; i++) {
          const uint32_t b = BAR + (B_FA + i) * 8, d = RING + (i & 3) * 24576;
          const int k0 = kb_at(i, j) * 64;
          mbar_wait(BAR + (B_EKV + 7 + ((0xCBA98520u >> (4 * i)) & 15)) * 8);
          mbar_expect_tx(b, 24576);
          tma2d(d, &P.w1, f0, k0, b);
          tma2d(d + 8192, &P.w3, f0, k0, b);
          tma2d(d + 16384, &P.w1h, fh, k0, b);
          tma2d(d + 20480, &P.w3h, fh, k0, b);
          PSTAMPW(2, 12 + i);
        }
        uint32_t d = RING;
#pragma unroll 1
        for (int i = 0; i < 8; i++) {
          const uint32_t b = BAR + (B_FB + i) * 8;
          const int k0 = kb_at(i, j) * 64;
          mbar_wait(BAR + (B_EA + 5 + i) * 8);
          mbar_expect_tx(b, 32768);
          tma2d(d, &P.w1, f0 + 64, k0, b);
          tma2d(d + 8192, &P.w3, f0 + 64, k0, b);
          tma2d(d + 16384, &P.w1, f0 + 128, k0, b);
          tma2d(d + 24576, &P.w3, f0 + 128, k0, b);
          d = d == RING + 65536 ? RING : d + 32768;
        }
#pragma unroll 1
        for (int m = 0; m < 8; m++) {
          const uint32_t b = BAR + (B_FT + m) * 8;
          mbar_wait(BAR + (B_EB + (m == 7 ? 8 : min(m + 3, 7))) * 8);
          mbar_expect_tx(b, 28672);
          tma2d(t_addr(m), &P.w2, 64 * ((j + 1 + m) & 7), 224 * j, b);
        }
        X->epoch[cta] = X->epoch[cta] + 1;
      }
    } else {
      const int part = warp - 9;
      uint32_t tag;
      if (part == 2) {
        tag = ld_epoch(X->epoch + cta);
        init_bars(-1);
        tag = (tag + 1) & 1;
        if (lane == 0) {
          asm volatile("st.shared.u32 [%0], %1;" ::"r"(TAGS), "r"(tag) : "memory");
          mbar_arrive(BAR + B_TAG * 8);
        }
      } else {
        init_bars(warp - 1);
        mbar_wait(BAR + B_TAG * 8);
        tag = lds32(TAGS);
      }
      PSTAMPW(3, 16 + part);
      const int xw0 = g * 8;
      auto clear8 = [&](uint4* p, int stride) {
#pragma unroll
        for (int i = 0; i < 8; i++) ll_st(p + i * stride + lane, 0, 0, 0, 0, tag ^ 1);
      };
#pragma unroll 1
      for (int u = part; u < 8; u += 3) clear8((u < 4 ? X->e2 : X->e3h) + (xw0 * 32 + 4 * j + (u & 3)) * 32, 1024);
      if (part == 2) {
        clear8(X->e1 + (g * 8 + j) * 256, 32);
#pragma unroll
        for (int i = 0; i < 4; i++)
          ll_st((i < 2 ? X->e2s : X->e3s) + ((xw0 + (i & 1) * 4 + (lane >> 3)) * 8 + j) * 8 + (lane & 7), 0, 0, 0, 0, tag ^ 1);
      }
      PSTAMPW(3, 20 + part);
      uint32_t v[8][4];
      if (part < 2) {
        float s[4] = {0.f, 0.f, 0.f, 0.f}, q[4] = {0.f, 0.f, 0.f, 0.f}, piv = 0.f;
        const uint32_t xa = H0 + part * 65536 + (8 * j + (lane >> 2)) * 128 + (lane & 3) * 16 + (lane & 4) * 16;
#pragma unroll 1
        for (int kb = 0; kb < 8; kb++) {
          mbar_wait(BAR + (B_FX + part * 8 + kb) * 8);
          lds128(v[0], xa + kb * 8192); lds128(v[1], (xa + kb * 8192) ^ 64);
          if (kb == 0) piv = __shfl_sync(0xffffffffu, bf_lo(v[0][0]), lane & 28);
#pragma unroll
          for (int e = 0; e < 8; e++) {
            const float a = bf_lo(v[e >> 2][e & 3]) - piv, b = bf_hi(v[e >> 2][e & 3]) - piv;
            s[e & 3] += a + b; q[e & 3] = fmaf(a, a, q[e & 3]); q[e & 3] = fmaf(b, b, q[e & 3]);
          }
        }
        float ss = (s[0] + s[1]) + (s[2] + s[3]), qq = (q[0] + q[1]) + (q[2] + q[3]);
#pragma unroll
        for (int o = 1; o <= 2; o <<= 1) { ss += __shfl_xor_sync(0xffffffffu, ss, o); qq += __shfl_xor_sync(0xffffffffu, qq, o); }
        const float dm = ss * (1.f / D_);
        const float rs = rsqrtf(fmaxf(fmaf(-dm, dm, qq * (1.f / D_)), 0.f) + 1e-5f);
        if ((lane & 3) == 0) ll_st(X->e0s + g * 128 + 2 * (8 * j + (lane >> 2)) + part, __float_as_uint(piv + dm), __float_as_uint(rs), 0, 0, tag);
      } else {
        mbar_wait(BAR + (B_FKV + SIDE_KB) * 8);
        const __nv_bfloat16* wr = wop + (size_t)(j * 64 + g * 4 + (lane >> 3)) * D_ + (lane & 7) * 8;
#pragma unroll
        for (int i = 0; i < 8; i++) ldg128_nc(v[i], wr + i * 64);
        float s[4];
#pragma unroll
        for (int e = 0; e < 4; e++) {
          s[e] = 0.f;
#pragma unroll
          for (int i = 0; i < 8; i++) s[e] += bf_lo(v[i][e]) + bf_hi(v[i][e]);
        }
        float ss = (s[0] + s[1]) + (s[2] + s[3]);
#pragma unroll
        for (int o = 1; o <= 4; o <<= 1) ss += __shfl_xor_sync(0xffffffffu, ss, o);
        if ((lane & 7) == 0) ll_st(X->e0w + j * 64 + g * 4 + (lane >> 3), __float_as_uint(ss * (1.f / D_)), 0, 0, 0, tag);
      }
      __syncwarp();
      if (lane == 0) mbar_arrive(BAR + B_PUB * 8);
      PSTAMPW(3, part * 4 + 2);
      mbar_wait(BAR + B_PUB * 8);
      PSTAMPW(3, part * 4 + 0);
      {
        uint32_t u[2][4];
        const uint4* us = (part == 2 ? X->e0w + j * 64 : X->e0s + g * 128 + part * 64) + lane;
        const uint4* vs = X->e0c + ((j * 3 + part) * 16 + (lane >> 4) * 8) * 16 + (lane & 15);
        uint32_t it = 0;
#pragma unroll 1
        do { ll_issue<2>(u, us, 32); ll_issue<8>(v, vs, 16); } while (ll_any(ll_acc<8>(v, tag, ll_acc<2>(u, tag))) && ++it < SPIN_LIMIT);
        ll_clear<2>(u); ll_clear<8>(v);
#pragma unroll
        for (int i = 0; i < 2; i++) {
          if (part == 2) asm volatile("st.shared.u32 [%0], %1;" ::"r"(WB + (i * 32 + lane) * 4), "r"(u[i][0]) : "memory");
          else asm volatile("st.shared.v2.u32 [%0], {%1,%2};" ::"r"(ST + (part * 64 + i * 32 + lane) * 8), "r"(u[i][0]), "r"(u[i][1]) : "memory");
        }
      }
      uint32_t o[4];
#pragma unroll
      for (int e = 0; e < 4; e++) {
        float s = 0.f;
#pragma unroll
        for (int i = 0; i < 8; i++) s += __uint_as_float(v[i][e]);
        o[e] = __float_as_uint(s + __shfl_xor_sync(0xffffffffu, s, 16));
      }
      if (lane < 16) sts128(CS + (part * 64 + lane * 4) * 4, o);
      __syncwarp();
      if (lane == 0) mbar_arrive(BAR + B_READY * 8);
      PSTAMPW(3, part * 4 + 1);
      if (lane == 0) l2_prefetch(part == 0 ? P.w1p + (size_t)cta * 4 * F_ : part == 1 ? P.w3p + (size_t)cta * 4 * F_ : P.w2p + (size_t)cta * 14 * D_, 14336);
      mbar_wait(BAR + (B_EA + 1) * 8);
#pragma unroll 1
      for (int u = 4 * E4_FIRST + part; u < 28; u += 3)
        clear8(X->e4 + ((size_t)xw0 * 64 + ((j + 1 + (u >> 2)) & 7) * 8 + j) * 128 + (u & 3) * 32, 8192);
      __syncwarp();
      if (lane == 0) mbar_arrive(BAR + B_CLR * 8);
      PSTAMPW(3, part * 4 + 3);
    }
  } else {
    const int p = warp >> 2, w = warp & 3;
    const int r = lane >> 2, c = lane & 3;
    init_bars(warp);
    asm volatile("setmaxnreg.inc.sync.aligned.u32 224;");
    PSTAMP(0);
    const uint32_t dAx = descA(H0) + p * 4096;
    const uint32_t Hn = H1 - p * 65536;
    const uint32_t moff = ((lane & 7) + ((lane >> 3) & 1) * 8) * 128 + (((lane >> 4) ^ (lane & 7)) << 4);
    const uint32_t Xw = H0 + p * 65536 + w * 2048;
    const int xw = (g * 2 + p) * 4 + w;
    if (p == 1) {
      uint32_t v[8][4];
      mbar_wait(BAR + (B_FKV + SIDE_KB) * 8);
      const int wp = w < 3 ? w : 0;
      const __nv_bfloat16* wr = wqkvp + (size_t)(g * 32 + (lane >> 3) * 8) * (3 * D_) + wp * D_ + j * 64 + (lane & 7) * 8;
#pragma unroll
      for (int i = 0; i < 8; i++) ldg128_nc(v[i], wr + (size_t)i * 3 * D_);
      mbar_wait(BAR + B_TAG * 8);
      const uint32_t tg = lds32(TAGS);
      float cs[8];
#pragma unroll
      for (int e = 0; e < 4; e++) {
        float a = 0.f, b = 0.f;
#pragma unroll
        for (int i = 0; i < 8; i++) { a += bf_lo(v[i][e]); b += bf_hi(v[i][e]); }
        cs[2 * e] = a; cs[2 * e + 1] = b;
      }
      const bool up = lane & 8;
#pragma unroll
      for (int e = 0; e < 4; e++) {
        const float keepv = up ? cs[4 + e] : cs[e], give = up ? cs[e] : cs[4 + e];
        cs[e] = keepv + __shfl_xor_sync(0xffffffffu, give, 8);
        cs[e] += __shfl_xor_sync(0xffffffffu, cs[e], 16);
      }
      if (lane < 16 && w < 3)
        ll_st(X->e0c + ((j * 3 + w) * 16 + g) * 16 + (lane & 7) * 2 + (lane >> 3), __float_as_uint(cs[0]), __float_as_uint(cs[1]),
              __float_as_uint(cs[2]), __float_as_uint(cs[3]), tg);
      __syncwarp();
      mbar_arrive_if(BAR + B_PUB * 8, lane == 0);
      PSTAMP(1);
      mbar_wait(BAR + B_LAG * 8);
    }

    float akv[64];
#pragma unroll 1
    for (int kb = 0; kb < 8; kb++) {
      mbar_wait(BAR + (B_FX + p * 8 + kb) * 8);
      mbar_wait(BAR + (B_FKV + kb) * 8);
      if (kb == 0) PSTAMP(2);
      const uint32_t da = dAx + kb * 512, db = descB(RING) + (kb < 6 ? kb : kb - 6) * 1024;
      wg_fence();
      wgmma_ss_n128(akv, da, db, kb);
#pragma unroll
      for (int k = 1; k < 4; k++) wgmma_ss_n128(akv, da + k * 2, db + k * 128, 1);
      wg_commit();
      mbar_arrive_if(BAR + B_LAG * 8, kb == LAG_KB - 1 && p == 0 && lane == 0);
      wg_wait<1>();
      mbar_arrive_if(BAR + (B_EKV + kb - 1) * 8, kb > 0 && lane == 0);
    }
    uint32_t xres[4][4];
#pragma unroll
    for (int u = 0; u < 4; u++) ldsm4(xres[u], Xw + j * 8192 + (moff ^ (u << 5)));

    float aq[32];
    auto qstep = [&](int kb) {
      mbar_wait(BAR + (B_FQ + kb) * 8);
      const uint32_t da = dAx + kb * 512, db = descB(RING + 32768) + kb * 512;
      wg_fence();
      wgmma_ss_n64(aq, da, db, kb);
#pragma unroll
      for (int k = 1; k < 4; k++) wgmma_ss_n64(aq, da + k * 2, db + k * 128, 1);
      wg_commit();
      wg_wait<1>();
      mbar_arrive_if(BAR + (B_EQ + kb - 1) * 8, lane == 0);
      mbar_arrive_if(BAR + (B_EX + kb - 2) * 8, lane == 0 && p == 0 && kb >= 2);
    };
    qstep(0);
    keep(akv);
    PSTAMP(3);
    qstep(1);
    mbar_wait(BAR + B_READY * 8);
    PSTAMP(19);
    const uint32_t tag = lds32(TAGS);
    const float2 st0 = lds64(ST + (2 * (16 * w + r) + p) * 8);
    const float2 st1 = lds64(ST + (2 * (16 * w + r + 8) + p) * 8);
    uint32_t hi[4][4], lo[4][4];
    {
      float2 cs[16];
      auto cvt = [&](uint32_t (&d)[4][4], int b0, int ofs, const float2& st) {
#pragma unroll
        for (int b = b0; b < b0 + 8; b++) {
          if (ofs == 2) cs[b] = lds64(CS + (64 + b * 8 + 2 * c) * 4);
          const uint32_t v = pack2(fmaf(-st.x, cs[b].x, akv[4 * b + ofs]) * st.y, fmaf(-st.x, cs[b].y, akv[4 * b + ofs + 1]) * st.y);
          d[b >> 2][b & 3] = b < 8 ? v : movm(v);
        }
      };
      cvt(hi, 0, 2, st1);
      keep(hi[0]); keep(hi[1]);
      qstep(2);
      cvt(hi, 8, 2, st1);
      if (w == 3 && g < 15) {
        uint4* dst = X->e1 + ((g * 8 + j) * 2 + p) * 128 + lane;
#pragma unroll
        for (int i = 0; i < 4; i++) ll_st(dst + i * 32, hi[i][0], hi[i][1], hi[i][2], hi[i][3], tag);
      }
      PSTAMP(20);
      wg_bar(p);
#pragma unroll
      for (int i = 0; i < 4; i++) sts128(Xw + lane * 16 + i * 512, hi[i]);
      qstep(3);
      cvt(lo, 0, 0, st0);
      keep(lo[0]); keep(lo[1]);
      qstep(4);
      cvt(lo, 8, 0, st0);
    }
    PSTAMP(21);
    wg_bar(p);
    uint32_t prev[4][4];
    if (w > 0) {
#pragma unroll
      for (int i = 0; i < 4; i++) lds128(prev[i], Xw - 2048 + lane * 16 + i * 512);
    }
    if (p == 0) {
      asm volatile("fence.proxy.async.shared::cta;" ::: "memory");
      __syncwarp();
      if (lane == 0) mbar_arrive(BAR + (B_EX + 7) * 8);
    }
    PSTAMP(22);
    const uint4* halo = X->e1 + (((g - 1) * 8 + j) * 2 + p) * 128 + lane;
    const bool use_halo = w == 0 && g > 0;
    qstep(5);
    if (use_halo) ll_issue<4>(prev, halo, 32);
    qstep(6);
    qstep(7);
    PSTAMP(23);
    if (w == 0) {
      if (g > 0) {
        if (__builtin_expect(ll_bad<4>(prev, pin(tag, zero)), 0)) ll_spin<4>(prev, halo, 32, tag);
        ll_clear<4>(prev);
      } else {
#pragma unroll
        for (int i = 0; i < 4; i++)
#pragma unroll
          for (int e = 0; e < 4; e++) prev[i][e] = 0;
      }
    }
    wg_wait<0>();
    keep(aq);
    mbar_arrive_if(BAR + (B_EQ + 7) * 8, lane == 0);
    mbar_arrive_if(BAR + (B_EX + 6) * 8, lane == 0 && p == 0);
    PSTAMP(4);

    uint32_t of[4][4];
    {
      const float sc = 0.25f * 1.4426950408889634f;
      const float nohalo = (g == 0 && w == 0) ? -INFINITY : 0.f;
      const bool up0 = 2 * c > r, up1 = 2 * c + 1 > r;
      const uint32_t mup = (up0 ? 0xffffu : 0u) | (up1 ? 0xffff0000u : 0u);
      uint4* dst = X->e2 + (xw * 32 + 4 * j) * 32 + lane;
      float d0 = 0.f, d1 = 0.f;
#pragma unroll 1
      for (int hp = 0; hp < 2; hp++) {
#pragma unroll
        for (int e = 0; e < 4; e++) { of[0][e] = of[2][e]; of[1][e] = of[3][e]; }
#pragma unroll
        for (int h = 0; h < 2; h++) {
          uint32_t qf[4];
          const uint32_t co = (32 * hp + 16 * h + 2 * c) * 4;
          {
            const float2 ca = lds64(CS + co), cb = lds64(CS + co + 32);
            qf[0] = pack2(fmaf(-st0.x, ca.x, aq[8 * h + 0]) * st0.y, fmaf(-st0.x, ca.y, aq[8 * h + 1]) * st0.y);
            qf[1] = pack2(fmaf(-st1.x, ca.x, aq[8 * h + 2]) * st1.y, fmaf(-st1.x, ca.y, aq[8 * h + 3]) * st1.y);
            qf[2] = pack2(fmaf(-st0.x, cb.x, aq[8 * h + 4]) * st0.y, fmaf(-st0.x, cb.y, aq[8 * h + 5]) * st0.y);
            qf[3] = pack2(fmaf(-st1.x, cb.x, aq[8 * h + 6]) * st1.y, fmaf(-st1.x, cb.y, aq[8 * h + 7]) * st1.y);
          }
          const int e0 = 2 * h;
          float sp[4], sl[4], sh[4];
          mma16816(sp, qf, prev[0][e0], prev[0][e0 + 1]);
          mma16816(sl, qf, lo[0][e0], lo[0][e0 + 1]);
          mma16816(sh, qf, hi[0][e0], hi[0][e0 + 1]);
          float a0 = up0 ? sp[0] + nohalo : sl[0], a1 = up1 ? sp[1] + nohalo : sl[1];
          float b0 = up0 ? sl[2] : sh[2], b1 = up1 ? sl[3] : sh[3];
          float ma = fmaxf(a0, a1), mb = fmaxf(b0, b1);
          ma = fmaxf(ma, __shfl_xor_sync(0xffffffffu, ma, 1)); mb = fmaxf(mb, __shfl_xor_sync(0xffffffffu, mb, 1));
          ma = fmaxf(ma, __shfl_xor_sync(0xffffffffu, ma, 2)); mb = fmaxf(mb, __shfl_xor_sync(0xffffffffu, mb, 2));
          a0 = ex2((a0 - ma) * sc); a1 = ex2((a1 - ma) * sc); b0 = ex2((b0 - mb) * sc); b1 = ex2((b1 - mb) * sc);
          float sa = a0 + a1, sbb = b0 + b1;
          sa += __shfl_xor_sync(0xffffffffu, sa, 1); sbb += __shfl_xor_sync(0xffffffffu, sbb, 1);
          sa += __shfl_xor_sync(0xffffffffu, sa, 2); sbb += __shfl_xor_sync(0xffffffffu, sbb, 2);
          const float ia = rcp(sa), ib = rcp(sbb);
          const uint32_t pa = pack2(a0 * ia, a1 * ia), pb = pack2(b0 * ib, b1 * ib);
          const uint32_t pf[4] = {pa & mup, 0u, pa & ~mup, pb & mup};
          const uint32_t ph = pb & ~mup;
          float o0[4], o1[4];
          mma16816(o0, pf, prev[2][e0], lo[2][e0]);
          mma16816(o1, pf, prev[2][e0 + 1], lo[2][e0 + 1]);
          mma1688_acc(o0, 0u, ph, hi[2][e0]);
          mma1688_acc(o1, 0u, ph, hi[2][e0 + 1]);
          of[2 + h][0] = pack2(o0[0], o0[1]); of[2 + h][1] = pack2(o0[2], o0[3]);
          of[2 + h][2] = pack2(o1[0], o1[1]); of[2 + h][3] = pack2(o1[2], o1[3]);
          ll_st(dst + (2 * hp + h) * 32, of[2 + h][0], of[2 + h][1], of[2 + h][2], of[2 + h][3], tag);
          const float2 wa = lds64(WB + co), wb = lds64(WB + co + 32);
          d0 = fmaf(o0[0], wa.x, d0); d0 = fmaf(o0[1], wa.y, d0); d0 = fmaf(o1[0], wb.x, d0); d0 = fmaf(o1[1], wb.y, d0);
          d1 = fmaf(o0[2], wa.x, d1); d1 = fmaf(o0[3], wa.y, d1); d1 = fmaf(o1[2], wb.x, d1); d1 = fmaf(o1[3], wb.y, d1);
        }
#pragma unroll
        for (int e = 0; e < 16; e++) aq[e] = aq[16 + e];
#pragma unroll
        for (int e = 0; e < 4; e++) {
          prev[0][e] = prev[1][e]; prev[2][e] = prev[3][e];
          lo[0][e] = lo[1][e]; lo[2][e] = lo[3][e];
          hi[0][e] = hi[1][e]; hi[2][e] = hi[3][e];
        }
      }
#pragma unroll
      for (int o = 1; o <= 2; o <<= 1) { d0 += __shfl_xor_sync(0xffffffffu, d0, o); d1 += __shfl_xor_sync(0xffffffffu, d1, o); }
      if (c == 0) ll_st(X->e2s + (xw * 8 + j) * 8 + r, __float_as_uint(d0), __float_as_uint(d1), 0, 0, tag);
    }
    PSTAMP(5);

    float ah[32];
    uint32_t sv[2][4];
    unpack32(ah, xres);
    {
      uint32_t og[2][14][4];
      const uint4* osrc[7];
#pragma unroll
      for (int i = 0; i < 7; i++) osrc[i] = X->e2 + (xw * 32 + 4 * kb_at(i + 1, j)) * 32 + lane;
      const uint4* ssrc = X->e2s + (xw * 8 + 2 * c) * 8 + r;
      auto oissue = [&](int hp) {
#pragma unroll
        for (int i = 0; i < 14; i++) ll_ld(og[hp][i], osrc[i >> 1] + (2 * hp + (i & 1)) * 32);
        if (hp == 1) ll_issue<2>(sv, ssrc, 8);
      };
      auto omma = [&](int hp) {
        ll_clear<14>(og[hp]);
        keep(og[hp]);
        wg_fence();
#pragma unroll
        for (int i = 0; i < 14; i++) wgmma_rs_n64(ah, og[hp][i], descB(H0) + kb_at((i >> 1) + 1, j) * 512 + (2 * hp + (i & 1)) * 128, 1);
        wg_commit();
      };
      mbar_wait(BAR + B_FWO * 8);
      keep(ah); keep(of);
      wg_fence();
#pragma unroll
      for (int k = 0; k < 4; k++) wgmma_rs_n64(ah, of[k], descB(H0) + j * 512 + k * 128, 1);
      wg_commit();
      uint32_t it = 0;
#pragma unroll 1
      do { oissue(0); } while (ll_bad<14>(og[0], tag) && ++it < SPIN_LIMIT);
      PSTAMP(6);
      oissue(1);
      omma(0);
      const uint32_t tg = pin(tag, zero);
      if (__builtin_expect(ll_any(ll_acc<14>(og[1], tg, ll_acc<2>(sv, tg))), 0)) {
#pragma unroll 1
        do { oissue(1); } while (ll_any(ll_acc<14>(og[1], tag, ll_acc<2>(sv, tag))) && ++it < SPIN_LIMIT);
      }
      PSTAMP(16);
      omma(1);
      ll_clear<2>(sv);
    }
    float m0 = __uint_as_float(sv[0][0]) + __uint_as_float(sv[1][0]), m1 = __uint_as_float(sv[0][1]) + __uint_as_float(sv[1][1]);
#pragma unroll
    for (int o = 1; o <= 2; o <<= 1) { m0 += __shfl_xor_sync(0xffffffffu, m0, o); m1 += __shfl_xor_sync(0xffffffffu, m1, o); }
    const uint32_t mu0 = pack2(m0 + st0.x, m0 + st0.x), mu1 = pack2(m1 + st1.x, m1 + st1.x);
    wg_wait<0>();
    keep(ah);
    if (lane == 0) mbar_arrive(BAR + B_WODONE * 8);
    PSTAMP(7);

    uint32_t hf[4][4], ra[4][4];
    pack32(hf, ah);
    {
      uint4* dst = X->e3h + (xw * 32 + 4 * j) * 32 + lane;
#pragma unroll
      for (int u = 0; u < 4; u++) {
        ra[u][0] = hsub2(hf[u][0], mu0); ra[u][1] = hsub2(hf[u][1], mu1);
        ra[u][2] = hsub2(hf[u][2], mu0); ra[u][3] = hsub2(hf[u][3], mu1);
        ll_st(dst + u * 32, ra[u][0], ra[u][1], ra[u][2], ra[u][3], tag);
      }
      float s0 = 0.f, q0 = 0.f, s1 = 0.f, q1 = 0.f;
#pragma unroll
      for (int b = 0; b < 8; b++) {
        s0 += ah[4 * b] + ah[4 * b + 1]; s1 += ah[4 * b + 2] + ah[4 * b + 3];
        q0 = fmaf(ah[4 * b], ah[4 * b], q0); q0 = fmaf(ah[4 * b + 1], ah[4 * b + 1], q0);
        q1 = fmaf(ah[4 * b + 2], ah[4 * b + 2], q1); q1 = fmaf(ah[4 * b + 3], ah[4 * b + 3], q1);
      }
#pragma unroll
      for (int o = 1; o <= 2; o <<= 1) {
        s0 += __shfl_xor_sync(0xffffffffu, s0, o); q0 += __shfl_xor_sync(0xffffffffu, q0, o);
        s1 += __shfl_xor_sync(0xffffffffu, s1, o); q1 += __shfl_xor_sync(0xffffffffu, q1, o);
      }
      if (c == 0) ll_st(X->e3s + (xw * 8 + j) * 8 + r, __float_as_uint(s0), __float_as_uint(q0), __float_as_uint(s1), __float_as_uint(q1), tag);
      mbar_wait(BAR + (p == 0 ? B_EQ + 7 : B_WODONE) * 8);
    }
    PSTAMP(8);

    float rs0, rs1;
    auto swiglu = [&](float g0, float g1, float u0, float u1, float rs) -> uint32_t {
      const float hr = 0.5f * rs;
      const float x0 = g0 * hr, x1 = g1 * hr;
      const float t0 = tanhf_hw(x0), t1 = tanhf_hw(x1);
      return pack2(fmaf(x0, t0, x0) * (u0 * rs), fmaf(x1, t1, x1) * (u1 * rs));
    };
    uint32_t hA[6][4];
    {
      float a1[64], a2[32];
      const uint4* src = X->e3h + xw * 32 * 32 + lane;
      uint32_t rb[4][4], rc[4][4], rd[4][4];
      auto fetch = [&](uint32_t (&a)[4][4], int i) { ll_issue<4>(a, src + kb_at(i, j) * 128, 32); };
      auto check = [&](uint32_t (&a)[4][4], uint32_t (&b)[4][4], int i) {
        const uint32_t tg = pin(tag, zero);
        if (__builtin_expect(ll_any(ll_acc<4>(a, tg, ll_acc<4>(b, tg))), 0)) {
          uint32_t it = 0;
#pragma unroll 1
          do { fetch(a, i); fetch(b, i + 1); } while (ll_any(ll_acc<4>(a, tag, ll_acc<4>(b, tag))) && ++it < SPIN_LIMIT);
        }
        ll_clear<4>(a); ll_clear<4>(b);
        keep(a); keep(b);
      };
      auto head = [&](uint32_t (&a)[4][4], int i) {
        mbar_wait(BAR + (B_FA + i) * 8);
        wg_fence();
        wgmma_rs_n64<DESC_HI64>(a2, a[0], descBh(RING + 16384) + (i & 3) * 1536, i);
        wgmma_rs_n128(a1, a[0], descB(RING) + (i & 3) * 1536, i);
        wg_commit();
#pragma unroll
        for (int u = 0; u < 4; u++) stsm4(Hn + w * 2048 + i * 8192 + (moff ^ (u << 5)), a[u]);
        wg_wait<1>();
        if (i > 0) mbar_arrive_if(BAR + (B_EA + i - 1) * 8, lane == 0);
      };
      auto rest = [&](uint32_t (&a)[4][4], int i) {
        wg_fence();
#pragma unroll
        for (int k = 1; k < 4; k++) {
          wgmma_rs_n64<DESC_HI64>(a2, a[k], descBh(RING + 16384) + (i & 3) * 1536 + k * 64, 1);
          wgmma_rs_n128(a1, a[k], descB(RING) + (i & 3) * 1536 + k * 128, 1);
        }
        wg_commit();
      };
      ll_clear<4>(ra);
      keep(ra);
      head(ra, 0); rest(ra, 0);
      ll_get<4>(rb, src + kb_at(1, j) * 128, 32, tag);
      keep(rb);
      PSTAMP(17);
      fetch(rc, 2); fetch(rd, 3);
      head(rb, 1); rest(rb, 1);
      check(rc, rd, 2);
      head(rc, 2); fetch(ra, 4); fetch(rb, 5); rest(rc, 2);
      head(rd, 3); rest(rd, 3);
      check(ra, rb, 4);
      head(ra, 4); fetch(rc, 6); fetch(rd, 7); ll_issue<2>(sv, X->e3s + (xw * 8 + 2 * c) * 8 + r, 8); rest(ra, 4);
      head(rb, 5); rest(rb, 5);
      check(rc, rd, 6);
      head(rc, 6); rest(rc, 6);
      head(rd, 7); rest(rd, 7);
      fence_async_smem();
      ll_wait<2>(sv, X->e3s + (xw * 8 + 2 * c) * 8 + r, 8, tag);
      float s0 = __uint_as_float(sv[0][0]) + __uint_as_float(sv[1][0]), q0 = __uint_as_float(sv[0][1]) + __uint_as_float(sv[1][1]);
      float s1 = __uint_as_float(sv[0][2]) + __uint_as_float(sv[1][2]), q1 = __uint_as_float(sv[0][3]) + __uint_as_float(sv[1][3]);
#pragma unroll
      for (int o = 1; o <= 2; o <<= 1) {
        s0 += __shfl_xor_sync(0xffffffffu, s0, o); q0 += __shfl_xor_sync(0xffffffffu, q0, o);
        s1 += __shfl_xor_sync(0xffffffffu, s1, o); q1 += __shfl_xor_sync(0xffffffffu, q1, o);
      }
      s0 *= 1.f / D_; s1 *= 1.f / D_;
      rs0 = rsqrtf(fmaxf(fmaf(-s0, s0, q0 * (1.f / D_)), 0.f) + 1e-5f);
      rs1 = rsqrtf(fmaxf(fmaf(-s1, s1, q1 * (1.f / D_)), 0.f) + 1e-5f);
      wg_wait<0>();
      keep(a1); keep(a2);
      if (lane == 0) mbar_arrive(BAR + (B_EA + 7) * 8);
      PSTAMP(9);
#pragma unroll
      for (int u = 0; u < 4; u++)
#pragma unroll
        for (int e = 0; e < 4; e++)
          hA[u][e] = swiglu(a1[8 * u + 2 * e], a1[8 * u + 2 * e + 1], a1[32 + 8 * u + 2 * e], a1[33 + 8 * u + 2 * e], (e & 1) ? rs1 : rs0);
#pragma unroll
      for (int u = 0; u < 2; u++)
#pragma unroll
        for (int e = 0; e < 4; e++)
          hA[4 + u][e] = swiglu(a2[8 * u + 2 * e], a2[8 * u + 2 * e + 1], a2[16 + 8 * u + 2 * e], a2[17 + 8 * u + 2 * e], (e & 1) ? rs1 : rs0);
      keep(hA);
      wg_bar(p);
    }
    PSTAMP(10);

    uint32_t hB[8][4];
    {
      float ab[128];
      uint32_t db = descB(RING);
      const uint32_t dAn = descA(H1) - p * 4096;
#pragma unroll 1
      for (int i = 0; i < 8; i++) {
        mbar_wait(BAR + (B_FB + i) * 8);
        const uint32_t da = dAn + i * 512;
        wg_fence();
        wgmma_ss_n256(ab, da, db, i);
#pragma unroll
        for (int k = 1; k < 4; k++) wgmma_ss_n256(ab, da + k * 2, db + k * 128, 1);
        wg_commit();
        wg_wait<1>();
        mbar_arrive_if(BAR + (B_EB + i - 1) * 8, i > 0 && lane == 0);
        db = db == descB(RING + 65536) ? descB(RING) : db + 2048;
      }
      wg_wait<0>();
      keep(ab);
      if (lane == 0) mbar_arrive(BAR + (B_EB + 7) * 8);
      PSTAMP(11);
#pragma unroll
      for (int u = 0; u < 8; u++) {
        const int o = (u >> 2) * 64 + (u & 3) * 8;
#pragma unroll
        for (int e = 0; e < 4; e++)
          hB[u][e] = swiglu(ab[o + 2 * e], ab[o + 2 * e + 1], ab[o + 32 + 2 * e], ab[o + 33 + 2 * e], (e & 1) ? rs1 : rs0);
      }
      keep(hB);
    }
    PSTAMP(12);

    {
      float y[32], sum[32];
      unpack32(sum, hf);
      const uint32_t offA = (j & 1) ? 256 : 0, offH = (j & 1) ? 0 : 1536;
      uint4* e4 = X->e4 + (size_t)xw * 64 * 128 + lane;
      uint32_t in[4][4];
#pragma unroll
      for (int u = 0; u < 4; u++) { in[u][0] = tag; in[u][1] = 0; in[u][2] = 0; in[u][3] = 0; }
      auto insrc = [&](int q) { return e4 + (j * 8 + ((j - 1 - q) & 7)) * 128; };
      mbar_wait(BAR + B_CLR * 8);
      const uint32_t ident = (2 * c == r ? 0x3f80u : 0u) | (2 * c + 1 == r ? 0x3f800000u : 0u);
      auto acc = [&]() {
#pragma unroll
        for (int u = 0; u < 4; u++) {
          mma1688_acc(*reinterpret_cast<float (*)[4]>(&sum[8 * u]), in[u][0] & ~1u, in[u][1], ident);
          mma1688_acc(*reinterpret_cast<float (*)[4]>(&sum[8 * u + 4]), in[u][2], in[u][3], ident);
        }
      };
#pragma unroll 1
      for (int m = 0; m < 8; m++) {
        if (m >= 2) ll_issue<4>(in, insrc(m - 2), 32);
        mbar_wait(BAR + (B_FT + m) * 8);
        const uint32_t T = descB(0) + (t_addr(m) >> 4);
        asm volatile("{\n.reg .pred p;\nsetp.ne.u32 p, %1, 0;\n@p bar.sync %0, 256;\n}\n"
                     ::"r"(6 + p), "r"((uint32_t)(p == 0 ? m > PP_AHEAD : m + PP_AHEAD < 8)) : "memory");
        wg_fence();
#pragma unroll
        for (int k = 0; k < 4; k++) wgmma_rs_n64(y, hA[k], T + offA + k * 128, k);
#pragma unroll
        for (int k = 0; k < 2; k++) wgmma_rs_n64(y, hA[4 + k], T + offH + k * 128, 1);
#pragma unroll
        for (int k = 0; k < 8; k++) wgmma_rs_n64(y, hB[k], T + offA + 512 + k * 128, 1);
        wg_commit();
        asm volatile("{\n.reg .pred p;\nsetp.ne.u32 p, %1, 0;\n@p bar.arrive %0, 256;\n}\n"
                     ::"r"(7 - p), "r"((uint32_t)(p == 0 ? m >= PP_AHEAD : m + PP_AHEAD < 7)) : "memory");
        wg_wait<0>();
        keep(y);
        mbar_arrive_if(BAR + B_ET0 * 8, m == 0 && lane == 0);
        uint4* dst = e4 + (((j + 1 + m) & 7) * 8 + j) * 128;
        uint32_t pk[4][4];
        pack32(pk, y);
#pragma unroll
        for (int u = 0; u < 4; u++) ll_st(dst + u * 32, pk[u][0], pk[u][1], pk[u][2], pk[u][3], tag);
        if (m == 7) PSTAMP(13);
        if (m == 1) PSTAMP(27);
        if (m == 3) PSTAMP(26);
        if (m == 5) PSTAMP(28);
        if (__builtin_expect(ll_bad<4>(in, pin(tag, zero)), 0)) ll_spin<4>(in, insrc(m - 2), 32, tag);
        acc();
      }
      ll_spin<4>(in, insrc(6), 32, tag);
      acc();
      PSTAMP(14);
      const uint32_t stg = H0 + p * 65536 + 28672 + (w >> 1) * 32768 + (w & 1) * 2048;
#pragma unroll
      for (int u = 0; u < 4; u++) {
        uint32_t o[4];
#pragma unroll
        for (int e = 0; e < 4; e++) o[e] = pack2(sum[8 * u + 2 * e] + y[8 * u + 2 * e], sum[8 * u + 2 * e + 1] + y[8 * u + 2 * e + 1]);
        stsm4(stg + (moff ^ (u << 5)), o);
      }
      fence_async_smem();
      __syncwarp();
      if (elect_one()) {
        tma3d_store(&P.out, stg, 64 * j, p, g * 64 + 16 * w);
        asm volatile("cp.async.bulk.commit_group;" ::: "memory");
        asm volatile("cp.async.bulk.wait_group.read 0;" ::: "memory");
      }
      PSTAMP(15);
    }
  }
}

typedef CUresult (*EncodeFn)(CUtensorMap*, CUtensorMapDataType, cuuint32_t, void*, const cuuint64_t*, const cuuint64_t*,
                             const cuuint32_t*, const cuuint32_t*, CUtensorMapInterleave, CUtensorMapSwizzle,
                             CUtensorMapL2promotion, CUtensorMapFloatOOBfill);

void enc2d(EncodeFn f, CUtensorMap* m, const void* base, uint64_t cols, uint64_t rows, uint32_t bc, uint32_t br, CUtensorMapSwizzle sw) {
  cuuint64_t gd[2] = {cols, rows}, gs[1] = {cols * 2};
  cuuint32_t bd[2] = {bc, br}, es[2] = {1, 1};
  f(m, CU_TENSOR_MAP_DATA_TYPE_BFLOAT16, 2, const_cast<void*>(base), gd, gs, bd, es, CU_TENSOR_MAP_INTERLEAVE_NONE, sw,
    CU_TENSOR_MAP_L2_PROMOTION_L2_128B, CU_TENSOR_MAP_FLOAT_OOB_FILL_NONE);
}
void enc_par(EncodeFn f, CUtensorMap* m, const void* base, uint32_t pairs) {
  cuuint64_t gd[3] = {(cuuint64_t)D_, 2, (cuuint64_t)S_ / 2}, gs[2] = {D_ * 2, D_ * 4};
  cuuint32_t bd[3] = {64, 1, pairs}, es[3] = {1, 1, 1};
  f(m, CU_TENSOR_MAP_DATA_TYPE_BFLOAT16, 3, const_cast<void*>(base), gd, gs, bd, es, CU_TENSOR_MAP_INTERLEAVE_NONE,
    CU_TENSOR_MAP_SWIZZLE_128B, CU_TENSOR_MAP_L2_PROMOTION_L2_128B, CU_TENSOR_MAP_FLOAT_OOB_FILL_NONE);
}

}

extern "C" void kernel_launch(void* const* d_in, const int* in_sizes, int n_in, void* d_out, int out_size) {
  (void)in_sizes; (void)n_in; (void)out_size;
  static EncodeFn enc = nullptr;
  static Scratch* scratch = nullptr;
  if (!enc) {
    void* fn = nullptr;
    cudaDriverEntryPointQueryResult q;
    cudaGetDriverEntryPoint("cuTensorMapEncodeTiled", &fn, cudaEnableDefault, &q);
    enc = (EncodeFn)fn;
    cudaGetSymbolAddress((void**)&scratch, g_scratch);
    cudaFuncSetAttribute(fused_block_kernel, cudaFuncAttributeMaxDynamicSharedMemorySize, SMEM_BYTES);
  }
  Params P;
  const __nv_bfloat16* xp = (const __nv_bfloat16*)d_in[0];
  const __nv_bfloat16* wqkvp = (const __nv_bfloat16*)d_in[1];
  const __nv_bfloat16* wop = (const __nv_bfloat16*)d_in[2];
  P.w1p = (const __nv_bfloat16*)d_in[4];
  P.w3p = (const __nv_bfloat16*)d_in[5];
  P.w2p = (const __nv_bfloat16*)d_in[6];
  enc_par(enc, &P.x, xp, 64);
  enc_par(enc, &P.out, d_out, 16);
  enc2d(enc, &P.wqkv, wqkvp, 3 * D_, D_, 64, 64, CU_TENSOR_MAP_SWIZZLE_128B);
  enc2d(enc, &P.wo, wop, D_, D_, 64, 64, CU_TENSOR_MAP_SWIZZLE_128B);
  enc2d(enc, &P.w1, P.w1p, F_, D_, 64, 64, CU_TENSOR_MAP_SWIZZLE_128B);
  enc2d(enc, &P.w3, P.w3p, F_, D_, 64, 64, CU_TENSOR_MAP_SWIZZLE_128B);
  enc2d(enc, &P.w1h, P.w1p, F_, D_, 32, 64, CU_TENSOR_MAP_SWIZZLE_64B);
  enc2d(enc, &P.w3h, P.w3p, F_, D_, 32, 64, CU_TENSOR_MAP_SWIZZLE_64B);
  enc2d(enc, &P.w2, P.w2p, D_, F_, 64, 224, CU_TENSOR_MAP_SWIZZLE_128B);

  cudaLaunchConfig_t cfg = {};
  cfg.gridDim = dim3(128);
  cfg.blockDim = dim3(384);
  cfg.dynamicSmemBytes = SMEM_BYTES;
  cfg.stream = cudaStreamPerThread;
  cudaLaunchAttribute at[1];
  at[0].id = cudaLaunchAttributeCooperative;
  at[0].val.cooperative = 1;
  cfg.attrs = at;
  cfg.numAttrs = 1;
  cudaLaunchKernelEx(&cfg, fused_block_kernel, scratch, xp, wqkvp, wop, 0u, P);
}
```

```cpp
#include <cuda_runtime.h>
#include <cuda.h>
#include <cuda_bf16.h>
#include <stdint.h>
#include <stddef.h>

namespace {

constexpr int S_ = 2048, D_ = 512, F_ = 1792;
#define LAG_KB 3
#define E4_FIRST 7
#define PP_AHEAD 1
#define SIDE_KB 0
#define CLR_MODE 0
#define W2_HEAD 3
#define XO_DELAY 2

constexpr uint32_t SPIN_LIMIT = 1u << 18;

struct Scratch {
  uint4 e4[16 * 2 * 4 * 8 * 8 * 4 * 32];
  uint4 e2[16 * 2 * 4 * 32 * 32];
  uint4 e3h[16 * 2 * 4 * 32 * 32];
  uint4 e1[16 * 8 * 2 * 4 * 32];
  uint4 e2s[16 * 2 * 4 * 8 * 8];
  uint4 e3s[16 * 2 * 4 * 8 * 8];
  uint4 e0c[8 * 3 * 16 * 16];
  uint4 e0s[2048];
  uint4 e0w[8 * 64];
  unsigned epoch[128];
};
__device__ Scratch g_scratch;
#define PSTAMP(i)
#define PSTAMPW(slot, i)
#define W2STAMP(i)

struct alignas(64) Params {
  CUtensorMap x, out, wqkv, wo, w1, w3, w1h, w3h, w2;
  const __nv_bfloat16 *w1p, *w3p, *w2p;
};

constexpr uint32_t SB = 1024;
constexpr uint32_t H0 = SB;
constexpr uint32_t H1 = SB + 65536;
constexpr uint32_t RING = SB + 131072;
constexpr uint32_t BAR = SB + 229376;
constexpr uint32_t TAGS = BAR + 1016;
constexpr uint32_t CS = BAR + 1024;
constexpr uint32_t ST = CS + 768;
constexpr uint32_t WB = ST + 1024;
constexpr uint32_t SMEM_BYTES = 232448;
static_assert(WB + 256 <= SB + SMEM_BYTES, "smem");

enum : int {
  B_FX = 0,
  B_FKV = 16, B_FQ = 24, B_FWO = 32, B_FA = 40, B_FB = 48, B_FT = 56,
  B_EKV = 64, B_EQ = 72, B_EA = 80, B_EB = 88, B_ET0 = 96,
  B_WODONE = 97,
  B_EX = 104,
  B_LAG = 112, B_READY = 113, B_PUB = 114, B_CLR = 115, B_CLR0 = 116, B_TAG = 117
};

__device__ __forceinline__ uint32_t smem_u32(const void* p) { return (uint32_t)__cvta_generic_to_shared(p); }
__device__ __forceinline__ void mbar_init(uint32_t b, uint32_t c) { asm volatile("mbarrier.init.shared::cta.b64 [%0], %1;" ::"r"(b), "r"(c) : "memory"); }
__device__ __forceinline__ void mbar_expect_tx(uint32_t b, uint32_t bytes) { asm volatile("mbarrier.arrive.expect_tx.shared::cta.b64 _, [%0], %1;" ::"r"(b), "r"(bytes) : "memory"); }
__device__ __forceinline__ void mbar_arrive(uint32_t b) { asm volatile("mbarrier.arrive.shared::cta.b64 _, [%0];" ::"r"(b) : "memory"); }
__device__ __forceinline__ void mbar_wait(uint32_t b) {
  asm volatile("{\n.reg .pred p;\n.reg .u32 c;\nmov.u32 c, 0;\nLW:\n.pragma \"nounroll\";\n"
               "mbarrier.try_wait.parity.shared::cta.b64 p, [%0], 0;\nadd.u32 c, c, 1;\nsetp.gt.or.u32 p, c, %1, p;\n@!p bra LW;\n}\n"
               ::"r"(b), "n"(SPIN_LIMIT) : "memory");
}
__device__ __forceinline__ bool elect_one() {
  uint32_t p;
  asm volatile("{\n.reg .pred P;\nelect.sync _|P, 0xffffffff;\nselp.u32 %0, 1, 0, P;\n}\n" : "=r"(p));
  return p;
}
__device__ __forceinline__ void tma2d(uint32_t dst, const CUtensorMap* m, int c0, int c1, uint32_t bar) {
  asm volatile("cp.async.bulk.tensor.2d.shared::cluster.global.mbarrier::complete_tx::bytes [%0], [%1, {%3, %4}], [%2];"
               ::"r"(dst), "l"(m), "r"(bar), "r"(c0), "r"(c1) : "memory");
}
__device__ __forceinline__ void tma3d(uint32_t dst, const CUtensorMap* m, int c0, int c1, int c2, uint32_t bar) {
  asm volatile("cp.async.bulk.tensor.3d.shared::cluster.global.mbarrier::complete_tx::bytes [%0], [%1, {%3, %4, %5}], [%2];"
               ::"r"(dst), "l"(m), "r"(bar), "r"(c0), "r"(c1), "r"(c2) : "memory");
}
__device__ __forceinline__ void tma3d_store(const CUtensorMap* m, uint32_t src, int c0, int c1, int c2) {
  asm volatile("cp.async.bulk.tensor.3d.global.shared::cta.bulk_group [%0, {%2, %3, %4}], [%1];"
               ::"l"(m), "r"(src), "r"(c0), "r"(c1), "r"(c2) : "memory");
}
__device__ __forceinline__ void l2_prefetch(const void* p, uint32_t bytes) {
  asm volatile("cp.async.bulk.prefetch.L2.global [%0], %1;" ::"l"(p), "r"(bytes) : "memory");
}
__device__ __forceinline__ void prefetch_map(const CUtensorMap* m) { asm volatile("prefetch.tensormap [%0];" ::"l"(m) : "memory"); }
__device__ __forceinline__ void fence_async_smem() { asm volatile("fence.proxy.async.shared::cta;" ::: "memory"); }
__device__ __forceinline__ void wg_fence() { asm volatile("wgmma.fence.sync.aligned;" ::: "memory"); }
__device__ __forceinline__ void wg_commit() { asm volatile("wgmma.commit_group.sync.aligned;" ::: "memory"); }
template <int N> __device__ __forceinline__ void wg_wait() { asm volatile("wgmma.wait_group.sync.aligned %0;" ::"n"(N) : "memory"); }
__device__ __forceinline__ void wg_bar(int p) {
  if (p == 0) asm volatile("bar.sync 1, 128;" ::: "memory"); else asm volatile("bar.sync 2, 128;" ::: "memory");
}
constexpr uint32_t DESC_HI128 = (1024 >> 4) | (1u << 30);
constexpr uint32_t DESC_HI64 = (512 >> 4) | (2u << 30);
__device__ __forceinline__ constexpr uint32_t descA(uint32_t addr) { return (addr >> 4) | (1u << 16); }
__device__ __forceinline__ constexpr uint32_t descB(uint32_t addr) { return (addr >> 4) | ((8192u >> 4) << 16); }
__device__ __forceinline__ constexpr uint32_t descBh(uint32_t addr) { return (addr >> 4) | ((4096u >> 4) << 16); }

__device__ __forceinline__ void wgmma_ss_n64(float (&d)[32], uint32_t da, uint32_t db, int sc) {
  asm volatile("{\n.reg .pred p;\n.reg .b64 da, db;\nsetp.ne.b32 p, %34, 0;\nmov.b64 da, {%32, %35};\nmov.b64 db, {%33, %35};\n"
    "wgmma.mma_async.sync.aligned.m64n64k16.f32.bf16.bf16 {%0, %1, %2, %3, %4, %5, %6, %7, %8, %9, %10, %11, %12, %13, %14, %15, %16, %17, %18, %19, %20, %21, %22, %23, %24, %25, %26, %27, %28, %29, %30, %31}, da, db, p, 1, 1, 0, 1;\n}\n"
    : "+f"(d[0]), "+f"(d[1]), "+f"(d[2]), "+f"(d[3]), "+f"(d[4]), "+f"(d[5]), "+f"(d[6]), "+f"(d[7]),
      "+f"(d[8]), "+f"(d[9]), "+f"(d[10]), "+f"(d[11]), "+f"(d[12]), "+f"(d[13]), "+f"(d[14]), "+f"(d[15]),
      "+f"(d[16]), "+f"(d[17]), "+f"(d[18]), "+f"(d[19]), "+f"(d[20]), "+f"(d[21]), "+f"(d[22]), "+f"(d[23]),
      "+f"(d[24]), "+f"(d[25]), "+f"(d[26]), "+f"(d[27]), "+f"(d[28]), "+f"(d[29]), "+f"(d[30]), "+f"(d[31])
    : "r"(da), "r"(db), "r"(sc), "n"(DESC_HI128));
}
__device__ __forceinline__ void wgmma_ss_n128(float (&d)[64], uint32_t da, uint32_t db, int sc) {
  asm volatile("{\n.reg .pred p;\n.reg .b64 da, db;\nsetp.ne.b32 p, %66, 0;\nmov.b64 da, {%64, %67};\nmov.b64 db, {%65, %67};\n"
    "wgmma.mma_async.sync.aligned.m64n128k16.f32.bf16.bf16 {%0, %1, %2, %3, %4, %5, %6, %7, %8, %9, %10, %11, %12, %13, %14, %15, %16, %17, %18, %19, %20, %21, %22, %23, %24, %25, %26, %27, %28, %29, %30, %31, %32, %33, %34, %35, %36, %37, %38, %39, %40, %41, %42, %43, %44, %45, %46, %47, %48, %49, %50, %51, %52, %53, %54, %55, %56, %57, %58, %59, %60, %61, %62, %63}, da, db, p, 1, 1, 0, 1;\n}\n"
    : "+f"(d[0]), "+f"(d[1]), "+f"(d[2]), "+f"(d[3]), "+f"(d[4]), "+f"(d[5]), "+f"(d[6]), "+f"(d[7]),
      "+f"(d[8]), "+f"(d[9]), "+f"(d[10]), "+f"(d[11]), "+f"(d[12]), "+f"(d[13]), "+f"(d[14]), "+f"(d[15]),
      "+f"(d[16]), "+f"(d[17]), "+f"(d[18]), "+f"(d[19]), "+f"(d[20]), "+f"(d[21]), "+f"(d[22]), "+f"(d[23]),
      "+f"(d[24]), "+f"(d[25]), "+f"(d[26]), "+f"(d[27]), "+f"(d[28]), "+f"(d[29]), "+f"(d[30]), "+f"(d[31]),
      "+f"(d[32]), "+f"(d[33]), "+f"(d[34]), "+f"(d[35]), "+f"(d[36]), "+f"(d[37]), "+f"(d[38]), "+f"(d[39]),
      "+f"(d[40]), "+f"(d[41]), "+f"(d[42]), "+f"(d[43]), "+f"(d[44]), "+f"(d[45]), "+f"(d[46]), "+f"(d[47]),
      "+f"(d[48]), "+f"(d[49]), "+f"(d[50]), "+f"(d[51]), "+f"(d[52]), "+f"(d[53]), "+f"(d[54]), "+f"(d[55]),
      "+f"(d[56]), "+f"(d[57]), "+f"(d[58]), "+f"(d[59]), "+f"(d[60]), "+f"(d[61]), "+f"(d[62]), "+f"(d[63])
    : "r"(da), "r"(db), "r"(sc), "n"(DESC_HI128));
}
__device__ __forceinline__ void wgmma_ss_n256(float (&d)[128], uint32_t da, uint32_t db, int sc) {
  asm volatile("{\n.reg .pred p;\n.reg .b64 da, db;\nsetp.ne.b32 p, %130, 0;\nmov.b64 da, {%128, %131};\nmov.b64 db, {%129, %131};\n"
    "wgmma.mma_async.sync.aligned.m64n256k16.f32.bf16.bf16 {%0, %1, %2, %3, %4, %5, %6, %7, %8, %9, %10, %11, %12, %13, %14, %15, %16, %17, %18, %19, %20, %21, %22, %23, %24, %25, %26, %27, %28, %29, %30, %31, %32, %33, %34, %35, %36, %37, %38, %39, %40, %41, %42, %43, %44, %45, %46, %47, %48, %49, %50, %51, %52, %53, %54, %55, %56, %57, %58, %59, %60, %61, %62, %63, %64, %65, %66, %67, %68, %69, %70, %71, %72, %73, %74, %75, %76, %77, %78, %79, %80, %81, %82, %83, %84, %85, %86, %87, %88, %89, %90, %91, %92, %93, %94, %95, %96, %97, %98, %99, %100, %101, %102, %103, %104, %105, %106, %107, %108, %109, %110, %111, %112, %113, %114, %115, %116, %117, %118, %119, %120, %121, %122, %123, %124, %125, %126, %127}, da, db, p, 1, 1, 0, 1;\n}\n"
    : "+f"(d[0]), "+f"(d[1]), "+f"(d[2]), "+f"(d[3]), "+f"(d[4]), "+f"(d[5]), "+f"(d[6]), "+f"(d[7]),
      "+f"(d[8]), "+f"(d[9]), "+f"(d[10]), "+f"(d[11]), "+f"(d[12]), "+f"(d[13]), "+f"(d[14]), "+f"(d[15]),
      "+f"(d[16]), "+f"(d[17]), "+f"(d[18]), "+f"(d[19]), "+f"(d[20]), "+f"(d[21]), "+f"(d[22]), "+f"(d[23]),
      "+f"(d[24]), "+f"(d[25]), "+f"(d[26]), "+f"(d[27]), "+f"(d[28]), "+f"(d[29]), "+f"(d[30]), "+f"(d[31]),
      "+f"(d[32]), "+f"(d[33]), "+f"(d[34]), "+f"(d[35]), "+f"(d[36]), "+f"(d[37]), "+f"(d[38]), "+f"(d[39]),
      "+f"(d[40]), "+f"(d[41]), "+f"(d[42]), "+f"(d[43]), "+f"(d[44]), "+f"(d[45]), "+f"(d[46]), "+f"(d[47]),
      "+f"(d[48]), "+f"(d[49]), "+f"(d[50]), "+f"(d[51]), "+f"(d[52]), "+f"(d[53]), "+f"(d[54]), "+f"(d[55]),
      "+f"(d[56]), "+f"(d[57]), "+f"(d[58]), "+f"(d[59]), "+f"(d[60]), "+f"(d[61]), "+f"(d[62]), "+f"(d[63]),
      "+f"(d[64]), "+f"(d[65]), "+f"(d[66]), "+f"(d[67]), "+f"(d[68]), "+f"(d[69]), "+f"(d[70]), "+f"(d[71]),
      "+f"(d[72]), "+f"(d[73]), "+f"(d[74]), "+f"(d[75]), "+f"(d[76]), "+f"(d[77]), "+f"(d[78]), "+f"(d[79]),
      "+f"(d[80]), "+f"(d[81]), "+f"(d[82]), "+f"(d[83]), "+f"(d[84]), "+f"(d[85]), "+f"(d[86]), "+f"(d[87]),
      "+f"(d[88]), "+f"(d[89]), "+f"(d[90]), "+f"(d[91]), "+f"(d[92]), "+f"(d[93]), "+f"(d[94]), "+f"(d[95]),
      "+f"(d[96]), "+f"(d[97]), "+f"(d[98]), "+f"(d[99]), "+f"(d[100]), "+f"(d[101]), "+f"(d[102]), "+f"(d[103]),
      "+f"(d[104]), "+f"(d[105]), "+f"(d[106]), "+f"(d[107]), "+f"(d[108]), "+f"(d[109]), "+f"(d[110]), "+f"(d[111]),
      "+f"(d[112]), "+f"(d[113]), "+f"(d[114]), "+f"(d[115]), "+f"(d[116]), "+f"(d[117]), "+f"(d[118]), "+f"(d[119]),
      "+f"(d[120]), "+f"(d[121]), "+f"(d[122]), "+f"(d[123]), "+f"(d[124]), "+f"(d[125]), "+f"(d[126]), "+f"(d[127])
    : "r"(da), "r"(db), "r"(sc), "n"(DESC_HI128));
}
template <uint32_t HI = DESC_HI128>
__device__ __forceinline__ void wgmma_rs_n64(float (&d)[32], const uint32_t (&a)[4], uint32_t db, int sc) {
  asm volatile("{\n.reg .pred p;\n.reg .b64 db;\nsetp.ne.b32 p, %37, 0;\nmov.b64 db, {%36, %38};\n"
    "wgmma.mma_async.sync.aligned.m64n64k16.f32.bf16.bf16 {%0, %1, %2, %3, %4, %5, %6, %7, %8, %9, %10, %11, %12, %13, %14, %15, %16, %17, %18, %19, %20, %21, %22, %23, %24, %25, %26, %27, %28, %29, %30, %31}, {%32, %33, %34, %35}, db, p, 1, 1, 1;\n}\n"
    : "+f"(d[0]), "+f"(d[1]), "+f"(d[2]), "+f"(d[3]), "+f"(d[4]), "+f"(d[5]), "+f"(d[6]), "+f"(d[7]),
      "+f"(d[8]), "+f"(d[9]), "+f"(d[10]), "+f"(d[11]), "+f"(d[12]), "+f"(d[13]), "+f"(d[14]), "+f"(d[15]),
      "+f"(d[16]), "+f"(d[17]), "+f"(d[18]), "+f"(d[19]), "+f"(d[20]), "+f"(d[21]), "+f"(d[22]), "+f"(d[23]),
      "+f"(d[24]), "+f"(d[25]), "+f"(d[26]), "+f"(d[27]), "+f"(d[28]), "+f"(d[29]), "+f"(d[30]), "+f"(d[31])
    : "r"(a[0]), "r"(a[1]), "r"(a[2]), "r"(a[3]), "r"(db), "r"(sc), "n"(HI));
}
template <uint32_t HI = DESC_HI128>
__device__ __forceinline__ void wgmma_rs_n128(float (&d)[64], const uint32_t (&a)[4], uint32_t db, int sc) {
  asm volatile("{\n.reg .pred p;\n.reg .b64 db;\nsetp.ne.b32 p, %69, 0;\nmov.b64 db, {%68, %70};\n"
    "wgmma.mma_async.sync.aligned.m64n128k16.f32.bf16.bf16 {%0, %1, %2, %3, %4, %5, %6, %7, %8, %9, %10, %11, %12, %13, %14, %15, %16, %17, %18, %19, %20, %21, %22, %23, %24, %25, %26, %27, %28, %29, %30, %31, %32, %33, %34, %35, %36, %37, %38, %39, %40, %41, %42, %43, %44, %45, %46, %47, %48, %49, %50, %51, %52, %53, %54, %55, %56, %57, %58, %59, %60, %61, %62, %63}, {%64, %65, %66, %67}, db, p, 1, 1, 1;\n}\n"
    : "+f"(d[0]), "+f"(d[1]), "+f"(d[2]), "+f"(d[3]), "+f"(d[4]), "+f"(d[5]), "+f"(d[6]), "+f"(d[7]),
      "+f"(d[8]), "+f"(d[9]), "+f"(d[10]), "+f"(d[11]), "+f"(d[12]), "+f"(d[13]), "+f"(d[14]), "+f"(d[15]),
      "+f"(d[16]), "+f"(d[17]), "+f"(d[18]), "+f"(d[19]), "+f"(d[20]), "+f"(d[21]), "+f"(d[22]), "+f"(d[23]),
      "+f"(d[24]), "+f"(d[25]), "+f"(d[26]), "+f"(d[27]), "+f"(d[28]), "+f"(d[29]), "+f"(d[30]), "+f"(d[31]),
      "+f"(d[32]), "+f"(d[33]), "+f"(d[34]), "+f"(d[35]), "+f"(d[36]), "+f"(d[37]), "+f"(d[38]), "+f"(d[39]),
      "+f"(d[40]), "+f"(d[41]), "+f"(d[42]), "+f"(d[43]), "+f"(d[44]), "+f"(d[45]), "+f"(d[46]), "+f"(d[47]),
      "+f"(d[48]), "+f"(d[49]), "+f"(d[50]), "+f"(d[51]), "+f"(d[52]), "+f"(d[53]), "+f"(d[54]), "+f"(d[55]),
      "+f"(d[56]), "+f"(d[57]), "+f"(d[58]), "+f"(d[59]), "+f"(d[60]), "+f"(d[61]), "+f"(d[62]), "+f"(d[63])
    : "r"(a[0]), "r"(a[1]), "r"(a[2]), "r"(a[3]), "r"(db), "r"(sc), "n"(HI));
}

template <int N> __device__ __forceinline__ void keep(float (&d)[N]) {
#pragma unroll
  for (int i = 0; i < N; i++) asm volatile("" : "+f"(d[i])::"memory");
}

__device__ __forceinline__ void keep(uint32_t (&d)[4]) { asm volatile("" : "+r"(d[0]), "+r"(d[1]), "+r"(d[2]), "+r"(d[3])::"memory"); }
template <int N> __device__ __forceinline__ void keep(uint32_t (&d)[N][4]) {
#pragma unroll
  for (int i = 0; i < N; i++) asm volatile("" : "+r"(d[i][0]), "+r"(d[i][1]), "+r"(d[i][2]), "+r"(d[i][3])::"memory");
}

__device__ __forceinline__ uint32_t pack2(float lo, float hi) {
  uint32_t r;
  asm("cvt.rn.bf16x2.f32 %0, %1, %2;" : "=r"(r) : "f"(hi), "f"(lo));
  return r;
}
__device__ __forceinline__ float bf_lo(uint32_t v) { return __uint_as_float(v << 16); }
__device__ __forceinline__ float bf_hi(uint32_t v) { return __uint_as_float(v & 0xffff0000u); }
__device__ __forceinline__ uint32_t hsub2(uint32_t a, uint32_t b) {
  uint32_t r;
  asm("sub.rn.bf16x2 %0, %1, %2;" : "=r"(r) : "r"(a), "r"(b));
  return r;
}
__device__ __forceinline__ uint32_t movm(uint32_t a) {
  uint32_t r;
  asm volatile("movmatrix.sync.aligned.m8n8.trans.b16 %0, %1;" : "=r"(r) : "r"(a));
  return r;
}
__device__ __forceinline__ void ldsm4(uint32_t (&v)[4], uint32_t a) {
  asm volatile("ldmatrix.sync.aligned.m8n8.x4.shared.b16 {%0,%1,%2,%3}, [%4];" : "=r"(v[0]), "=r"(v[1]), "=r"(v[2]), "=r"(v[3]) : "r"(a) : "memory");
}
__device__ __forceinline__ void stsm4(uint32_t a, const uint32_t (&v)[4]) {
  asm volatile("stmatrix.sync.aligned.m8n8.x4.shared.b16 [%0], {%1,%2,%3,%4};" ::"r"(a), "r"(v[0]), "r"(v[1]), "r"(v[2]), "r"(v[3]) : "memory");
}
__device__ __forceinline__ void mma16816(float (&d)[4], const uint32_t (&a)[4], uint32_t b0, uint32_t b1) {
  asm volatile("mma.sync.aligned.m16n8k16.row.col.f32.bf16.bf16.f32 {%0,%1,%2,%3}, {%4,%5,%6,%7}, {%8,%9}, {%10,%10,%10,%10};"
               : "=f"(d[0]), "=f"(d[1]), "=f"(d[2]), "=f"(d[3])
               : "r"(a[0]), "r"(a[1]), "r"(a[2]), "r"(a[3]), "r"(b0), "r"(b1), "f"(0.f));
}
__device__ __forceinline__ void mma1688_acc(float (&d)[4], uint32_t a0, uint32_t a1, uint32_t b0) {
  asm volatile("mma.sync.aligned.m16n8k8.row.col.f32.bf16.bf16.f32 {%0,%1,%2,%3}, {%4,%5}, {%6}, {%0,%1,%2,%3};"
               : "+f"(d[0]), "+f"(d[1]), "+f"(d[2]), "+f"(d[3]) : "r"(a0), "r"(a1), "r"(b0));
}
__device__ __forceinline__ float ex2(float x) { float y; asm("ex2.approx.ftz.f32 %0, %1;" : "=f"(y) : "f"(x)); return y; }
__device__ __forceinline__ float rcp(float x) { float y; asm("rcp.approx.ftz.f32 %0, %1;" : "=f"(y) : "f"(x)); return y; }
__device__ __forceinline__ float tanhf_hw(float x) { float y; asm("tanh.approx.f32 %0, %1;" : "=f"(y) : "f"(x)); return y; }
__device__ __forceinline__ uint32_t lds32(uint32_t a) { uint32_t v; asm volatile("ld.shared.u32 %0, [%1];" : "=r"(v) : "r"(a) : "memory"); return v; }
__device__ __forceinline__ float2 lds64(uint32_t a) { float2 v; asm volatile("ld.shared.v2.f32 {%0,%1}, [%2];" : "=f"(v.x), "=f"(v.y) : "r"(a) : "memory"); return v; }
__device__ __forceinline__ void lds128(uint32_t (&v)[4], uint32_t a) { asm volatile("ld.shared.v4.u32 {%0,%1,%2,%3}, [%4];" : "=r"(v[0]), "=r"(v[1]), "=r"(v[2]), "=r"(v[3]) : "r"(a) : "memory"); }
__device__ __forceinline__ void sts128(uint32_t a, const uint32_t (&v)[4]) { asm volatile("st.shared.v4.u32 [%0], {%1,%2,%3,%4};" ::"r"(a), "r"(v[0]), "r"(v[1]), "r"(v[2]), "r"(v[3]) : "memory"); }
__device__ __forceinline__ void ldg128_nc(uint32_t (&v)[4], const void* p) {
  asm volatile("ld.global.nc.L1::no_allocate.v4.u32 {%0,%1,%2,%3}, [%4];" : "=r"(v[0]), "=r"(v[1]), "=r"(v[2]), "=r"(v[3]) : "l"(p));
}
__device__ __forceinline__ uint32_t pin(uint32_t v, uint32_t zero) {
  asm volatile("{\n.reg .pred p;\n.reg .u32 c;\nmov.u32 c, %1;\nLP:\n.pragma \"nounroll\";\nsetp.eq.u32 p, c, 0;\n@p bra LD;\n"
               "nanosleep.u32 c;\nadd.u32 %0, %0, c;\nsub.u32 c, c, 1;\nbra LP;\nLD:\n}\n" : "+r"(v) : "r"(zero) : "memory");
  return v;
}
__device__ __forceinline__ void mbar_arrive_if(uint32_t b, bool cond) {
  asm volatile("{\n.reg .pred p;\nsetp.ne.u32 p, %1, 0;\n@p mbarrier.arrive.shared::cta.b64 _, [%0];\n}\n" ::"r"(b), "r"((uint32_t)cond) : "memory");
}
__device__ __forceinline__ uint32_t ld_epoch(const unsigned* p) {
  uint32_t v;
  asm volatile("ld.relaxed.gpu.global.u32 %0, [%1];" : "=r"(v) : "l"(p) : "memory");
  return v;
}
__device__ __forceinline__ void ll_st(uint4* p, uint32_t a, uint32_t b, uint32_t c, uint32_t d, uint32_t tag) {
  asm volatile("st.relaxed.gpu.global.v4.b32 [%0], {%1, %2, %3, %4};" ::"l"(p), "r"((a & ~1u) | tag), "r"(b), "r"(c), "r"(d) : "memory");
}
__device__ __forceinline__ void ll_ld(uint32_t (&v)[4], const uint4* p) {
  asm volatile("{\n.reg .b128 t;\n.reg .b64 lo, hi;\nld.relaxed.gpu.global.b128 t, [%4];\nmov.b128 {lo, hi}, t;\n"
               "mov.b64 {%0, %1}, lo;\nmov.b64 {%2, %3}, hi;\n}\n"
               : "=r"(v[0]), "=r"(v[1]), "=r"(v[2]), "=r"(v[3]) : "l"(p) : "memory");
}
template <int N> __device__ __forceinline__ void ll_issue(uint32_t (&v)[N][4], const uint4* p, int stride) {
#pragma unroll
  for (int i = 0; i < N; i++) ll_ld(v[i], p + i * stride);
}
template <int N> __device__ __forceinline__ uint32_t ll_acc(const uint32_t (&v)[N][4], uint32_t tag, uint32_t acc = 0) {
#pragma unroll
  for (int i = 0; i < N; i++) asm("lop3.b32 %0, %1, %2, %0, 0xBE;" : "+r"(acc) : "r"(v[i][0]), "r"(tag));
  return acc;
}
__device__ __forceinline__ bool ll_any(uint32_t acc) { return __any_sync(0xffffffffu, acc & 1u); }
template <int N> __device__ __forceinline__ bool ll_bad(const uint32_t (&v)[N][4], uint32_t tag) { return ll_any(ll_acc<N>(v, tag)); }
template <int N> __device__ __forceinline__ void ll_clear(uint32_t (&v)[N][4]) {
#pragma unroll
  for (int i = 0; i < N; i++) v[i][0] &= ~1u;
}
template <int N> __device__ __forceinline__ void ll_spin(uint32_t (&v)[N][4], const uint4* p, int stride, uint32_t tag) {
  uint32_t it = 0;
#pragma unroll 1
  do { ll_issue<N>(v, p, stride); } while (ll_bad<N>(v, tag) && ++it < SPIN_LIMIT);
}
template <int N> __device__ __forceinline__ void ll_get(uint32_t (&v)[N][4], const uint4* p, int stride, uint32_t tag) {
  ll_spin<N>(v, p, stride, tag);
  ll_clear<N>(v);
}
template <int N> __device__ __forceinline__ void ll_wait(uint32_t (&v)[N][4], const uint4* p, int stride, uint32_t tag) {
  if (__builtin_expect(ll_bad<N>(v, tag), 0)) ll_spin<N>(v, p, stride, tag);
  ll_clear<N>(v);
}
__device__ __forceinline__ void unpack32(float (&d)[32], const uint32_t (&v)[4][4]) {
#pragma unroll
  for (int u = 0; u < 4; u++)
#pragma unroll
    for (int e = 0; e < 4; e++) { d[8 * u + 2 * e] = bf_lo(v[u][e]); d[8 * u + 2 * e + 1] = bf_hi(v[u][e]); }
}
__device__ __forceinline__ void pack32(uint32_t (&v)[4][4], const float (&d)[32]) {
#pragma unroll
  for (int u = 0; u < 4; u++)
#pragma unroll
    for (int e = 0; e < 4; e++) v[u][e] = pack2(d[8 * u + 2 * e], d[8 * u + 2 * e + 1]);
}
__device__ __forceinline__ uint32_t t_addr(int m) { return SB + ((0x03514620u >> (4 * m)) & 7u) * 32768u; }

__device__ __forceinline__ int kb_at(int i, int j) { return i == 0 ? j : (i - 1 + (i - 1 >= j ? 1 : 0)); }

__device__ __forceinline__ void init_bars(int set) {
  if (set >= 0 && elect_one()) {
    const uint32_t cnt = set < 5 ? 1 : 8;
#pragma unroll
    for (int i = 0; i < 8; i++) mbar_init(BAR + (24 + 8 * set + i) * 8, cnt);
    if (set == 9) {
#pragma unroll
      for (int i = 0; i < 9; i++) mbar_init(BAR + (B_EX + i) * 8, 4);
#pragma unroll
      for (int i = 0; i < 4; i++) mbar_init(BAR + (B_READY + i) * 8, i == 1 ? 7 : 3);
      mbar_init(BAR + B_TAG * 8, 1);
    }
    asm volatile("fence.mbarrier_init.release.cluster;" ::: "memory");
  }
  __syncwarp();
  asm volatile("bar.arrive 4, 384;" ::: "memory");
  asm volatile("bar.sync 3, 384;" ::: "memory");
}

__global__ void __launch_bounds__(384, 1) fused_block_kernel(Scratch* __restrict__ X, const __nv_bfloat16* __restrict__ xp,
                                                             const __nv_bfloat16* __restrict__ wqkvp, const __nv_bfloat16* __restrict__ wop, const uint32_t zero,
                                                             const __grid_constant__ Params P) {
  extern __shared__ __align__(1024) uint8_t smem_raw[];
  if (smem_u32(smem_raw) != SB) return;
  const int tid = threadIdx.x;
  const int warp = __shfl_sync(0xffffffffu, tid >> 5, 0);
  const int lane = tid & 31;
  const int cta = blockIdx.x;
  const int j = (cta >> 6) * 4 + (cta & 3);
  const int g = (cta & 63) >> 2;

  if (warp >= 8) {
    asm volatile("setmaxnreg.dec.sync.aligned.u32 56;");
    if (warp == 8) {
      PSTAMPW(2, 0);
      const bool leader = elect_one();
      if (leader) {
        prefetch_map(&P.x); prefetch_map(&P.wqkv);
#pragma unroll
        for (int i = 0; i < 24; i++) mbar_init(BAR + i * 8, 1);
        asm volatile("fence.mbarrier_init.release.cluster;" ::: "memory");
      }
      __syncwarp();
      asm volatile("bar.arrive 3, 384;" ::: "memory");
      PSTAMPW(2, 20);
      auto ldx = [&](int p, int kb) {
        const uint32_t b = BAR + (B_FX + p * 8 + kb) * 8;
        mbar_expect_tx(b, 8192);
        tma3d(H0 + p * 65536 + kb * 8192, &P.x, kb * 64, p, g * 64, b);
      };
      auto ldkv = [&](int kb, int slot) {
        const uint32_t b = BAR + (B_FKV + kb) * 8, d = RING + slot * 16384;
        mbar_expect_tx(b, 16384);
        tma2d(d, &P.wqkv, 512 + 64 * j, kb * 64, b);
        tma2d(d + 8192, &P.wqkv, 1024 + 64 * j, kb * 64, b);
      };
      if (leader) {
#pragma unroll 1
        for (int i = 0; i < 8 + XO_DELAY; i++) {
          if (i < 8) ldx(0, i);
          if (i < 6) ldkv(i, i);
          if (i >= XO_DELAY) ldx(1, i - XO_DELAY);
          if (i == 0) PSTAMPW(2, 21);
        }
        PSTAMPW(2, 2);
      }
      __syncwarp();
      asm volatile("bar.sync 4, 384;" ::: "memory");
      if (leader) {
        const int f0 = 224 * j + ((j & 1) ? 32 : 0);
        const int fh = 224 * j + ((j & 1) ? 0 : 192);
        prefetch_map(&P.wo); prefetch_map(&P.w1); prefetch_map(&P.w3); prefetch_map(&P.w1h);
        prefetch_map(&P.w3h); prefetch_map(&P.w2); prefetch_map(&P.out);
#pragma unroll 1
        for (int i = 0; i < 2; i++) { mbar_wait(BAR + (B_EKV + i) * 8); ldkv(6 + i, i); }
#pragma unroll 1
        for (int i = 0; i < 8; i++) {
          const uint32_t b = BAR + (B_FQ + i) * 8;
          mbar_wait(BAR + (B_EKV + 2 + (i >> 1)) * 8);
          mbar_expect_tx(b, 8192);
          tma2d(RING + (4 + i) * 8192, &P.wqkv, 64 * j, i * 64, b);
        }
        mbar_expect_tx(BAR + B_FWO * 8, 65536);
#pragma unroll 1
        for (int i = 0; i < 8; i++) {
          const int kb = (i + 1) & 7;
          mbar_wait(BAR + (B_EX + i) * 8);
          tma2d(H0 + kb * 8192, &P.wo, 64 * j, kb * 64, BAR + B_FWO * 8);
          PSTAMPW(2, 4 + i);
        }
#pragma unroll 1
        for (int i = 0; i < 8; i++) {
          const uint32_t b = BAR + (B_FA + i) * 8, d = RING + (i & 3) * 24576;
          const int k0 = kb_at(i, j) * 64;
          mbar_wait(BAR + (B_EKV + 7 + ((0xCBA98520u >> (4 * i)) & 15)) * 8);
          mbar_expect_tx(b, 24576);
          tma2d(d, &P.w1, f0, k0, b);
          tma2d(d + 8192, &P.w3, f0, k0, b);
          tma2d(d + 16384, &P.w1h, fh, k0, b);
          tma2d(d + 20480, &P.w3h, fh, k0, b);
          PSTAMPW(2, 12 + i);
        }
        uint32_t d = RING;
#pragma unroll 1
        for (int i = 0; i < 8; i++) {
          const uint32_t b = BAR + (B_FB + i) * 8;
          const int k0 = kb_at(i, j) * 64;
          mbar_wait(BAR + (B_EA + 5 + i) * 8);
          mbar_expect_tx(b, 32768);
          tma2d(d, &P.w1, f0 + 64, k0, b);
          tma2d(d + 8192, &P.w3, f0 + 64, k0, b);
          tma2d(d + 16384, &P.w1, f0 + 128, k0, b);
          tma2d(d + 24576, &P.w3, f0 + 128, k0, b);
          d = d == RING + 65536 ? RING : d + 32768;
        }
#pragma unroll 1
        for (int m = 0; m < 8; m++) {
          const uint32_t b = BAR + (B_FT + m) * 8;
          mbar_wait(BAR + (B_EB + (m == 7 ? 8 : min(m + 3, 7))) * 8);
          mbar_expect_tx(b, 28672);
          tma2d(t_addr(m), &P.w2, 64 * ((j + 1 + m) & 7), 224 * j, b);
        }
        X->epoch[cta] = X->epoch[cta] + 1;
      }
    } else {
      const int part = warp - 9;
      uint32_t tag;
      if (part == 2) {
        tag = ld_epoch(X->epoch + cta);
        init_bars(-1);
        tag = (tag + 1) & 1;
        if (lane == 0) {
          asm volatile("st.shared.u32 [%0], %1;" ::"r"(TAGS), "r"(tag) : "memory");
          mbar_arrive(BAR + B_TAG * 8);
        }
      } else {
        init_bars(warp - 1);
        mbar_wait(BAR + B_TAG * 8);
        tag = lds32(TAGS);
      }
      PSTAMPW(3, 16 + part);
      const int xw0 = g * 8;
      auto clear8 = [&](uint4* p, int stride) {
#pragma unroll
        for (int i = 0; i < 8; i++) ll_st(p + i * stride + lane, 0, 0, 0, 0, tag ^ 1);
      };
      auto clear_front = [&]() {
#pragma unroll 1
      for (int u = part; u < 8; u += 3) clear8((u < 4 ? X->e2 : X->e3h) + (xw0 * 32 + 4 * j + (u & 3)) * 32, 1024);
      if (part == 2) {
        clear8(X->e1 + (g * 8 + j) * 256, 32);
#pragma unroll
        for (int i = 0; i < 4; i++)
          ll_st((i < 2 ? X->e2s : X->e3s) + ((xw0 + (i & 1) * 4 + (lane >> 3)) * 8 + j) * 8 + (lane & 7), 0, 0, 0, 0, tag ^ 1);
      }
      };
      if (CLR_MODE == 1) clear_front();
      PSTAMPW(3, 20 + part);
      uint32_t v[8][4];
      if (part < 2) {
        float s[4] = {0.f, 0.f, 0.f, 0.f}, q[4] = {0.f, 0.f, 0.f, 0.f}, piv = 0.f;
        const uint32_t xa = H0 + part * 65536 + (8 * j + (lane >> 2)) * 128 + (lane & 3) * 16 + (lane & 4) * 16;
#pragma unroll 1
        for (int kb = 0; kb < 8; kb++) {
          mbar_wait(BAR + (B_FX + part * 8 + kb) * 8);
          lds128(v[0], xa + kb * 8192); lds128(v[1], (xa + kb * 8192) ^ 64);
          if (kb == 0) piv = __shfl_sync(0xffffffffu, bf_lo(v[0][0]), lane & 28);
#pragma unroll
          for (int e = 0; e < 8; e++) {
            const float a = bf_lo(v[e >> 2][e & 3]) - piv, b = bf_hi(v[e >> 2][e & 3]) - piv;
            s[e & 3] += a + b; q[e & 3] = fmaf(a, a, q[e & 3]); q[e & 3] = fmaf(b, b, q[e & 3]);
          }
        }
        float ss = (s[0] + s[1]) + (s[2] + s[3]), qq = (q[0] + q[1]) + (q[2] + q[3]);
#pragma unroll
        for (int o = 1; o <= 2; o <<= 1) { ss += __shfl_xor_sync(0xffffffffu, ss, o); qq += __shfl_xor_sync(0xffffffffu, qq, o); }
        const float dm = ss * (1.f / D_);
        const float rs = rsqrtf(fmaxf(fmaf(-dm, dm, qq * (1.f / D_)), 0.f) + 1e-5f);
        if ((lane & 3) == 0) ll_st(X->e0s + g * 128 + 2 * (8 * j + (lane >> 2)) + part, __float_as_uint(piv + dm), __float_as_uint(rs), 0, 0, tag);
      } else {
        mbar_wait(BAR + (B_FKV + SIDE_KB) * 8);
        const __nv_bfloat16* wr = wop + (size_t)(j * 64 + g * 4 + (lane >> 3)) * D_ + (lane & 7) * 8;
#pragma unroll
        for (int i = 0; i < 8; i++) ldg128_nc(v[i], wr + i * 64);
        float s[4];
#pragma unroll
        for (int e = 0; e < 4; e++) {
          s[e] = 0.f;
#pragma unroll
          for (int i = 0; i < 8; i++) s[e] += bf_lo(v[i][e]) + bf_hi(v[i][e]);
        }
        float ss = (s[0] + s[1]) + (s[2] + s[3]);
#pragma unroll
        for (int o = 1; o <= 4; o <<= 1) ss += __shfl_xor_sync(0xffffffffu, ss, o);
        if ((lane & 7) == 0) ll_st(X->e0w + j * 64 + g * 4 + (lane >> 3), __float_as_uint(ss * (1.f / D_)), 0, 0, 0, tag);
      }
      __syncwarp();
      if (lane == 0) mbar_arrive(BAR + B_PUB * 8);
      PSTAMPW(3, part * 4 + 2);
      mbar_wait(BAR + B_PUB * 8);
      PSTAMPW(3, part * 4 + 0);
      {
        uint32_t u[2][4];
        const uint4* us = (part == 2 ? X->e0w + j * 64 : X->e0s + g * 128 + part * 64) + lane;
        const uint4* vs = X->e0c + ((j * 3 + part) * 16 + (lane >> 4) * 8) * 16 + (lane & 15);
        uint32_t it = 0;
#pragma unroll 1
        do { ll_issue<2>(u, us, 32); ll_issue<8>(v, vs, 16); } while (ll_any(ll_acc<8>(v, tag, ll_acc<2>(u, tag))) && ++it < SPIN_LIMIT);
        ll_clear<2>(u); ll_clear<8>(v);
#pragma unroll
        for (int i = 0; i < 2; i++) {
          if (part == 2) asm volatile("st.shared.u32 [%0], %1;" ::"r"(WB + (i * 32 + lane) * 4), "r"(u[i][0]) : "memory");
          else asm volatile("st.shared.v2.u32 [%0], {%1,%2};" ::"r"(ST + (part * 64 + i * 32 + lane) * 8), "r"(u[i][0]), "r"(u[i][1]) : "memory");
        }
      }
      uint32_t o[4];
#pragma unroll
      for (int e = 0; e < 4; e++) {
        float s = 0.f;
#pragma unroll
        for (int i = 0; i < 8; i++) s += __uint_as_float(v[i][e]);
        o[e] = __float_as_uint(s + __shfl_xor_sync(0xffffffffu, s, 16));
      }
      if (lane < 16) sts128(CS + (part * 64 + lane * 4) * 4, o);
      __syncwarp();
      if (lane == 0) mbar_arrive(BAR + B_READY * 8);
      PSTAMPW(3, part * 4 + 1);
      if (CLR_MODE == 2) clear_front();
      __syncwarp();
      if (lane == 0) mbar_arrive(BAR + B_CLR0 * 8);
      PSTAMPW(3, 24 + part);
      if (lane == 0) l2_prefetch(part == 0 ? P.w1p + (size_t)cta * 4 * F_ : part == 1 ? P.w3p + (size_t)cta * 4 * F_ : P.w2p + (size_t)cta * 14 * D_, 14336);
      mbar_wait(BAR + (B_EA + 1) * 8);
#pragma unroll 1
      for (int u = 4 * E4_FIRST + part; u < 28; u += 3)
        clear8(X->e4 + ((size_t)xw0 * 64 + ((j + 1 + (u >> 2)) & 7) * 8 + j) * 128 + (u & 3) * 32, 8192);
      __syncwarp();
      if (lane == 0) mbar_arrive(BAR + B_CLR * 8);
      PSTAMPW(3, part * 4 + 3);
    }
  } else {
    const int p = warp >> 2, w = warp & 3;
    const int r = lane >> 2, c = lane & 3;
    init_bars(warp);
    asm volatile("setmaxnreg.inc.sync.aligned.u32 224;");
    PSTAMP(0);
    const uint32_t dAx = descA(H0) + p * 4096;
    const uint32_t Hn = H1 - p * 65536;
    const uint32_t moff = ((lane & 7) + ((lane >> 3) & 1) * 8) * 128 + (((lane >> 4) ^ (lane & 7)) << 4);
    const uint32_t Xw = H0 + p * 65536 + w * 2048;
    const int xw = (g * 2 + p) * 4 + w;
    if (p == 1) {
      uint32_t v[8][4];
      mbar_wait(BAR + (B_FKV + SIDE_KB) * 8);
      const int wp = w < 3 ? w : 0;
      const __nv_bfloat16* wr = wqkvp + (size_t)(g * 32 + (lane >> 3) * 8) * (3 * D_) + wp * D_ + j * 64 + (lane & 7) * 8;
#pragma unroll
      for (int i = 0; i < 8; i++) ldg128_nc(v[i], wr + (size_t)i * 3 * D_);
      mbar_wait(BAR + B_TAG * 8);
      const uint32_t tg = lds32(TAGS);
      float cs[8];
#pragma unroll
      for (int e = 0; e < 4; e++) {
        float a = 0.f, b = 0.f;
#pragma unroll
        for (int i = 0; i < 8; i++) { a += bf_lo(v[i][e]); b += bf_hi(v[i][e]); }
        cs[2 * e] = a; cs[2 * e + 1] = b;
      }
      const bool up = lane & 8;
#pragma unroll
      for (int e = 0; e < 4; e++) {
        const float keepv = up ? cs[4 + e] : cs[e], give = up ? cs[e] : cs[4 + e];
        cs[e] = keepv + __shfl_xor_sync(0xffffffffu, give, 8);
        cs[e] += __shfl_xor_sync(0xffffffffu, cs[e], 16);
      }
      if (lane < 16 && w < 3)
        ll_st(X->e0c + ((j * 3 + w) * 16 + g) * 16 + (lane & 7) * 2 + (lane >> 3), __float_as_uint(cs[0]), __float_as_uint(cs[1]),
              __float_as_uint(cs[2]), __float_as_uint(cs[3]), tg);
      __syncwarp();
      mbar_arrive_if(BAR + B_PUB * 8, lane == 0);
      PSTAMP(1);
      mbar_wait(BAR + B_LAG * 8);
    }

    float akv[64];
#pragma unroll 1
    for (int kb = 0; kb < 8; kb++) {
      mbar_wait(BAR + (B_FX + p * 8 + kb) * 8);
      mbar_wait(BAR + (B_FKV + kb) * 8);
      if (kb == 0) PSTAMP(2);
      const uint32_t da = dAx + kb * 512, db = descB(RING) + (kb < 6 ? kb : kb - 6) * 1024;
      wg_fence();
      wgmma_ss_n128(akv, da, db, kb);
#pragma unroll
      for (int k = 1; k < 4; k++) wgmma_ss_n128(akv, da + k * 2, db + k * 128, 1);
      wg_commit();
      mbar_arrive_if(BAR + B_LAG * 8, kb == LAG_KB - 1 && p == 0 && lane == 0);
      wg_wait<1>();
      mbar_arrive_if(BAR + (B_EKV + kb - 1) * 8, kb > 0 && lane == 0);
    }
    uint32_t xres[4][4];
#pragma unroll
    for (int u = 0; u < 4; u++) ldsm4(xres[u], Xw + j * 8192 + (moff ^ (u << 5)));

    float aq[32];
    auto qstep = [&](int kb) {
      mbar_wait(BAR + (B_FQ + kb) * 8);
      const uint32_t da = dAx + kb * 512, db = descB(RING + 32768) + kb * 512;
      wg_fence();
      wgmma_ss_n64(aq, da, db, kb);
#pragma unroll
      for (int k = 1; k < 4; k++) wgmma_ss_n64(aq, da + k * 2, db + k * 128, 1);
      wg_commit();
      wg_wait<1>();
      mbar_arrive_if(BAR + (B_EQ + kb - 1) * 8, lane == 0);
      mbar_arrive_if(BAR + (B_EX + kb - 2) * 8, lane == 0 && p == 0 && kb >= 2);
    };
    qstep(0);
    keep(akv);
    PSTAMP(3);
    qstep(1);
    mbar_wait(BAR + B_READY * 8);
    PSTAMP(19);
    const uint32_t tag = lds32(TAGS);
    uint4* const xb = reinterpret_cast<uint4*>(X) + lane + (tag >> 1);
    constexpr int O_E4 = offsetof(Scratch, e4) / 16, O_E2 = offsetof(Scratch, e2) / 16, O_E3H = offsetof(Scratch, e3h) / 16;
    const float2 st0 = lds64(ST + (2 * (16 * w + r) + p) * 8);
    const float2 st1 = lds64(ST + (2 * (16 * w + r + 8) + p) * 8);
    uint32_t hi[4][4], lo[4][4];
    {
      float2 cs[16];
      auto cvt = [&](uint32_t (&d)[4][4], int b0, int ofs, const float2& st) {
#pragma unroll
        for (int b = b0; b < b0 + 8; b++) {
          if (ofs == 2) cs[b] = lds64(CS + (64 + b * 8 + 2 * c) * 4);
          const uint32_t v = pack2(fmaf(-st.x, cs[b].x, akv[4 * b + ofs]) * st.y, fmaf(-st.x, cs[b].y, akv[4 * b + ofs + 1]) * st.y);
          d[b >> 2][b & 3] = b < 8 ? v : movm(v);
        }
      };
      cvt(hi, 0, 2, st1);
      keep(hi[0]); keep(hi[1]);
      qstep(2);
      cvt(hi, 8, 2, st1);
      mbar_wait(BAR + B_CLR0 * 8);
      if (w == 3 && g < 15) {
        uint4* dst = X->e1 + ((g * 8 + j) * 2 + p) * 128 + lane;
#pragma unroll
        for (int i = 0; i < 4; i++) ll_st(dst + i * 32, hi[i][0], hi[i][1], hi[i][2], hi[i][3], tag);
      }
      PSTAMP(20);
      wg_bar(p);
#pragma unroll
      for (int i = 0; i < 4; i++) sts128(Xw + lane * 16 + i * 512, hi[i]);
      qstep(3);
      cvt(lo, 0, 0, st0);
      keep(lo[0]); keep(lo[1]);
      qstep(4);
      cvt(lo, 8, 0, st0);
    }
    PSTAMP(21);
    wg_bar(p);
    uint32_t prev[4][4];
    if (w > 0) {
#pragma unroll
      for (int i = 0; i < 4; i++) lds128(prev[i], Xw - 2048 + lane * 16 + i * 512);
    }
    if (p == 0) {
      asm volatile("fence.proxy.async.shared::cta;" ::: "memory");
      __syncwarp();
      if (lane == 0) mbar_arrive(BAR + (B_EX + 7) * 8);
    }
    PSTAMP(22);
    const uint4* halo = X->e1 + (((g - 1) * 8 + j) * 2 + p) * 128 + lane;
    const bool use_halo = w == 0 && g > 0;
    qstep(5);
    if (use_halo) ll_issue<4>(prev, halo, 32);
    qstep(6);
    qstep(7);
    PSTAMP(23);
    if (w == 0) {
      if (g > 0) {
        if (__builtin_expect(ll_bad<4>(prev, pin(tag, zero)), 0)) ll_spin<4>(prev, halo, 32, tag);
        ll_clear<4>(prev);
      } else {
#pragma unroll
        for (int i = 0; i < 4; i++)
#pragma unroll
          for (int e = 0; e < 4; e++) prev[i][e] = 0;
      }
    }
    wg_wait<0>();
    keep(aq);
    mbar_arrive_if(BAR + (B_EQ + 7) * 8, lane == 0);
    mbar_arrive_if(BAR + (B_EX + 6) * 8, lane == 0 && p == 0);
    PSTAMP(4);

    uint32_t of[4][4];
    {
      const float sc = 0.25f * 1.4426950408889634f;
      const float nohalo = (g == 0 && w == 0) ? -INFINITY : 0.f;
      const bool up0 = 2 * c > r, up1 = 2 * c + 1 > r;
      const uint32_t mup = (up0 ? 0xffffu : 0u) | (up1 ? 0xffff0000u : 0u);
      uint4* dst = xb + O_E2 + (xw * 32 + 4 * j) * 32;
      float d0 = 0.f, d1 = 0.f;
#pragma unroll 1
      for (int hp = 0; hp < 2; hp++) {
#pragma unroll
        for (int e = 0; e < 4; e++) { of[0][e] = of[2][e]; of[1][e] = of[3][e]; }
#pragma unroll
        for (int h = 0; h < 2; h++) {
          uint32_t qf[4];
          const uint32_t co = (32 * hp + 16 * h + 2 * c) * 4;
          {
            const float2 ca = lds64(CS + co), cb = lds64(CS + co + 32);
            qf[0] = pack2(fmaf(-st0.x, ca.x, aq[8 * h + 0]) * st0.y, fmaf(-st0.x, ca.y, aq[8 * h + 1]) * st0.y);
            qf[1] = pack2(fmaf(-st1.x, ca.x, aq[8 * h + 2]) * st1.y, fmaf(-st1.x, ca.y, aq[8 * h + 3]) * st1.y);
            qf[2] = pack2(fmaf(-st0.x, cb.x, aq[8 * h + 4]) * st0.y, fmaf(-st0.x, cb.y, aq[8 * h + 5]) * st0.y);
            qf[3] = pack2(fmaf(-st1.x, cb.x, aq[8 * h + 6]) * st1.y, fmaf(-st1.x, cb.y, aq[8 * h + 7]) * st1.y);
          }
          const int e0 = 2 * h;
          float sp[4], sl[4], sh[4];
          mma16816(sp, qf, prev[0][e0], prev[0][e0 + 1]);
          mma16816(sl, qf, lo[0][e0], lo[0][e0 + 1]);
          mma16816(sh, qf, hi[0][e0], hi[0][e0 + 1]);
          float a0 = up0 ? sp[0] + nohalo : sl[0], a1 = up1 ? sp[1] + nohalo : sl[1];
          float b0 = up0 ? sl[2] : sh[2], b1 = up1 ? sl[3] : sh[3];
          float ma = fmaxf(a0, a1), mb = fmaxf(b0, b1);
          ma = fmaxf(ma, __shfl_xor_sync(0xffffffffu, ma, 1)); mb = fmaxf(mb, __shfl_xor_sync(0xffffffffu, mb, 1));
          ma = fmaxf(ma, __shfl_xor_sync(0xffffffffu, ma, 2)); mb = fmaxf(mb, __shfl_xor_sync(0xffffffffu, mb, 2));
          a0 = ex2((a0 - ma) * sc); a1 = ex2((a1 - ma) * sc); b0 = ex2((b0 - mb) * sc); b1 = ex2((b1 - mb) * sc);
          float sa = a0 + a1, sbb = b0 + b1;
          sa += __shfl_xor_sync(0xffffffffu, sa, 1); sbb += __shfl_xor_sync(0xffffffffu, sbb, 1);
          sa += __shfl_xor_sync(0xffffffffu, sa, 2); sbb += __shfl_xor_sync(0xffffffffu, sbb, 2);
          const float ia = rcp(sa), ib = rcp(sbb);
          const uint32_t pa = pack2(a0 * ia, a1 * ia), pb = pack2(b0 * ib, b1 * ib);
          const uint32_t pf[4] = {pa & mup, 0u, pa & ~mup, pb & mup};
          const uint32_t ph = pb & ~mup;
          float o0[4], o1[4];
          mma16816(o0, pf, prev[2][e0], lo[2][e0]);
          mma16816(o1, pf, prev[2][e0 + 1], lo[2][e0 + 1]);
          mma1688_acc(o0, 0u, ph, hi[2][e0]);
          mma1688_acc(o1, 0u, ph, hi[2][e0 + 1]);
          of[2 + h][0] = pack2(o0[0], o0[1]); of[2 + h][1] = pack2(o0[2], o0[3]);
          of[2 + h][2] = pack2(o1[0], o1[1]); of[2 + h][3] = pack2(o1[2], o1[3]);
          ll_st(dst + (2 * hp + h) * 32, of[2 + h][0], of[2 + h][1], of[2 + h][2], of[2 + h][3], tag);
          const float2 wa = lds64(WB + co), wb = lds64(WB + co + 32);
          d0 = fmaf(o0[0], wa.x, d0); d0 = fmaf(o0[1], wa.y, d0); d0 = fmaf(o1[0], wb.x, d0); d0 = fmaf(o1[1], wb.y, d0);
          d1 = fmaf(o0[2], wa.x, d1); d1 = fmaf(o0[3], wa.y, d1); d1 = fmaf(o1[2], wb.x, d1); d1 = fmaf(o1[3], wb.y, d1);
        }
#pragma unroll
        for (int e = 0; e < 16; e++) aq[e] = aq[16 + e];
#pragma unroll
        for (int e = 0; e < 4; e++) {
          prev[0][e] = prev[1][e]; prev[2][e] = prev[3][e];
          lo[0][e] = lo[1][e]; lo[2][e] = lo[3][e];
          hi[0][e] = hi[1][e]; hi[2][e] = hi[3][e];
        }
      }
#pragma unroll
      for (int o = 1; o <= 2; o <<= 1) { d0 += __shfl_xor_sync(0xffffffffu, d0, o); d1 += __shfl_xor_sync(0xffffffffu, d1, o); }
      if (c == 0) ll_st(X->e2s + (xw * 8 + j) * 8 + r, __float_as_uint(d0), __float_as_uint(d1), 0, 0, tag);
    }
    PSTAMP(5);

    float ah[32];
    uint32_t sv[2][4];
    unpack32(ah, xres);
    {
      uint32_t og[2][14][4];
      const uint4* osrc[7];
#pragma unroll
      for (int i = 0; i < 7; i++) osrc[i] = xb + O_E2 + (xw * 32 + 4 * kb_at(i + 1, j)) * 32;
      const uint4* ssrc = X->e2s + (xw * 8 + 2 * c) * 8 + r;
      auto oissue = [&](int hp) {
#pragma unroll
        for (int i = 0; i < 14; i++) ll_ld(og[hp][i], osrc[i >> 1] + (2 * hp + (i & 1)) * 32);
        if (hp == 1) ll_issue<2>(sv, ssrc, 8);
      };
      auto omma = [&](int hp) {
        ll_clear<14>(og[hp]);
        keep(og[hp]);
        wg_fence();
#pragma unroll
        for (int i = 0; i < 14; i++) wgmma_rs_n64(ah, og[hp][i], descB(H0) + kb_at((i >> 1) + 1, j) * 512 + (2 * hp + (i & 1)) * 128, 1);
        wg_commit();
      };
      mbar_wait(BAR + B_FWO * 8);
      keep(ah); keep(of);
      wg_fence();
#pragma unroll
      for (int k = 0; k < 4; k++) wgmma_rs_n64(ah, of[k], descB(H0) + j * 512 + k * 128, 1);
      wg_commit();
      uint32_t it = 0;
#pragma unroll 1
      do { oissue(0); } while (ll_bad<14>(og[0], tag) && ++it < SPIN_LIMIT);
      PSTAMP(6);
      oissue(1);
      omma(0);
      const uint32_t tg = pin(tag, zero);
      if (__builtin_expect(ll_any(ll_acc<14>(og[1], tg, ll_acc<2>(sv, tg))), 0)) {
#pragma unroll 1
        do { oissue(1); } while (ll_any(ll_acc<14>(og[1], tag, ll_acc<2>(sv, tag))) && ++it < SPIN_LIMIT);
      }
      PSTAMP(16);
      omma(1);
      ll_clear<2>(sv);
    }
    float m0 = __uint_as_float(sv[0][0]) + __uint_as_float(sv[1][0]), m1 = __uint_as_float(sv[0][1]) + __uint_as_float(sv[1][1]);
#pragma unroll
    for (int o = 1; o <= 2; o <<= 1) { m0 += __shfl_xor_sync(0xffffffffu, m0, o); m1 += __shfl_xor_sync(0xffffffffu, m1, o); }
    const uint32_t mu0 = pack2(m0 + st0.x, m0 + st0.x), mu1 = pack2(m1 + st1.x, m1 + st1.x);
    wg_wait<0>();
    keep(ah);
    if (lane == 0) mbar_arrive(BAR + B_WODONE * 8);
    PSTAMP(7);

    uint32_t hf[4][4], ra[4][4];
    pack32(hf, ah);
    {
      uint4* dst = xb + O_E3H + (xw * 32 + 4 * j) * 32;
#pragma unroll
      for (int u = 0; u < 4; u++) {
        ra[u][0] = hsub2(hf[u][0], mu0); ra[u][1] = hsub2(hf[u][1], mu1);
        ra[u][2] = hsub2(hf[u][2], mu0); ra[u][3] = hsub2(hf[u][3], mu1);
        ll_st(dst + u * 32, ra[u][0], ra[u][1], ra[u][2], ra[u][3], tag);
      }
      float s0 = 0.f, q0 = 0.f, s1 = 0.f, q1 = 0.f;
#pragma unroll
      for (int b = 0; b < 8; b++) {
        s0 += ah[4 * b] + ah[4 * b + 1]; s1 += ah[4 * b + 2] + ah[4 * b + 3];
        q0 = fmaf(ah[4 * b], ah[4 * b], q0); q0 = fmaf(ah[4 * b + 1], ah[4 * b + 1], q0);
        q1 = fmaf(ah[4 * b + 2], ah[4 * b + 2], q1); q1 = fmaf(ah[4 * b + 3], ah[4 * b + 3], q1);
      }
#pragma unroll
      for (int o = 1; o <= 2; o <<= 1) {
        s0 += __shfl_xor_sync(0xffffffffu, s0, o); q0 += __shfl_xor_sync(0xffffffffu, q0, o);
        s1 += __shfl_xor_sync(0xffffffffu, s1, o); q1 += __shfl_xor_sync(0xffffffffu, q1, o);
      }
      if (c == 0) ll_st(X->e3s + (xw * 8 + j) * 8 + r, __float_as_uint(s0), __float_as_uint(q0), __float_as_uint(s1), __float_as_uint(q1), tag);
      mbar_wait(BAR + (p == 0 ? B_EQ + 7 : B_WODONE) * 8);
    }
    PSTAMP(8);

    float rs0, rs1;
    auto swiglu = [&](float g0, float g1, float u0, float u1, float rs) -> uint32_t {
      const float hr = 0.5f * rs;
      const float x0 = g0 * hr, x1 = g1 * hr;
      const float t0 = tanhf_hw(x0), t1 = tanhf_hw(x1);
      return pack2(fmaf(x0, t0, x0) * (u0 * rs), fmaf(x1, t1, x1) * (u1 * rs));
    };
    uint32_t hA[6][4];
    {
      float a1[64], a2[32];
      const uint4* src = xb + O_E3H + xw * 32 * 32;
      uint32_t rb[4][4], rc[4][4], rd[4][4];
      auto fetch = [&](uint32_t (&a)[4][4], int i) { ll_issue<4>(a, src + kb_at(i, j) * 128, 32); };
      auto check = [&](uint32_t (&a)[4][4], uint32_t (&b)[4][4], int i) {
        const uint32_t tg = pin(tag, zero);
        if (__builtin_expect(ll_any(ll_acc<4>(a, tg, ll_acc<4>(b, tg))), 0)) {
          uint32_t it = 0;
#pragma unroll 1
          do { fetch(a, i); fetch(b, i + 1); } while (ll_any(ll_acc<4>(a, tag, ll_acc<4>(b, tag))) && ++it < SPIN_LIMIT);
        }
        ll_clear<4>(a); ll_clear<4>(b);
        keep(a); keep(b);
      };
      auto head = [&](uint32_t (&a)[4][4], int i) {
        mbar_wait(BAR + (B_FA + i) * 8);
        wg_fence();
        wgmma_rs_n64<DESC_HI64>(a2, a[0], descBh(RING + 16384) + (i & 3) * 1536, i);
        wgmma_rs_n128(a1, a[0], descB(RING) + (i & 3) * 1536, i);
        wg_commit();
#pragma unroll
        for (int u = 0; u < 4; u++) stsm4(Hn + w * 2048 + i * 8192 + (moff ^ (u << 5)), a[u]);
        wg_wait<1>();
        if (i > 0) mbar_arrive_if(BAR + (B_EA + i - 1) * 8, lane == 0);
      };
      auto rest = [&](uint32_t (&a)[4][4], int i) {
        wg_fence();
#pragma unroll
        for (int k = 1; k < 4; k++) {
          wgmma_rs_n64<DESC_HI64>(a2, a[k], descBh(RING + 16384) + (i & 3) * 1536 + k * 64, 1);
          wgmma_rs_n128(a1, a[k], descB(RING) + (i & 3) * 1536 + k * 128, 1);
        }
        wg_commit();
      };
      ll_clear<4>(ra);
      keep(ra);
      head(ra, 0); rest(ra, 0);
      ll_get<4>(rb, src + kb_at(1, j) * 128, 32, tag);
      keep(rb);
      PSTAMP(17);
      fetch(rc, 2); fetch(rd, 3);
      head(rb, 1); rest(rb, 1);
      check(rc, rd, 2);
      head(rc, 2); fetch(ra, 4); fetch(rb, 5); rest(rc, 2);
      head(rd, 3); rest(rd, 3);
      check(ra, rb, 4);
      head(ra, 4); fetch(rc, 6); fetch(rd, 7); ll_issue<2>(sv, X->e3s + (xw * 8 + 2 * c) * 8 + r, 8); rest(ra, 4);
      head(rb, 5); rest(rb, 5);
      check(rc, rd, 6);
      head(rc, 6); rest(rc, 6);
      head(rd, 7); rest(rd, 7);
      fence_async_smem();
      ll_wait<2>(sv, X->e3s + (xw * 8 + 2 * c) * 8 + r, 8, tag);
      float s0 = __uint_as_float(sv[0][0]) + __uint_as_float(sv[1][0]), q0 = __uint_as_float(sv[0][1]) + __uint_as_float(sv[1][1]);
      float s1 = __uint_as_float(sv[0][2]) + __uint_as_float(sv[1][2]), q1 = __uint_as_float(sv[0][3]) + __uint_as_float(sv[1][3]);
#pragma unroll
      for (int o = 1; o <= 2; o <<= 1) {
        s0 += __shfl_xor_sync(0xffffffffu, s0, o); q0 += __shfl_xor_sync(0xffffffffu, q0, o);
        s1 += __shfl_xor_sync(0xffffffffu, s1, o); q1 += __shfl_xor_sync(0xffffffffu, q1, o);
      }
      s0 *= 1.f / D_; s1 *= 1.f / D_;
      rs0 = rsqrtf(fmaxf(fmaf(-s0, s0, q0 * (1.f / D_)), 0.f) + 1e-5f);
      rs1 = rsqrtf(fmaxf(fmaf(-s1, s1, q1 * (1.f / D_)), 0.f) + 1e-5f);
      wg_wait<0>();
      keep(a1); keep(a2);
      if (lane == 0) mbar_arrive(BAR + (B_EA + 7) * 8);
      PSTAMP(9);
#pragma unroll
      for (int u = 0; u < 4; u++)
#pragma unroll
        for (int e = 0; e < 4; e++)
          hA[u][e] = swiglu(a1[8 * u + 2 * e], a1[8 * u + 2 * e + 1], a1[32 + 8 * u + 2 * e], a1[33 + 8 * u + 2 * e], (e & 1) ? rs1 : rs0);
#pragma unroll
      for (int u = 0; u < 2; u++)
#pragma unroll
        for (int e = 0; e < 4; e++)
          hA[4 + u][e] = swiglu(a2[8 * u + 2 * e], a2[8 * u + 2 * e + 1], a2[16 + 8 * u + 2 * e], a2[17 + 8 * u + 2 * e], (e & 1) ? rs1 : rs0);
      keep(hA);
      wg_bar(p);
    }
    PSTAMP(10);

    uint32_t hB[8][4];
    {
      float ab[128];
      uint32_t db = descB(RING);
      const uint32_t dAn = descA(H1) - p * 4096;
#pragma unroll 1
      for (int i = 0; i < 8; i++) {
        mbar_wait(BAR + (B_FB + i) * 8);
        const uint32_t da = dAn + i * 512;
        wg_fence();
        wgmma_ss_n256(ab, da, db, i);
#pragma unroll
        for (int k = 1; k < 4; k++) wgmma_ss_n256(ab, da + k * 2, db + k * 128, 1);
        wg_commit();
        wg_wait<1>();
        mbar_arrive_if(BAR + (B_EB + i - 1) * 8, i > 0 && lane == 0);
        db = db == descB(RING + 65536) ? descB(RING) : db + 2048;
      }
      wg_wait<0>();
      keep(ab);
      if (lane == 0) mbar_arrive(BAR + (B_EB + 7) * 8);
      PSTAMP(11);
#pragma unroll
      for (int u = 0; u < 8; u++) {
        const int o = (u >> 2) * 64 + (u & 3) * 8;
#pragma unroll
        for (int e = 0; e < 4; e++)
          hB[u][e] = swiglu(ab[o + 2 * e], ab[o + 2 * e + 1], ab[o + 32 + 2 * e], ab[o + 33 + 2 * e], (e & 1) ? rs1 : rs0);
      }
      keep(hB);
    }
    PSTAMP(12);

    {
      float ya[32], y[32], sum[32];
      const uint32_t offA = (j & 1) ? 256 : 0, offH = (j & 1) ? 0 : 1536;
      uint4* e4 = xb + O_E4 + xw * 64 * 128;
      asm volatile("" : "+l"(e4));
      uint32_t in[8][4];
      auto fetch = [&](int q) {
        const uint4* s0 = e4 + (j * 8 + ((j - 1 - q) & 7)) * 128;
        const uint4* s1 = e4 + (j * 8 + ((j - 2 - q) & 7)) * 128;
#pragma unroll
        for (int u = 0; u < 4; u++) { ll_ld(in[u], s0 + u * 32); ll_ld(in[4 + u], s1 + u * 32); }
      };
      const uint32_t ident = (2 * c == r ? 0x3f80u : 0u) | (2 * c + 1 == r ? 0x3f800000u : 0u);
      auto acc = [&](int q) {
        if (__builtin_expect(ll_bad<8>(in, pin(tag, zero)), 0)) {
          uint32_t it = 0;
#pragma unroll 1
          do { fetch(q); } while (ll_bad<8>(in, tag) && ++it < SPIN_LIMIT);
        }
        ll_clear<8>(in);
#pragma unroll
        for (int u = 0; u < 8; u++) {
          mma1688_acc(*reinterpret_cast<float (*)[4]>(&sum[8 * (u & 3)]), in[u][0], in[u][1], ident);
          mma1688_acc(*reinterpret_cast<float (*)[4]>(&sum[8 * (u & 3) + 4]), in[u][2], in[u][3], ident);
        }
      };
      uint32_t T;
      auto mm = [&](float (&d)[32], int k0, int k1) {
        wg_fence();
#pragma unroll
        for (int k = k0; k < k1; k++) {
          if (k < 4) wgmma_rs_n64(d, hA[k], T + offA + k * 128, k);
          else if (k < 6) wgmma_rs_n64(d, hA[k], T + offH + (k - 4) * 128, 1);
          else wgmma_rs_n64(d, hB[k - 6], T + offA + 512 + (k - 6) * 128, 1);
        }
        wg_commit();
      };
      auto start = [&](float (&d)[32], float (&dp)[32], int m) {
        const int mt = min(m, 7);
        mbar_wait(BAR + (B_FT + mt) * 8);
        T = descB(0) + (t_addr(mt) >> 4);
        mm(d, 0, W2_HEAD);
        wg_wait<1>();
        keep(dp);
        mbar_arrive_if(BAR + B_ET0 * 8, m == 1 && lane == 0);
        uint4* dst = e4 + (((j + m) & 7) * 8 + j) * 128;
        uint32_t pk[4][4];
        pack32(pk, dp);
        const uint32_t tg = pin(tag, zero);
#pragma unroll
        for (int u = 0; u < 4; u++)
          if (m < 8) ll_st(dst + u * 32, pk[u][0], pk[u][1], pk[u][2], pk[u][3], tg);
      };
      mbar_wait(BAR + B_CLR * 8);
      mbar_wait(BAR + B_FT * 8);
      T = descB(0) + (t_addr(0) >> 4);
      mm(ya, 0, W2_HEAD);
      unpack32(sum, hf);
      keep(sum);
#pragma unroll
      for (int u = 0; u < 4; u++) ll_st(e4 + j * 9 * 128 + u * 32, 0, 0, 0, 0, tag);
      wg_wait<0>();
#pragma unroll 1
      for (int m = 0; m < 8; m += 2) {
        if (m >= 2) fetch(m - 3);
        mm(ya, W2_HEAD, 14);
        start(y, ya, m + 1);
        mm(y, W2_HEAD, 9);
        if (m >= 2) acc(m - 3);
        if (m == 6) fetch(5);
        mm(y, 9, 14);
        start(ya, y, m + 2);
        wg_wait<0>();
        if (m == 0) PSTAMP(27);
        if (m == 2) PSTAMP(26);
        if (m == 4) PSTAMP(28);
      }
      PSTAMP(13);
      acc(5);
      PSTAMP(14);
      const uint32_t stg = H0 + p * 65536 + 28672 + (w >> 1) * 32768 + (w & 1) * 2048;
#pragma unroll
      for (int u = 0; u < 4; u++) {
        uint32_t o[4];
#pragma unroll
        for (int e = 0; e < 4; e++) o[e] = pack2(sum[8 * u + 2 * e] + y[8 * u + 2 * e], sum[8 * u + 2 * e + 1] + y[8 * u + 2 * e + 1]);
        stsm4(stg + (moff ^ (u << 5)), o);
      }
      fence_async_smem();
      __syncwarp();
      if (elect_one()) {
        tma3d_store(&P.out, stg, 64 * j, p, g * 64 + 16 * w);
        asm volatile("cp.async.bulk.commit_group;" ::: "memory");
        asm volatile("cp.async.bulk.wait_group.read 0;" ::: "memory");
      }
      PSTAMP(15);
    }
  }
}

typedef CUresult (*EncodeFn)(CUtensorMap*, CUtensorMapDataType, cuuint32_t, void*, const cuuint64_t*, const cuuint64_t*,
                             const cuuint32_t*, const cuuint32_t*, CUtensorMapInterleave, CUtensorMapSwizzle,
                             CUtensorMapL2promotion, CUtensorMapFloatOOBfill);

void enc2d(EncodeFn f, CUtensorMap* m, const void* base, uint64_t cols, uint64_t rows, uint32_t bc, uint32_t br, CUtensorMapSwizzle sw) {
  cuuint64_t gd[2] = {cols, rows}, gs[1] = {cols * 2};
  cuuint32_t bd[2] = {bc, br}, es[2] = {1, 1};
  f(m, CU_TENSOR_MAP_DATA_TYPE_BFLOAT16, 2, const_cast<void*>(base), gd, gs, bd, es, CU_TENSOR_MAP_INTERLEAVE_NONE, sw,
    CU_TENSOR_MAP_L2_PROMOTION_L2_128B, CU_TENSOR_MAP_FLOAT_OOB_FILL_NONE);
}
void enc_par(EncodeFn f, CUtensorMap* m, const void* base, uint32_t pairs) {
  cuuint64_t gd[3] = {(cuuint64_t)D_, 2, (cuuint64_t)S_ / 2}, gs[2] = {D_ * 2, D_ * 4};
  cuuint32_t bd[3] = {64, 1, pairs}, es[3] = {1, 1, 1};
  f(m, CU_TENSOR_MAP_DATA_TYPE_BFLOAT16, 3, const_cast<void*>(base), gd, gs, bd, es, CU_TENSOR_MAP_INTERLEAVE_NONE,
    CU_TENSOR_MAP_SWIZZLE_128B, CU_TENSOR_MAP_L2_PROMOTION_L2_128B, CU_TENSOR_MAP_FLOAT_OOB_FILL_NONE);
}

}

extern "C" void kernel_launch(void* const* d_in, const int* in_sizes, int n_in, void* d_out, int out_size) {
  (void)in_sizes; (void)n_in; (void)out_size;
  static EncodeFn enc = nullptr;
  static Scratch* scratch = nullptr;
  if (!enc) {
    void* fn = nullptr;
    cudaDriverEntryPointQueryResult q;
    cudaGetDriverEntryPoint("cuTensorMapEncodeTiled", &fn, cudaEnableDefault, &q);
    enc = (EncodeFn)fn;
    cudaGetSymbolAddress((void**)&scratch, g_scratch);
    cudaFuncSetAttribute(fused_block_kernel, cudaFuncAttributeMaxDynamicSharedMemorySize, SMEM_BYTES);
  }
  Params P;
  const __nv_bfloat16* xp = (const __nv_bfloat16*)d_in[0];
  const __nv_bfloat16* wqkvp = (const __nv_bfloat16*)d_in[1];
  const __nv_bfloat16* wop = (const __nv_bfloat16*)d_in[2];
  P.w1p = (const __nv_bfloat16*)d_in[4];
  P.w3p = (const __nv_bfloat16*)d_in[5];
  P.w2p = (const __nv_bfloat16*)d_in[6];
  enc_par(enc, &P.x, xp, 64);
  enc_par(enc, &P.out, d_out, 16);
  enc2d(enc, &P.wqkv, wqkvp, 3 * D_, D_, 64, 64, CU_TENSOR_MAP_SWIZZLE_128B);
  enc2d(enc, &P.wo, wop, D_, D_, 64, 64, CU_TENSOR_MAP_SWIZZLE_128B);
  enc2d(enc, &P.w1, P.w1p, F_, D_, 64, 64, CU_TENSOR_MAP_SWIZZLE_128B);
  enc2d(enc, &P.w3, P.w3p, F_, D_, 64, 64, CU_TENSOR_MAP_SWIZZLE_128B);
  enc2d(enc, &P.w1h, P.w1p, F_, D_, 32, 64, CU_TENSOR_MAP_SWIZZLE_64B);
  enc2d(enc, &P.w3h, P.w3p, F_, D_, 32, 64, CU_TENSOR_MAP_SWIZZLE_64B);
  enc2d(enc, &P.w2, P.w2p, D_, F_, 64, 224, CU_TENSOR_MAP_SWIZZLE_128B);

  cudaLaunchConfig_t cfg = {};
  cfg.gridDim = dim3(128);
  cfg.blockDim = dim3(384);
  cfg.dynamicSmemBytes = SMEM_BYTES;
  cfg.stream = cudaStreamPerThread;
  cudaLaunchAttribute at[1];
  at[0].id = cudaLaunchAttributeCooperative;
  at[0].val.cooperative = 1;
  cfg.attrs = at;
  cfg.numAttrs = 1;
  cudaLaunchKernelEx(&cfg, fused_block_kernel, scratch, xp, wqkvp, wop, 0u, P);
}
```

```cpp
#include <cuda_runtime.h>
#include <cuda.h>
#include <cuda_bf16.h>
#include <stdint.h>
#include <stddef.h>

namespace {

constexpr int S_ = 2048, D_ = 512, F_ = 1792;
#define LAG_KB 3
#define E4_FIRST 7
#define PP_AHEAD 1
#define SIDE_KB 0
#define CLR_MODE 0
#define W2_HEAD 3
#define XO_DELAY 2

constexpr uint32_t SPIN_LIMIT = 1u << 18;

struct Scratch {
  uint4 e4[16 * 2 * 4 * 8 * 8 * 4 * 32];
  uint4 e2[16 * 2 * 4 * 32 * 32];
  uint4 e3h[16 * 2 * 4 * 32 * 32];
  uint4 e1[16 * 8 * 2 * 4 * 32];
  uint4 e2s[16 * 2 * 4 * 8 * 8];
  uint4 e3s[16 * 2 * 4 * 8 * 8];
  uint4 e0c[8 * 3 * 16 * 16];
  uint4 e0s[2048];
  uint4 e0w[8 * 64];
  unsigned epoch[128];
};
__device__ Scratch g_scratch;
#define PSTAMP(i)
#define PSTAMPW(slot, i)
#define W2STAMP(i)

struct alignas(64) Params {
  CUtensorMap x, out, wqkv, wo, w1, w3, w1h, w3h, w2;
  const __nv_bfloat16 *w1p, *w3p, *w2p;
};

constexpr uint32_t SB = 1024;
constexpr uint32_t H0 = SB;
constexpr uint32_t H1 = SB + 65536;
constexpr uint32_t RING = SB + 131072;
constexpr uint32_t BAR = SB + 229376;
constexpr uint32_t TAGS = BAR + 1016;
constexpr uint32_t CS = BAR + 1024;
constexpr uint32_t ST = CS + 768;
constexpr uint32_t WB = ST + 1024;
constexpr uint32_t SMEM_BYTES = 232448;
static_assert(WB + 256 <= SB + SMEM_BYTES, "smem");

enum : int {
  B_FX = 0,
  B_FKV = 16, B_FQ = 24, B_FWO = 32, B_FA = 40, B_FB = 48, B_FT = 56,
  B_EKV = 64, B_EQ = 72, B_EA = 80, B_EB = 88, B_ET0 = 96,
  B_WODONE = 97,
  B_EX = 104,
  B_LAG = 112, B_READY = 113, B_PUB = 114, B_CLR = 115, B_CLR0 = 116, B_TAG = 117,
  B_IN = 118
};

__device__ __forceinline__ uint32_t smem_u32(const void* p) { return (uint32_t)__cvta_generic_to_shared(p); }
__device__ __forceinline__ void mbar_init(uint32_t b, uint32_t c) { asm volatile("mbarrier.init.shared::cta.b64 [%0], %1;" ::"r"(b), "r"(c) : "memory"); }
__device__ __forceinline__ void mbar_expect_tx(uint32_t b, uint32_t bytes) { asm volatile("mbarrier.arrive.expect_tx.shared::cta.b64 _, [%0], %1;" ::"r"(b), "r"(bytes) : "memory"); }
__device__ __forceinline__ void mbar_arrive(uint32_t b) { asm volatile("mbarrier.arrive.shared::cta.b64 _, [%0];" ::"r"(b) : "memory"); }
__device__ __forceinline__ void mbar_wait(uint32_t b) {
  asm volatile("{\n.reg .pred p;\n.reg .u32 c;\nmov.u32 c, 0;\nLW:\n.pragma \"nounroll\";\n"
               "mbarrier.try_wait.parity.shared::cta.b64 p, [%0], 0;\nadd.u32 c, c, 1;\nsetp.gt.or.u32 p, c, %1, p;\n@!p bra LW;\n}\n"
               ::"r"(b), "n"(SPIN_LIMIT) : "memory");
}
__device__ __forceinline__ void mbar_wait_par(uint32_t b, uint32_t parity) {
  asm volatile("{\n.reg .pred p;\n.reg .u32 c;\nmov.u32 c, 0;\nLW:\n.pragma \"nounroll\";\n"
               "mbarrier.try_wait.parity.shared::cta.b64 p, [%0], %2;\nadd.u32 c, c, 1;\nsetp.gt.or.u32 p, c, %1, p;\n@!p bra LW;\n}\n"
               ::"r"(b), "n"(SPIN_LIMIT), "r"(parity) : "memory");
}
__device__ __forceinline__ bool elect_one() {
  uint32_t p;
  asm volatile("{\n.reg .pred P;\nelect.sync _|P, 0xffffffff;\nselp.u32 %0, 1, 0, P;\n}\n" : "=r"(p));
  return p;
}
__device__ __forceinline__ void tma2d(uint32_t dst, const CUtensorMap* m, int c0, int c1, uint32_t bar) {
  asm volatile("cp.async.bulk.tensor.2d.shared::cluster.global.mbarrier::complete_tx::bytes [%0], [%1, {%3, %4}], [%2];"
               ::"r"(dst), "l"(m), "r"(bar), "r"(c0), "r"(c1) : "memory");
}
__device__ __forceinline__ void tma3d(uint32_t dst, const CUtensorMap* m, int c0, int c1, int c2, uint32_t bar) {
  asm volatile("cp.async.bulk.tensor.3d.shared::cluster.global.mbarrier::complete_tx::bytes [%0], [%1, {%3, %4, %5}], [%2];"
               ::"r"(dst), "l"(m), "r"(bar), "r"(c0), "r"(c1), "r"(c2) : "memory");
}
__device__ __forceinline__ void tma3d_store(const CUtensorMap* m, uint32_t src, int c0, int c1, int c2) {
  asm volatile("cp.async.bulk.tensor.3d.global.shared::cta.bulk_group [%0, {%2, %3, %4}], [%1];"
               ::"l"(m), "r"(src), "r"(c0), "r"(c1), "r"(c2) : "memory");
}
__device__ __forceinline__ void l2_prefetch(const void* p, uint32_t bytes) {
  asm volatile("cp.async.bulk.prefetch.L2.global [%0], %1;" ::"l"(p), "r"(bytes) : "memory");
}
__device__ __forceinline__ void prefetch_map(const CUtensorMap* m) { asm volatile("prefetch.tensormap [%0];" ::"l"(m) : "memory"); }
__device__ __forceinline__ void fence_async_smem() { asm volatile("fence.proxy.async.shared::cta;" ::: "memory"); }
__device__ __forceinline__ void wg_fence() { asm volatile("wgmma.fence.sync.aligned;" ::: "memory"); }
__device__ __forceinline__ void wg_commit() { asm volatile("wgmma.commit_group.sync.aligned;" ::: "memory"); }
template <int N> __device__ __forceinline__ void wg_wait() { asm volatile("wgmma.wait_group.sync.aligned %0;" ::"n"(N) : "memory"); }
__device__ __forceinline__ void wg_bar(int p) {
  if (p == 0) asm volatile("bar.sync 1, 128;" ::: "memory"); else asm volatile("bar.sync 2, 128;" ::: "memory");
}
constexpr uint32_t DESC_HI128 = (1024 >> 4) | (1u << 30);
constexpr uint32_t DESC_HI64 = (512 >> 4) | (2u << 30);
__device__ __forceinline__ constexpr uint32_t descA(uint32_t addr) { return (addr >> 4) | (1u << 16); }
__device__ __forceinline__ constexpr uint32_t descB(uint32_t addr) { return (addr >> 4) | ((8192u >> 4) << 16); }
__device__ __forceinline__ constexpr uint32_t descBh(uint32_t addr) { return (addr >> 4) | ((4096u >> 4) << 16); }

__device__ __forceinline__ void wgmma_ss_n64(float (&d)[32], uint32_t da, uint32_t db, int sc) {
  asm volatile("{\n.reg .pred p;\n.reg .b64 da, db;\nsetp.ne.b32 p, %34, 0;\nmov.b64 da, {%32, %35};\nmov.b64 db, {%33, %35};\n"
    "wgmma.mma_async.sync.aligned.m64n64k16.f32.bf16.bf16 {%0, %1, %2, %3, %4, %5, %6, %7, %8, %9, %10, %11, %12, %13, %14, %15, %16, %17, %18, %19, %20, %21, %22, %23, %24, %25, %26, %27, %28, %29, %30, %31}, da, db, p, 1, 1, 0, 1;\n}\n"
    : "+f"(d[0]), "+f"(d[1]), "+f"(d[2]), "+f"(d[3]), "+f"(d[4]), "+f"(d[5]), "+f"(d[6]), "+f"(d[7]),
      "+f"(d[8]), "+f"(d[9]), "+f"(d[10]), "+f"(d[11]), "+f"(d[12]), "+f"(d[13]), "+f"(d[14]), "+f"(d[15]),
      "+f"(d[16]), "+f"(d[17]), "+f"(d[18]), "+f"(d[19]), "+f"(d[20]), "+f"(d[21]), "+f"(d[22]), "+f"(d[23]),
      "+f"(d[24]), "+f"(d[25]), "+f"(d[26]), "+f"(d[27]), "+f"(d[28]), "+f"(d[29]), "+f"(d[30]), "+f"(d[31])
    : "r"(da), "r"(db), "r"(sc), "n"(DESC_HI128));
}
__device__ __forceinline__ void wgmma_ss_n128(float (&d)[64], uint32_t da, uint32_t db, int sc) {
  asm volatile("{\n.reg .pred p;\n.reg .b64 da, db;\nsetp.ne.b32 p, %66, 0;\nmov.b64 da, {%64, %67};\nmov.b64 db, {%65, %67};\n"
    "wgmma.mma_async.sync.aligned.m64n128k16.f32.bf16.bf16 {%0, %1, %2, %3, %4, %5, %6, %7, %8, %9, %10, %11, %12, %13, %14, %15, %16, %17, %18, %19, %20, %21, %22, %23, %24, %25, %26, %27, %28, %29, %30, %31, %32, %33, %34, %35, %36, %37, %38, %39, %40, %41, %42, %43, %44, %45, %46, %47, %48, %49, %50, %51, %52, %53, %54, %55, %56, %57, %58, %59, %60, %61, %62, %63}, da, db, p, 1, 1, 0, 1;\n}\n"
    : "+f"(d[0]), "+f"(d[1]), "+f"(d[2]), "+f"(d[3]), "+f"(d[4]), "+f"(d[5]), "+f"(d[6]), "+f"(d[7]),
      "+f"(d[8]), "+f"(d[9]), "+f"(d[10]), "+f"(d[11]), "+f"(d[12]), "+f"(d[13]), "+f"(d[14]), "+f"(d[15]),
      "+f"(d[16]), "+f"(d[17]), "+f"(d[18]), "+f"(d[19]), "+f"(d[20]), "+f"(d[21]), "+f"(d[22]), "+f"(d[23]),
      "+f"(d[24]), "+f"(d[25]), "+f"(d[26]), "+f"(d[27]), "+f"(d[28]), "+f"(d[29]), "+f"(d[30]), "+f"(d[31]),
      "+f"(d[32]), "+f"(d[33]), "+f"(d[34]), "+f"(d[35]), "+f"(d[36]), "+f"(d[37]), "+f"(d[38]), "+f"(d[39]),
      "+f"(d[40]), "+f"(d[41]), "+f"(d[42]), "+f"(d[43]), "+f"(d[44]), "+f"(d[45]), "+f"(d[46]), "+f"(d[47]),
      "+f"(d[48]), "+f"(d[49]), "+f"(d[50]), "+f"(d[51]), "+f"(d[52]), "+f"(d[53]), "+f"(d[54]), "+f"(d[55]),
      "+f"(d[56]), "+f"(d[57]), "+f"(d[58]), "+f"(d[59]), "+f"(d[60]), "+f"(d[61]), "+f"(d[62]), "+f"(d[63])
    : "r"(da), "r"(db), "r"(sc), "n"(DESC_HI128));
}
__device__ __forceinline__ void wgmma_ss_n256(float (&d)[128], uint32_t da, uint32_t db, int sc) {
  asm volatile("{\n.reg .pred p;\n.reg .b64 da, db;\nsetp.ne.b32 p, %130, 0;\nmov.b64 da, {%128, %131};\nmov.b64 db, {%129, %131};\n"
    "wgmma.mma_async.sync.aligned.m64n256k16.f32.bf16.bf16 {%0, %1, %2, %3, %4, %5, %6, %7, %8, %9, %10, %11, %12, %13, %14, %15, %16, %17, %18, %19, %20, %21, %22, %23, %24, %25, %26, %27, %28, %29, %30, %31, %32, %33, %34, %35, %36, %37, %38, %39, %40, %41, %42, %43, %44, %45, %46, %47, %48, %49, %50, %51, %52, %53, %54, %55, %56, %57, %58, %59, %60, %61, %62, %63, %64, %65, %66, %67, %68, %69, %70, %71, %72, %73, %74, %75, %76, %77, %78, %79, %80, %81, %82, %83, %84, %85, %86, %87, %88, %89, %90, %91, %92, %93, %94, %95, %96, %97, %98, %99, %100, %101, %102, %103, %104, %105, %106, %107, %108, %109, %110, %111, %112, %113, %114, %115, %116, %117, %118, %119, %120, %121, %122, %123, %124, %125, %126, %127}, da, db, p, 1, 1, 0, 1;\n}\n"
    : "+f"(d[0]), "+f"(d[1]), "+f"(d[2]), "+f"(d[3]), "+f"(d[4]), "+f"(d[5]), "+f"(d[6]), "+f"(d[7]),
      "+f"(d[8]), "+f"(d[9]), "+f"(d[10]), "+f"(d[11]), "+f"(d[12]), "+f"(d[13]), "+f"(d[14]), "+f"(d[15]),
      "+f"(d[16]), "+f"(d[17]), "+f"(d[18]), "+f"(d[19]), "+f"(d[20]), "+f"(d[21]), "+f"(d[22]), "+f"(d[23]),
      "+f"(d[24]), "+f"(d[25]), "+f"(d[26]), "+f"(d[27]), "+f"(d[28]), "+f"(d[29]), "+f"(d[30]), "+f"(d[31]),
      "+f"(d[32]), "+f"(d[33]), "+f"(d[34]), "+f"(d[35]), "+f"(d[36]), "+f"(d[37]), "+f"(d[38]), "+f"(d[39]),
      "+f"(d[40]), "+f"(d[41]), "+f"(d[42]), "+f"(d[43]), "+f"(d[44]), "+f"(d[45]), "+f"(d[46]), "+f"(d[47]),
      "+f"(d[48]), "+f"(d[49]), "+f"(d[50]), "+f"(d[51]), "+f"(d[52]), "+f"(d[53]), "+f"(d[54]), "+f"(d[55]),
      "+f"(d[56]), "+f"(d[57]), "+f"(d[58]), "+f"(d[59]), "+f"(d[60]), "+f"(d[61]), "+f"(d[62]), "+f"(d[63]),
      "+f"(d[64]), "+f"(d[65]), "+f"(d[66]), "+f"(d[67]), "+f"(d[68]), "+f"(d[69]), "+f"(d[70]), "+f"(d[71]),
      "+f"(d[72]), "+f"(d[73]), "+f"(d[74]), "+f"(d[75]), "+f"(d[76]), "+f"(d[77]), "+f"(d[78]), "+f"(d[79]),
      "+f"(d[80]), "+f"(d[81]), "+f"(d[82]), "+f"(d[83]), "+f"(d[84]), "+f"(d[85]), "+f"(d[86]), "+f"(d[87]),
      "+f"(d[88]), "+f"(d[89]), "+f"(d[90]), "+f"(d[91]), "+f"(d[92]), "+f"(d[93]), "+f"(d[94]), "+f"(d[95]),
      "+f"(d[96]), "+f"(d[97]), "+f"(d[98]), "+f"(d[99]), "+f"(d[100]), "+f"(d[101]), "+f"(d[102]), "+f"(d[103]),
      "+f"(d[104]), "+f"(d[105]), "+f"(d[106]), "+f"(d[107]), "+f"(d[108]), "+f"(d[109]), "+f"(d[110]), "+f"(d[111]),
      "+f"(d[112]), "+f"(d[113]), "+f"(d[114]), "+f"(d[115]), "+f"(d[116]), "+f"(d[117]), "+f"(d[118]), "+f"(d[119]),
      "+f"(d[120]), "+f"(d[121]), "+f"(d[122]), "+f"(d[123]), "+f"(d[124]), "+f"(d[125]), "+f"(d[126]), "+f"(d[127])
    : "r"(da), "r"(db), "r"(sc), "n"(DESC_HI128));
}
template <uint32_t HI = DESC_HI128>
__device__ __forceinline__ void wgmma_rs_n64(float (&d)[32], const uint32_t (&a)[4], uint32_t db, int sc) {
  asm volatile("{\n.reg .pred p;\n.reg .b64 db;\nsetp.ne.b32 p, %37, 0;\nmov.b64 db, {%36, %38};\n"
    "wgmma.mma_async.sync.aligned.m64n64k16.f32.bf16.bf16 {%0, %1, %2, %3, %4, %5, %6, %7, %8, %9, %10, %11, %12, %13, %14, %15, %16, %17, %18, %19, %20, %21, %22, %23, %24, %25, %26, %27, %28, %29, %30, %31}, {%32, %33, %34, %35}, db, p, 1, 1, 1;\n}\n"
    : "+f"(d[0]), "+f"(d[1]), "+f"(d[2]), "+f"(d[3]), "+f"(d[4]), "+f"(d[5]), "+f"(d[6]), "+f"(d[7]),
      "+f"(d[8]), "+f"(d[9]), "+f"(d[10]), "+f"(d[11]), "+f"(d[12]), "+f"(d[13]), "+f"(d[14]), "+f"(d[15]),
      "+f"(d[16]), "+f"(d[17]), "+f"(d[18]), "+f"(d[19]), "+f"(d[20]), "+f"(d[21]), "+f"(d[22]), "+f"(d[23]),
      "+f"(d[24]), "+f"(d[25]), "+f"(d[26]), "+f"(d[27]), "+f"(d[28]), "+f"(d[29]), "+f"(d[30]), "+f"(d[31])
    : "r"(a[0]), "r"(a[1]), "r"(a[2]), "r"(a[3]), "r"(db), "r"(sc), "n"(HI));
}
template <uint32_t HI = DESC_HI128>
__device__ __forceinline__ void wgmma_rs_n128(float (&d)[64], const uint32_t (&a)[4], uint32_t db, int sc) {
  asm volatile("{\n.reg .pred p;\n.reg .b64 db;\nsetp.ne.b32 p, %69, 0;\nmov.b64 db, {%68, %70};\n"
    "wgmma.mma_async.sync.aligned.m64n128k16.f32.bf16.bf16 {%0, %1, %2, %3, %4, %5, %6, %7, %8, %9, %10, %11, %12, %13, %14, %15, %16, %17, %18, %19, %20, %21, %22, %23, %24, %25, %26, %27, %28, %29, %30, %31, %32, %33, %34, %35, %36, %37, %38, %39, %40, %41, %42, %43, %44, %45, %46, %47, %48, %49, %50, %51, %52, %53, %54, %55, %56, %57, %58, %59, %60, %61, %62, %63}, {%64, %65, %66, %67}, db, p, 1, 1, 1;\n}\n"
    : "+f"(d[0]), "+f"(d[1]), "+f"(d[2]), "+f"(d[3]), "+f"(d[4]), "+f"(d[5]), "+f"(d[6]), "+f"(d[7]),
      "+f"(d[8]), "+f"(d[9]), "+f"(d[10]), "+f"(d[11]), "+f"(d[12]), "+f"(d[13]), "+f"(d[14]), "+f"(d[15]),
      "+f"(d[16]), "+f"(d[17]), "+f"(d[18]), "+f"(d[19]), "+f"(d[20]), "+f"(d[21]), "+f"(d[22]), "+f"(d[23]),
      "+f"(d[24]), "+f"(d[25]), "+f"(d[26]), "+f"(d[27]), "+f"(d[28]), "+f"(d[29]), "+f"(d[30]), "+f"(d[31]),
      "+f"(d[32]), "+f"(d[33]), "+f"(d[34]), "+f"(d[35]), "+f"(d[36]), "+f"(d[37]), "+f"(d[38]), "+f"(d[39]),
      "+f"(d[40]), "+f"(d[41]), "+f"(d[42]), "+f"(d[43]), "+f"(d[44]), "+f"(d[45]), "+f"(d[46]), "+f"(d[47]),
      "+f"(d[48]), "+f"(d[49]), "+f"(d[50]), "+f"(d[51]), "+f"(d[52]), "+f"(d[53]), "+f"(d[54]), "+f"(d[55]),
      "+f"(d[56]), "+f"(d[57]), "+f"(d[58]), "+f"(d[59]), "+f"(d[60]), "+f"(d[61]), "+f"(d[62]), "+f"(d[63])
    : "r"(a[0]), "r"(a[1]), "r"(a[2]), "r"(a[3]), "r"(db), "r"(sc), "n"(HI));
}

template <int N> __device__ __forceinline__ void keep(float (&d)[N]) {
#pragma unroll
  for (int i = 0; i < N; i++) asm volatile("" : "+f"(d[i])::"memory");
}

__device__ __forceinline__ void keep(uint32_t (&d)[4]) { asm volatile("" : "+r"(d[0]), "+r"(d[1]), "+r"(d[2]), "+r"(d[3])::"memory"); }
template <int N> __device__ __forceinline__ void keep(uint32_t (&d)[N][4]) {
#pragma unroll
  for (int i = 0; i < N; i++) asm volatile("" : "+r"(d[i][0]), "+r"(d[i][1]), "+r"(d[i][2]), "+r"(d[i][3])::"memory");
}

__device__ __forceinline__ uint32_t pack2(float lo, float hi) {
  uint32_t r;
  asm("cvt.rn.bf16x2.f32 %0, %1, %2;" : "=r"(r) : "f"(hi), "f"(lo));
  return r;
}
__device__ __forceinline__ float bf_lo(uint32_t v) { return __uint_as_float(v << 16); }
__device__ __forceinline__ float bf_hi(uint32_t v) { return __uint_as_float(v & 0xffff0000u); }
__device__ __forceinline__ uint32_t hsub2(uint32_t a, uint32_t b) {
  uint32_t r;
  asm("sub.rn.bf16x2 %0, %1, %2;" : "=r"(r) : "r"(a), "r"(b));
  return r;
}
__device__ __forceinline__ uint32_t movm(uint32_t a) {
  uint32_t r;
  asm volatile("movmatrix.sync.aligned.m8n8.trans.b16 %0, %1;" : "=r"(r) : "r"(a));
  return r;
}
__device__ __forceinline__ void ldsm4(uint32_t (&v)[4], uint32_t a) {
  asm volatile("ldmatrix.sync.aligned.m8n8.x4.shared.b16 {%0,%1,%2,%3}, [%4];" : "=r"(v[0]), "=r"(v[1]), "=r"(v[2]), "=r"(v[3]) : "r"(a) : "memory");
}
__device__ __forceinline__ void stsm4(uint32_t a, const uint32_t (&v)[4]) {
  asm volatile("stmatrix.sync.aligned.m8n8.x4.shared.b16 [%0], {%1,%2,%3,%4};" ::"r"(a), "r"(v[0]), "r"(v[1]), "r"(v[2]), "r"(v[3]) : "memory");
}
__device__ __forceinline__ void mma16816(float (&d)[4], const uint32_t (&a)[4], uint32_t b0, uint32_t b1) {
  asm volatile("mma.sync.aligned.m16n8k16.row.col.f32.bf16.bf16.f32 {%0,%1,%2,%3}, {%4,%5,%6,%7}, {%8,%9}, {%10,%10,%10,%10};"
               : "=f"(d[0]), "=f"(d[1]), "=f"(d[2]), "=f"(d[3])
               : "r"(a[0]), "r"(a[1]), "r"(a[2]), "r"(a[3]), "r"(b0), "r"(b1), "f"(0.f));
}
__device__ __forceinline__ void mma1688_acc(float (&d)[4], uint32_t a0, uint32_t a1, uint32_t b0) {
  asm volatile("mma.sync.aligned.m16n8k8.row.col.f32.bf16.bf16.f32 {%0,%1,%2,%3}, {%4,%5}, {%6}, {%0,%1,%2,%3};"
               : "+f"(d[0]), "+f"(d[1]), "+f"(d[2]), "+f"(d[3]) : "r"(a0), "r"(a1), "r"(b0));
}
__device__ __forceinline__ float ex2(float x) { float y; asm("ex2.approx.ftz.f32 %0, %1;" : "=f"(y) : "f"(x)); return y; }
__device__ __forceinline__ float rcp(float x) { float y; asm("rcp.approx.ftz.f32 %0, %1;" : "=f"(y) : "f"(x)); return y; }
__device__ __forceinline__ float tanhf_hw(float x) { float y; asm("tanh.approx.f32 %0, %1;" : "=f"(y) : "f"(x)); return y; }
__device__ __forceinline__ uint32_t lds32(uint32_t a) { uint32_t v; asm volatile("ld.shared.u32 %0, [%1];" : "=r"(v) : "r"(a) : "memory"); return v; }
__device__ __forceinline__ float2 lds64(uint32_t a) { float2 v; asm volatile("ld.shared.v2.f32 {%0,%1}, [%2];" : "=f"(v.x), "=f"(v.y) : "r"(a) : "memory"); return v; }
__device__ __forceinline__ void lds128(uint32_t (&v)[4], uint32_t a) { asm volatile("ld.shared.v4.u32 {%0,%1,%2,%3}, [%4];" : "=r"(v[0]), "=r"(v[1]), "=r"(v[2]), "=r"(v[3]) : "r"(a) : "memory"); }
__device__ __forceinline__ void sts128(uint32_t a, const uint32_t (&v)[4]) { asm volatile("st.shared.v4.u32 [%0], {%1,%2,%3,%4};" ::"r"(a), "r"(v[0]), "r"(v[1]), "r"(v[2]), "r"(v[3]) : "memory"); }
__device__ __forceinline__ void ldg128_nc(uint32_t (&v)[4], const void* p) {
  asm volatile("ld.global.nc.L1::no_allocate.v4.u32 {%0,%1,%2,%3}, [%4];" : "=r"(v[0]), "=r"(v[1]), "=r"(v[2]), "=r"(v[3]) : "l"(p));
}
__device__ __forceinline__ uint32_t pin(uint32_t v, uint32_t zero) {
  asm volatile("{\n.reg .pred p;\n.reg .u32 c;\nmov.u32 c, %1;\nLP:\n.pragma \"nounroll\";\nsetp.eq.u32 p, c, 0;\n@p bra LD;\n"
               "nanosleep.u32 c;\nadd.u32 %0, %0, c;\nsub.u32 c, c, 1;\nbra LP;\nLD:\n}\n" : "+r"(v) : "r"(zero) : "memory");
  return v;
}
__device__ __forceinline__ void mbar_arrive_if(uint32_t b, bool cond) {
  asm volatile("{\n.reg .pred p;\nsetp.ne.u32 p, %1, 0;\n@p mbarrier.arrive.shared::cta.b64 _, [%0];\n}\n" ::"r"(b), "r"((uint32_t)cond) : "memory");
}
__device__ __forceinline__ uint32_t ld_epoch(const unsigned* p) {
  uint32_t v;
  asm volatile("ld.relaxed.gpu.global.u32 %0, [%1];" : "=r"(v) : "l"(p) : "memory");
  return v;
}
__device__ __forceinline__ void ll_st(uint4* p, uint32_t a, uint32_t b, uint32_t c, uint32_t d, uint32_t tag) {
  asm volatile("st.relaxed.gpu.global.v4.b32 [%0], {%1, %2, %3, %4};" ::"l"(p), "r"((a & ~1u) | tag), "r"(b), "r"(c), "r"(d) : "memory");
}
__device__ __forceinline__ void ll_ld(uint32_t (&v)[4], const uint4* p) {
  asm volatile("{\n.reg .b128 t;\n.reg .b64 lo, hi;\nld.relaxed.gpu.global.b128 t, [%4];\nmov.b128 {lo, hi}, t;\n"
               "mov.b64 {%0, %1}, lo;\nmov.b64 {%2, %3}, hi;\n}\n"
               : "=r"(v[0]), "=r"(v[1]), "=r"(v[2]), "=r"(v[3]) : "l"(p) : "memory");
}
template <int N> __device__ __forceinline__ void ll_issue(uint32_t (&v)[N][4], const uint4* p, int stride) {
#pragma unroll
  for (int i = 0; i < N; i++) ll_ld(v[i], p + i * stride);
}
template <int N> __device__ __forceinline__ uint32_t ll_acc(const uint32_t (&v)[N][4], uint32_t tag, uint32_t acc = 0) {
#pragma unroll
  for (int i = 0; i < N; i++) asm("lop3.b32 %0, %1, %2, %0, 0xBE;" : "+r"(acc) : "r"(v[i][0]), "r"(tag));
  return acc;
}
__device__ __forceinline__ bool ll_any(uint32_t acc) { return __any_sync(0xffffffffu, acc & 1u); }
template <int N> __device__ __forceinline__ bool ll_bad(const uint32_t (&v)[N][4], uint32_t tag) { return ll_any(ll_acc<N>(v, tag)); }
template <int N> __device__ __forceinline__ void ll_clear(uint32_t (&v)[N][4]) {
#pragma unroll
  for (int i = 0; i < N; i++) v[i][0] &= ~1u;
}
template <int N> __device__ __forceinline__ void ll_spin(uint32_t (&v)[N][4], const uint4* p, int stride, uint32_t tag) {
  uint32_t it = 0;
#pragma unroll 1
  do { ll_issue<N>(v, p, stride); } while (ll_bad<N>(v, tag) && ++it < SPIN_LIMIT);
}
template <int N> __device__ __forceinline__ void ll_get(uint32_t (&v)[N][4], const uint4* p, int stride, uint32_t tag) {
  ll_spin<N>(v, p, stride, tag);
  ll_clear<N>(v);
}
template <int N> __device__ __forceinline__ void ll_wait(uint32_t (&v)[N][4], const uint4* p, int stride, uint32_t tag) {
  if (__builtin_expect(ll_bad<N>(v, tag), 0)) ll_spin<N>(v, p, stride, tag);
  ll_clear<N>(v);
}
__device__ __forceinline__ void unpack32(float (&d)[32], const uint32_t (&v)[4][4]) {
#pragma unroll
  for (int u = 0; u < 4; u++)
#pragma unroll
    for (int e = 0; e < 4; e++) { d[8 * u + 2 * e] = bf_lo(v[u][e]); d[8 * u + 2 * e + 1] = bf_hi(v[u][e]); }
}
__device__ __forceinline__ void pack32(uint32_t (&v)[4][4], const float (&d)[32]) {
#pragma unroll
  for (int u = 0; u < 4; u++)
#pragma unroll
    for (int e = 0; e < 4; e++) v[u][e] = pack2(d[8 * u + 2 * e], d[8 * u + 2 * e + 1]);
}
__device__ __forceinline__ uint32_t t_addr(int m) { return SB + ((0x03514620u >> (4 * m)) & 7u) * 32768u; }

__device__ __forceinline__ int kb_at(int i, int j) { return i == 0 ? j : (i - 1 + (i - 1 >= j ? 1 : 0)); }

__device__ __forceinline__ void init_bars(int set) {
  if (set >= 0 && elect_one()) {
    const uint32_t cnt = set < 5 ? 1 : 8;
#pragma unroll
    for (int i = 0; i < 8; i++) mbar_init(BAR + (24 + 8 * set + i) * 8, cnt);
    if (set == 9) {
#pragma unroll
      for (int i = 0; i < 9; i++) mbar_init(BAR + (B_EX + i) * 8, 4);
#pragma unroll
      for (int i = 0; i < 4; i++) mbar_init(BAR + (B_READY + i) * 8, i == 1 ? 7 : 3);
#pragma unroll
      for (int i = 0; i < 9; i++) mbar_init(BAR + (B_TAG + i) * 8, 1);
    }
    asm volatile("fence.mbarrier_init.release.cluster;" ::: "memory");
  }
  __syncwarp();
  asm volatile("bar.arrive 4, 384;" ::: "memory");
  asm volatile("bar.sync 3, 384;" ::: "memory");
}

__global__ void __launch_bounds__(384, 1) fused_block_kernel(Scratch* __restrict__ X, const __nv_bfloat16* __restrict__ xp,
                                                             const __nv_bfloat16* __restrict__ wqkvp, const __nv_bfloat16* __restrict__ wop, const uint32_t zero,
                                                             const __grid_constant__ Params P) {
  extern __shared__ __align__(1024) uint8_t smem_raw[];
  if (smem_u32(smem_raw) != SB) return;
  const int tid = threadIdx.x;
  const int warp = __shfl_sync(0xffffffffu, tid >> 5, 0);
  const int lane = tid & 31;
  const int cta = blockIdx.x;
  const int j = (cta >> 6) * 4 + (cta & 3);
  const int g = (cta & 63) >> 2;

  if (warp >= 8) {
    asm volatile("setmaxnreg.dec.sync.aligned.u32 56;");
    if (warp == 8) {
      PSTAMPW(2, 0);
      const bool leader = elect_one();
      if (leader) {
        prefetch_map(&P.x); prefetch_map(&P.wqkv);
#pragma unroll
        for (int i = 0; i < 24; i++) mbar_init(BAR + i * 8, 1);
        asm volatile("fence.mbarrier_init.release.cluster;" ::: "memory");
      }
      __syncwarp();
      asm volatile("bar.arrive 3, 384;" ::: "memory");
      PSTAMPW(2, 20);
      auto ldx = [&](int p, int kb) {
        const uint32_t b = BAR + (B_FX + p * 8 + kb) * 8;
        mbar_expect_tx(b, 8192);
        tma3d(H0 + p * 65536 + kb * 8192, &P.x, kb * 64, p, g * 64, b);
      };
      auto ldkv = [&](int kb, int slot) {
        const uint32_t b = BAR + (B_FKV + kb) * 8, d = RING + slot * 16384;
        mbar_expect_tx(b, 16384);
        tma2d(d, &P.wqkv, 512 + 64 * j, kb * 64, b);
        tma2d(d + 8192, &P.wqkv, 1024 + 64 * j, kb * 64, b);
      };
      if (leader) {
#pragma unroll 1
        for (int i = 0; i < 8 + XO_DELAY; i++) {
          if (i < 8) ldx(0, i);
          if (i < 6) ldkv(i, i);
          if (i >= XO_DELAY) ldx(1, i - XO_DELAY);
          if (i == 0) PSTAMPW(2, 21);
        }
        PSTAMPW(2, 2);
      }
      __syncwarp();
      asm volatile("bar.sync 4, 384;" ::: "memory");
      if (leader) {
        const int f0 = 224 * j + ((j & 1) ? 32 : 0);
        const int fh = 224 * j + ((j & 1) ? 0 : 192);
        prefetch_map(&P.wo); prefetch_map(&P.w1); prefetch_map(&P.w3); prefetch_map(&P.w1h);
        prefetch_map(&P.w3h); prefetch_map(&P.w2); prefetch_map(&P.out);
#pragma unroll 1
        for (int i = 0; i < 2; i++) { mbar_wait(BAR + (B_EKV + i) * 8); ldkv(6 + i, i); }
#pragma unroll 1
        for (int i = 0; i < 8; i++) {
          const uint32_t b = BAR + (B_FQ + i) * 8;
          mbar_wait(BAR + (B_EKV + 2 + (i >> 1)) * 8);
          mbar_expect_tx(b, 8192);
          tma2d(RING + (4 + i) * 8192, &P.wqkv, 64 * j, i * 64, b);
        }
        mbar_expect_tx(BAR + B_FWO * 8, 65536);
#pragma unroll 1
        for (int i = 0; i < 8; i++) {
          const int kb = (i + 1) & 7;
          mbar_wait(BAR + (B_EX + i) * 8);
          tma2d(H0 + kb * 8192, &P.wo, 64 * j, kb * 64, BAR + B_FWO * 8);
          PSTAMPW(2, 4 + i);
        }
#pragma unroll 1
        for (int i = 0; i < 8; i++) {
          const uint32_t b = BAR + (B_FA + i) * 8, d = RING + (i & 3) * 24576;
          const int k0 = kb_at(i, j) * 64;
          mbar_wait(BAR + (B_EKV + 7 + ((0xCBA98520u >> (4 * i)) & 15)) * 8);
          mbar_expect_tx(b, 24576);
          tma2d(d, &P.w1, f0, k0, b);
          tma2d(d + 8192, &P.w3, f0, k0, b);
          tma2d(d + 16384, &P.w1h, fh, k0, b);
          tma2d(d + 20480, &P.w3h, fh, k0, b);
          PSTAMPW(2, 12 + i);
        }
        uint32_t d = RING;
#pragma unroll 1
        for (int i = 0; i < 8; i++) {
          const uint32_t b = BAR + (B_FB + i) * 8;
          const int k0 = kb_at(i, j) * 64;
          mbar_wait(BAR + (B_EA + 5 + i) * 8);
          mbar_expect_tx(b, 32768);
          tma2d(d, &P.w1, f0 + 64, k0, b);
          tma2d(d + 8192, &P.w3, f0 + 64, k0, b);
          tma2d(d + 16384, &P.w1, f0 + 128, k0, b);
          tma2d(d + 24576, &P.w3, f0 + 128, k0, b);
          d = d == RING + 65536 ? RING : d + 32768;
        }
#pragma unroll 1
        for (int m = 0; m < 8; m++) {
          const uint32_t b = BAR + (B_FT + m) * 8;
          mbar_wait(BAR + (B_EB + (m == 7 ? 8 : min(m + 3, 7))) * 8);
          mbar_expect_tx(b, 28672);
          tma2d(t_addr(m), &P.w2, 64 * ((j + 1 + m) & 7), 224 * j, b);
        }
        X->epoch[cta] = X->epoch[cta] + 1;
      }
    } else {
      const int part = warp - 9;
      uint32_t tag;
      if (part == 2) {
        tag = ld_epoch(X->epoch + cta);
        init_bars(-1);
        tag = (tag + 1) & 1;
        if (lane == 0) {
          asm volatile("st.shared.u32 [%0], %1;" ::"r"(TAGS), "r"(tag) : "memory");
          mbar_arrive(BAR + B_TAG * 8);
        }
      } else {
        init_bars(warp - 1);
        mbar_wait(BAR + B_TAG * 8);
        tag = lds32(TAGS);
      }
      PSTAMPW(3, 16 + part);
      const int xw0 = g * 8;
      auto clear8 = [&](uint4* p, int stride) {
#pragma unroll
        for (int i = 0; i < 8; i++) ll_st(p + i * stride + lane, 0, 0, 0, 0, tag ^ 1);
      };
      auto clear_front = [&]() {
#pragma unroll 1
      for (int u = part; u < 8; u += 3) clear8((u < 4 ? X->e2 : X->e3h) + (xw0 * 32 + 4 * j + (u & 3)) * 32, 1024);
      if (part == 2) {
        clear8(X->e1 + (g * 8 + j) * 256, 32);
#pragma unroll
        for (int i = 0; i < 4; i++)
          ll_st((i < 2 ? X->e2s : X->e3s) + ((xw0 + (i & 1) * 4 + (lane >> 3)) * 8 + j) * 8 + (lane & 7), 0, 0, 0, 0, tag ^ 1);
      }
      };
      if (CLR_MODE == 1) clear_front();
      PSTAMPW(3, 20 + part);
      uint32_t v[8][4];
      if (part < 2) {
        float s[4] = {0.f, 0.f, 0.f, 0.f}, q[4] = {0.f, 0.f, 0.f, 0.f}, piv = 0.f;
        const uint32_t xa = H0 + part * 65536 + (8 * j + (lane >> 2)) * 128 + (lane & 3) * 16 + (lane & 4) * 16;
#pragma unroll 1
        for (int kb = 0; kb < 8; kb++) {
          mbar_wait(BAR + (B_FX + part * 8 + kb) * 8);
          lds128(v[0], xa + kb * 8192); lds128(v[1], (xa + kb * 8192) ^ 64);
          if (kb == 0) piv = __shfl_sync(0xffffffffu, bf_lo(v[0][0]), lane & 28);
#pragma unroll
          for (int e = 0; e < 8; e++) {
            const float a = bf_lo(v[e >> 2][e & 3]) - piv, b = bf_hi(v[e >> 2][e & 3]) - piv;
            s[e & 3] += a + b; q[e & 3] = fmaf(a, a, q[e & 3]); q[e & 3] = fmaf(b, b, q[e & 3]);
          }
        }
        float ss = (s[0] + s[1]) + (s[2] + s[3]), qq = (q[0] + q[1]) + (q[2] + q[3]);
#pragma unroll
        for (int o = 1; o <= 2; o <<= 1) { ss += __shfl_xor_sync(0xffffffffu, ss, o); qq += __shfl_xor_sync(0xffffffffu, qq, o); }
        const float dm = ss * (1.f / D_);
        const float rs = rsqrtf(fmaxf(fmaf(-dm, dm, qq * (1.f / D_)), 0.f) + 1e-5f);
        if ((lane & 3) == 0) ll_st(X->e0s + g * 128 + 2 * (8 * j + (lane >> 2)) + part, __float_as_uint(piv + dm), __float_as_uint(rs), 0, 0, tag);
      } else {
        mbar_wait(BAR + (B_FKV + SIDE_KB) * 8);
        const __nv_bfloat16* wr = wop + (size_t)(j * 64 + g * 4 + (lane >> 3)) * D_ + (lane & 7) * 8;
#pragma unroll
        for (int i = 0; i < 8; i++) ldg128_nc(v[i], wr + i * 64);
        float s[4];
#pragma unroll
        for (int e = 0; e < 4; e++) {
          s[e] = 0.f;
#pragma unroll
          for (int i = 0; i < 8; i++) s[e] += bf_lo(v[i][e]) + bf_hi(v[i][e]);
        }
        float ss = (s[0] + s[1]) + (s[2] + s[3]);
#pragma unroll
        for (int o = 1; o <= 4; o <<= 1) ss += __shfl_xor_sync(0xffffffffu, ss, o);
        if ((lane & 7) == 0) ll_st(X->e0w + j * 64 + g * 4 + (lane >> 3), __float_as_uint(ss * (1.f / D_)), 0, 0, 0, tag);
      }
      __syncwarp();
      if (lane == 0) mbar_arrive(BAR + B_PUB * 8);
      PSTAMPW(3, part * 4 + 2);
      mbar_wait(BAR + B_PUB * 8);
      PSTAMPW(3, part * 4 + 0);
      {
        uint32_t u[2][4];
        const uint4* us = (part == 2 ? X->e0w + j * 64 : X->e0s + g * 128 + part * 64) + lane;
        const uint4* vs = X->e0c + ((j * 3 + part) * 16 + (lane >> 4) * 8) * 16 + (lane & 15);
        uint32_t it = 0;
#pragma unroll 1
        do { ll_issue<2>(u, us, 32); ll_issue<8>(v, vs, 16); } while (ll_any(ll_acc<8>(v, tag, ll_acc<2>(u, tag))) && ++it < SPIN_LIMIT);
        ll_clear<2>(u); ll_clear<8>(v);
#pragma unroll
        for (int i = 0; i < 2; i++) {
          if (part == 2) asm volatile("st.shared.u32 [%0], %1;" ::"r"(WB + (i * 32 + lane) * 4), "r"(u[i][0]) : "memory");
          else asm volatile("st.shared.v2.u32 [%0], {%1,%2};" ::"r"(ST + (part * 64 + i * 32 + lane) * 8), "r"(u[i][0]), "r"(u[i][1]) : "memory");
        }
      }
      uint32_t o[4];
#pragma unroll
      for (int e = 0; e < 4; e++) {
        float s = 0.f;
#pragma unroll
        for (int i = 0; i < 8; i++) s += __uint_as_float(v[i][e]);
        o[e] = __float_as_uint(s + __shfl_xor_sync(0xffffffffu, s, 16));
      }
      if (lane < 16) sts128(CS + (part * 64 + lane * 4) * 4, o);
      __syncwarp();
      if (lane == 0) mbar_arrive(BAR + B_READY * 8);
      PSTAMPW(3, part * 4 + 1);
      if (CLR_MODE == 2) clear_front();
      __syncwarp();
      if (lane == 0) mbar_arrive(BAR + B_CLR0 * 8);
      PSTAMPW(3, 24 + part);
      if (lane == 0) l2_prefetch(part == 0 ? P.w1p + (size_t)cta * 4 * F_ : part == 1 ? P.w3p + (size_t)cta * 4 * F_ : P.w2p + (size_t)cta * 14 * D_, 14336);
      mbar_wait(BAR + (B_EA + 1) * 8);
#pragma unroll 1
      for (int u = 4 * E4_FIRST + part; u < 28; u += 3)
        clear8(X->e4 + ((size_t)xw0 * 64 + ((j + 1 + (u >> 2)) & 7) * 8 + j) * 128 + (u & 3) * 32, 8192);
      __syncwarp();
      if (lane == 0) mbar_arrive(BAR + B_CLR * 8);
      PSTAMPW(3, part * 4 + 3);
    }
  } else {
    const int p = warp >> 2, w = warp & 3;
    const int r = lane >> 2, c = lane & 3;
    init_bars(warp);
    asm volatile("setmaxnreg.inc.sync.aligned.u32 224;");
    PSTAMP(0);
    const uint32_t dAx = descA(H0) + p * 4096;
    const uint32_t Hn = H1 - p * 65536;
    const uint32_t moff = ((lane & 7) + ((lane >> 3) & 1) * 8) * 128 + (((lane >> 4) ^ (lane & 7)) << 4);
    const uint32_t Xw = H0 + p * 65536 + w * 2048;
    const int xw = (g * 2 + p) * 4 + w;
    if (p == 1) {
      uint32_t v[8][4];
      mbar_wait(BAR + (B_FKV + SIDE_KB) * 8);
      const int wp = w < 3 ? w : 0;
      const __nv_bfloat16* wr = wqkvp + (size_t)(g * 32 + (lane >> 3) * 8) * (3 * D_) + wp * D_ + j * 64 + (lane & 7) * 8;
#pragma unroll
      for (int i = 0; i < 8; i++) ldg128_nc(v[i], wr + (size_t)i * 3 * D_);
      mbar_wait(BAR + B_TAG * 8);
      const uint32_t tg = lds32(TAGS);
      float cs[8];
#pragma unroll
      for (int e = 0; e < 4; e++) {
        float a = 0.f, b = 0.f;
#pragma unroll
        for (int i = 0; i < 8; i++) { a += bf_lo(v[i][e]); b += bf_hi(v[i][e]); }
        cs[2 * e] = a; cs[2 * e + 1] = b;
      }
      const bool up = lane & 8;
#pragma unroll
      for (int e = 0; e < 4; e++) {
        const float keepv = up ? cs[4 + e] : cs[e], give = up ? cs[e] : cs[4 + e];
        cs[e] = keepv + __shfl_xor_sync(0xffffffffu, give, 8);
        cs[e] += __shfl_xor_sync(0xffffffffu, cs[e], 16);
      }
      if (lane < 16 && w < 3)
        ll_st(X->e0c + ((j * 3 + w) * 16 + g) * 16 + (lane & 7) * 2 + (lane >> 3), __float_as_uint(cs[0]), __float_as_uint(cs[1]),
              __float_as_uint(cs[2]), __float_as_uint(cs[3]), tg);
      __syncwarp();
      mbar_arrive_if(BAR + B_PUB * 8, lane == 0);
      PSTAMP(1);
      mbar_wait(BAR + B_LAG * 8);
    }

    float akv[64];
#pragma unroll 1
    for (int kb = 0; kb < 8; kb++) {
      mbar_wait(BAR + (B_FX + p * 8 + kb) * 8);
      mbar_wait(BAR + (B_FKV + kb) * 8);
      if (kb == 0) PSTAMP(2);
      const uint32_t da = dAx + kb * 512, db = descB(RING) + (kb < 6 ? kb : kb - 6) * 1024;
      wg_fence();
      wgmma_ss_n128(akv, da, db, kb);
#pragma unroll
      for (int k = 1; k < 4; k++) wgmma_ss_n128(akv, da + k * 2, db + k * 128, 1);
      wg_commit();
      mbar_arrive_if(BAR + B_LAG * 8, kb == LAG_KB - 1 && p == 0 && lane == 0);
      wg_wait<1>();
      mbar_arrive_if(BAR + (B_EKV + kb - 1) * 8, kb > 0 && lane == 0);
    }
    uint32_t xres[4][4];
#pragma unroll
    for (int u = 0; u < 4; u++) ldsm4(xres[u], Xw + j * 8192 + (moff ^ (u << 5)));

    float aq[32];
    auto qstep = [&](int kb) {
      mbar_wait(BAR + (B_FQ + kb) * 8);
      const uint32_t da = dAx + kb * 512, db = descB(RING + 32768) + kb * 512;
      wg_fence();
      wgmma_ss_n64(aq, da, db, kb);
#pragma unroll
      for (int k = 1; k < 4; k++) wgmma_ss_n64(aq, da + k * 2, db + k * 128, 1);
      wg_commit();
      wg_wait<1>();
      mbar_arrive_if(BAR + (B_EQ + kb - 1) * 8, lane == 0);
      mbar_arrive_if(BAR + (B_EX + kb - 2) * 8, lane == 0 && p == 0 && kb >= 2);
    };
    qstep(0);
    keep(akv);
    PSTAMP(3);
    qstep(1);
    mbar_wait(BAR + B_READY * 8);
    PSTAMP(19);
    const uint32_t tag = lds32(TAGS);
    uint4* const xb = reinterpret_cast<uint4*>(X) + lane + (tag >> 1);
    constexpr int O_E4 = offsetof(Scratch, e4) / 16, O_E2 = offsetof(Scratch, e2) / 16, O_E3H = offsetof(Scratch, e3h) / 16;
    const float2 st0 = lds64(ST + (2 * (16 * w + r) + p) * 8);
    const float2 st1 = lds64(ST + (2 * (16 * w + r + 8) + p) * 8);
    uint32_t hi[4][4], lo[4][4];
    {
      float2 cs[16];
      auto cvt = [&](uint32_t (&d)[4][4], int b0, int ofs, const float2& st) {
#pragma unroll
        for (int b = b0; b < b0 + 8; b++) {
          if (ofs == 2) cs[b] = lds64(CS + (64 + b * 8 + 2 * c) * 4);
          const uint32_t v = pack2(fmaf(-st.x, cs[b].x, akv[4 * b + ofs]) * st.y, fmaf(-st.x, cs[b].y, akv[4 * b + ofs + 1]) * st.y);
          d[b >> 2][b & 3] = b < 8 ? v : movm(v);
        }
      };
      cvt(hi, 0, 2, st1);
      keep(hi[0]); keep(hi[1]);
      qstep(2);
      cvt(hi, 8, 2, st1);
      mbar_wait(BAR + B_CLR0 * 8);
      if (w == 3 && g < 15) {
        uint4* dst = X->e1 + ((g * 8 + j) * 2 + p) * 128 + lane;
#pragma unroll
        for (int i = 0; i < 4; i++) ll_st(dst + i * 32, hi[i][0], hi[i][1], hi[i][2], hi[i][3], tag);
      }
      PSTAMP(20);
      wg_bar(p);
#pragma unroll
      for (int i = 0; i < 4; i++) sts128(Xw + lane * 16 + i * 512, hi[i]);
      qstep(3);
      cvt(lo, 0, 0, st0);
      keep(lo[0]); keep(lo[1]);
      qstep(4);
      cvt(lo, 8, 0, st0);
    }
    PSTAMP(21);
    wg_bar(p);
    uint32_t prev[4][4];
    if (w > 0) {
#pragma unroll
      for (int i = 0; i < 4; i++) lds128(prev[i], Xw - 2048 + lane * 16 + i * 512);
    }
    if (p == 0) {
      asm volatile("fence.proxy.async.shared::cta;" ::: "memory");
      __syncwarp();
      if (lane == 0) mbar_arrive(BAR + (B_EX + 7) * 8);
    }
    PSTAMP(22);
    const uint4* halo = X->e1 + (((g - 1) * 8 + j) * 2 + p) * 128 + lane;
    const bool use_halo = w == 0 && g > 0;
    qstep(5);
    if (use_halo) ll_issue<4>(prev, halo, 32);
    qstep(6);
    qstep(7);
    PSTAMP(23);
    if (w == 0) {
      if (g > 0) {
        if (__builtin_expect(ll_bad<4>(prev, pin(tag, zero)), 0)) ll_spin<4>(prev, halo, 32, tag);
        ll_clear<4>(prev);
      } else {
#pragma unroll
        for (int i = 0; i < 4; i++)
#pragma unroll
          for (int e = 0; e < 4; e++) prev[i][e] = 0;
      }
    }
    wg_wait<0>();
    keep(aq);
    mbar_arrive_if(BAR + (B_EQ + 7) * 8, lane == 0);
    mbar_arrive_if(BAR + (B_EX + 6) * 8, lane == 0 && p == 0);
    PSTAMP(4);

    uint32_t of[4][4];
    {
      const float sc = 0.25f * 1.4426950408889634f;
      const float nohalo = (g == 0 && w == 0) ? -INFINITY : 0.f;
      const bool up0 = 2 * c > r, up1 = 2 * c + 1 > r;
      const uint32_t mup = (up0 ? 0xffffu : 0u) | (up1 ? 0xffff0000u : 0u);
      uint4* dst = xb + O_E2 + (xw * 32 + 4 * j) * 32;
      float d0 = 0.f, d1 = 0.f;
#pragma unroll 1
      for (int hp = 0; hp < 2; hp++) {
#pragma unroll
        for (int e = 0; e < 4; e++) { of[0][e] = of[2][e]; of[1][e] = of[3][e]; }
#pragma unroll
        for (int h = 0; h < 2; h++) {
          uint32_t qf[4];
          const uint32_t co = (32 * hp + 16 * h + 2 * c) * 4;
          {
            const float2 ca = lds64(CS + co), cb = lds64(CS + co + 32);
            qf[0] = pack2(fmaf(-st0.x, ca.x, aq[8 * h + 0]) * st0.y, fmaf(-st0.x, ca.y, aq[8 * h + 1]) * st0.y);
            qf[1] = pack2(fmaf(-st1.x, ca.x, aq[8 * h + 2]) * st1.y, fmaf(-st1.x, ca.y, aq[8 * h + 3]) * st1.y);
            qf[2] = pack2(fmaf(-st0.x, cb.x, aq[8 * h + 4]) * st0.y, fmaf(-st0.x, cb.y, aq[8 * h + 5]) * st0.y);
            qf[3] = pack2(fmaf(-st1.x, cb.x, aq[8 * h + 6]) * st1.y, fmaf(-st1.x, cb.y, aq[8 * h + 7]) * st1.y);
          }
          const int e0 = 2 * h;
          float sp[4], sl[4], sh[4];
          mma16816(sp, qf, prev[0][e0], prev[0][e0 + 1]);
          mma16816(sl, qf, lo[0][e0], lo[0][e0 + 1]);
          mma16816(sh, qf, hi[0][e0], hi[0][e0 + 1]);
          float a0 = up0 ? sp[0] + nohalo : sl[0], a1 = up1 ? sp[1] + nohalo : sl[1];
          float b0 = up0 ? sl[2] : sh[2], b1 = up1 ? sl[3] : sh[3];
          float ma = fmaxf(a0, a1), mb = fmaxf(b0, b1);
          ma = fmaxf(ma, __shfl_xor_sync(0xffffffffu, ma, 1)); mb = fmaxf(mb, __shfl_xor_sync(0xffffffffu, mb, 1));
          ma = fmaxf(ma, __shfl_xor_sync(0xffffffffu, ma, 2)); mb = fmaxf(mb, __shfl_xor_sync(0xffffffffu, mb, 2));
          a0 = ex2((a0 - ma) * sc); a1 = ex2((a1 - ma) * sc); b0 = ex2((b0 - mb) * sc); b1 = ex2((b1 - mb) * sc);
          float sa = a0 + a1, sbb = b0 + b1;
          sa += __shfl_xor_sync(0xffffffffu, sa, 1); sbb += __shfl_xor_sync(0xffffffffu, sbb, 1);
          sa += __shfl_xor_sync(0xffffffffu, sa, 2); sbb += __shfl_xor_sync(0xffffffffu, sbb, 2);
          const float ia = rcp(sa), ib = rcp(sbb);
          const uint32_t pa = pack2(a0 * ia, a1 * ia), pb = pack2(b0 * ib, b1 * ib);
          const uint32_t pf[4] = {pa & mup, 0u, pa & ~mup, pb & mup};
          const uint32_t ph = pb & ~mup;
          float o0[4], o1[4];
          mma16816(o0, pf, prev[2][e0], lo[2][e0]);
          mma16816(o1, pf, prev[2][e0 + 1], lo[2][e0 + 1]);
          mma1688_acc(o0, 0u, ph, hi[2][e0]);
          mma1688_acc(o1, 0u, ph, hi[2][e0 + 1]);
          of[2 + h][0] = pack2(o0[0], o0[1]); of[2 + h][1] = pack2(o0[2], o0[3]);
          of[2 + h][2] = pack2(o1[0], o1[1]); of[2 + h][3] = pack2(o1[2], o1[3]);
          ll_st(dst + (2 * hp + h) * 32, of[2 + h][0], of[2 + h][1], of[2 + h][2], of[2 + h][3], tag);
          const float2 wa = lds64(WB + co), wb = lds64(WB + co + 32);
          d0 = fmaf(o0[0], wa.x, d0); d0 = fmaf(o0[1], wa.y, d0); d0 = fmaf(o1[0], wb.x, d0); d0 = fmaf(o1[1], wb.y, d0);
          d1 = fmaf(o0[2], wa.x, d1); d1 = fmaf(o0[3], wa.y, d1); d1 = fmaf(o1[2], wb.x, d1); d1 = fmaf(o1[3], wb.y, d1);
        }
#pragma unroll
        for (int e = 0; e < 16; e++) aq[e] = aq[16 + e];
#pragma unroll
        for (int e = 0; e < 4; e++) {
          prev[0][e] = prev[1][e]; prev[2][e] = prev[3][e];
          lo[0][e] = lo[1][e]; lo[2][e] = lo[3][e];
          hi[0][e] = hi[1][e]; hi[2][e] = hi[3][e];
        }
      }
#pragma unroll
      for (int o = 1; o <= 2; o <<= 1) { d0 += __shfl_xor_sync(0xffffffffu, d0, o); d1 += __shfl_xor_sync(0xffffffffu, d1, o); }
      if (c == 0) ll_st(X->e2s + (xw * 8 + j) * 8 + r, __float_as_uint(d0), __float_as_uint(d1), 0, 0, tag);
    }
    PSTAMP(5);

    float ah[32];
    uint32_t sv[2][4];
    unpack32(ah, xres);
    {
      uint32_t og[2][14][4];
      const uint4* osrc[7];
#pragma unroll
      for (int i = 0; i < 7; i++) osrc[i] = xb + O_E2 + (xw * 32 + 4 * kb_at(i + 1, j)) * 32;
      const uint4* ssrc = X->e2s + (xw * 8 + 2 * c) * 8 + r;
      auto oissue = [&](int hp) {
#pragma unroll
        for (int i = 0; i < 14; i++) ll_ld(og[hp][i], osrc[i >> 1] + (2 * hp + (i & 1)) * 32);
        if (hp == 1) ll_issue<2>(sv, ssrc, 8);
      };
      auto omma = [&](int hp) {
        ll_clear<14>(og[hp]);
        keep(og[hp]);
        wg_fence();
#pragma unroll
        for (int i = 0; i < 14; i++) wgmma_rs_n64(ah, og[hp][i], descB(H0) + kb_at((i >> 1) + 1, j) * 512 + (2 * hp + (i & 1)) * 128, 1);
        wg_commit();
      };
      mbar_wait(BAR + B_FWO * 8);
      keep(ah); keep(of);
      wg_fence();
#pragma unroll
      for (int k = 0; k < 4; k++) wgmma_rs_n64(ah, of[k], descB(H0) + j * 512 + k * 128, 1);
      wg_commit();
      uint32_t it = 0;
#pragma unroll 1
      do { oissue(0); } while (ll_bad<14>(og[0], tag) && ++it < SPIN_LIMIT);
      PSTAMP(6);
      oissue(1);
      omma(0);
      const uint32_t tg = pin(tag, zero);
      if (__builtin_expect(ll_any(ll_acc<14>(og[1], tg, ll_acc<2>(sv, tg))), 0)) {
#pragma unroll 1
        do { oissue(1); } while (ll_any(ll_acc<14>(og[1], tag, ll_acc<2>(sv, tag))) && ++it < SPIN_LIMIT);
      }
      PSTAMP(16);
      omma(1);
      ll_clear<2>(sv);
    }
    float m0 = __uint_as_float(sv[0][0]) + __uint_as_float(sv[1][0]), m1 = __uint_as_float(sv[0][1]) + __uint_as_float(sv[1][1]);
#pragma unroll
    for (int o = 1; o <= 2; o <<= 1) { m0 += __shfl_xor_sync(0xffffffffu, m0, o); m1 += __shfl_xor_sync(0xffffffffu, m1, o); }
    const uint32_t mu0 = pack2(m0 + st0.x, m0 + st0.x), mu1 = pack2(m1 + st1.x, m1 + st1.x);
    wg_wait<0>();
    keep(ah);
    if (lane == 0) mbar_arrive(BAR + B_WODONE * 8);
    PSTAMP(7);

    uint32_t hf[4][4], ra[4][4];
    pack32(hf, ah);
    {
      uint4* dst = xb + O_E3H + (xw * 32 + 4 * j) * 32;
#pragma unroll
      for (int u = 0; u < 4; u++) {
        ra[u][0] = hsub2(hf[u][0], mu0); ra[u][1] = hsub2(hf[u][1], mu1);
        ra[u][2] = hsub2(hf[u][2], mu0); ra[u][3] = hsub2(hf[u][3], mu1);
        ll_st(dst + u * 32, ra[u][0], ra[u][1], ra[u][2], ra[u][3], tag);
      }
      float s0 = 0.f, q0 = 0.f, s1 = 0.f, q1 = 0.f;
#pragma unroll
      for (int b = 0; b < 8; b++) {
        s0 += ah[4 * b] + ah[4 * b + 1]; s1 += ah[4 * b + 2] + ah[4 * b + 3];
        q0 = fmaf(ah[4 * b], ah[4 * b], q0); q0 = fmaf(ah[4 * b + 1], ah[4 * b + 1], q0);
        q1 = fmaf(ah[4 * b + 2], ah[4 * b + 2], q1); q1 = fmaf(ah[4 * b + 3], ah[4 * b + 3], q1);
      }
#pragma unroll
      for (int o = 1; o <= 2; o <<= 1) {
        s0 += __shfl_xor_sync(0xffffffffu, s0, o); q0 += __shfl_xor_sync(0xffffffffu, q0, o);
        s1 += __shfl_xor_sync(0xffffffffu, s1, o); q1 += __shfl_xor_sync(0xffffffffu, q1, o);
      }
      if (c == 0) ll_st(X->e3s + (xw * 8 + j) * 8 + r, __float_as_uint(s0), __float_as_uint(q0), __float_as_uint(s1), __float_as_uint(q1), tag);
      mbar_wait(BAR + (p == 0 ? B_EQ + 7 : B_WODONE) * 8);
    }
    PSTAMP(8);

    float rs0, rs1;
    auto swiglu = [&](float g0, float g1, float u0, float u1, float rs) -> uint32_t {
      const float hr = 0.5f * rs;
      const float x0 = g0 * hr, x1 = g1 * hr;
      const float t0 = tanhf_hw(x0), t1 = tanhf_hw(x1);
      return pack2(fmaf(x0, t0, x0) * (u0 * rs), fmaf(x1, t1, x1) * (u1 * rs));
    };
    uint32_t hA[6][4];
    {
      float a1[64], a2[32];
      const uint4* src = xb + O_E3H + xw * 32 * 32;
      uint32_t rb[4][4], rc[4][4], rd[4][4];
      auto fetch = [&](uint32_t (&a)[4][4], int i) { ll_issue<4>(a, src + kb_at(i, j) * 128, 32); };
      auto check = [&](uint32_t (&a)[4][4], uint32_t (&b)[4][4], int i) {
        const uint32_t tg = pin(tag, zero);
        if (__builtin_expect(ll_any(ll_acc<4>(a, tg, ll_acc<4>(b, tg))), 0)) {
          uint32_t it = 0;
#pragma unroll 1
          do { fetch(a, i); fetch(b, i + 1); } while (ll_any(ll_acc<4>(a, tag, ll_acc<4>(b, tag))) && ++it < SPIN_LIMIT);
        }
        ll_clear<4>(a); ll_clear<4>(b);
        keep(a); keep(b);
      };
      auto head = [&](uint32_t (&a)[4][4], int i) {
        mbar_wait(BAR + (B_FA + i) * 8);
        wg_fence();
        wgmma_rs_n64<DESC_HI64>(a2, a[0], descBh(RING + 16384) + (i & 3) * 1536, i);
        wgmma_rs_n128(a1, a[0], descB(RING) + (i & 3) * 1536, i);
        wg_commit();
#pragma unroll
        for (int u = 0; u < 4; u++) stsm4(Hn + w * 2048 + i * 8192 + (moff ^ (u << 5)), a[u]);
        wg_wait<1>();
        if (i > 0) mbar_arrive_if(BAR + (B_EA + i - 1) * 8, lane == 0);
      };
      auto rest = [&](uint32_t (&a)[4][4], int i) {
        wg_fence();
#pragma unroll
        for (int k = 1; k < 4; k++) {
          wgmma_rs_n64<DESC_HI64>(a2, a[k], descBh(RING + 16384) + (i & 3) * 1536 + k * 64, 1);
          wgmma_rs_n128(a1, a[k], descB(RING) + (i & 3) * 1536 + k * 128, 1);
        }
        wg_commit();
      };
      ll_clear<4>(ra);
      keep(ra);
      head(ra, 0); rest(ra, 0);
      ll_get<4>(rb, src + kb_at(1, j) * 128, 32, tag);
      keep(rb);
      PSTAMP(17);
      fetch(rc, 2); fetch(rd, 3);
      head(rb, 1); rest(rb, 1);
      check(rc, rd, 2);
      head(rc, 2); fetch(ra, 4); fetch(rb, 5); rest(rc, 2);
      head(rd, 3); rest(rd, 3);
      check(ra, rb, 4);
      head(ra, 4); fetch(rc, 6); fetch(rd, 7); ll_issue<2>(sv, X->e3s + (xw * 8 + 2 * c) * 8 + r, 8); rest(ra, 4);
      head(rb, 5); rest(rb, 5);
      check(rc, rd, 6);
      head(rc, 6); rest(rc, 6);
      head(rd, 7); rest(rd, 7);
      fence_async_smem();
      ll_wait<2>(sv, X->e3s + (xw * 8 + 2 * c) * 8 + r, 8, tag);
      float s0 = __uint_as_float(sv[0][0]) + __uint_as_float(sv[1][0]), q0 = __uint_as_float(sv[0][1]) + __uint_as_float(sv[1][1]);
      float s1 = __uint_as_float(sv[0][2]) + __uint_as_float(sv[1][2]), q1 = __uint_as_float(sv[0][3]) + __uint_as_float(sv[1][3]);
#pragma unroll
      for (int o = 1; o <= 2; o <<= 1) {
        s0 += __shfl_xor_sync(0xffffffffu, s0, o); q0 += __shfl_xor_sync(0xffffffffu, q0, o);
        s1 += __shfl_xor_sync(0xffffffffu, s1, o); q1 += __shfl_xor_sync(0xffffffffu, q1, o);
      }
      s0 *= 1.f / D_; s1 *= 1.f / D_;
      rs0 = rsqrtf(fmaxf(fmaf(-s0, s0, q0 * (1.f / D_)), 0.f) + 1e-5f);
      rs1 = rsqrtf(fmaxf(fmaf(-s1, s1, q1 * (1.f / D_)), 0.f) + 1e-5f);
      wg_wait<0>();
      keep(a1); keep(a2);
      if (lane == 0) mbar_arrive(BAR + (B_EA + 7) * 8);
      PSTAMP(9);
#pragma unroll
      for (int u = 0; u < 4; u++)
#pragma unroll
        for (int e = 0; e < 4; e++)
          hA[u][e] = swiglu(a1[8 * u + 2 * e], a1[8 * u + 2 * e + 1], a1[32 + 8 * u + 2 * e], a1[33 + 8 * u + 2 * e], (e & 1) ? rs1 : rs0);
#pragma unroll
      for (int u = 0; u < 2; u++)
#pragma unroll
        for (int e = 0; e < 4; e++)
          hA[4 + u][e] = swiglu(a2[8 * u + 2 * e], a2[8 * u + 2 * e + 1], a2[16 + 8 * u + 2 * e], a2[17 + 8 * u + 2 * e], (e & 1) ? rs1 : rs0);
      keep(hA);
      wg_bar(p);
    }
    PSTAMP(10);

    uint32_t hB[8][4];
    {
      float ab[128];
      uint32_t db = descB(RING);
      const uint32_t dAn = descA(H1) - p * 4096;
#pragma unroll 1
      for (int i = 0; i < 8; i++) {
        mbar_wait(BAR + (B_FB + i) * 8);
        const uint32_t da = dAn + i * 512;
        wg_fence();
        wgmma_ss_n256(ab, da, db, i);
#pragma unroll
        for (int k = 1; k < 4; k++) wgmma_ss_n256(ab, da + k * 2, db + k * 128, 1);
        wg_commit();
        wg_wait<1>();
        mbar_arrive_if(BAR + (B_EB + i - 1) * 8, i > 0 && lane == 0);
        db = db == descB(RING + 65536) ? descB(RING) : db + 2048;
      }
      wg_wait<0>();
      keep(ab);
      if (lane == 0) mbar_arrive(BAR + (B_EB + 7) * 8);
      PSTAMP(11);
#pragma unroll
      for (int u = 0; u < 8; u++) {
        const int o = (u >> 2) * 64 + (u & 3) * 8;
#pragma unroll
        for (int e = 0; e < 4; e++)
          hB[u][e] = swiglu(ab[o + 2 * e], ab[o + 2 * e + 1], ab[o + 32 + 2 * e], ab[o + 33 + 2 * e], (e & 1) ? rs1 : rs0);
      }
      keep(hB);
    }
    PSTAMP(12);

    {
      float ya[32], y[32], sum[32];
      const uint32_t offA = (j & 1) ? 256 : 0, offH = (j & 1) ? 0 : 1536;
      uint4* e4 = xb + O_E4 + xw * 64 * 128;
      const uint32_t stg = H0 + p * 131072 + (w >> 1) * 65536 + 28672 + (w & 1) * 2048;
      const uint32_t inbar = BAR + (B_IN + warp) * 8;
      uint32_t in[4][4], pk[4][4];
      auto insrc = [&](int q) { return e4 + (j * 8 + ((j - 1 - q) & 7)) * 128; };
      const uint32_t ident = (2 * c == r ? 0x3f80u : 0u) | (2 * c + 1 == r ? 0x3f800000u : 0u);
      auto acc = [&]() {
        ll_clear<4>(in);
#pragma unroll
        for (int u = 0; u < 4; u++) {
          mma1688_acc(*reinterpret_cast<float (*)[4]>(&sum[8 * u]), in[u][0], in[u][1], ident);
          mma1688_acc(*reinterpret_cast<float (*)[4]>(&sum[8 * u + 4]), in[u][2], in[u][3], ident);
        }
      };
      uint32_t T;
      auto mm = [&](float (&d)[32], int k0, int k1) {
        wg_fence();
#pragma unroll
        for (int k = k0; k < k1; k++) {
          if (k < 4) wgmma_rs_n64(d, hA[k], T + offA + k * 128, k);
          else if (k < 6) wgmma_rs_n64(d, hA[k], T + offH + (k - 4) * 128, 1);
          else wgmma_rs_n64(d, hB[k - 6], T + offA + 512 + (k - 6) * 128, 1);
        }
        wg_commit();
      };
      auto start = [&](float (&d)[32], float (&dp)[32], int m) {
        const int mt = min(m, 7);
        mbar_wait(BAR + (B_FT + mt) * 8);
        T = descB(0) + (t_addr(mt) >> 4);
        mm(d, 0, 3);
        if (m >= 2 && m < 8 && lane == 0) {
          mbar_expect_tx(inbar, 2048);
          asm volatile("cp.async.bulk.shared::cluster.global.mbarrier::complete_tx::bytes [%0], [%1], 2048, [%2];"
                       ::"r"(stg), "l"(insrc(m - 2)), "r"(inbar) : "memory");
        }
        wg_wait<1>();
        keep(dp);
        mbar_arrive_if(BAR + B_ET0 * 8, m == 1 && lane == 0);
        pack32(pk, dp);
      };
      auto rest = [&](float (&d)[32], int m) {
        uint4* dst = e4 + (((j + m) & 7) * 8 + j) * 128;
#pragma unroll
        for (int u = 0; u < 4; u++) {
          ll_st(dst + u * 32, pk[u][0], pk[u][1], pk[u][2], pk[u][3], u ? pin(tag, zero) : tag);
          mm(d, u ? 4 + 2 * u : 3, 6 + 2 * u);
        }
        if (m >= 2) {
          mbar_wait_par(inbar, m & 1);
#pragma unroll
          for (int u = 0; u < 4; u++) lds128(in[u], stg + lane * 16 + u * 512);
          if (__builtin_expect(ll_bad<4>(in, tag), 0)) ll_spin<4>(in, insrc(m - 2), 32, tag);
          acc();
        }
        mm(d, 12, 14);
      };
      mbar_wait(BAR + B_CLR * 8);
      mbar_wait(BAR + (B_EB + 3 + 3 * p) * 8);
      mbar_wait(BAR + B_FT * 8);
      T = descB(0) + (t_addr(0) >> 4);
      mm(ya, 0, 3);
      unpack32(sum, hf);
      keep(sum);
#pragma unroll
      for (int u = 0; u < 4; u++) { pk[u][0] = 0; pk[u][1] = 0; pk[u][2] = 0; pk[u][3] = 0; }
      wg_wait<0>();
#pragma unroll 1
      for (int m = 0; m < 8; m += 2) {
        rest(ya, m);
        start(y, ya, m + 1);
        rest(y, m + 1);
        start(ya, y, m + 2);
        wg_wait<0>();
        if (m == 0) PSTAMP(27);
        if (m == 2) PSTAMP(26);
        if (m == 4) PSTAMP(28);
      }
      PSTAMP(13);
      ll_spin<4>(in, insrc(6), 32, tag);
      acc();
      PSTAMP(14);
#pragma unroll
      for (int u = 0; u < 4; u++) {
        uint32_t o[4];
#pragma unroll
        for (int e = 0; e < 4; e++) o[e] = pack2(sum[8 * u + 2 * e] + y[8 * u + 2 * e], sum[8 * u + 2 * e + 1] + y[8 * u + 2 * e + 1]);
        stsm4(stg + (moff ^ (u << 5)), o);
      }
      fence_async_smem();
      __syncwarp();
      if (elect_one()) {
        tma3d_store(&P.out, stg, 64 * j, p, g * 64 + 16 * w);
        asm volatile("cp.async.bulk.commit_group;" ::: "memory");
        asm volatile("cp.async.bulk.wait_group.read 0;" ::: "memory");
      }
      PSTAMP(15);
    }
  }
}

typedef CUresult (*EncodeFn)(CUtensorMap*, CUtensorMapDataType, cuuint32_t, void*, const cuuint64_t*, const cuuint64_t*,
                             const cuuint32_t*, const cuuint32_t*, CUtensorMapInterleave, CUtensorMapSwizzle,
                             CUtensorMapL2promotion, CUtensorMapFloatOOBfill);

void enc2d(EncodeFn f, CUtensorMap* m, const void* base, uint64_t cols, uint64_t rows, uint32_t bc, uint32_t br, CUtensorMapSwizzle sw) {
  cuuint64_t gd[2] = {cols, rows}, gs[1] = {cols * 2};
  cuuint32_t bd[2] = {bc, br}, es[2] = {1, 1};
  f(m, CU_TENSOR_MAP_DATA_TYPE_BFLOAT16, 2, const_cast<void*>(base), gd, gs, bd, es, CU_TENSOR_MAP_INTERLEAVE_NONE, sw,
    CU_TENSOR_MAP_L2_PROMOTION_L2_128B, CU_TENSOR_MAP_FLOAT_OOB_FILL_NONE);
}
void enc_par(EncodeFn f, CUtensorMap* m, const void* base, uint32_t pairs) {
  cuuint64_t gd[3] = {(cuuint64_t)D_, 2, (cuuint64_t)S_ / 2}, gs[2] = {D_ * 2, D_ * 4};
  cuuint32_t bd[3] = {64, 1, pairs}, es[3] = {1, 1, 1};
  f(m, CU_TENSOR_MAP_DATA_TYPE_BFLOAT16, 3, const_cast<void*>(base), gd, gs, bd, es, CU_TENSOR_MAP_INTERLEAVE_NONE,
    CU_TENSOR_MAP_SWIZZLE_128B, CU_TENSOR_MAP_L2_PROMOTION_L2_128B, CU_TENSOR_MAP_FLOAT_OOB_FILL_NONE);
}

}

extern "C" void kernel_launch(void* const* d_in, const int* in_sizes, int n_in, void* d_out, int out_size) {
  (void)in_sizes; (void)n_in; (void)out_size;
  static EncodeFn enc = nullptr;
  static Scratch* scratch = nullptr;
  if (!enc) {
    void* fn = nullptr;
    cudaDriverEntryPointQueryResult q;
    cudaGetDriverEntryPoint("cuTensorMapEncodeTiled", &fn, cudaEnableDefault, &q);
    enc = (EncodeFn)fn;
    cudaGetSymbolAddress((void**)&scratch, g_scratch);
    cudaFuncSetAttribute(fused_block_kernel, cudaFuncAttributeMaxDynamicSharedMemorySize, SMEM_BYTES);
  }
  Params P;
  const __nv_bfloat16* xp = (const __nv_bfloat16*)d_in[0];
  const __nv_bfloat16* wqkvp = (const __nv_bfloat16*)d_in[1];
  const __nv_bfloat16* wop = (const __nv_bfloat16*)d_in[2];
  P.w1p = (const __nv_bfloat16*)d_in[4];
  P.w3p = (const __nv_bfloat16*)d_in[5];
  P.w2p = (const __nv_bfloat16*)d_in[6];
  enc_par(enc, &P.x, xp, 64);
  enc_par(enc, &P.out, d_out, 16);
  enc2d(enc, &P.wqkv, wqkvp, 3 * D_, D_, 64, 64, CU_TENSOR_MAP_SWIZZLE_128B);
  enc2d(enc, &P.wo, wop, D_, D_, 64, 64, CU_TENSOR_MAP_SWIZZLE_128B);
  enc2d(enc, &P.w1, P.w1p, F_, D_, 64, 64, CU_TENSOR_MAP_SWIZZLE_128B);
  enc2d(enc, &P.w3, P.w3p, F_, D_, 64, 64, CU_TENSOR_MAP_SWIZZLE_128B);
  enc2d(enc, &P.w1h, P.w1p, F_, D_, 32, 64, CU_TENSOR_MAP_SWIZZLE_64B);
  enc2d(enc, &P.w3h, P.w3p, F_, D_, 32, 64, CU_TENSOR_MAP_SWIZZLE_64B);
  enc2d(enc, &P.w2, P.w2p, D_, F_, 64, 224, CU_TENSOR_MAP_SWIZZLE_128B);

  cudaLaunchConfig_t cfg = {};
  cfg.gridDim = dim3(128);
  cfg.blockDim = dim3(384);
  cfg.dynamicSmemBytes = SMEM_BYTES;
  cfg.stream = cudaStreamPerThread;
  cudaLaunchAttribute at[1];
  at[0].id = cudaLaunchAttributeCooperative;
  at[0].val.cooperative = 1;
  cfg.attrs = at;
  cfg.numAttrs = 1;
  cudaLaunchKernelEx(&cfg, fused_block_kernel, scratch, xp, wqkvp, wop, 0u, P);
}
```

```cpp
#include <cuda_runtime.h>
#include <cuda.h>
#include <cuda_bf16.h>
#include <stdint.h>
#include <stddef.h>

namespace {

constexpr int S_ = 2048, D_ = 512, F_ = 1792;
#define LAG_KB 3
#define E4_FIRST 7
#define PP_AHEAD 1
#define SIDE_KB 0
#define CLR_MODE 0
#define W2_HEAD 3
#define XO_DELAY 2

constexpr uint32_t SPIN_LIMIT = 1u << 18;

struct Scratch {
  uint4 e4[16 * 2 * 4 * 8 * 8 * 4 * 32];
  uint4 e2[16 * 2 * 4 * 32 * 32];
  uint4 e3h[16 * 2 * 4 * 32 * 32];
  uint4 e1[16 * 8 * 2 * 4 * 32];
  uint4 e2s[16 * 2 * 4 * 8 * 8];
  uint4 e3s[16 * 2 * 4 * 8 * 8];
  uint4 e0c[8 * 3 * 16 * 16];
  uint4 e0s[2048];
  uint4 e0w[8 * 64];
  unsigned epoch[128];
};
__device__ Scratch g_scratch;
#define PSTAMP(i)
#define PSTAMPW(slot, i)
#define W2STAMP(i)

struct alignas(64) Params {
  CUtensorMap x, out, wqkv, wo, w1, w3, w1h, w3h, w2;
  const __nv_bfloat16 *w1p, *w3p, *w2p;
};

constexpr uint32_t SB = 1024;
constexpr uint32_t H0 = SB;
constexpr uint32_t H1 = SB + 65536;
constexpr uint32_t RING = SB + 131072;
constexpr uint32_t BAR = SB + 229376;
constexpr uint32_t TAGS = BAR + 1016;
constexpr uint32_t CS = BAR + 1024;
constexpr uint32_t ST = CS + 768;
constexpr uint32_t WB = ST + 1024;
constexpr uint32_t SMEM_BYTES = 232448;
static_assert(WB + 256 <= SB + SMEM_BYTES, "smem");

enum : int {
  B_FX = 0,
  B_FKV = 16, B_FQ = 24, B_FWO = 32, B_FA = 40, B_FB = 48, B_FT = 56,
  B_EKV = 64, B_EQ = 72, B_EA = 80, B_EB = 88, B_ET0 = 96,
  B_WODONE = 97, B_ET2 = 98,
  B_FIN = 33,
  B_EX = 104,
  B_LAG = 112, B_READY = 113, B_PUB = 114, B_CLR = 115, B_CLR0 = 116, B_TAG = 117
};

__device__ __forceinline__ uint32_t smem_u32(const void* p) { return (uint32_t)__cvta_generic_to_shared(p); }
__device__ __forceinline__ void mbar_init(uint32_t b, uint32_t c) { asm volatile("mbarrier.init.shared::cta.b64 [%0], %1;" ::"r"(b), "r"(c) : "memory"); }
__device__ __forceinline__ void mbar_expect_tx(uint32_t b, uint32_t bytes) { asm volatile("mbarrier.arrive.expect_tx.shared::cta.b64 _, [%0], %1;" ::"r"(b), "r"(bytes) : "memory"); }
__device__ __forceinline__ void mbar_arrive(uint32_t b) { asm volatile("mbarrier.arrive.shared::cta.b64 _, [%0];" ::"r"(b) : "memory"); }
__device__ __forceinline__ void mbar_wait(uint32_t b) {
  asm volatile("{\n.reg .pred p;\n.reg .u32 c;\nmov.u32 c, 0;\nLW:\n.pragma \"nounroll\";\n"
               "mbarrier.try_wait.parity.shared::cta.b64 p, [%0], 0;\nadd.u32 c, c, 1;\nsetp.gt.or.u32 p, c, %1, p;\n@!p bra LW;\n}\n"
               ::"r"(b), "n"(SPIN_LIMIT) : "memory");
}
__device__ __forceinline__ bool elect_one() {
  uint32_t p;
  asm volatile("{\n.reg .pred P;\nelect.sync _|P, 0xffffffff;\nselp.u32 %0, 1, 0, P;\n}\n" : "=r"(p));
  return p;
}
__device__ __forceinline__ void tma2d(uint32_t dst, const CUtensorMap* m, int c0, int c1, uint32_t bar) {
  asm volatile("cp.async.bulk.tensor.2d.shared::cluster.global.mbarrier::complete_tx::bytes [%0], [%1, {%3, %4}], [%2];"
               ::"r"(dst), "l"(m), "r"(bar), "r"(c0), "r"(c1) : "memory");
}
__device__ __forceinline__ void tma3d(uint32_t dst, const CUtensorMap* m, int c0, int c1, int c2, uint32_t bar) {
  asm volatile("cp.async.bulk.tensor.3d.shared::cluster.global.mbarrier::complete_tx::bytes [%0], [%1, {%3, %4, %5}], [%2];"
               ::"r"(dst), "l"(m), "r"(bar), "r"(c0), "r"(c1), "r"(c2) : "memory");
}
__device__ __forceinline__ void tma3d_store(const CUtensorMap* m, uint32_t src, int c0, int c1, int c2) {
  asm volatile("cp.async.bulk.tensor.3d.global.shared::cta.bulk_group [%0, {%2, %3, %4}], [%1];"
               ::"l"(m), "r"(src), "r"(c0), "r"(c1), "r"(c2) : "memory");
}
__device__ __forceinline__ void l2_prefetch(const void* p, uint32_t bytes) {
  asm volatile("cp.async.bulk.prefetch.L2.global [%0], %1;" ::"l"(p), "r"(bytes) : "memory");
}
__device__ __forceinline__ void prefetch_map(const CUtensorMap* m) { asm volatile("prefetch.tensormap [%0];" ::"l"(m) : "memory"); }
__device__ __forceinline__ void fence_async_smem() { asm volatile("fence.proxy.async.shared::cta;" ::: "memory"); }
__device__ __forceinline__ void wg_fence() { asm volatile("wgmma.fence.sync.aligned;" ::: "memory"); }
__device__ __forceinline__ void wg_commit() { asm volatile("wgmma.commit_group.sync.aligned;" ::: "memory"); }
template <int N> __device__ __forceinline__ void wg_wait() { asm volatile("wgmma.wait_group.sync.aligned %0;" ::"n"(N) : "memory"); }
__device__ __forceinline__ void wg_bar(int p) {
  if (p == 0) asm volatile("bar.sync 1, 128;" ::: "memory"); else asm volatile("bar.sync 2, 128;" ::: "memory");
}
constexpr uint32_t DESC_HI128 = (1024 >> 4) | (1u << 30);
constexpr uint32_t DESC_HI64 = (512 >> 4) | (2u << 30);
__device__ __forceinline__ constexpr uint32_t descA(uint32_t addr) { return (addr >> 4) | (1u << 16); }
__device__ __forceinline__ constexpr uint32_t descB(uint32_t addr) { return (addr >> 4) | ((8192u >> 4) << 16); }
__device__ __forceinline__ constexpr uint32_t descBh(uint32_t addr) { return (addr >> 4) | ((4096u >> 4) << 16); }

__device__ __forceinline__ void wgmma_ss_n64(float (&d)[32], uint32_t da, uint32_t db, int sc) {
  asm volatile("{\n.reg .pred p;\n.reg .b64 da, db;\nsetp.ne.b32 p, %34, 0;\nmov.b64 da, {%32, %35};\nmov.b64 db, {%33, %35};\n"
    "wgmma.mma_async.sync.aligned.m64n64k16.f32.bf16.bf16 {%0, %1, %2, %3, %4, %5, %6, %7, %8, %9, %10, %11, %12, %13, %14, %15, %16, %17, %18, %19, %20, %21, %22, %23, %24, %25, %26, %27, %28, %29, %30, %31}, da, db, p, 1, 1, 0, 1;\n}\n"
    : "+f"(d[0]), "+f"(d[1]), "+f"(d[2]), "+f"(d[3]), "+f"(d[4]), "+f"(d[5]), "+f"(d[6]), "+f"(d[7]),
      "+f"(d[8]), "+f"(d[9]), "+f"(d[10]), "+f"(d[11]), "+f"(d[12]), "+f"(d[13]), "+f"(d[14]), "+f"(d[15]),
      "+f"(d[16]), "+f"(d[17]), "+f"(d[18]), "+f"(d[19]), "+f"(d[20]), "+f"(d[21]), "+f"(d[22]), "+f"(d[23]),
      "+f"(d[24]), "+f"(d[25]), "+f"(d[26]), "+f"(d[27]), "+f"(d[28]), "+f"(d[29]), "+f"(d[30]), "+f"(d[31])
    : "r"(da), "r"(db), "r"(sc), "n"(DESC_HI128));
}
__device__ __forceinline__ void wgmma_ss_n128(float (&d)[64], uint32_t da, uint32_t db, int sc) {
  asm volatile("{\n.reg .pred p;\n.reg .b64 da, db;\nsetp.ne.b32 p, %66, 0;\nmov.b64 da, {%64, %67};\nmov.b64 db, {%65, %67};\n"
    "wgmma.mma_async.sync.aligned.m64n128k16.f32.bf16.bf16 {%0, %1, %2, %3, %4, %5, %6, %7, %8, %9, %10, %11, %12, %13, %14, %15, %16, %17, %18, %19, %20, %21, %22, %23, %24, %25, %26, %27, %28, %29, %30, %31, %32, %33, %34, %35, %36, %37, %38, %39, %40, %41, %42, %43, %44, %45, %46, %47, %48, %49, %50, %51, %52, %53, %54, %55, %56, %57, %58, %59, %60, %61, %62, %63}, da, db, p, 1, 1, 0, 1;\n}\n"
    : "+f"(d[0]), "+f"(d[1]), "+f"(d[2]), "+f"(d[3]), "+f"(d[4]), "+f"(d[5]), "+f"(d[6]), "+f"(d[7]),
      "+f"(d[8]), "+f"(d[9]), "+f"(d[10]), "+f"(d[11]), "+f"(d[12]), "+f"(d[13]), "+f"(d[14]), "+f"(d[15]),
      "+f"(d[16]), "+f"(d[17]), "+f"(d[18]), "+f"(d[19]), "+f"(d[20]), "+f"(d[21]), "+f"(d[22]), "+f"(d[23]),
      "+f"(d[24]), "+f"(d[25]), "+f"(d[26]), "+f"(d[27]), "+f"(d[28]), "+f"(d[29]), "+f"(d[30]), "+f"(d[31]),
      "+f"(d[32]), "+f"(d[33]), "+f"(d[34]), "+f"(d[35]), "+f"(d[36]), "+f"(d[37]), "+f"(d[38]), "+f"(d[39]),
      "+f"(d[40]), "+f"(d[41]), "+f"(d[42]), "+f"(d[43]), "+f"(d[44]), "+f"(d[45]), "+f"(d[46]), "+f"(d[47]),
      "+f"(d[48]), "+f"(d[49]), "+f"(d[50]), "+f"(d[51]), "+f"(d[52]), "+f"(d[53]), "+f"(d[54]), "+f"(d[55]),
      "+f"(d[56]), "+f"(d[57]), "+f"(d[58]), "+f"(d[59]), "+f"(d[60]), "+f"(d[61]), "+f"(d[62]), "+f"(d[63])
    : "r"(da), "r"(db), "r"(sc), "n"(DESC_HI128));
}
__device__ __forceinline__ void wgmma_ss_n256(float (&d)[128], uint32_t da, uint32_t db, int sc) {
  asm volatile("{\n.reg .pred p;\n.reg .b64 da, db;\nsetp.ne.b32 p, %130, 0;\nmov.b64 da, {%128, %131};\nmov.b64 db, {%129, %131};\n"
    "wgmma.mma_async.sync.aligned.m64n256k16.f32.bf16.bf16 {%0, %1, %2, %3, %4, %5, %6, %7, %8, %9, %10, %11, %12, %13, %14, %15, %16, %17, %18, %19, %20, %21, %22, %23, %24, %25, %26, %27, %28, %29, %30, %31, %32, %33, %34, %35, %36, %37, %38, %39, %40, %41, %42, %43, %44, %45, %46, %47, %48, %49, %50, %51, %52, %53, %54, %55, %56, %57, %58, %59, %60, %61, %62, %63, %64, %65, %66, %67, %68, %69, %70, %71, %72, %73, %74, %75, %76, %77, %78, %79, %80, %81, %82, %83, %84, %85, %86, %87, %88, %89, %90, %91, %92, %93, %94, %95, %96, %97, %98, %99, %100, %101, %102, %103, %104, %105, %106, %107, %108, %109, %110, %111, %112, %113, %114, %115, %116, %117, %118, %119, %120, %121, %122, %123, %124, %125, %126, %127}, da, db, p, 1, 1, 0, 1;\n}\n"
    : "+f"(d[0]), "+f"(d[1]), "+f"(d[2]), "+f"(d[3]), "+f"(d[4]), "+f"(d[5]), "+f"(d[6]), "+f"(d[7]),
      "+f"(d[8]), "+f"(d[9]), "+f"(d[10]), "+f"(d[11]), "+f"(d[12]), "+f"(d[13]), "+f"(d[14]), "+f"(d[15]),
      "+f"(d[16]), "+f"(d[17]), "+f"(d[18]), "+f"(d[19]), "+f"(d[20]), "+f"(d[21]), "+f"(d[22]), "+f"(d[23]),
      "+f"(d[24]), "+f"(d[25]), "+f"(d[26]), "+f"(d[27]), "+f"(d[28]), "+f"(d[29]), "+f"(d[30]), "+f"(d[31]),
      "+f"(d[32]), "+f"(d[33]), "+f"(d[34]), "+f"(d[35]), "+f"(d[36]), "+f"(d[37]), "+f"(d[38]), "+f"(d[39]),
      "+f"(d[40]), "+f"(d[41]), "+f"(d[42]), "+f"(d[43]), "+f"(d[44]), "+f"(d[45]), "+f"(d[46]), "+f"(d[47]),
      "+f"(d[48]), "+f"(d[49]), "+f"(d[50]), "+f"(d[51]), "+f"(d[52]), "+f"(d[53]), "+f"(d[54]), "+f"(d[55]),
      "+f"(d[56]), "+f"(d[57]), "+f"(d[58]), "+f"(d[59]), "+f"(d[60]), "+f"(d[61]), "+f"(d[62]), "+f"(d[63]),
      "+f"(d[64]), "+f"(d[65]), "+f"(d[66]), "+f"(d[67]), "+f"(d[68]), "+f"(d[69]), "+f"(d[70]), "+f"(d[71]),
      "+f"(d[72]), "+f"(d[73]), "+f"(d[74]), "+f"(d[75]), "+f"(d[76]), "+f"(d[77]), "+f"(d[78]), "+f"(d[79]),
      "+f"(d[80]), "+f"(d[81]), "+f"(d[82]), "+f"(d[83]), "+f"(d[84]), "+f"(d[85]), "+f"(d[86]), "+f"(d[87]),
      "+f"(d[88]), "+f"(d[89]), "+f"(d[90]), "+f"(d[91]), "+f"(d[92]), "+f"(d[93]), "+f"(d[94]), "+f"(d[95]),
      "+f"(d[96]), "+f"(d[97]), "+f"(d[98]), "+f"(d[99]), "+f"(d[100]), "+f"(d[101]), "+f"(d[102]), "+f"(d[103]),
      "+f"(d[104]), "+f"(d[105]), "+f"(d[106]), "+f"(d[107]), "+f"(d[108]), "+f"(d[109]), "+f"(d[110]), "+f"(d[111]),
      "+f"(d[112]), "+f"(d[113]), "+f"(d[114]), "+f"(d[115]), "+f"(d[116]), "+f"(d[117]), "+f"(d[118]), "+f"(d[119]),
      "+f"(d[120]), "+f"(d[121]), "+f"(d[122]), "+f"(d[123]), "+f"(d[124]), "+f"(d[125]), "+f"(d[126]), "+f"(d[127])
    : "r"(da), "r"(db), "r"(sc), "n"(DESC_HI128));
}
template <uint32_t HI = DESC_HI128>
__device__ __forceinline__ void wgmma_rs_n64(float (&d)[32], const uint32_t (&a)[4], uint32_t db, int sc) {
  asm volatile("{\n.reg .pred p;\n.reg .b64 db;\nsetp.ne.b32 p, %37, 0;\nmov.b64 db, {%36, %38};\n"
    "wgmma.mma_async.sync.aligned.m64n64k16.f32.bf16.bf16 {%0, %1, %2, %3, %4, %5, %6, %7, %8, %9, %10, %11, %12, %13, %14, %15, %16, %17, %18, %19, %20, %21, %22, %23, %24, %25, %26, %27, %28, %29, %30, %31}, {%32, %33, %34, %35}, db, p, 1, 1, 1;\n}\n"
    : "+f"(d[0]), "+f"(d[1]), "+f"(d[2]), "+f"(d[3]), "+f"(d[4]), "+f"(d[5]), "+f"(d[6]), "+f"(d[7]),
      "+f"(d[8]), "+f"(d[9]), "+f"(d[10]), "+f"(d[11]), "+f"(d[12]), "+f"(d[13]), "+f"(d[14]), "+f"(d[15]),
      "+f"(d[16]), "+f"(d[17]), "+f"(d[18]), "+f"(d[19]), "+f"(d[20]), "+f"(d[21]), "+f"(d[22]), "+f"(d[23]),
      "+f"(d[24]), "+f"(d[25]), "+f"(d[26]), "+f"(d[27]), "+f"(d[28]), "+f"(d[29]), "+f"(d[30]), "+f"(d[31])
    : "r"(a[0]), "r"(a[1]), "r"(a[2]), "r"(a[3]), "r"(db), "r"(sc), "n"(HI));
}
template <uint32_t HI = DESC_HI128>
__device__ __forceinline__ void wgmma_rs_n128(float (&d)[64], const uint32_t (&a)[4], uint32_t db, int sc) {
  asm volatile("{\n.reg .pred p;\n.reg .b64 db;\nsetp.ne.b32 p, %69, 0;\nmov.b64 db, {%68, %70};\n"
    "wgmma.mma_async.sync.aligned.m64n128k16.f32.bf16.bf16 {%0, %1, %2, %3, %4, %5, %6, %7, %8, %9, %10, %11, %12, %13, %14, %15, %16, %17, %18, %19, %20, %21, %22, %23, %24, %25, %26, %27, %28, %29, %30, %31, %32, %33, %34, %35, %36, %37, %38, %39, %40, %41, %42, %43, %44, %45, %46, %47, %48, %49, %50, %51, %52, %53, %54, %55, %56, %57, %58, %59, %60, %61, %62, %63}, {%64, %65, %66, %67}, db, p, 1, 1, 1;\n}\n"
    : "+f"(d[0]), "+f"(d[1]), "+f"(d[2]), "+f"(d[3]), "+f"(d[4]), "+f"(d[5]), "+f"(d[6]), "+f"(d[7]),
      "+f"(d[8]), "+f"(d[9]), "+f"(d[10]), "+f"(d[11]), "+f"(d[12]), "+f"(d[13]), "+f"(d[14]), "+f"(d[15]),
      "+f"(d[16]), "+f"(d[17]), "+f"(d[18]), "+f"(d[19]), "+f"(d[20]), "+f"(d[21]), "+f"(d[22]), "+f"(d[23]),
      "+f"(d[24]), "+f"(d[25]), "+f"(d[26]), "+f"(d[27]), "+f"(d[28]), "+f"(d[29]), "+f"(d[30]), "+f"(d[31]),
      "+f"(d[32]), "+f"(d[33]), "+f"(d[34]), "+f"(d[35]), "+f"(d[36]), "+f"(d[37]), "+f"(d[38]), "+f"(d[39]),
      "+f"(d[40]), "+f"(d[41]), "+f"(d[42]), "+f"(d[43]), "+f"(d[44]), "+f"(d[45]), "+f"(d[46]), "+f"(d[47]),
      "+f"(d[48]), "+f"(d[49]), "+f"(d[50]), "+f"(d[51]), "+f"(d[52]), "+f"(d[53]), "+f"(d[54]), "+f"(d[55]),
      "+f"(d[56]), "+f"(d[57]), "+f"(d[58]), "+f"(d[59]), "+f"(d[60]), "+f"(d[61]), "+f"(d[62]), "+f"(d[63])
    : "r"(a[0]), "r"(a[1]), "r"(a[2]), "r"(a[3]), "r"(db), "r"(sc), "n"(HI));
}

template <int N> __device__ __forceinline__ void keep(float (&d)[N]) {
#pragma unroll
  for (int i = 0; i < N; i++) asm volatile("" : "+f"(d[i])::"memory");
}

__device__ __forceinline__ void keep(uint32_t (&d)[4]) { asm volatile("" : "+r"(d[0]), "+r"(d[1]), "+r"(d[2]), "+r"(d[3])::"memory"); }
template <int N> __device__ __forceinline__ void keep(uint32_t (&d)[N][4]) {
#pragma unroll
  for (int i = 0; i < N; i++) asm volatile("" : "+r"(d[i][0]), "+r"(d[i][1]), "+r"(d[i][2]), "+r"(d[i][3])::"memory");
}

__device__ __forceinline__ uint32_t pack2(float lo, float hi) {
  uint32_t r;
  asm("cvt.rn.bf16x2.f32 %0, %1, %2;" : "=r"(r) : "f"(hi), "f"(lo));
  return r;
}
__device__ __forceinline__ float bf_lo(uint32_t v) { return __uint_as_float(v << 16); }
__device__ __forceinline__ float bf_hi(uint32_t v) { return __uint_as_float(v & 0xffff0000u); }
__device__ __forceinline__ uint32_t hsub2(uint32_t a, uint32_t b) {
  uint32_t r;
  asm("sub.rn.bf16x2 %0, %1, %2;" : "=r"(r) : "r"(a), "r"(b));
  return r;
}
__device__ __forceinline__ uint32_t movm(uint32_t a) {
  uint32_t r;
  asm volatile("movmatrix.sync.aligned.m8n8.trans.b16 %0, %1;" : "=r"(r) : "r"(a));
  return r;
}
__device__ __forceinline__ void ldsm4(uint32_t (&v)[4], uint32_t a) {
  asm volatile("ldmatrix.sync.aligned.m8n8.x4.shared.b16 {%0,%1,%2,%3}, [%4];" : "=r"(v[0]), "=r"(v[1]), "=r"(v[2]), "=r"(v[3]) : "r"(a) : "memory");
}
__device__ __forceinline__ void stsm4(uint32_t a, const uint32_t (&v)[4]) {
  asm volatile("stmatrix.sync.aligned.m8n8.x4.shared.b16 [%0], {%1,%2,%3,%4};" ::"r"(a), "r"(v[0]), "r"(v[1]), "r"(v[2]), "r"(v[3]) : "memory");
}
__device__ __forceinline__ void mma16816(float (&d)[4], const uint32_t (&a)[4], uint32_t b0, uint32_t b1) {
  asm volatile("mma.sync.aligned.m16n8k16.row.col.f32.bf16.bf16.f32 {%0,%1,%2,%3}, {%4,%5,%6,%7}, {%8,%9}, {%10,%10,%10,%10};"
               : "=f"(d[0]), "=f"(d[1]), "=f"(d[2]), "=f"(d[3])
               : "r"(a[0]), "r"(a[1]), "r"(a[2]), "r"(a[3]), "r"(b0), "r"(b1), "f"(0.f));
}
__device__ __forceinline__ void mma1688_acc(float (&d)[4], uint32_t a0, uint32_t a1, uint32_t b0) {
  asm volatile("mma.sync.aligned.m16n8k8.row.col.f32.bf16.bf16.f32 {%0,%1,%2,%3}, {%4,%5}, {%6}, {%0,%1,%2,%3};"
               : "+f"(d[0]), "+f"(d[1]), "+f"(d[2]), "+f"(d[3]) : "r"(a0), "r"(a1), "r"(b0));
}
__device__ __forceinline__ float ex2(float x) { float y; asm("ex2.approx.ftz.f32 %0, %1;" : "=f"(y) : "f"(x)); return y; }
__device__ __forceinline__ float rcp(float x) { float y; asm("rcp.approx.ftz.f32 %0, %1;" : "=f"(y) : "f"(x)); return y; }
__device__ __forceinline__ float tanhf_hw(float x) { float y; asm("tanh.approx.f32 %0, %1;" : "=f"(y) : "f"(x)); return y; }
__device__ __forceinline__ uint32_t lds32(uint32_t a) { uint32_t v; asm volatile("ld.shared.u32 %0, [%1];" : "=r"(v) : "r"(a) : "memory"); return v; }
__device__ __forceinline__ float2 lds64(uint32_t a) { float2 v; asm volatile("ld.shared.v2.f32 {%0,%1}, [%2];" : "=f"(v.x), "=f"(v.y) : "r"(a) : "memory"); return v; }
__device__ __forceinline__ void lds128(uint32_t (&v)[4], uint32_t a) { asm volatile("ld.shared.v4.u32 {%0,%1,%2,%3}, [%4];" : "=r"(v[0]), "=r"(v[1]), "=r"(v[2]), "=r"(v[3]) : "r"(a) : "memory"); }
__device__ __forceinline__ void sts128(uint32_t a, const uint32_t (&v)[4]) { asm volatile("st.shared.v4.u32 [%0], {%1,%2,%3,%4};" ::"r"(a), "r"(v[0]), "r"(v[1]), "r"(v[2]), "r"(v[3]) : "memory"); }
__device__ __forceinline__ void ldg128_nc(uint32_t (&v)[4], const void* p) {
  asm volatile("ld.global.nc.L1::no_allocate.v4.u32 {%0,%1,%2,%3}, [%4];" : "=r"(v[0]), "=r"(v[1]), "=r"(v[2]), "=r"(v[3]) : "l"(p));
}
__device__ __forceinline__ uint32_t pin(uint32_t v, uint32_t zero) {
  asm volatile("{\n.reg .pred p;\n.reg .u32 c;\nmov.u32 c, %1;\nLP:\n.pragma \"nounroll\";\nsetp.eq.u32 p, c, 0;\n@p bra LD;\n"
               "nanosleep.u32 c;\nadd.u32 %0, %0, c;\nsub.u32 c, c, 1;\nbra LP;\nLD:\n}\n" : "+r"(v) : "r"(zero) : "memory");
  return v;
}
__device__ __forceinline__ void mbar_arrive_if(uint32_t b, bool cond) {
  asm volatile("{\n.reg .pred p;\nsetp.ne.u32 p, %1, 0;\n@p mbarrier.arrive.shared::cta.b64 _, [%0];\n}\n" ::"r"(b), "r"((uint32_t)cond) : "memory");
}
__device__ __forceinline__ uint32_t ld_epoch(const unsigned* p) {
  uint32_t v;
  asm volatile("ld.relaxed.gpu.global.u32 %0, [%1];" : "=r"(v) : "l"(p) : "memory");
  return v;
}
__device__ __forceinline__ void ll_st(uint4* p, uint32_t a, uint32_t b, uint32_t c, uint32_t d, uint32_t tag) {
  asm volatile("st.relaxed.gpu.global.v4.b32 [%0], {%1, %2, %3, %4};" ::"l"(p), "r"((a & ~1u) | tag), "r"(b), "r"(c), "r"(d) : "memory");
}
__device__ __forceinline__ void ll_ld(uint32_t (&v)[4], const uint4* p) {
  asm volatile("{\n.reg .b128 t;\n.reg .b64 lo, hi;\nld.relaxed.gpu.global.b128 t, [%4];\nmov.b128 {lo, hi}, t;\n"
               "mov.b64 {%0, %1}, lo;\nmov.b64 {%2, %3}, hi;\n}\n"
               : "=r"(v[0]), "=r"(v[1]), "=r"(v[2]), "=r"(v[3]) : "l"(p) : "memory");
}
template <int N> __device__ __forceinline__ void ll_issue(uint32_t (&v)[N][4], const uint4* p, int stride) {
#pragma unroll
  for (int i = 0; i < N; i++) ll_ld(v[i], p + i * stride);
}
template <int N> __device__ __forceinline__ uint32_t ll_acc(const uint32_t (&v)[N][4], uint32_t tag, uint32_t acc = 0) {
#pragma unroll
  for (int i = 0; i < N; i++) asm("lop3.b32 %0, %1, %2, %0, 0xBE;" : "+r"(acc) : "r"(v[i][0]), "r"(tag));
  return acc;
}
__device__ __forceinline__ bool ll_any(uint32_t acc) { return __any_sync(0xffffffffu, acc & 1u); }
template <int N> __device__ __forceinline__ bool ll_bad(const uint32_t (&v)[N][4], uint32_t tag) { return ll_any(ll_acc<N>(v, tag)); }
template <int N> __device__ __forceinline__ void ll_clear(uint32_t (&v)[N][4]) {
#pragma unroll
  for (int i = 0; i < N; i++) v[i][0] &= ~1u;
}
template <int N> __device__ __forceinline__ void ll_spin(uint32_t (&v)[N][4], const uint4* p, int stride, uint32_t tag) {
  uint32_t it = 0;
#pragma unroll 1
  do { ll_issue<N>(v, p, stride); } while (ll_bad<N>(v, tag) && ++it < SPIN_LIMIT);
}
template <int N> __device__ __forceinline__ void ll_get(uint32_t (&v)[N][4], const uint4* p, int stride, uint32_t tag) {
  ll_spin<N>(v, p, stride, tag);
  ll_clear<N>(v);
}
template <int N> __device__ __forceinline__ void ll_wait(uint32_t (&v)[N][4], const uint4* p, int stride, uint32_t tag) {
  if (__builtin_expect(ll_bad<N>(v, tag), 0)) ll_spin<N>(v, p, stride, tag);
  ll_clear<N>(v);
}
__device__ __forceinline__ void unpack32(float (&d)[32], const uint32_t (&v)[4][4]) {
#pragma unroll
  for (int u = 0; u < 4; u++)
#pragma unroll
    for (int e = 0; e < 4; e++) { d[8 * u + 2 * e] = bf_lo(v[u][e]); d[8 * u + 2 * e + 1] = bf_hi(v[u][e]); }
}
__device__ __forceinline__ void pack32(uint32_t (&v)[4][4], const float (&d)[32]) {
#pragma unroll
  for (int u = 0; u < 4; u++)
#pragma unroll
    for (int e = 0; e < 4; e++) v[u][e] = pack2(d[8 * u + 2 * e], d[8 * u + 2 * e + 1]);
}
__device__ __forceinline__ uint32_t t_addr(int m) { return SB + ((0x03514620u >> (4 * m)) & 7u) * 32768u; }

__device__ __forceinline__ int kb_at(int i, int j) { return i == 0 ? j : (i - 1 + (i - 1 >= j ? 1 : 0)); }

__device__ __forceinline__ void init_bars(int set) {
  if (set >= 0 && elect_one()) {
    const uint32_t cnt = set < 5 ? 1 : 8;
#pragma unroll
    for (int i = 0; i < 8; i++) mbar_init(BAR + (24 + 8 * set + i) * 8, cnt);
    if (set == 9) {
#pragma unroll
      for (int i = 0; i < 9; i++) mbar_init(BAR + (B_EX + i) * 8, 4);
#pragma unroll
      for (int i = 0; i < 4; i++) mbar_init(BAR + (B_READY + i) * 8, i == 1 ? 7 : 3);
      mbar_init(BAR + B_TAG * 8, 1);
    }
    asm volatile("fence.mbarrier_init.release.cluster;" ::: "memory");
  }
  __syncwarp();
  asm volatile("bar.arrive 4, 384;" ::: "memory");
  asm volatile("bar.sync 3, 384;" ::: "memory");
}

__global__ void __launch_bounds__(384, 1) fused_block_kernel(Scratch* __restrict__ X, const __nv_bfloat16* __restrict__ xp,
                                                             const __nv_bfloat16* __restrict__ wqkvp, const __nv_bfloat16* __restrict__ wop, const uint32_t zero,
                                                             const __grid_constant__ Params P) {
  extern __shared__ __align__(1024) uint8_t smem_raw[];
  if (smem_u32(smem_raw) != SB) return;
  const int tid = threadIdx.x;
  const int warp = __shfl_sync(0xffffffffu, tid >> 5, 0);
  const int lane = tid & 31;
  const int cta = blockIdx.x;
  const int j = (cta >> 6) * 4 + (cta & 3);
  const int g = (cta & 63) >> 2;

  if (warp >= 8) {
    asm volatile("setmaxnreg.dec.sync.aligned.u32 56;");
    if (warp == 8) {
      PSTAMPW(2, 0);
      const bool leader = elect_one();
      if (leader) {
        prefetch_map(&P.x); prefetch_map(&P.wqkv);
#pragma unroll
        for (int i = 0; i < 24; i++) mbar_init(BAR + i * 8, 1);
        asm volatile("fence.mbarrier_init.release.cluster;" ::: "memory");
      }
      __syncwarp();
      asm volatile("bar.arrive 3, 384;" ::: "memory");
      PSTAMPW(2, 20);
      auto ldx = [&](int p, int kb) {
        const uint32_t b = BAR + (B_FX + p * 8 + kb) * 8;
        mbar_expect_tx(b, 8192);
        tma3d(H0 + p * 65536 + kb * 8192, &P.x, kb * 64, p, g * 64, b);
      };
      auto ldkv = [&](int kb, int slot) {
        const uint32_t b = BAR + (B_FKV + kb) * 8, d = RING + slot * 16384;
        mbar_expect_tx(b, 16384);
        tma2d(d, &P.wqkv, 512 + 64 * j, kb * 64, b);
        tma2d(d + 8192, &P.wqkv, 1024 + 64 * j, kb * 64, b);
      };
      if (leader) {
#pragma unroll 1
        for (int i = 0; i < 8 + XO_DELAY; i++) {
          if (i < 8) ldx(0, i);
          if (i < 6) ldkv(i, i);
          if (i >= XO_DELAY) ldx(1, i - XO_DELAY);
          if (i == 0) PSTAMPW(2, 21);
        }
        PSTAMPW(2, 2);
      }
      __syncwarp();
      asm volatile("bar.sync 4, 384;" ::: "memory");
      if (leader) {
        const int f0 = 224 * j + ((j & 1) ? 32 : 0);
        const int fh = 224 * j + ((j & 1) ? 0 : 192);
        prefetch_map(&P.wo); prefetch_map(&P.w1); prefetch_map(&P.w3); prefetch_map(&P.w1h);
        prefetch_map(&P.w3h); prefetch_map(&P.w2); prefetch_map(&P.out);
#pragma unroll 1
        for (int i = 0; i < 2; i++) { mbar_wait(BAR + (B_EKV + i) * 8); ldkv(6 + i, i); }
#pragma unroll 1
        for (int i = 0; i < 8; i++) {
          const uint32_t b = BAR + (B_FQ + i) * 8;
          mbar_wait(BAR + (B_EKV + 2 + (i >> 1)) * 8);
          mbar_expect_tx(b, 8192);
          tma2d(RING + (4 + i) * 8192, &P.wqkv, 64 * j, i * 64, b);
        }
        mbar_expect_tx(BAR + B_FWO * 8, 65536);
#pragma unroll 1
        for (int i = 0; i < 8; i++) {
          const int kb = (i + 1) & 7;
          mbar_wait(BAR + (B_EX + i) * 8);
          tma2d(H0 + kb * 8192, &P.wo, 64 * j, kb * 64, BAR + B_FWO * 8);
          PSTAMPW(2, 4 + i);
        }
#pragma unroll 1
        for (int i = 0; i < 8; i++) {
          const uint32_t b = BAR + (B_FA + i) * 8, d = RING + (i & 3) * 24576;
          const int k0 = kb_at(i, j) * 64;
          mbar_wait(BAR + (B_EKV + 7 + ((0xCBA98520u >> (4 * i)) & 15)) * 8);
          mbar_expect_tx(b, 24576);
          tma2d(d, &P.w1, f0, k0, b);
          tma2d(d + 8192, &P.w3, f0, k0, b);
          tma2d(d + 16384, &P.w1h, fh, k0, b);
          tma2d(d + 20480, &P.w3h, fh, k0, b);
          PSTAMPW(2, 12 + i);
        }
        uint32_t d = RING;
#pragma unroll 1
        for (int i = 0; i < 8; i++) {
          const uint32_t b = BAR + (B_FB + i) * 8;
          const int k0 = kb_at(i, j) * 64;
          mbar_wait(BAR + (B_EA + 5 + i) * 8);
          mbar_expect_tx(b, 32768);
          tma2d(d, &P.w1, f0 + 64, k0, b);
          tma2d(d + 8192, &P.w3, f0 + 64, k0, b);
          tma2d(d + 16384, &P.w1, f0 + 128, k0, b);
          tma2d(d + 24576, &P.w3, f0 + 128, k0, b);
          d = d == RING + 65536 ? RING : d + 32768;
        }
#pragma unroll 1
        for (int m = 0; m < 8; m++) {
          const uint32_t b = BAR + (B_FT + m) * 8;
          mbar_wait(BAR + (B_EB + (m == 7 ? 8 : min(m + 3, 7))) * 8);
          mbar_expect_tx(b, 28672);
          tma2d(t_addr(m), &P.w2, 64 * ((j + 1 + m) & 7), 224 * j, b);
        }
        mbar_expect_tx(BAR + B_FIN * 8, 5 * 16384);
#pragma unroll 1
        for (int q = 0; q < 5; q++) {
          mbar_wait(BAR + (B_ET2 + q) * 8);
          asm volatile("cp.async.bulk.shared::cluster.global.mbarrier::complete_tx::bytes [%0], [%1], 16384, [%2];"
                       ::"r"(t_addr(q + 1)), "l"(X->e4 + ((g * 8 + j) * 8 + ((j - 1 - q) & 7)) * 1024), "r"(BAR + B_FIN * 8) : "memory");
        }
        X->epoch[cta] = X->epoch[cta] + 1;
      }
    } else {
      const int part = warp - 9;
      uint32_t tag;
      if (part == 2) {
        tag = ld_epoch(X->epoch + cta);
        init_bars(-1);
        tag = (tag + 1) & 1;
        if (lane == 0) {
          asm volatile("st.shared.u32 [%0], %1;" ::"r"(TAGS), "r"(tag) : "memory");
          mbar_arrive(BAR + B_TAG * 8);
        }
      } else {
        init_bars(warp - 1);
        mbar_wait(BAR + B_TAG * 8);
        tag = lds32(TAGS);
      }
      PSTAMPW(3, 16 + part);
      const int xw0 = g * 8;
      auto clear8 = [&](uint4* p, int stride) {
#pragma unroll
        for (int i = 0; i < 8; i++) ll_st(p + i * stride + lane, 0, 0, 0, 0, tag ^ 1);
      };
      auto clear_front = [&]() {
#pragma unroll 1
      for (int u = part; u < 8; u += 3) clear8((u < 4 ? X->e2 : X->e3h) + (xw0 * 32 + 4 * j + (u & 3)) * 32, 1024);
      if (part == 2) {
        clear8(X->e1 + (g * 8 + j) * 256, 32);
#pragma unroll
        for (int i = 0; i < 4; i++)
          ll_st((i < 2 ? X->e2s : X->e3s) + ((xw0 + (i & 1) * 4 + (lane >> 3)) * 8 + j) * 8 + (lane & 7), 0, 0, 0, 0, tag ^ 1);
      }
      };
      if (CLR_MODE == 1) clear_front();
      PSTAMPW(3, 20 + part);
      uint32_t v[8][4];
      if (part < 2) {
        float s[4] = {0.f, 0.f, 0.f, 0.f}, q[4] = {0.f, 0.f, 0.f, 0.f}, piv = 0.f;
        const uint32_t xa = H0 + part * 65536 + (8 * j + (lane >> 2)) * 128 + (lane & 3) * 16 + (lane & 4) * 16;
#pragma unroll 1
        for (int kb = 0; kb < 8; kb++) {
          mbar_wait(BAR + (B_FX + part * 8 + kb) * 8);
          lds128(v[0], xa + kb * 8192); lds128(v[1], (xa + kb * 8192) ^ 64);
          if (kb == 0) piv = __shfl_sync(0xffffffffu, bf_lo(v[0][0]), lane & 28);
#pragma unroll
          for (int e = 0; e < 8; e++) {
            const float a = bf_lo(v[e >> 2][e & 3]) - piv, b = bf_hi(v[e >> 2][e & 3]) - piv;
            s[e & 3] += a + b; q[e & 3] = fmaf(a, a, q[e & 3]); q[e & 3] = fmaf(b, b, q[e & 3]);
          }
        }
        float ss = (s[0] + s[1]) + (s[2] + s[3]), qq = (q[0] + q[1]) + (q[2] + q[3]);
#pragma unroll
        for (int o = 1; o <= 2; o <<= 1) { ss += __shfl_xor_sync(0xffffffffu, ss, o); qq += __shfl_xor_sync(0xffffffffu, qq, o); }
        const float dm = ss * (1.f / D_);
        const float rs = rsqrtf(fmaxf(fmaf(-dm, dm, qq * (1.f / D_)), 0.f) + 1e-5f);
        if ((lane & 3) == 0) ll_st(X->e0s + g * 128 + 2 * (8 * j + (lane >> 2)) + part, __float_as_uint(piv + dm), __float_as_uint(rs), 0, 0, tag);
      } else {
        mbar_wait(BAR + (B_FKV + SIDE_KB) * 8);
        const __nv_bfloat16* wr = wop + (size_t)(j * 64 + g * 4 + (lane >> 3)) * D_ + (lane & 7) * 8;
#pragma unroll
        for (int i = 0; i < 8; i++) ldg128_nc(v[i], wr + i * 64);
        float s[4];
#pragma unroll
        for (int e = 0; e < 4; e++) {
          s[e] = 0.f;
#pragma unroll
          for (int i = 0; i < 8; i++) s[e] += bf_lo(v[i][e]) + bf_hi(v[i][e]);
        }
        float ss = (s[0] + s[1]) + (s[2] + s[3]);
#pragma unroll
        for (int o = 1; o <= 4; o <<= 1) ss += __shfl_xor_sync(0xffffffffu, ss, o);
        if ((lane & 7) == 0) ll_st(X->e0w + j * 64 + g * 4 + (lane >> 3), __float_as_uint(ss * (1.f / D_)), 0, 0, 0, tag);
      }
      __syncwarp();
      if (lane == 0) mbar_arrive(BAR + B_PUB * 8);
      PSTAMPW(3, part * 4 + 2);
      mbar_wait(BAR + B_PUB * 8);
      PSTAMPW(3, part * 4 + 0);
      {
        uint32_t u[2][4];
        const uint4* us = (part == 2 ? X->e0w + j * 64 : X->e0s + g * 128 + part * 64) + lane;
        const uint4* vs = X->e0c + ((j * 3 + part) * 16 + (lane >> 4) * 8) * 16 + (lane & 15);
        uint32_t it = 0;
#pragma unroll 1
        do { ll_issue<2>(u, us, 32); ll_issue<8>(v, vs, 16); } while (ll_any(ll_acc<8>(v, tag, ll_acc<2>(u, tag))) && ++it < SPIN_LIMIT);
        ll_clear<2>(u); ll_clear<8>(v);
#pragma unroll
        for (int i = 0; i < 2; i++) {
          if (part == 2) asm volatile("st.shared.u32 [%0], %1;" ::"r"(WB + (i * 32 + lane) * 4), "r"(u[i][0]) : "memory");
          else asm volatile("st.shared.v2.u32 [%0], {%1,%2};" ::"r"(ST + (part * 64 + i * 32 + lane) * 8), "r"(u[i][0]), "r"(u[i][1]) : "memory");
        }
      }
      uint32_t o[4];
#pragma unroll
      for (int e = 0; e < 4; e++) {
        float s = 0.f;
#pragma unroll
        for (int i = 0; i < 8; i++) s += __uint_as_float(v[i][e]);
        o[e] = __float_as_uint(s + __shfl_xor_sync(0xffffffffu, s, 16));
      }
      if (lane < 16) sts128(CS + (part * 64 + lane * 4) * 4, o);
      __syncwarp();
      if (lane == 0) mbar_arrive(BAR + B_READY * 8);
      PSTAMPW(3, part * 4 + 1);
      if (CLR_MODE == 2) clear_front();
      __syncwarp();
      if (lane == 0) mbar_arrive(BAR + B_CLR0 * 8);
      PSTAMPW(3, 24 + part);
      if (lane == 0) l2_prefetch(part == 0 ? P.w1p + (size_t)cta * 4 * F_ : part == 1 ? P.w3p + (size_t)cta * 4 * F_ : P.w2p + (size_t)cta * 14 * D_, 14336);
      mbar_wait(BAR + (B_EA + 1) * 8);
#pragma unroll 1
      for (int u = 4 * E4_FIRST + part; u < 28; u += 3)
        clear8(X->e4 + ((g * 8 + ((j + 1 + (u >> 2)) & 7)) * 8 + j) * 1024 + (u & 3) * 32, 128);
      __syncwarp();
      if (lane == 0) mbar_arrive(BAR + B_CLR * 8);
      PSTAMPW(3, part * 4 + 3);
    }
  } else {
    const int p = warp >> 2, w = warp & 3;
    const int r = lane >> 2, c = lane & 3;
    init_bars(warp);
    asm volatile("setmaxnreg.inc.sync.aligned.u32 224;");
    PSTAMP(0);
    const uint32_t dAx = descA(H0) + p * 4096;
    const uint32_t Hn = H1 - p * 65536;
    const uint32_t moff = ((lane & 7) + ((lane >> 3) & 1) * 8) * 128 + (((lane >> 4) ^ (lane & 7)) << 4);
    const uint32_t Xw = H0 + p * 65536 + w * 2048;
    const int xw = (g * 2 + p) * 4 + w;
    if (p == 1) {
      uint32_t v[8][4];
      mbar_wait(BAR + (B_FKV + SIDE_KB) * 8);
      const int wp = w < 3 ? w : 0;
      const __nv_bfloat16* wr = wqkvp + (size_t)(g * 32 + (lane >> 3) * 8) * (3 * D_) + wp * D_ + j * 64 + (lane & 7) * 8;
#pragma unroll
      for (int i = 0; i < 8; i++) ldg128_nc(v[i], wr + (size_t)i * 3 * D_);
      mbar_wait(BAR + B_TAG * 8);
      const uint32_t tg = lds32(TAGS);
      float cs[8];
#pragma unroll
      for (int e = 0; e < 4; e++) {
        float a = 0.f, b = 0.f;
#pragma unroll
        for (int i = 0; i < 8; i++) { a += bf_lo(v[i][e]); b += bf_hi(v[i][e]); }
        cs[2 * e] = a; cs[2 * e + 1] = b;
      }
      const bool up = lane & 8;
#pragma unroll
      for (int e = 0; e < 4; e++) {
        const float keepv = up ? cs[4 + e] : cs[e], give = up ? cs[e] : cs[4 + e];
        cs[e] = keepv + __shfl_xor_sync(0xffffffffu, give, 8);
        cs[e] += __shfl_xor_sync(0xffffffffu, cs[e], 16);
      }
      if (lane < 16 && w < 3)
        ll_st(X->e0c + ((j * 3 + w) * 16 + g) * 16 + (lane & 7) * 2 + (lane >> 3), __float_as_uint(cs[0]), __float_as_uint(cs[1]),
              __float_as_uint(cs[2]), __float_as_uint(cs[3]), tg);
      __syncwarp();
      mbar_arrive_if(BAR + B_PUB * 8, lane == 0);
      PSTAMP(1);
      mbar_wait(BAR + B_LAG * 8);
    }

    float akv[64];
#pragma unroll 1
    for (int kb = 0; kb < 8; kb++) {
      mbar_wait(BAR + (B_FX + p * 8 + kb) * 8);
      mbar_wait(BAR + (B_FKV + kb) * 8);
      if (kb == 0) PSTAMP(2);
      const uint32_t da = dAx + kb * 512, db = descB(RING) + (kb < 6 ? kb : kb - 6) * 1024;
      wg_fence();
      wgmma_ss_n128(akv, da, db, kb);
#pragma unroll
      for (int k = 1; k < 4; k++) wgmma_ss_n128(akv, da + k * 2, db + k * 128, 1);
      wg_commit();
      mbar_arrive_if(BAR + B_LAG * 8, kb == LAG_KB - 1 && p == 0 && lane == 0);
      wg_wait<1>();
      mbar_arrive_if(BAR + (B_EKV + kb - 1) * 8, kb > 0 && lane == 0);
    }
    uint32_t xres[4][4];
#pragma unroll
    for (int u = 0; u < 4; u++) ldsm4(xres[u], Xw + j * 8192 + (moff ^ (u << 5)));

    float aq[32];
    auto qstep = [&](int kb) {
      mbar_wait(BAR + (B_FQ + kb) * 8);
      const uint32_t da = dAx + kb * 512, db = descB(RING + 32768) + kb * 512;
      wg_fence();
      wgmma_ss_n64(aq, da, db, kb);
#pragma unroll
      for (int k = 1; k < 4; k++) wgmma_ss_n64(aq, da + k * 2, db + k * 128, 1);
      wg_commit();
      wg_wait<1>();
      mbar_arrive_if(BAR + (B_EQ + kb - 1) * 8, lane == 0);
      mbar_arrive_if(BAR + (B_EX + kb - 2) * 8, lane == 0 && p == 0 && kb >= 2);
    };
    qstep(0);
    keep(akv);
    PSTAMP(3);
    qstep(1);
    mbar_wait(BAR + B_READY * 8);
    PSTAMP(19);
    const uint32_t tag = lds32(TAGS);
    uint4* const xb = reinterpret_cast<uint4*>(X) + lane + (tag >> 1);
    constexpr int O_E4 = offsetof(Scratch, e4) / 16, O_E2 = offsetof(Scratch, e2) / 16, O_E3H = offsetof(Scratch, e3h) / 16;
    const float2 st0 = lds64(ST + (2 * (16 * w + r) + p) * 8);
    const float2 st1 = lds64(ST + (2 * (16 * w + r + 8) + p) * 8);
    uint32_t hi[4][4], lo[4][4];
    {
      float2 cs[16];
      auto cvt = [&](uint32_t (&d)[4][4], int b0, int ofs, const float2& st) {
#pragma unroll
        for (int b = b0; b < b0 + 8; b++) {
          if (ofs == 2) cs[b] = lds64(CS + (64 + b * 8 + 2 * c) * 4);
          const uint32_t v = pack2(fmaf(-st.x, cs[b].x, akv[4 * b + ofs]) * st.y, fmaf(-st.x, cs[b].y, akv[4 * b + ofs + 1]) * st.y);
          d[b >> 2][b & 3] = b < 8 ? v : movm(v);
        }
      };
      cvt(hi, 0, 2, st1);
      keep(hi[0]); keep(hi[1]);
      qstep(2);
      cvt(hi, 8, 2, st1);
      mbar_wait(BAR + B_CLR0 * 8);
      if (w == 3 && g < 15) {
        uint4* dst = X->e1 + ((g * 8 + j) * 2 + p) * 128 + lane;
#pragma unroll
        for (int i = 0; i < 4; i++) ll_st(dst + i * 32, hi[i][0], hi[i][1], hi[i][2], hi[i][3], tag);
      }
      PSTAMP(20);
      wg_bar(p);
#pragma unroll
      for (int i = 0; i < 4; i++) sts128(Xw + lane * 16 + i * 512, hi[i]);
      qstep(3);
      cvt(lo, 0, 0, st0);
      keep(lo[0]); keep(lo[1]);
      qstep(4);
      cvt(lo, 8, 0, st0);
    }
    PSTAMP(21);
    wg_bar(p);
    uint32_t prev[4][4];
    if (w > 0) {
#pragma unroll
      for (int i = 0; i < 4; i++) lds128(prev[i], Xw - 2048 + lane * 16 + i * 512);
    }
    if (p == 0) {
      asm volatile("fence.proxy.async.shared::cta;" ::: "memory");
      __syncwarp();
      if (lane == 0) mbar_arrive(BAR + (B_EX + 7) * 8);
    }
    PSTAMP(22);
    const uint4* halo = X->e1 + (((g - 1) * 8 + j) * 2 + p) * 128 + lane;
    const bool use_halo = w == 0 && g > 0;
    qstep(5);
    if (use_halo) ll_issue<4>(prev, halo, 32);
    qstep(6);
    qstep(7);
    PSTAMP(23);
    if (w == 0) {
      if (g > 0) {
        if (__builtin_expect(ll_bad<4>(prev, pin(tag, zero)), 0)) ll_spin<4>(prev, halo, 32, tag);
        ll_clear<4>(prev);
      } else {
#pragma unroll
        for (int i = 0; i < 4; i++)
#pragma unroll
          for (int e = 0; e < 4; e++) prev[i][e] = 0;
      }
    }
    wg_wait<0>();
    keep(aq);
    mbar_arrive_if(BAR + (B_EQ + 7) * 8, lane == 0);
    mbar_arrive_if(BAR + (B_EX + 6) * 8, lane == 0 && p == 0);
    PSTAMP(4);

    uint32_t of[4][4];
    {
      const float sc = 0.25f * 1.4426950408889634f;
      const float nohalo = (g == 0 && w == 0) ? -INFINITY : 0.f;
      const bool up0 = 2 * c > r, up1 = 2 * c + 1 > r;
      const uint32_t mup = (up0 ? 0xffffu : 0u) | (up1 ? 0xffff0000u : 0u);
      uint4* dst = xb + O_E2 + (xw * 32 + 4 * j) * 32;
      float d0 = 0.f, d1 = 0.f;
#pragma unroll 1
      for (int hp = 0; hp < 2; hp++) {
#pragma unroll
        for (int e = 0; e < 4; e++) { of[0][e] = of[2][e]; of[1][e] = of[3][e]; }
#pragma unroll
        for (int h = 0; h < 2; h++) {
          uint32_t qf[4];
          const uint32_t co = (32 * hp + 16 * h + 2 * c) * 4;
          {
            const float2 ca = lds64(CS + co), cb = lds64(CS + co + 32);
            qf[0] = pack2(fmaf(-st0.x, ca.x, aq[8 * h + 0]) * st0.y, fmaf(-st0.x, ca.y, aq[8 * h + 1]) * st0.y);
            qf[1] = pack2(fmaf(-st1.x, ca.x, aq[8 * h + 2]) * st1.y, fmaf(-st1.x, ca.y, aq[8 * h + 3]) * st1.y);
            qf[2] = pack2(fmaf(-st0.x, cb.x, aq[8 * h + 4]) * st0.y, fmaf(-st0.x, cb.y, aq[8 * h + 5]) * st0.y);
            qf[3] = pack2(fmaf(-st1.x, cb.x, aq[8 * h + 6]) * st1.y, fmaf(-st1.x, cb.y, aq[8 * h + 7]) * st1.y);
          }
          const int e0 = 2 * h;
          float sp[4], sl[4], sh[4];
          mma16816(sp, qf, prev[0][e0], prev[0][e0 + 1]);
          mma16816(sl, qf, lo[0][e0], lo[0][e0 + 1]);
          mma16816(sh, qf, hi[0][e0], hi[0][e0 + 1]);
          float a0 = up0 ? sp[0] + nohalo : sl[0], a1 = up1 ? sp[1] + nohalo : sl[1];
          float b0 = up0 ? sl[2] : sh[2], b1 = up1 ? sl[3] : sh[3];
          float ma = fmaxf(a0, a1), mb = fmaxf(b0, b1);
          ma = fmaxf(ma, __shfl_xor_sync(0xffffffffu, ma, 1)); mb = fmaxf(mb, __shfl_xor_sync(0xffffffffu, mb, 1));
          ma = fmaxf(ma, __shfl_xor_sync(0xffffffffu, ma, 2)); mb = fmaxf(mb, __shfl_xor_sync(0xffffffffu, mb, 2));
          a0 = ex2((a0 - ma) * sc); a1 = ex2((a1 - ma) * sc); b0 = ex2((b0 - mb) * sc); b1 = ex2((b1 - mb) * sc);
          float sa = a0 + a1, sbb = b0 + b1;
          sa += __shfl_xor_sync(0xffffffffu, sa, 1); sbb += __shfl_xor_sync(0xffffffffu, sbb, 1);
          sa += __shfl_xor_sync(0xffffffffu, sa, 2); sbb += __shfl_xor_sync(0xffffffffu, sbb, 2);
          const float ia = rcp(sa), ib = rcp(sbb);
          const uint32_t pa = pack2(a0 * ia, a1 * ia), pb = pack2(b0 * ib, b1 * ib);
          const uint32_t pf[4] = {pa & mup, 0u, pa & ~mup, pb & mup};
          const uint32_t ph = pb & ~mup;
          float o0[4], o1[4];
          mma16816(o0, pf, prev[2][e0], lo[2][e0]);
          mma16816(o1, pf, prev[2][e0 + 1], lo[2][e0 + 1]);
          mma1688_acc(o0, 0u, ph, hi[2][e0]);
          mma1688_acc(o1, 0u, ph, hi[2][e0 + 1]);
          of[2 + h][0] = pack2(o0[0], o0[1]); of[2 + h][1] = pack2(o0[2], o0[3]);
          of[2 + h][2] = pack2(o1[0], o1[1]); of[2 + h][3] = pack2(o1[2], o1[3]);
          ll_st(dst + (2 * hp + h) * 32, of[2 + h][0], of[2 + h][1], of[2 + h][2], of[2 + h][3], tag);
          const float2 wa = lds64(WB + co), wb = lds64(WB + co + 32);
          d0 = fmaf(o0[0], wa.x, d0); d0 = fmaf(o0[1], wa.y, d0); d0 = fmaf(o1[0], wb.x, d0); d0 = fmaf(o1[1], wb.y, d0);
          d1 = fmaf(o0[2], wa.x, d1); d1 = fmaf(o0[3], wa.y, d1); d1 = fmaf(o1[2], wb.x, d1); d1 = fmaf(o1[3], wb.y, d1);
        }
#pragma unroll
        for (int e = 0; e < 16; e++) aq[e] = aq[16 + e];
#pragma unroll
        for (int e = 0; e < 4; e++) {
          prev[0][e] = prev[1][e]; prev[2][e] = prev[3][e];
          lo[0][e] = lo[1][e]; lo[2][e] = lo[3][e];
          hi[0][e] = hi[1][e]; hi[2][e] = hi[3][e];
        }
      }
#pragma unroll
      for (int o = 1; o <= 2; o <<= 1) { d0 += __shfl_xor_sync(0xffffffffu, d0, o); d1 += __shfl_xor_sync(0xffffffffu, d1, o); }
      if (c == 0) ll_st(X->e2s + (xw * 8 + j) * 8 + r, __float_as_uint(d0), __float_as_uint(d1), 0, 0, tag);
    }
    PSTAMP(5);

    float ah[32];
    uint32_t sv[2][4];
    unpack32(ah, xres);
    {
      uint32_t og[2][14][4];
      const uint4* osrc[7];
#pragma unroll
      for (int i = 0; i < 7; i++) osrc[i] = xb + O_E2 + (xw * 32 + 4 * kb_at(i + 1, j)) * 32;
      const uint4* ssrc = X->e2s + (xw * 8 + 2 * c) * 8 + r;
      auto oissue = [&](int hp) {
#pragma unroll
        for (int i = 0; i < 14; i++) ll_ld(og[hp][i], osrc[i >> 1] + (2 * hp + (i & 1)) * 32);
        if (hp == 1) ll_issue<2>(sv, ssrc, 8);
      };
      auto omma = [&](int hp) {
        ll_clear<14>(og[hp]);
        keep(og[hp]);
        wg_fence();
#pragma unroll
        for (int i = 0; i < 14; i++) wgmma_rs_n64(ah, og[hp][i], descB(H0) + kb_at((i >> 1) + 1, j) * 512 + (2 * hp + (i & 1)) * 128, 1);
        wg_commit();
      };
      mbar_wait(BAR + B_FWO * 8);
      keep(ah); keep(of);
      wg_fence();
#pragma unroll
      for (int k = 0; k < 4; k++) wgmma_rs_n64(ah, of[k], descB(H0) + j * 512 + k * 128, 1);
      wg_commit();
      uint32_t it = 0;
#pragma unroll 1
      do { oissue(0); } while (ll_bad<14>(og[0], tag) && ++it < SPIN_LIMIT);
      PSTAMP(6);
      oissue(1);
      omma(0);
      const uint32_t tg = pin(tag, zero);
      if (__builtin_expect(ll_any(ll_acc<14>(og[1], tg, ll_acc<2>(sv, tg))), 0)) {
#pragma unroll 1
        do { oissue(1); } while (ll_any(ll_acc<14>(og[1], tag, ll_acc<2>(sv, tag))) && ++it < SPIN_LIMIT);
      }
      PSTAMP(16);
      omma(1);
      ll_clear<2>(sv);
    }
    float m0 = __uint_as_float(sv[0][0]) + __uint_as_float(sv[1][0]), m1 = __uint_as_float(sv[0][1]) + __uint_as_float(sv[1][1]);
#pragma unroll
    for (int o = 1; o <= 2; o <<= 1) { m0 += __shfl_xor_sync(0xffffffffu, m0, o); m1 += __shfl_xor_sync(0xffffffffu, m1, o); }
    const uint32_t mu0 = pack2(m0 + st0.x, m0 + st0.x), mu1 = pack2(m1 + st1.x, m1 + st1.x);
    wg_wait<0>();
    keep(ah);
    if (lane == 0) mbar_arrive(BAR + B_WODONE * 8);
    PSTAMP(7);

    uint32_t hf[4][4], ra[4][4];
    pack32(hf, ah);
    {
      uint4* dst = xb + O_E3H + (xw * 32 + 4 * j) * 32;
#pragma unroll
      for (int u = 0; u < 4; u++) {
        ra[u][0] = hsub2(hf[u][0], mu0); ra[u][1] = hsub2(hf[u][1], mu1);
        ra[u][2] = hsub2(hf[u][2], mu0); ra[u][3] = hsub2(hf[u][3], mu1);
        ll_st(dst + u * 32, ra[u][0], ra[u][1], ra[u][2], ra[u][3], tag);
      }
      float s0 = 0.f, q0 = 0.f, s1 = 0.f, q1 = 0.f;
#pragma unroll
      for (int b = 0; b < 8; b++) {
        s0 += ah[4 * b] + ah[4 * b + 1]; s1 += ah[4 * b + 2] + ah[4 * b + 3];
        q0 = fmaf(ah[4 * b], ah[4 * b], q0); q0 = fmaf(ah[4 * b + 1], ah[4 * b + 1], q0);
        q1 = fmaf(ah[4 * b + 2], ah[4 * b + 2], q1); q1 = fmaf(ah[4 * b + 3], ah[4 * b + 3], q1);
      }
#pragma unroll
      for (int o = 1; o <= 2; o <<= 1) {
        s0 += __shfl_xor_sync(0xffffffffu, s0, o); q0 += __shfl_xor_sync(0xffffffffu, q0, o);
        s1 += __shfl_xor_sync(0xffffffffu, s1, o); q1 += __shfl_xor_sync(0xffffffffu, q1, o);
      }
      if (c == 0) ll_st(X->e3s + (xw * 8 + j) * 8 + r, __float_as_uint(s0), __float_as_uint(q0), __float_as_uint(s1), __float_as_uint(q1), tag);
      mbar_wait(BAR + (p == 0 ? B_EQ + 7 : B_WODONE) * 8);
    }
    PSTAMP(8);

    float rs0, rs1;
    auto swiglu = [&](float g0, float g1, float u0, float u1, float rs) -> uint32_t {
      const float hr = 0.5f * rs;
      const float x0 = g0 * hr, x1 = g1 * hr;
      const float t0 = tanhf_hw(x0), t1 = tanhf_hw(x1);
      return pack2(fmaf(x0, t0, x0) * (u0 * rs), fmaf(x1, t1, x1) * (u1 * rs));
    };
    uint32_t hA[6][4];
    {
      float a1[64], a2[32];
      const uint4* src = xb + O_E3H + xw * 32 * 32;
      uint32_t rb[4][4], rc[4][4], rd[4][4];
      auto fetch = [&](uint32_t (&a)[4][4], int i) { ll_issue<4>(a, src + kb_at(i, j) * 128, 32); };
      auto check = [&](uint32_t (&a)[4][4], uint32_t (&b)[4][4], int i) {
        const uint32_t tg = pin(tag, zero);
        if (__builtin_expect(ll_any(ll_acc<4>(a, tg, ll_acc<4>(b, tg))), 0)) {
          uint32_t it = 0;
#pragma unroll 1
          do { fetch(a, i); fetch(b, i + 1); } while (ll_any(ll_acc<4>(a, tag, ll_acc<4>(b, tag))) && ++it < SPIN_LIMIT);
        }
        ll_clear<4>(a); ll_clear<4>(b);
        keep(a); keep(b);
      };
      auto head = [&](uint32_t (&a)[4][4], int i) {
        mbar_wait(BAR + (B_FA + i) * 8);
        wg_fence();
        wgmma_rs_n64<DESC_HI64>(a2, a[0], descBh(RING + 16384) + (i & 3) * 1536, i);
        wgmma_rs_n128(a1, a[0], descB(RING) + (i & 3) * 1536, i);
        wg_commit();
#pragma unroll
        for (int u = 0; u < 4; u++) stsm4(Hn + w * 2048 + i * 8192 + (moff ^ (u << 5)), a[u]);
        wg_wait<1>();
        if (i > 0) mbar_arrive_if(BAR + (B_EA + i - 1) * 8, lane == 0);
      };
      auto rest = [&](uint32_t (&a)[4][4], int i) {
        wg_fence();
#pragma unroll
        for (int k = 1; k < 4; k++) {
          wgmma_rs_n64<DESC_HI64>(a2, a[k], descBh(RING + 16384) + (i & 3) * 1536 + k * 64, 1);
          wgmma_rs_n128(a1, a[k], descB(RING) + (i & 3) * 1536 + k * 128, 1);
        }
        wg_commit();
      };
      ll_clear<4>(ra);
      keep(ra);
      head(ra, 0); rest(ra, 0);
      ll_get<4>(rb, src + kb_at(1, j) * 128, 32, tag);
      keep(rb);
      PSTAMP(17);
      fetch(rc, 2); fetch(rd, 3);
      head(rb, 1); rest(rb, 1);
      check(rc, rd, 2);
      head(rc, 2); fetch(ra, 4); fetch(rb, 5); rest(rc, 2);
      head(rd, 3); rest(rd, 3);
      check(ra, rb, 4);
      head(ra, 4); fetch(rc, 6); fetch(rd, 7); ll_issue<2>(sv, X->e3s + (xw * 8 + 2 * c) * 8 + r, 8); rest(ra, 4);
      head(rb, 5); rest(rb, 5);
      check(rc, rd, 6);
      head(rc, 6); rest(rc, 6);
      head(rd, 7); rest(rd, 7);
      fence_async_smem();
      ll_wait<2>(sv, X->e3s + (xw * 8 + 2 * c) * 8 + r, 8, tag);
      float s0 = __uint_as_float(sv[0][0]) + __uint_as_float(sv[1][0]), q0 = __uint_as_float(sv[0][1]) + __uint_as_float(sv[1][1]);
      float s1 = __uint_as_float(sv[0][2]) + __uint_as_float(sv[1][2]), q1 = __uint_as_float(sv[0][3]) + __uint_as_float(sv[1][3]);
#pragma unroll
      for (int o = 1; o <= 2; o <<= 1) {
        s0 += __shfl_xor_sync(0xffffffffu, s0, o); q0 += __shfl_xor_sync(0xffffffffu, q0, o);
        s1 += __shfl_xor_sync(0xffffffffu, s1, o); q1 += __shfl_xor_sync(0xffffffffu, q1, o);
      }
      s0 *= 1.f / D_; s1 *= 1.f / D_;
      rs0 = rsqrtf(fmaxf(fmaf(-s0, s0, q0 * (1.f / D_)), 0.f) + 1e-5f);
      rs1 = rsqrtf(fmaxf(fmaf(-s1, s1, q1 * (1.f / D_)), 0.f) + 1e-5f);
      wg_wait<0>();
      keep(a1); keep(a2);
      if (lane == 0) mbar_arrive(BAR + (B_EA + 7) * 8);
      PSTAMP(9);
#pragma unroll
      for (int u = 0; u < 4; u++)
#pragma unroll
        for (int e = 0; e < 4; e++)
          hA[u][e] = swiglu(a1[8 * u + 2 * e], a1[8 * u + 2 * e + 1], a1[32 + 8 * u + 2 * e], a1[33 + 8 * u + 2 * e], (e & 1) ? rs1 : rs0);
#pragma unroll
      for (int u = 0; u < 2; u++)
#pragma unroll
        for (int e = 0; e < 4; e++)
          hA[4 + u][e] = swiglu(a2[8 * u + 2 * e], a2[8 * u + 2 * e + 1], a2[16 + 8 * u + 2 * e], a2[17 + 8 * u + 2 * e], (e & 1) ? rs1 : rs0);
      keep(hA);
      wg_bar(p);
    }
    PSTAMP(10);

    uint32_t hB[8][4];
    {
      float ab[128];
      uint32_t db = descB(RING);
      const uint32_t dAn = descA(H1) - p * 4096;
#pragma unroll 1
      for (int i = 0; i < 8; i++) {
        mbar_wait(BAR + (B_FB + i) * 8);
        const uint32_t da = dAn + i * 512;
        wg_fence();
        wgmma_ss_n256(ab, da, db, i);
#pragma unroll
        for (int k = 1; k < 4; k++) wgmma_ss_n256(ab, da + k * 2, db + k * 128, 1);
        wg_commit();
        wg_wait<1>();
        mbar_arrive_if(BAR + (B_EB + i - 1) * 8, i > 0 && lane == 0);
        db = db == descB(RING + 65536) ? descB(RING) : db + 2048;
      }
      wg_wait<0>();
      keep(ab);
      if (lane == 0) mbar_arrive(BAR + (B_EB + 7) * 8);
      PSTAMP(11);
#pragma unroll
      for (int u = 0; u < 8; u++) {
        const int o = (u >> 2) * 64 + (u & 3) * 8;
#pragma unroll
        for (int e = 0; e < 4; e++)
          hB[u][e] = swiglu(ab[o + 2 * e], ab[o + 2 * e + 1], ab[o + 32 + 2 * e], ab[o + 33 + 2 * e], (e & 1) ? rs1 : rs0);
      }
      keep(hB);
    }
    PSTAMP(12);

    {
      float ya[32], y[32], sum[32];
      const uint32_t offA = (j & 1) ? 256 : 0, offH = (j & 1) ? 0 : 1536;
      uint4* e4 = xb + O_E4 + g * 65536 + warp * 128;
      const uint32_t stg = H0 + p * 65536 + 28672 + (w >> 1) * 32768 + (w & 1) * 2048;
      uint32_t in[4][4], pk[4][4];
      auto insrc = [&](int q) { return e4 + (j * 8 + ((j - 1 - q) & 7)) * 1024; };
      const uint32_t ident = (2 * c == r ? 0x3f80u : 0u) | (2 * c + 1 == r ? 0x3f800000u : 0u);
      auto acc = [&]() {
        ll_clear<4>(in);
#pragma unroll
        for (int u = 0; u < 4; u++) {
          mma1688_acc(*reinterpret_cast<float (*)[4]>(&sum[8 * u]), in[u][0], in[u][1], ident);
          mma1688_acc(*reinterpret_cast<float (*)[4]>(&sum[8 * u + 4]), in[u][2], in[u][3], ident);
        }
      };
      uint32_t T;
      auto mm = [&](float (&d)[32], int k0, int k1) {
        wg_fence();
#pragma unroll
        for (int k = k0; k < k1; k++) {
          if (k < 4) wgmma_rs_n64(d, hA[k], T + offA + k * 128, k);
          else if (k < 6) wgmma_rs_n64(d, hA[k], T + offH + (k - 4) * 128, 1);
          else wgmma_rs_n64(d, hB[k - 6], T + offA + 512 + (k - 6) * 128, 1);
        }
        wg_commit();
      };
      auto start = [&](float (&d)[32], float (&dp)[32], int m) {
        const int mt = min(m, 7);
        mbar_wait(BAR + (B_FT + mt) * 8);
        T = descB(0) + (t_addr(mt) >> 4);
        mm(d, 0, 3);
        wg_wait<1>();
        keep(dp);
        mbar_arrive_if(BAR + (B_ET0 + m - 1) * 8, m != 2 && m < 8 && lane == 0);
        pack32(pk, dp);
      };
      auto rest = [&](float (&d)[32], int m) {
        uint4* dst = e4 + (((j + m) & 7) * 8 + j) * 1024;
#pragma unroll
        for (int u = 0; u < 4; u++) {
          ll_st(dst + u * 32, pk[u][0], pk[u][1], pk[u][2], pk[u][3], u ? pin(tag, zero) : tag);
          mm(d, u ? 4 + 2 * u : 3, u < 3 ? 6 + 2 * u : 14);
        }
      };
      mbar_wait(BAR + B_CLR * 8);
      mbar_wait(BAR + B_FT * 8);
      T = descB(0) + (t_addr(0) >> 4);
      mm(ya, 0, 3);
      unpack32(sum, hf);
      keep(sum);
#pragma unroll
      for (int u = 0; u < 4; u++) { pk[u][0] = 0; pk[u][1] = 0; pk[u][2] = 0; pk[u][3] = 0; }
      wg_wait<0>();
#pragma unroll 1
      for (int m = 0; m < 8; m += 2) {
        rest(ya, m);
        start(y, ya, m + 1);
        rest(y, m + 1);
        start(ya, y, m + 2);
        wg_wait<0>();
        if (m == 0) PSTAMP(27);
        if (m == 2) PSTAMP(26);
        if (m == 4) PSTAMP(28);
      }
      PSTAMP(13);
      mbar_wait(BAR + B_FIN * 8);
      PSTAMP(24);
#pragma unroll 1
      for (int q = 0; q < 7; q++) {
        if (q < 5) {
#pragma unroll
          for (int u = 0; u < 4; u++) lds128(in[u], t_addr(q + 1) + warp * 2048 + lane * 16 + u * 512);
        }
        if (q >= 5 || ll_bad<4>(in, tag)) ll_spin<4>(in, insrc(q), 32, tag);
        acc();
        if (q == 4) PSTAMP(25);
      }
      PSTAMP(14);
#pragma unroll
      for (int u = 0; u < 4; u++) {
        uint32_t o[4];
#pragma unroll
        for (int e = 0; e < 4; e++) o[e] = pack2(sum[8 * u + 2 * e] + y[8 * u + 2 * e], sum[8 * u + 2 * e + 1] + y[8 * u + 2 * e + 1]);
        stsm4(stg + (moff ^ (u << 5)), o);
      }
      fence_async_smem();
      __syncwarp();
      if (elect_one()) {
        tma3d_store(&P.out, stg, 64 * j, p, g * 64 + 16 * w);
        asm volatile("cp.async.bulk.commit_group;" ::: "memory");
        asm volatile("cp.async.bulk.wait_group.read 0;" ::: "memory");
      }
      PSTAMP(15);
    }
  }
}

typedef CUresult (*EncodeFn)(CUtensorMap*, CUtensorMapDataType, cuuint32_t, void*, const cuuint64_t*, const cuuint64_t*,
                             const cuuint32_t*, const cuuint32_t*, CUtensorMapInterleave, CUtensorMapSwizzle,
                             CUtensorMapL2promotion, CUtensorMapFloatOOBfill);

void enc2d(EncodeFn f, CUtensorMap* m, const void* base, uint64_t cols, uint64_t rows, uint32_t bc, uint32_t br, CUtensorMapSwizzle sw) {
  cuuint64_t gd[2] = {cols, rows}, gs[1] = {cols * 2};
  cuuint32_t bd[2] = {bc, br}, es[2] = {1, 1};
  f(m, CU_TENSOR_MAP_DATA_TYPE_BFLOAT16, 2, const_cast<void*>(base), gd, gs, bd, es, CU_TENSOR_MAP_INTERLEAVE_NONE, sw,
    CU_TENSOR_MAP_L2_PROMOTION_L2_128B, CU_TENSOR_MAP_FLOAT_OOB_FILL_NONE);
}
void enc_par(EncodeFn f, CUtensorMap* m, const void* base, uint32_t pairs) {
  cuuint64_t gd[3] = {(cuuint64_t)D_, 2, (cuuint64_t)S_ / 2}, gs[2] = {D_ * 2, D_ * 4};
  cuuint32_t bd[3] = {64, 1, pairs}, es[3] = {1, 1, 1};
  f(m, CU_TENSOR_MAP_DATA_TYPE_BFLOAT16, 3, const_cast<void*>(base), gd, gs, bd, es, CU_TENSOR_MAP_INTERLEAVE_NONE,
    CU_TENSOR_MAP_SWIZZLE_128B, CU_TENSOR_MAP_L2_PROMOTION_L2_128B, CU_TENSOR_MAP_FLOAT_OOB_FILL_NONE);
}

}

extern "C" void kernel_launch(void* const* d_in, const int* in_sizes, int n_in, void* d_out, int out_size) {
  (void)in_sizes; (void)n_in; (void)out_size;
  static EncodeFn enc = nullptr;
  static Scratch* scratch = nullptr;
  if (!enc) {
    void* fn = nullptr;
    cudaDriverEntryPointQueryResult q;
    cudaGetDriverEntryPoint("cuTensorMapEncodeTiled", &fn, cudaEnableDefault, &q);
    enc = (EncodeFn)fn;
    cudaGetSymbolAddress((void**)&scratch, g_scratch);
    cudaFuncSetAttribute(fused_block_kernel, cudaFuncAttributeMaxDynamicSharedMemorySize, SMEM_BYTES);
  }
  Params P;
  const __nv_bfloat16* xp = (const __nv_bfloat16*)d_in[0];
  const __nv_bfloat16* wqkvp = (const __nv_bfloat16*)d_in[1];
  const __nv_bfloat16* wop = (const __nv_bfloat16*)d_in[2];
  P.w1p = (const __nv_bfloat16*)d_in[4];
  P.w3p = (const __nv_bfloat16*)d_in[5];
  P.w2p = (const __nv_bfloat16*)d_in[6];
  enc_par(enc, &P.x, xp, 64);
  enc_par(enc, &P.out, d_out, 16);
  enc2d(enc, &P.wqkv, wqkvp, 3 * D_, D_, 64, 64, CU_TENSOR_MAP_SWIZZLE_128B);
  enc2d(enc, &P.wo, wop, D_, D_, 64, 64, CU_TENSOR_MAP_SWIZZLE_128B);
  enc2d(enc, &P.w1, P.w1p, F_, D_, 64, 64, CU_TENSOR_MAP_SWIZZLE_128B);
  enc2d(enc, &P.w3, P.w3p, F_, D_, 64, 64, CU_TENSOR_MAP_SWIZZLE_128B);
  enc2d(enc, &P.w1h, P.w1p, F_, D_, 32, 64, CU_TENSOR_MAP_SWIZZLE_64B);
  enc2d(enc, &P.w3h, P.w3p, F_, D_, 32, 64, CU_TENSOR_MAP_SWIZZLE_64B);
  enc2d(enc, &P.w2, P.w2p, D_, F_, 64, 224, CU_TENSOR_MAP_SWIZZLE_128B);

  cudaLaunchConfig_t cfg = {};
  cfg.gridDim = dim3(128);
  cfg.blockDim = dim3(384);
  cfg.dynamicSmemBytes = SMEM_BYTES;
  cfg.stream = cudaStreamPerThread;
  cudaLaunchAttribute at[1];
  at[0].id = cudaLaunchAttributeCooperative;
  at[0].val.cooperative = 1;
  cfg.attrs = at;
  cfg.numAttrs = 1;
  cudaLaunchKernelEx(&cfg, fused_block_kernel, scratch, xp, wqkvp, wop, 0u, P);
}
```

```cpp
#include <cuda_runtime.h>
#include <cuda.h>
#include <cuda_bf16.h>
#include <stdint.h>
#include <stddef.h>

namespace {

constexpr int S_ = 2048, D_ = 512, F_ = 1792;
#define LAG_KB 3
#define E4_FIRST 7
#define PP_AHEAD 1
#define SIDE_KB 0
#define CLR_MODE 0
#define W2_HEAD 3
#define CLR_SLEEP 400
#define XO_DELAY 2

constexpr uint32_t SPIN_LIMIT = 1u << 18;

struct Scratch {
  uint4 e4[16 * 2 * 4 * 8 * 8 * 4 * 32];
  uint4 e2[16 * 2 * 4 * 32 * 32];
  uint4 e3h[16 * 2 * 4 * 32 * 32];
  uint4 e1[16 * 8 * 2 * 4 * 32];
  uint4 e2s[16 * 2 * 4 * 8 * 8];
  uint4 e3s[16 * 2 * 4 * 8 * 8];
  uint4 e0c[8 * 3 * 16 * 16];
  uint4 e0s[2048];
  uint4 e0w[8 * 64];
  unsigned epoch[128];
};
__device__ Scratch g_scratch;
#define PSTAMP(i)
#define PSTAMPW(slot, i)
#define W2STAMP(i)

struct alignas(64) Params {
  CUtensorMap x, out, wqkv, wo, w1, w3, w1h, w3h, w2;
  const __nv_bfloat16 *w1p, *w3p, *w2p;
};

constexpr uint32_t SB = 1024;
constexpr uint32_t H0 = SB;
constexpr uint32_t H1 = SB + 65536;
constexpr uint32_t RING = SB + 131072;
constexpr uint32_t BAR = SB + 229376;
constexpr uint32_t TAGS = BAR + 1016;
constexpr uint32_t CS = BAR + 1024;
constexpr uint32_t ST = CS + 768;
constexpr uint32_t WB = ST + 1024;
constexpr uint32_t SMEM_BYTES = 232448;
static_assert(WB + 256 <= SB + SMEM_BYTES, "smem");

enum : int {
  B_FX = 0,
  B_FKV = 16, B_FQ = 24, B_FWO = 32, B_FA = 40, B_FB = 48, B_FT = 56,
  B_EKV = 64, B_EQ = 72, B_EA = 80, B_EB = 88, B_ET0 = 96,
  B_WODONE = 97, B_ET2 = 98,
  B_FIN = 33,
  B_EX = 104,
  B_LAG = 112, B_READY = 113, B_PUB = 114, B_CLR = 115, B_CLR0 = 116, B_TAG = 117,
  B_OE = 118, B_OF = 120
};

__device__ __forceinline__ uint32_t smem_u32(const void* p) { return (uint32_t)__cvta_generic_to_shared(p); }
__device__ __forceinline__ void mbar_init(uint32_t b, uint32_t c) { asm volatile("mbarrier.init.shared::cta.b64 [%0], %1;" ::"r"(b), "r"(c) : "memory"); }
__device__ __forceinline__ void mbar_expect_tx(uint32_t b, uint32_t bytes) { asm volatile("mbarrier.arrive.expect_tx.shared::cta.b64 _, [%0], %1;" ::"r"(b), "r"(bytes) : "memory"); }
__device__ __forceinline__ void mbar_arrive(uint32_t b) { asm volatile("mbarrier.arrive.shared::cta.b64 _, [%0];" ::"r"(b) : "memory"); }
__device__ __forceinline__ void mbar_wait(uint32_t b) {
  asm volatile("{\n.reg .pred p;\n.reg .u32 c;\nmov.u32 c, 0;\nLW:\n.pragma \"nounroll\";\n"
               "mbarrier.try_wait.parity.shared::cta.b64 p, [%0], 0;\nadd.u32 c, c, 1;\nsetp.gt.or.u32 p, c, %1, p;\n@!p bra LW;\n}\n"
               ::"r"(b), "n"(SPIN_LIMIT) : "memory");
}
__device__ __forceinline__ void mbar_wait_par(uint32_t b, uint32_t parity) {
  asm volatile("{\n.reg .pred p;\n.reg .u32 c;\nmov.u32 c, 0;\nLW:\n.pragma \"nounroll\";\n"
               "mbarrier.try_wait.parity.shared::cta.b64 p, [%0], %2;\nadd.u32 c, c, 1;\nsetp.gt.or.u32 p, c, %1, p;\n@!p bra LW;\n}\n"
               ::"r"(b), "n"(SPIN_LIMIT), "r"(parity) : "memory");
}
__device__ __forceinline__ bool elect_one() {
  uint32_t p;
  asm volatile("{\n.reg .pred P;\nelect.sync _|P, 0xffffffff;\nselp.u32 %0, 1, 0, P;\n}\n" : "=r"(p));
  return p;
}
__device__ __forceinline__ void tma2d(uint32_t dst, const CUtensorMap* m, int c0, int c1, uint32_t bar) {
  asm volatile("cp.async.bulk.tensor.2d.shared::cluster.global.mbarrier::complete_tx::bytes [%0], [%1, {%3, %4}], [%2];"
               ::"r"(dst), "l"(m), "r"(bar), "r"(c0), "r"(c1) : "memory");
}
__device__ __forceinline__ void tma3d(uint32_t dst, const CUtensorMap* m, int c0, int c1, int c2, uint32_t bar) {
  asm volatile("cp.async.bulk.tensor.3d.shared::cluster.global.mbarrier::complete_tx::bytes [%0], [%1, {%3, %4, %5}], [%2];"
               ::"r"(dst), "l"(m), "r"(bar), "r"(c0), "r"(c1), "r"(c2) : "memory");
}
__device__ __forceinline__ void tma3d_store(const CUtensorMap* m, uint32_t src, int c0, int c1, int c2) {
  asm volatile("cp.async.bulk.tensor.3d.global.shared::cta.bulk_group [%0, {%2, %3, %4}], [%1];"
               ::"l"(m), "r"(src), "r"(c0), "r"(c1), "r"(c2) : "memory");
}
__device__ __forceinline__ void l2_prefetch(const void* p, uint32_t bytes) {
  asm volatile("cp.async.bulk.prefetch.L2.global [%0], %1;" ::"l"(p), "r"(bytes) : "memory");
}
__device__ __forceinline__ void prefetch_map(const CUtensorMap* m) { asm volatile("prefetch.tensormap [%0];" ::"l"(m) : "memory"); }
__device__ __forceinline__ void fence_async_smem() { asm volatile("fence.proxy.async.shared::cta;" ::: "memory"); }
__device__ __forceinline__ void wg_fence() { asm volatile("wgmma.fence.sync.aligned;" ::: "memory"); }
__device__ __forceinline__ void wg_commit() { asm volatile("wgmma.commit_group.sync.aligned;" ::: "memory"); }
template <int N> __device__ __forceinline__ void wg_wait() { asm volatile("wgmma.wait_group.sync.aligned %0;" ::"n"(N) : "memory"); }
__device__ __forceinline__ void wg_bar(int p) {
  if (p == 0) asm volatile("bar.sync 1, 128;" ::: "memory"); else asm volatile("bar.sync 2, 128;" ::: "memory");
}
constexpr uint32_t DESC_HI128 = (1024 >> 4) | (1u << 30);
constexpr uint32_t DESC_HI64 = (512 >> 4) | (2u << 30);
__device__ __forceinline__ constexpr uint32_t descA(uint32_t addr) { return (addr >> 4) | (1u << 16); }
__device__ __forceinline__ constexpr uint32_t descB(uint32_t addr) { return (addr >> 4) | ((8192u >> 4) << 16); }
__device__ __forceinline__ constexpr uint32_t descBh(uint32_t addr) { return (addr >> 4) | ((4096u >> 4) << 16); }

__device__ __forceinline__ void wgmma_ss_n64(float (&d)[32], uint32_t da, uint32_t db, int sc) {
  asm volatile("{\n.reg .pred p;\n.reg .b64 da, db;\nsetp.ne.b32 p, %34, 0;\nmov.b64 da, {%32, %35};\nmov.b64 db, {%33, %35};\n"
    "wgmma.mma_async.sync.aligned.m64n64k16.f32.bf16.bf16 {%0, %1, %2, %3, %4, %5, %6, %7, %8, %9, %10, %11, %12, %13, %14, %15, %16, %17, %18, %19, %20, %21, %22, %23, %24, %25, %26, %27, %28, %29, %30, %31}, da, db, p, 1, 1, 0, 1;\n}\n"
    : "+f"(d[0]), "+f"(d[1]), "+f"(d[2]), "+f"(d[3]), "+f"(d[4]), "+f"(d[5]), "+f"(d[6]), "+f"(d[7]),
      "+f"(d[8]), "+f"(d[9]), "+f"(d[10]), "+f"(d[11]), "+f"(d[12]), "+f"(d[13]), "+f"(d[14]), "+f"(d[15]),
      "+f"(d[16]), "+f"(d[17]), "+f"(d[18]), "+f"(d[19]), "+f"(d[20]), "+f"(d[21]), "+f"(d[22]), "+f"(d[23]),
      "+f"(d[24]), "+f"(d[25]), "+f"(d[26]), "+f"(d[27]), "+f"(d[28]), "+f"(d[29]), "+f"(d[30]), "+f"(d[31])
    : "r"(da), "r"(db), "r"(sc), "n"(DESC_HI128));
}
__device__ __forceinline__ void wgmma_ss_n128(float (&d)[64], uint32_t da, uint32_t db, int sc) {
  asm volatile("{\n.reg .pred p;\n.reg .b64 da, db;\nsetp.ne.b32 p, %66, 0;\nmov.b64 da, {%64, %67};\nmov.b64 db, {%65, %67};\n"
    "wgmma.mma_async.sync.aligned.m64n128k16.f32.bf16.bf16 {%0, %1, %2, %3, %4, %5, %6, %7, %8, %9, %10, %11, %12, %13, %14, %15, %16, %17, %18, %19, %20, %21, %22, %23, %24, %25, %26, %27, %28, %29, %30, %31, %32, %33, %34, %35, %36, %37, %38, %39, %40, %41, %42, %43, %44, %45, %46, %47, %48, %49, %50, %51, %52, %53, %54, %55, %56, %57, %58, %59, %60, %61, %62, %63}, da, db, p, 1, 1, 0, 1;\n}\n"
    : "+f"(d[0]), "+f"(d[1]), "+f"(d[2]), "+f"(d[3]), "+f"(d[4]), "+f"(d[5]), "+f"(d[6]), "+f"(d[7]),
      "+f"(d[8]), "+f"(d[9]), "+f"(d[10]), "+f"(d[11]), "+f"(d[12]), "+f"(d[13]), "+f"(d[14]), "+f"(d[15]),
      "+f"(d[16]), "+f"(d[17]), "+f"(d[18]), "+f"(d[19]), "+f"(d[20]), "+f"(d[21]), "+f"(d[22]), "+f"(d[23]),
      "+f"(d[24]), "+f"(d[25]), "+f"(d[26]), "+f"(d[27]), "+f"(d[28]), "+f"(d[29]), "+f"(d[30]), "+f"(d[31]),
      "+f"(d[32]), "+f"(d[33]), "+f"(d[34]), "+f"(d[35]), "+f"(d[36]), "+f"(d[37]), "+f"(d[38]), "+f"(d[39]),
      "+f"(d[40]), "+f"(d[41]), "+f"(d[42]), "+f"(d[43]), "+f"(d[44]), "+f"(d[45]), "+f"(d[46]), "+f"(d[47]),
      "+f"(d[48]), "+f"(d[49]), "+f"(d[50]), "+f"(d[51]), "+f"(d[52]), "+f"(d[53]), "+f"(d[54]), "+f"(d[55]),
      "+f"(d[56]), "+f"(d[57]), "+f"(d[58]), "+f"(d[59]), "+f"(d[60]), "+f"(d[61]), "+f"(d[62]), "+f"(d[63])
    : "r"(da), "r"(db), "r"(sc), "n"(DESC_HI128));
}
__device__ __forceinline__ void wgmma_ss_n256(float (&d)[128], uint32_t da, uint32_t db, int sc) {
  asm volatile("{\n.reg .pred p;\n.reg .b64 da, db;\nsetp.ne.b32 p, %130, 0;\nmov.b64 da, {%128, %131};\nmov.b64 db, {%129, %131};\n"
    "wgmma.mma_async.sync.aligned.m64n256k16.f32.bf16.bf16 {%0, %1, %2, %3, %4, %5, %6, %7, %8, %9, %10, %11, %12, %13, %14, %15, %16, %17, %18, %19, %20, %21, %22, %23, %24, %25, %26, %27, %28, %29, %30, %31, %32, %33, %34, %35, %36, %37, %38, %39, %40, %41, %42, %43, %44, %45, %46, %47, %48, %49, %50, %51, %52, %53, %54, %55, %56, %57, %58, %59, %60, %61, %62, %63, %64, %65, %66, %67, %68, %69, %70, %71, %72, %73, %74, %75, %76, %77, %78, %79, %80, %81, %82, %83, %84, %85, %86, %87, %88, %89, %90, %91, %92, %93, %94, %95, %96, %97, %98, %99, %100, %101, %102, %103, %104, %105, %106, %107, %108, %109, %110, %111, %112, %113, %114, %115, %116, %117, %118, %119, %120, %121, %122, %123, %124, %125, %126, %127}, da, db, p, 1, 1, 0, 1;\n}\n"
    : "+f"(d[0]), "+f"(d[1]), "+f"(d[2]), "+f"(d[3]), "+f"(d[4]), "+f"(d[5]), "+f"(d[6]), "+f"(d[7]),
      "+f"(d[8]), "+f"(d[9]), "+f"(d[10]), "+f"(d[11]), "+f"(d[12]), "+f"(d[13]), "+f"(d[14]), "+f"(d[15]),
      "+f"(d[16]), "+f"(d[17]), "+f"(d[18]), "+f"(d[19]), "+f"(d[20]), "+f"(d[21]), "+f"(d[22]), "+f"(d[23]),
      "+f"(d[24]), "+f"(d[25]), "+f"(d[26]), "+f"(d[27]), "+f"(d[28]), "+f"(d[29]), "+f"(d[30]), "+f"(d[31]),
      "+f"(d[32]), "+f"(d[33]), "+f"(d[34]), "+f"(d[35]), "+f"(d[36]), "+f"(d[37]), "+f"(d[38]), "+f"(d[39]),
      "+f"(d[40]), "+f"(d[41]), "+f"(d[42]), "+f"(d[43]), "+f"(d[44]), "+f"(d[45]), "+f"(d[46]), "+f"(d[47]),
      "+f"(d[48]), "+f"(d[49]), "+f"(d[50]), "+f"(d[51]), "+f"(d[52]), "+f"(d[53]), "+f"(d[54]), "+f"(d[55]),
      "+f"(d[56]), "+f"(d[57]), "+f"(d[58]), "+f"(d[59]), "+f"(d[60]), "+f"(d[61]), "+f"(d[62]), "+f"(d[63]),
      "+f"(d[64]), "+f"(d[65]), "+f"(d[66]), "+f"(d[67]), "+f"(d[68]), "+f"(d[69]), "+f"(d[70]), "+f"(d[71]),
      "+f"(d[72]), "+f"(d[73]), "+f"(d[74]), "+f"(d[75]), "+f"(d[76]), "+f"(d[77]), "+f"(d[78]), "+f"(d[79]),
      "+f"(d[80]), "+f"(d[81]), "+f"(d[82]), "+f"(d[83]), "+f"(d[84]), "+f"(d[85]), "+f"(d[86]), "+f"(d[87]),
      "+f"(d[88]), "+f"(d[89]), "+f"(d[90]), "+f"(d[91]), "+f"(d[92]), "+f"(d[93]), "+f"(d[94]), "+f"(d[95]),
      "+f"(d[96]), "+f"(d[97]), "+f"(d[98]), "+f"(d[99]), "+f"(d[100]), "+f"(d[101]), "+f"(d[102]), "+f"(d[103]),
      "+f"(d[104]), "+f"(d[105]), "+f"(d[106]), "+f"(d[107]), "+f"(d[108]), "+f"(d[109]), "+f"(d[110]), "+f"(d[111]),
      "+f"(d[112]), "+f"(d[113]), "+f"(d[114]), "+f"(d[115]), "+f"(d[116]), "+f"(d[117]), "+f"(d[118]), "+f"(d[119]),
      "+f"(d[120]), "+f"(d[121]), "+f"(d[122]), "+f"(d[123]), "+f"(d[124]), "+f"(d[125]), "+f"(d[126]), "+f"(d[127])
    : "r"(da), "r"(db), "r"(sc), "n"(DESC_HI128));
}
template <uint32_t HI = DESC_HI128>
__device__ __forceinline__ void wgmma_rs_n64(float (&d)[32], const uint32_t (&a)[4], uint32_t db, int sc) {
  asm volatile("{\n.reg .pred p;\n.reg .b64 db;\nsetp.ne.b32 p, %37, 0;\nmov.b64 db, {%36, %38};\n"
    "wgmma.mma_async.sync.aligned.m64n64k16.f32.bf16.bf16 {%0, %1, %2, %3, %4, %5, %6, %7, %8, %9, %10, %11, %12, %13, %14, %15, %16, %17, %18, %19, %20, %21, %22, %23, %24, %25, %26, %27, %28, %29, %30, %31}, {%32, %33, %34, %35}, db, p, 1, 1, 1;\n}\n"
    : "+f"(d[0]), "+f"(d[1]), "+f"(d[2]), "+f"(d[3]), "+f"(d[4]), "+f"(d[5]), "+f"(d[6]), "+f"(d[7]),
      "+f"(d[8]), "+f"(d[9]), "+f"(d[10]), "+f"(d[11]), "+f"(d[12]), "+f"(d[13]), "+f"(d[14]), "+f"(d[15]),
      "+f"(d[16]), "+f"(d[17]), "+f"(d[18]), "+f"(d[19]), "+f"(d[20]), "+f"(d[21]), "+f"(d[22]), "+f"(d[23]),
      "+f"(d[24]), "+f"(d[25]), "+f"(d[26]), "+f"(d[27]), "+f"(d[28]), "+f"(d[29]), "+f"(d[30]), "+f"(d[31])
    : "r"(a[0]), "r"(a[1]), "r"(a[2]), "r"(a[3]), "r"(db), "r"(sc), "n"(HI));
}
template <uint32_t HI = DESC_HI128>
__device__ __forceinline__ void wgmma_rs_n128(float (&d)[64], const uint32_t (&a)[4], uint32_t db, int sc) {
  asm volatile("{\n.reg .pred p;\n.reg .b64 db;\nsetp.ne.b32 p, %69, 0;\nmov.b64 db, {%68, %70};\n"
    "wgmma.mma_async.sync.aligned.m64n128k16.f32.bf16.bf16 {%0, %1, %2, %3, %4, %5, %6, %7, %8, %9, %10, %11, %12, %13, %14, %15, %16, %17, %18, %19, %20, %21, %22, %23, %24, %25, %26, %27, %28, %29, %30, %31, %32, %33, %34, %35, %36, %37, %38, %39, %40, %41, %42, %43, %44, %45, %46, %47, %48, %49, %50, %51, %52, %53, %54, %55, %56, %57, %58, %59, %60, %61, %62, %63}, {%64, %65, %66, %67}, db, p, 1, 1, 1;\n}\n"
    : "+f"(d[0]), "+f"(d[1]), "+f"(d[2]), "+f"(d[3]), "+f"(d[4]), "+f"(d[5]), "+f"(d[6]), "+f"(d[7]),
      "+f"(d[8]), "+f"(d[9]), "+f"(d[10]), "+f"(d[11]), "+f"(d[12]), "+f"(d[13]), "+f"(d[14]), "+f"(d[15]),
      "+f"(d[16]), "+f"(d[17]), "+f"(d[18]), "+f"(d[19]), "+f"(d[20]), "+f"(d[21]), "+f"(d[22]), "+f"(d[23]),
      "+f"(d[24]), "+f"(d[25]), "+f"(d[26]), "+f"(d[27]), "+f"(d[28]), "+f"(d[29]), "+f"(d[30]), "+f"(d[31]),
      "+f"(d[32]), "+f"(d[33]), "+f"(d[34]), "+f"(d[35]), "+f"(d[36]), "+f"(d[37]), "+f"(d[38]), "+f"(d[39]),
      "+f"(d[40]), "+f"(d[41]), "+f"(d[42]), "+f"(d[43]), "+f"(d[44]), "+f"(d[45]), "+f"(d[46]), "+f"(d[47]),
      "+f"(d[48]), "+f"(d[49]), "+f"(d[50]), "+f"(d[51]), "+f"(d[52]), "+f"(d[53]), "+f"(d[54]), "+f"(d[55]),
      "+f"(d[56]), "+f"(d[57]), "+f"(d[58]), "+f"(d[59]), "+f"(d[60]), "+f"(d[61]), "+f"(d[62]), "+f"(d[63])
    : "r"(a[0]), "r"(a[1]), "r"(a[2]), "r"(a[3]), "r"(db), "r"(sc), "n"(HI));
}

template <int N> __device__ __forceinline__ void keep(float (&d)[N]) {
#pragma unroll
  for (int i = 0; i < N; i++) asm volatile("" : "+f"(d[i])::"memory");
}

__device__ __forceinline__ void keep(uint32_t (&d)[4]) { asm volatile("" : "+r"(d[0]), "+r"(d[1]), "+r"(d[2]), "+r"(d[3])::"memory"); }
template <int N> __device__ __forceinline__ void keep(uint32_t (&d)[N][4]) {
#pragma unroll
  for (int i = 0; i < N; i++) asm volatile("" : "+r"(d[i][0]), "+r"(d[i][1]), "+r"(d[i][2]), "+r"(d[i][3])::"memory");
}

__device__ __forceinline__ uint32_t pack2(float lo, float hi) {
  uint32_t r;
  asm("cvt.rn.bf16x2.f32 %0, %1, %2;" : "=r"(r) : "f"(hi), "f"(lo));
  return r;
}
__device__ __forceinline__ float bf_lo(uint32_t v) { return __uint_as_float(v << 16); }
__device__ __forceinline__ float bf_hi(uint32_t v) { return __uint_as_float(v & 0xffff0000u); }
__device__ __forceinline__ uint32_t hsub2(uint32_t a, uint32_t b) {
  uint32_t r;
  asm("sub.rn.bf16x2 %0, %1, %2;" : "=r"(r) : "r"(a), "r"(b));
  return r;
}
__device__ __forceinline__ uint32_t movm(uint32_t a) {
  uint32_t r;
  asm volatile("movmatrix.sync.aligned.m8n8.trans.b16 %0, %1;" : "=r"(r) : "r"(a));
  return r;
}
__device__ __forceinline__ void ldsm4(uint32_t (&v)[4], uint32_t a) {
  asm volatile("ldmatrix.sync.aligned.m8n8.x4.shared.b16 {%0,%1,%2,%3}, [%4];" : "=r"(v[0]), "=r"(v[1]), "=r"(v[2]), "=r"(v[3]) : "r"(a) : "memory");
}
__device__ __forceinline__ void stsm4(uint32_t a, const uint32_t (&v)[4]) {
  asm volatile("stmatrix.sync.aligned.m8n8.x4.shared.b16 [%0], {%1,%2,%3,%4};" ::"r"(a), "r"(v[0]), "r"(v[1]), "r"(v[2]), "r"(v[3]) : "memory");
}
__device__ __forceinline__ void mma16816(float (&d)[4], const uint32_t (&a)[4], uint32_t b0, uint32_t b1) {
  asm volatile("mma.sync.aligned.m16n8k16.row.col.f32.bf16.bf16.f32 {%0,%1,%2,%3}, {%4,%5,%6,%7}, {%8,%9}, {%10,%10,%10,%10};"
               : "=f"(d[0]), "=f"(d[1]), "=f"(d[2]), "=f"(d[3])
               : "r"(a[0]), "r"(a[1]), "r"(a[2]), "r"(a[3]), "r"(b0), "r"(b1), "f"(0.f));
}
__device__ __forceinline__ void mma1688_acc(float (&d)[4], uint32_t a0, uint32_t a1, uint32_t b0) {
  asm volatile("mma.sync.aligned.m16n8k8.row.col.f32.bf16.bf16.f32 {%0,%1,%2,%3}, {%4,%5}, {%6}, {%0,%1,%2,%3};"
               : "+f"(d[0]), "+f"(d[1]), "+f"(d[2]), "+f"(d[3]) : "r"(a0), "r"(a1), "r"(b0));
}
__device__ __forceinline__ float ex2(float x) { float y; asm("ex2.approx.ftz.f32 %0, %1;" : "=f"(y) : "f"(x)); return y; }
__device__ __forceinline__ float rcp(float x) { float y; asm("rcp.approx.ftz.f32 %0, %1;" : "=f"(y) : "f"(x)); return y; }
__device__ __forceinline__ float tanhf_hw(float x) { float y; asm("tanh.approx.f32 %0, %1;" : "=f"(y) : "f"(x)); return y; }
__device__ __forceinline__ uint32_t lds32(uint32_t a) { uint32_t v; asm volatile("ld.shared.u32 %0, [%1];" : "=r"(v) : "r"(a) : "memory"); return v; }
__device__ __forceinline__ float2 lds64(uint32_t a) { float2 v; asm volatile("ld.shared.v2.f32 {%0,%1}, [%2];" : "=f"(v.x), "=f"(v.y) : "r"(a) : "memory"); return v; }
__device__ __forceinline__ void lds128(uint32_t (&v)[4], uint32_t a) { asm volatile("ld.shared.v4.u32 {%0,%1,%2,%3}, [%4];" : "=r"(v[0]), "=r"(v[1]), "=r"(v[2]), "=r"(v[3]) : "r"(a) : "memory"); }
__device__ __forceinline__ void sts128(uint32_t a, const uint32_t (&v)[4]) { asm volatile("st.shared.v4.u32 [%0], {%1,%2,%3,%4};" ::"r"(a), "r"(v[0]), "r"(v[1]), "r"(v[2]), "r"(v[3]) : "memory"); }
__device__ __forceinline__ void ldg128_nc(uint32_t (&v)[4], const void* p) {
  asm volatile("ld.global.nc.L1::no_allocate.v4.u32 {%0,%1,%2,%3}, [%4];" : "=r"(v[0]), "=r"(v[1]), "=r"(v[2]), "=r"(v[3]) : "l"(p));
}
__device__ __forceinline__ uint32_t pin(uint32_t v, uint32_t zero) {
  asm volatile("{\n.reg .pred p;\n.reg .u32 c;\nmov.u32 c, %1;\nLP:\n.pragma \"nounroll\";\nsetp.eq.u32 p, c, 0;\n@p bra LD;\n"
               "nanosleep.u32 c;\nadd.u32 %0, %0, c;\nsub.u32 c, c, 1;\nbra LP;\nLD:\n}\n" : "+r"(v) : "r"(zero) : "memory");
  return v;
}
__device__ __forceinline__ void mbar_arrive_if(uint32_t b, bool cond) {
  asm volatile("{\n.reg .pred p;\nsetp.ne.u32 p, %1, 0;\n@p mbarrier.arrive.shared::cta.b64 _, [%0];\n}\n" ::"r"(b), "r"((uint32_t)cond) : "memory");
}
__device__ __forceinline__ uint32_t ld_epoch(const unsigned* p) {
  uint32_t v;
  asm volatile("ld.relaxed.gpu.global.u32 %0, [%1];" : "=r"(v) : "l"(p) : "memory");
  return v;
}
__device__ __forceinline__ void ll_st(uint4* p, uint32_t a, uint32_t b, uint32_t c, uint32_t d, uint32_t tag) {
  asm volatile("st.relaxed.gpu.global.v4.b32 [%0], {%1, %2, %3, %4};" ::"l"(p), "r"((a & ~1u) | tag), "r"(b), "r"(c), "r"(d) : "memory");
}
__device__ __forceinline__ void ll_ld(uint32_t (&v)[4], const uint4* p) {
  asm volatile("{\n.reg .b128 t;\n.reg .b64 lo, hi;\nld.relaxed.gpu.global.b128 t, [%4];\nmov.b128 {lo, hi}, t;\n"
               "mov.b64 {%0, %1}, lo;\nmov.b64 {%2, %3}, hi;\n}\n"
               : "=r"(v[0]), "=r"(v[1]), "=r"(v[2]), "=r"(v[3]) : "l"(p) : "memory");
}
template <int N> __device__ __forceinline__ void ll_issue(uint32_t (&v)[N][4], const uint4* p, int stride) {
#pragma unroll
  for (int i = 0; i < N; i++) ll_ld(v[i], p + i * stride);
}
template <int N> __device__ __forceinline__ uint32_t ll_acc(const uint32_t (&v)[N][4], uint32_t tag, uint32_t acc = 0) {
#pragma unroll
  for (int i = 0; i < N; i++) asm("lop3.b32 %0, %1, %2, %0, 0xBE;" : "+r"(acc) : "r"(v[i][0]), "r"(tag));
  return acc;
}
__device__ __forceinline__ bool ll_any(uint32_t acc) { return __any_sync(0xffffffffu, acc & 1u); }
template <int N> __device__ __forceinline__ bool ll_bad(const uint32_t (&v)[N][4], uint32_t tag) { return ll_any(ll_acc<N>(v, tag)); }
template <int N> __device__ __forceinline__ void ll_clear(uint32_t (&v)[N][4]) {
#pragma unroll
  for (int i = 0; i < N; i++) v[i][0] &= ~1u;
}
template <int N> __device__ __forceinline__ void ll_spin(uint32_t (&v)[N][4], const uint4* p, int stride, uint32_t tag) {
  uint32_t it = 0;
#pragma unroll 1
  do { ll_issue<N>(v, p, stride); } while (ll_bad<N>(v, tag) && ++it < SPIN_LIMIT);
}
template <int N> __device__ __forceinline__ void ll_get(uint32_t (&v)[N][4], const uint4* p, int stride, uint32_t tag) {
  ll_spin<N>(v, p, stride, tag);
  ll_clear<N>(v);
}
template <int N> __device__ __forceinline__ void ll_wait(uint32_t (&v)[N][4], const uint4* p, int stride, uint32_t tag) {
  if (__builtin_expect(ll_bad<N>(v, tag), 0)) ll_spin<N>(v, p, stride, tag);
  ll_clear<N>(v);
}
__device__ __forceinline__ void unpack32(float (&d)[32], const uint32_t (&v)[4][4]) {
#pragma unroll
  for (int u = 0; u < 4; u++)
#pragma unroll
    for (int e = 0; e < 4; e++) { d[8 * u + 2 * e] = bf_lo(v[u][e]); d[8 * u + 2 * e + 1] = bf_hi(v[u][e]); }
}
__device__ __forceinline__ void pack32(uint32_t (&v)[4][4], const float (&d)[32]) {
#pragma unroll
  for (int u = 0; u < 4; u++)
#pragma unroll
    for (int e = 0; e < 4; e++) v[u][e] = pack2(d[8 * u + 2 * e], d[8 * u + 2 * e + 1]);
}
__device__ __forceinline__ uint32_t t_addr(int m) { return SB + ((0x03514620u >> (4 * m)) & 7u) * 32768u; }

__device__ __forceinline__ int kb_at(int i, int j) { return i == 0 ? j : (i - 1 + (i - 1 >= j ? 1 : 0)); }

__device__ __forceinline__ void init_bars(int set) {
  if (set >= 0 && elect_one()) {
    const uint32_t cnt = set < 5 ? 1 : 8;
#pragma unroll
    for (int i = 0; i < 8; i++) mbar_init(BAR + (24 + 8 * set + i) * 8, cnt);
    if (set == 9) {
#pragma unroll
      for (int i = 0; i < 9; i++) mbar_init(BAR + (B_EX + i) * 8, 4);
#pragma unroll
      for (int i = 0; i < 4; i++) mbar_init(BAR + (B_READY + i) * 8, i == 1 ? 7 : 3);
#pragma unroll
      for (int i = 0; i < 5; i++) mbar_init(BAR + (B_TAG + i) * 8, i < 3 ? 1 : 4);
    }
    asm volatile("fence.mbarrier_init.release.cluster;" ::: "memory");
  }
  __syncwarp();
  asm volatile("bar.arrive 4, 384;" ::: "memory");
  asm volatile("bar.sync 3, 384;" ::: "memory");
}

__global__ void __launch_bounds__(384, 1) fused_block_kernel(Scratch* __restrict__ X, const __nv_bfloat16* __restrict__ xp,
                                                             const __nv_bfloat16* __restrict__ wqkvp, const __nv_bfloat16* __restrict__ wop, const uint32_t zero,
                                                             const __grid_constant__ Params P) {
  extern __shared__ __align__(1024) uint8_t smem_raw[];
  if (smem_u32(smem_raw) != SB) return;
  const int tid = threadIdx.x;
  const int warp = __shfl_sync(0xffffffffu, tid >> 5, 0);
  const int lane = tid & 31;
  const int cta = blockIdx.x;
  const int j = (cta >> 6) * 4 + (cta & 3);
  const int g = (cta & 63) >> 2;

  if (warp >= 8) {
    asm volatile("setmaxnreg.dec.sync.aligned.u32 56;");
    if (warp == 8) {
      PSTAMPW(2, 0);
      const bool leader = elect_one();
      if (leader) {
        prefetch_map(&P.x); prefetch_map(&P.wqkv);
#pragma unroll
        for (int i = 0; i < 24; i++) mbar_init(BAR + i * 8, 1);
        asm volatile("fence.mbarrier_init.release.cluster;" ::: "memory");
      }
      __syncwarp();
      asm volatile("bar.arrive 3, 384;" ::: "memory");
      PSTAMPW(2, 20);
      auto ldx = [&](int p, int kb) {
        const uint32_t b = BAR + (B_FX + p * 8 + kb) * 8;
        mbar_expect_tx(b, 8192);
        tma3d(H0 + p * 65536 + kb * 8192, &P.x, kb * 64, p, g * 64, b);
      };
      auto ldkv = [&](int kb, int slot) {
        const uint32_t b = BAR + (B_FKV + kb) * 8, d = RING + slot * 16384;
        mbar_expect_tx(b, 16384);
        tma2d(d, &P.wqkv, 512 + 64 * j, kb * 64, b);
        tma2d(d + 8192, &P.wqkv, 1024 + 64 * j, kb * 64, b);
      };
      if (leader) {
#pragma unroll 1
        for (int i = 0; i < 8 + XO_DELAY; i++) {
          if (i < 8) ldx(0, i);
          if (i < 6) ldkv(i, i);
          if (i >= XO_DELAY) ldx(1, i - XO_DELAY);
          if (i == 0) PSTAMPW(2, 21);
        }
        PSTAMPW(2, 2);
      }
      __syncwarp();
      asm volatile("bar.sync 4, 384;" ::: "memory");
      if (leader) {
        const int f0 = 224 * j + ((j & 1) ? 32 : 0);
        const int fh = 224 * j + ((j & 1) ? 0 : 192);
        prefetch_map(&P.wo); prefetch_map(&P.w1); prefetch_map(&P.w3); prefetch_map(&P.w1h);
        prefetch_map(&P.w3h); prefetch_map(&P.w2); prefetch_map(&P.out);
#pragma unroll 1
        for (int i = 0; i < 2; i++) { mbar_wait(BAR + (B_EKV + i) * 8); ldkv(6 + i, i); }
#pragma unroll 1
        for (int i = 0; i < 8; i++) {
          const uint32_t b = BAR + (B_FQ + i) * 8;
          mbar_wait(BAR + (B_EKV + 2 + (i >> 1)) * 8);
          mbar_expect_tx(b, 8192);
          tma2d(RING + (4 + i) * 8192, &P.wqkv, 64 * j, i * 64, b);
        }
        mbar_expect_tx(BAR + B_FWO * 8, 65536);
#pragma unroll 1
        for (int i = 0; i < 8; i++) {
          const int kb = (i + 1) & 7;
          mbar_wait(BAR + (B_EX + i) * 8);
          tma2d(H0 + kb * 8192, &P.wo, 64 * j, kb * 64, BAR + B_FWO * 8);
          PSTAMPW(2, 4 + i);
        }
#pragma unroll 1
        for (int i = 0; i < 8; i++) {
          const uint32_t b = BAR + (B_FA + i) * 8, d = RING + (i & 3) * 24576;
          const int k0 = kb_at(i, j) * 64;
          mbar_wait(BAR + (B_EKV + 7 + ((0xCBA98520u >> (4 * i)) & 15)) * 8);
          mbar_expect_tx(b, 24576);
          tma2d(d, &P.w1, f0, k0, b);
          tma2d(d + 8192, &P.w3, f0, k0, b);
          tma2d(d + 16384, &P.w1h, fh, k0, b);
          tma2d(d + 20480, &P.w3h, fh, k0, b);
          PSTAMPW(2, 12 + i);
        }
        uint32_t d = RING;
#pragma unroll 1
        for (int i = 0; i < 8; i++) {
          const uint32_t b = BAR + (B_FB + i) * 8;
          const int k0 = kb_at(i, j) * 64;
          mbar_wait(BAR + (B_EA + 5 + i) * 8);
          mbar_expect_tx(b, 32768);
          tma2d(d, &P.w1, f0 + 64, k0, b);
          tma2d(d + 8192, &P.w3, f0 + 64, k0, b);
          tma2d(d + 16384, &P.w1, f0 + 128, k0, b);
          tma2d(d + 24576, &P.w3, f0 + 128, k0, b);
          d = d == RING + 65536 ? RING : d + 32768;
        }
#pragma unroll 1
        for (int m = 0; m < 8; m++) {
          const uint32_t b = BAR + (B_FT + m) * 8;
          mbar_wait(BAR + (B_EB + (m == 7 ? 8 : min(m + 3, 7))) * 8);
          mbar_expect_tx(b, 28672);
          tma2d(t_addr(m), &P.w2, 64 * ((j + 1 + m) & 7), 224 * j, b);
          if (m >= 4) PSTAMPW(2, 23 + m);
        }
        mbar_expect_tx(BAR + B_FIN * 8, 4 * 16384);
#pragma unroll 1
        for (int q = 0; q < 4; q++) {
          mbar_wait(BAR + (B_ET2 + 1 + q) * 8);
          PSTAMPW(2, 22 + q);
          asm volatile("cp.async.bulk.shared::cluster.global.mbarrier::complete_tx::bytes [%0], [%1], 16384, [%2];"
                       ::"r"(t_addr(q + 1)), "l"(X->e4 + ((g * 8 + j) * 8 + ((j - 1 - q) & 7)) * 1024), "r"(BAR + B_FIN * 8) : "memory");
        }
        X->epoch[cta] = X->epoch[cta] + 1;
      }
    } else {
      const int part = warp - 9;
      uint32_t tag;
      if (part == 2) {
        tag = ld_epoch(X->epoch + cta);
        init_bars(-1);
        tag = (tag + 1) & 1;
        if (lane == 0) {
          asm volatile("st.shared.u32 [%0], %1;" ::"r"(TAGS), "r"(tag) : "memory");
          mbar_arrive(BAR + B_TAG * 8);
        }
      } else {
        init_bars(warp - 1);
        mbar_wait(BAR + B_TAG * 8);
        tag = lds32(TAGS);
      }
      PSTAMPW(3, 16 + part);
      const int xw0 = g * 8;
      auto clear8 = [&](uint4* p, int stride) {
#pragma unroll
        for (int i = 0; i < 8; i++) ll_st(p + i * stride + lane, 0, 0, 0, 0, tag ^ 1);
      };
      auto clear_front = [&]() {
#pragma unroll 1
      for (int u = part; u < 8; u += 3) clear8((u < 4 ? X->e2 : X->e3h) + (xw0 * 32 + 4 * j + (u & 3)) * 32, 1024);
      if (part == 2) {
        clear8(X->e1 + (g * 8 + j) * 256, 32);
#pragma unroll
        for (int i = 0; i < 4; i++)
          ll_st((i < 2 ? X->e2s : X->e3s) + ((xw0 + (i & 1) * 4 + (lane >> 3)) * 8 + j) * 8 + (lane & 7), 0, 0, 0, 0, tag ^ 1);
      }
      };
      if (CLR_MODE == 1) clear_front();
      PSTAMPW(3, 20 + part);
      uint32_t v[8][4];
      if (part < 2) {
        float s[4] = {0.f, 0.f, 0.f, 0.f}, q[4] = {0.f, 0.f, 0.f, 0.f}, piv = 0.f;
        const uint32_t xa = H0 + part * 65536 + (8 * j + (lane >> 2)) * 128 + (lane & 3) * 16 + (lane & 4) * 16;
#pragma unroll 1
        for (int kb = 0; kb < 8; kb++) {
          mbar_wait(BAR + (B_FX + part * 8 + kb) * 8);
          lds128(v[0], xa + kb * 8192); lds128(v[1], (xa + kb * 8192) ^ 64);
          if (kb == 0) piv = __shfl_sync(0xffffffffu, bf_lo(v[0][0]), lane & 28);
#pragma unroll
          for (int e = 0; e < 8; e++) {
            const float a = bf_lo(v[e >> 2][e & 3]) - piv, b = bf_hi(v[e >> 2][e & 3]) - piv;
            s[e & 3] += a + b; q[e & 3] = fmaf(a, a, q[e & 3]); q[e & 3] = fmaf(b, b, q[e & 3]);
          }
        }
        float ss = (s[0] + s[1]) + (s[2] + s[3]), qq = (q[0] + q[1]) + (q[2] + q[3]);
#pragma unroll
        for (int o = 1; o <= 2; o <<= 1) { ss += __shfl_xor_sync(0xffffffffu, ss, o); qq += __shfl_xor_sync(0xffffffffu, qq, o); }
        const float dm = ss * (1.f / D_);
        const float rs = rsqrtf(fmaxf(fmaf(-dm, dm, qq * (1.f / D_)), 0.f) + 1e-5f);
        if ((lane & 3) == 0) ll_st(X->e0s + g * 128 + 2 * (8 * j + (lane >> 2)) + part, __float_as_uint(piv + dm), __float_as_uint(rs), 0, 0, tag);
      } else {
        mbar_wait(BAR + (B_FKV + SIDE_KB) * 8);
        const __nv_bfloat16* wr = wop + (size_t)(j * 64 + g * 4 + (lane >> 3)) * D_ + (lane & 7) * 8;
#pragma unroll
        for (int i = 0; i < 8; i++) ldg128_nc(v[i], wr + i * 64);
        float s[4];
#pragma unroll
        for (int e = 0; e < 4; e++) {
          s[e] = 0.f;
#pragma unroll
          for (int i = 0; i < 8; i++) s[e] += bf_lo(v[i][e]) + bf_hi(v[i][e]);
        }
        float ss = (s[0] + s[1]) + (s[2] + s[3]);
#pragma unroll
        for (int o = 1; o <= 4; o <<= 1) ss += __shfl_xor_sync(0xffffffffu, ss, o);
        if ((lane & 7) == 0) ll_st(X->e0w + j * 64 + g * 4 + (lane >> 3), __float_as_uint(ss * (1.f / D_)), 0, 0, 0, tag);
      }
      __syncwarp();
      if (lane == 0) mbar_arrive(BAR + B_PUB * 8);
      PSTAMPW(3, part * 4 + 2);
      mbar_wait(BAR + B_PUB * 8);
      PSTAMPW(3, part * 4 + 0);
      {
        uint32_t u[2][4];
        const uint4* us = (part == 2 ? X->e0w + j * 64 : X->e0s + g * 128 + part * 64) + lane;
        const uint4* vs = X->e0c + ((j * 3 + part) * 16 + (lane >> 4) * 8) * 16 + (lane & 15);
        uint32_t it = 0;
#pragma unroll 1
        do { ll_issue<2>(u, us, 32); ll_issue<8>(v, vs, 16); } while (ll_any(ll_acc<8>(v, tag, ll_acc<2>(u, tag))) && ++it < SPIN_LIMIT);
        ll_clear<2>(u); ll_clear<8>(v);
#pragma unroll
        for (int i = 0; i < 2; i++) {
          if (part == 2) asm volatile("st.shared.u32 [%0], %1;" ::"r"(WB + (i * 32 + lane) * 4), "r"(u[i][0]) : "memory");
          else asm volatile("st.shared.v2.u32 [%0], {%1,%2};" ::"r"(ST + (part * 64 + i * 32 + lane) * 8), "r"(u[i][0]), "r"(u[i][1]) : "memory");
        }
      }
      uint32_t o[4];
#pragma unroll
      for (int e = 0; e < 4; e++) {
        float s = 0.f;
#pragma unroll
        for (int i = 0; i < 8; i++) s += __uint_as_float(v[i][e]);
        o[e] = __float_as_uint(s + __shfl_xor_sync(0xffffffffu, s, 16));
      }
      if (lane < 16) sts128(CS + (part * 64 + lane * 4) * 4, o);
      __syncwarp();
      if (lane == 0) mbar_arrive(BAR + B_READY * 8);
      PSTAMPW(3, part * 4 + 1);
      if (CLR_MODE == 2) clear_front();
      __syncwarp();
      if (lane == 0) mbar_arrive(BAR + B_CLR0 * 8);
      PSTAMPW(3, 24 + part);
      if (lane == 0) l2_prefetch(part == 0 ? P.w1p + (size_t)cta * 4 * F_ : part == 1 ? P.w3p + (size_t)cta * 4 * F_ : P.w2p + (size_t)cta * 14 * D_, 14336);
      mbar_wait(BAR + (B_EA + 7) * 8);
#pragma unroll 1
      for (int u = 4 * E4_FIRST + part; u < 28; u += 3) {
        clear8(X->e4 + ((g * 8 + ((j + 1 + (u >> 2)) & 7)) * 8 + j) * 1024 + (u & 3) * 32, 128);
        __nanosleep(CLR_SLEEP);
      }
      PSTAMPW(3, part * 4 + 3);
      asm volatile("bar.sync 5, 96;" ::: "memory");
      if (part < 2 && elect_one()) {
        asm volatile("fence.proxy.async.global;" ::: "memory");
#pragma unroll 1
        for (int m = 0; m < 7; m++) {
          mbar_wait_par(BAR + (B_OF + part) * 8, m & 1);
          fence_async_smem();
          const uint4* dst = X->e4 + ((g * 8 + ((j + 1 + m) & 7)) * 8 + j) * 1024 + part * 512;
#pragma unroll
          for (int i = 0; i < 2; i++)
            asm volatile("cp.async.bulk.global.shared::cta.bulk_group [%0], [%1], 4096;"
                         ::"l"(dst + i * 256), "r"(H0 + part * 131072 + i * 65536 + 28672) : "memory");
          asm volatile("cp.async.bulk.commit_group;" ::: "memory");
          asm volatile("cp.async.bulk.wait_group.read 0;" ::: "memory");
          mbar_arrive(BAR + (B_OE + part) * 8);
        }
      }
    }
  } else {
    const int p = warp >> 2, w = warp & 3;
    const int r = lane >> 2, c = lane & 3;
    init_bars(warp);
    asm volatile("setmaxnreg.inc.sync.aligned.u32 224;");
    PSTAMP(0);
    const uint32_t dAx = descA(H0) + p * 4096;
    const uint32_t Hn = H1 - p * 65536;
    const uint32_t moff = ((lane & 7) + ((lane >> 3) & 1) * 8) * 128 + (((lane >> 4) ^ (lane & 7)) << 4);
    const uint32_t Xw = H0 + p * 65536 + w * 2048;
    const int xw = (g * 2 + p) * 4 + w;
    if (p == 1) {
      uint32_t v[8][4];
      mbar_wait(BAR + (B_FKV + SIDE_KB) * 8);
      const int wp = w < 3 ? w : 0;
      const __nv_bfloat16* wr = wqkvp + (size_t)(g * 32 + (lane >> 3) * 8) * (3 * D_) + wp * D_ + j * 64 + (lane & 7) * 8;
#pragma unroll
      for (int i = 0; i < 8; i++) ldg128_nc(v[i], wr + (size_t)i * 3 * D_);
      mbar_wait(BAR + B_TAG * 8);
      const uint32_t tg = lds32(TAGS);
      float cs[8];
#pragma unroll
      for (int e = 0; e < 4; e++) {
        float a = 0.f, b = 0.f;
#pragma unroll
        for (int i = 0; i < 8; i++) { a += bf_lo(v[i][e]); b += bf_hi(v[i][e]); }
        cs[2 * e] = a; cs[2 * e + 1] = b;
      }
      const bool up = lane & 8;
#pragma unroll
      for (int e = 0; e < 4; e++) {
        const float keepv = up ? cs[4 + e] : cs[e], give = up ? cs[e] : cs[4 + e];
        cs[e] = keepv + __shfl_xor_sync(0xffffffffu, give, 8);
        cs[e] += __shfl_xor_sync(0xffffffffu, cs[e], 16);
      }
      if (lane < 16 && w < 3)
        ll_st(X->e0c + ((j * 3 + w) * 16 + g) * 16 + (lane & 7) * 2 + (lane >> 3), __float_as_uint(cs[0]), __float_as_uint(cs[1]),
              __float_as_uint(cs[2]), __float_as_uint(cs[3]), tg);
      __syncwarp();
      mbar_arrive_if(BAR + B_PUB * 8, lane == 0);
      PSTAMP(1);
      mbar_wait(BAR + B_LAG * 8);
    }

    float akv[64];
#pragma unroll 1
    for (int kb = 0; kb < 8; kb++) {
      mbar_wait(BAR + (B_FX + p * 8 + kb) * 8);
      mbar_wait(BAR + (B_FKV + kb) * 8);
      if (kb == 0) PSTAMP(2);
      const uint32_t da = dAx + kb * 512, db = descB(RING) + (kb < 6 ? kb : kb - 6) * 1024;
      wg_fence();
      wgmma_ss_n128(akv, da, db, kb);
#pragma unroll
      for (int k = 1; k < 4; k++) wgmma_ss_n128(akv, da + k * 2, db + k * 128, 1);
      wg_commit();
      mbar_arrive_if(BAR + B_LAG * 8, kb == LAG_KB - 1 && p == 0 && lane == 0);
      wg_wait<1>();
      mbar_arrive_if(BAR + (B_EKV + kb - 1) * 8, kb > 0 && lane == 0);
    }
    uint32_t xres[4][4];
#pragma unroll
    for (int u = 0; u < 4; u++) ldsm4(xres[u], Xw + j * 8192 + (moff ^ (u << 5)));

    float aq[32];
    auto qstep = [&](int kb) {
      mbar_wait(BAR + (B_FQ + kb) * 8);
      const uint32_t da = dAx + kb * 512, db = descB(RING + 32768) + kb * 512;
      wg_fence();
      wgmma_ss_n64(aq, da, db, kb);
#pragma unroll
      for (int k = 1; k < 4; k++) wgmma_ss_n64(aq, da + k * 2, db + k * 128, 1);
      wg_commit();
      wg_wait<1>();
      mbar_arrive_if(BAR + (B_EQ + kb - 1) * 8, lane == 0);
      mbar_arrive_if(BAR + (B_EX + kb - 2) * 8, lane == 0 && p == 0 && kb >= 2);
    };
    qstep(0);
    keep(akv);
    PSTAMP(3);
    qstep(1);
    mbar_wait(BAR + B_READY * 8);
    PSTAMP(19);
    const uint32_t tag = lds32(TAGS);
    uint4* const xb = reinterpret_cast<uint4*>(X) + lane + (tag >> 1);
    constexpr int O_E4 = offsetof(Scratch, e4) / 16, O_E2 = offsetof(Scratch, e2) / 16, O_E3H = offsetof(Scratch, e3h) / 16;
    const float2 st0 = lds64(ST + (2 * (16 * w + r) + p) * 8);
    const float2 st1 = lds64(ST + (2 * (16 * w + r + 8) + p) * 8);
    uint32_t hi[4][4], lo[4][4];
    {
      float2 cs[16];
      auto cvt = [&](uint32_t (&d)[4][4], int b0, int ofs, const float2& st) {
#pragma unroll
        for (int b = b0; b < b0 + 8; b++) {
          if (ofs == 2) cs[b] = lds64(CS + (64 + b * 8 + 2 * c) * 4);
          const uint32_t v = pack2(fmaf(-st.x, cs[b].x, akv[4 * b + ofs]) * st.y, fmaf(-st.x, cs[b].y, akv[4 * b + ofs + 1]) * st.y);
          d[b >> 2][b & 3] = b < 8 ? v : movm(v);
        }
      };
      cvt(hi, 0, 2, st1);
      keep(hi[0]); keep(hi[1]);
      qstep(2);
      cvt(hi, 8, 2, st1);
      mbar_wait(BAR + B_CLR0 * 8);
      if (w == 3 && g < 15) {
        uint4* dst = X->e1 + ((g * 8 + j) * 2 + p) * 128 + lane;
#pragma unroll
        for (int i = 0; i < 4; i++) ll_st(dst + i * 32, hi[i][0], hi[i][1], hi[i][2], hi[i][3], tag);
      }
      PSTAMP(20);
      wg_bar(p);
#pragma unroll
      for (int i = 0; i < 4; i++) sts128(Xw + lane * 16 + i * 512, hi[i]);
      qstep(3);
      cvt(lo, 0, 0, st0);
      keep(lo[0]); keep(lo[1]);
      qstep(4);
      cvt(lo, 8, 0, st0);
    }
    PSTAMP(21);
    wg_bar(p);
    uint32_t prev[4][4];
    if (w > 0) {
#pragma unroll
      for (int i = 0; i < 4; i++) lds128(prev[i], Xw - 2048 + lane * 16 + i * 512);
    }
    if (p == 0) {
      asm volatile("fence.proxy.async.shared::cta;" ::: "memory");
      __syncwarp();
      if (lane == 0) mbar_arrive(BAR + (B_EX + 7) * 8);
    }
    PSTAMP(22);
    const uint4* halo = X->e1 + (((g - 1) * 8 + j) * 2 + p) * 128 + lane;
    const bool use_halo = w == 0 && g > 0;
    qstep(5);
    if (use_halo) ll_issue<4>(prev, halo, 32);
    qstep(6);
    qstep(7);
    PSTAMP(23);
    if (w == 0) {
      if (g > 0) {
        if (__builtin_expect(ll_bad<4>(prev, pin(tag, zero)), 0)) ll_spin<4>(prev, halo, 32, tag);
        ll_clear<4>(prev);
      } else {
#pragma unroll
        for (int i = 0; i < 4; i++)
#pragma unroll
          for (int e = 0; e < 4; e++) prev[i][e] = 0;
      }
    }
    wg_wait<0>();
    keep(aq);
    mbar_arrive_if(BAR + (B_EQ + 7) * 8, lane == 0);
    mbar_arrive_if(BAR + (B_EX + 6) * 8, lane == 0 && p == 0);
    PSTAMP(4);

    uint32_t of[4][4];
    {
      const float sc = 0.25f * 1.4426950408889634f;
      const float nohalo = (g == 0 && w == 0) ? -INFINITY : 0.f;
      const bool up0 = 2 * c > r, up1 = 2 * c + 1 > r;
      const uint32_t mup = (up0 ? 0xffffu : 0u) | (up1 ? 0xffff0000u : 0u);
      uint4* dst = xb + O_E2 + (xw * 32 + 4 * j) * 32;
      float d0 = 0.f, d1 = 0.f;
#pragma unroll 1
      for (int hp = 0; hp < 2; hp++) {
#pragma unroll
        for (int e = 0; e < 4; e++) { of[0][e] = of[2][e]; of[1][e] = of[3][e]; }
#pragma unroll
        for (int h = 0; h < 2; h++) {
          uint32_t qf[4];
          const uint32_t co = (32 * hp + 16 * h + 2 * c) * 4;
          {
            const float2 ca = lds64(CS + co), cb = lds64(CS + co + 32);
            qf[0] = pack2(fmaf(-st0.x, ca.x, aq[8 * h + 0]) * st0.y, fmaf(-st0.x, ca.y, aq[8 * h + 1]) * st0.y);
            qf[1] = pack2(fmaf(-st1.x, ca.x, aq[8 * h + 2]) * st1.y, fmaf(-st1.x, ca.y, aq[8 * h + 3]) * st1.y);
            qf[2] = pack2(fmaf(-st0.x, cb.x, aq[8 * h + 4]) * st0.y, fmaf(-st0.x, cb.y, aq[8 * h + 5]) * st0.y);
            qf[3] = pack2(fmaf(-st1.x, cb.x, aq[8 * h + 6]) * st1.y, fmaf(-st1.x, cb.y, aq[8 * h + 7]) * st1.y);
          }
          const int e0 = 2 * h;
          float sp[4], sl[4], sh[4];
          mma16816(sp, qf, prev[0][e0], prev[0][e0 + 1]);
          mma16816(sl, qf, lo[0][e0], lo[0][e0 + 1]);
          mma16816(sh, qf, hi[0][e0], hi[0][e0 + 1]);
          float a0 = up0 ? sp[0] + nohalo : sl[0], a1 = up1 ? sp[1] + nohalo : sl[1];
          float b0 = up0 ? sl[2] : sh[2], b1 = up1 ? sl[3] : sh[3];
          float ma = fmaxf(a0, a1), mb = fmaxf(b0, b1);
          ma = fmaxf(ma, __shfl_xor_sync(0xffffffffu, ma, 1)); mb = fmaxf(mb, __shfl_xor_sync(0xffffffffu, mb, 1));
          ma = fmaxf(ma, __shfl_xor_sync(0xffffffffu, ma, 2)); mb = fmaxf(mb, __shfl_xor_sync(0xffffffffu, mb, 2));
          a0 = ex2((a0 - ma) * sc); a1 = ex2((a1 - ma) * sc); b0 = ex2((b0 - mb) * sc); b1 = ex2((b1 - mb) * sc);
          float sa = a0 + a1, sbb = b0 + b1;
          sa += __shfl_xor_sync(0xffffffffu, sa, 1); sbb += __shfl_xor_sync(0xffffffffu, sbb, 1);
          sa += __shfl_xor_sync(0xffffffffu, sa, 2); sbb += __shfl_xor_sync(0xffffffffu, sbb, 2);
          const float ia = rcp(sa), ib = rcp(sbb);
          const uint32_t pa = pack2(a0 * ia, a1 * ia), pb = pack2(b0 * ib, b1 * ib);
          const uint32_t pf[4] = {pa & mup, 0u, pa & ~mup, pb & mup};
          const uint32_t ph = pb & ~mup;
          float o0[4], o1[4];
          mma16816(o0, pf, prev[2][e0], lo[2][e0]);
          mma16816(o1, pf, prev[2][e0 + 1], lo[2][e0 + 1]);
          mma1688_acc(o0, 0u, ph, hi[2][e0]);
          mma1688_acc(o1, 0u, ph, hi[2][e0 + 1]);
          of[2 + h][0] = pack2(o0[0], o0[1]); of[2 + h][1] = pack2(o0[2], o0[3]);
          of[2 + h][2] = pack2(o1[0], o1[1]); of[2 + h][3] = pack2(o1[2], o1[3]);
          ll_st(dst + (2 * hp + h) * 32, of[2 + h][0], of[2 + h][1], of[2 + h][2], of[2 + h][3], tag);
          const float2 wa = lds64(WB + co), wb = lds64(WB + co + 32);
          d0 = fmaf(o0[0], wa.x, d0); d0 = fmaf(o0[1], wa.y, d0); d0 = fmaf(o1[0], wb.x, d0); d0 = fmaf(o1[1], wb.y, d0);
          d1 = fmaf(o0[2], wa.x, d1); d1 = fmaf(o0[3], wa.y, d1); d1 = fmaf(o1[2], wb.x, d1); d1 = fmaf(o1[3], wb.y, d1);
        }
#pragma unroll
        for (int e = 0; e < 16; e++) aq[e] = aq[16 + e];
#pragma unroll
        for (int e = 0; e < 4; e++) {
          prev[0][e] = prev[1][e]; prev[2][e] = prev[3][e];
          lo[0][e] = lo[1][e]; lo[2][e] = lo[3][e];
          hi[0][e] = hi[1][e]; hi[2][e] = hi[3][e];
        }
      }
#pragma unroll
      for (int o = 1; o <= 2; o <<= 1) { d0 += __shfl_xor_sync(0xffffffffu, d0, o); d1 += __shfl_xor_sync(0xffffffffu, d1, o); }
      if (c == 0) ll_st(X->e2s + (xw * 8 + j) * 8 + r, __float_as_uint(d0), __float_as_uint(d1), 0, 0, tag);
    }
    PSTAMP(5);

    float ah[32];
    uint32_t sv[2][4];
    unpack32(ah, xres);
    {
      uint32_t og[2][14][4];
      const uint4* osrc[7];
#pragma unroll
      for (int i = 0; i < 7; i++) osrc[i] = xb + O_E2 + (xw * 32 + 4 * kb_at(i + 1, j)) * 32;
      const uint4* ssrc = X->e2s + (xw * 8 + 2 * c) * 8 + r;
      auto oissue = [&](int hp) {
#pragma unroll
        for (int i = 0; i < 14; i++) ll_ld(og[hp][i], osrc[i >> 1] + (2 * hp + (i & 1)) * 32);
        if (hp == 1) ll_issue<2>(sv, ssrc, 8);
      };
      auto omma = [&](int hp) {
        ll_clear<14>(og[hp]);
        keep(og[hp]);
        wg_fence();
#pragma unroll
        for (int i = 0; i < 14; i++) wgmma_rs_n64(ah, og[hp][i], descB(H0) + kb_at((i >> 1) + 1, j) * 512 + (2 * hp + (i & 1)) * 128, 1);
        wg_commit();
      };
      mbar_wait(BAR + B_FWO * 8);
      keep(ah); keep(of);
      wg_fence();
#pragma unroll
      for (int k = 0; k < 4; k++) wgmma_rs_n64(ah, of[k], descB(H0) + j * 512 + k * 128, 1);
      wg_commit();
      uint32_t it = 0;
#pragma unroll 1
      do { oissue(0); } while (ll_bad<14>(og[0], tag) && ++it < SPIN_LIMIT);
      PSTAMP(6);
      oissue(1);
      omma(0);
      const uint32_t tg = pin(tag, zero);
      if (__builtin_expect(ll_any(ll_acc<14>(og[1], tg, ll_acc<2>(sv, tg))), 0)) {
#pragma unroll 1
        do { oissue(1); } while (ll_any(ll_acc<14>(og[1], tag, ll_acc<2>(sv, tag))) && ++it < SPIN_LIMIT);
      }
      PSTAMP(16);
      omma(1);
      ll_clear<2>(sv);
    }
    float m0 = __uint_as_float(sv[0][0]) + __uint_as_float(sv[1][0]), m1 = __uint_as_float(sv[0][1]) + __uint_as_float(sv[1][1]);
#pragma unroll
    for (int o = 1; o <= 2; o <<= 1) { m0 += __shfl_xor_sync(0xffffffffu, m0, o); m1 += __shfl_xor_sync(0xffffffffu, m1, o); }
    const uint32_t mu0 = pack2(m0 + st0.x, m0 + st0.x), mu1 = pack2(m1 + st1.x, m1 + st1.x);
    wg_wait<0>();
    keep(ah);
    if (lane == 0) mbar_arrive(BAR + B_WODONE * 8);
    PSTAMP(7);

    uint32_t hf[4][4], ra[4][4];
    pack32(hf, ah);
    {
      uint4* dst = xb + O_E3H + (xw * 32 + 4 * j) * 32;
#pragma unroll
      for (int u = 0; u < 4; u++) {
        ra[u][0] = hsub2(hf[u][0], mu0); ra[u][1] = hsub2(hf[u][1], mu1);
        ra[u][2] = hsub2(hf[u][2], mu0); ra[u][3] = hsub2(hf[u][3], mu1);
        ll_st(dst + u * 32, ra[u][0], ra[u][1], ra[u][2], ra[u][3], tag);
      }
      float s0 = 0.f, q0 = 0.f, s1 = 0.f, q1 = 0.f;
#pragma unroll
      for (int b = 0; b < 8; b++) {
        s0 += ah[4 * b] + ah[4 * b + 1]; s1 += ah[4 * b + 2] + ah[4 * b + 3];
        q0 = fmaf(ah[4 * b], ah[4 * b], q0); q0 = fmaf(ah[4 * b + 1], ah[4 * b + 1], q0);
        q1 = fmaf(ah[4 * b + 2], ah[4 * b + 2], q1); q1 = fmaf(ah[4 * b + 3], ah[4 * b + 3], q1);
      }
#pragma unroll
      for (int o = 1; o <= 2; o <<= 1) {
        s0 += __shfl_xor_sync(0xffffffffu, s0, o); q0 += __shfl_xor_sync(0xffffffffu, q0, o);
        s1 += __shfl_xor_sync(0xffffffffu, s1, o); q1 += __shfl_xor_sync(0xffffffffu, q1, o);
      }
      if (c == 0) ll_st(X->e3s + (xw * 8 + j) * 8 + r, __float_as_uint(s0), __float_as_uint(q0), __float_as_uint(s1), __float_as_uint(q1), tag);
      mbar_wait(BAR + (p == 0 ? B_EQ + 7 : B_WODONE) * 8);
    }
    PSTAMP(8);

    float rs0, rs1;
    auto swiglu = [&](float g0, float g1, float u0, float u1, float rs) -> uint32_t {
      const float hr = 0.5f * rs;
      const float x0 = g0 * hr, x1 = g1 * hr;
      const float t0 = tanhf_hw(x0), t1 = tanhf_hw(x1);
      return pack2(fmaf(x0, t0, x0) * (u0 * rs), fmaf(x1, t1, x1) * (u1 * rs));
    };
    uint32_t hA[6][4];
    {
      float a1[64], a2[32];
      const uint4* src = xb + O_E3H + xw * 32 * 32;
      uint32_t rb[4][4], rc[4][4], rd[4][4];
      auto fetch = [&](uint32_t (&a)[4][4], int i) { ll_issue<4>(a, src + kb_at(i, j) * 128, 32); };
      auto check = [&](uint32_t (&a)[4][4], uint32_t (&b)[4][4], int i) {
        const uint32_t tg = pin(tag, zero);
        if (__builtin_expect(ll_any(ll_acc<4>(a, tg, ll_acc<4>(b, tg))), 0)) {
          uint32_t it = 0;
#pragma unroll 1
          do { fetch(a, i); fetch(b, i + 1); } while (ll_any(ll_acc<4>(a, tag, ll_acc<4>(b, tag))) && ++it < SPIN_LIMIT);
        }
        ll_clear<4>(a); ll_clear<4>(b);
        keep(a); keep(b);
      };
      auto head = [&](uint32_t (&a)[4][4], int i) {
        mbar_wait(BAR + (B_FA + i) * 8);
        wg_fence();
        wgmma_rs_n64<DESC_HI64>(a2, a[0], descBh(RING + 16384) + (i & 3) * 1536, i);
        wgmma_rs_n128(a1, a[0], descB(RING) + (i & 3) * 1536, i);
        wg_commit();
#pragma unroll
        for (int u = 0; u < 4; u++) stsm4(Hn + w * 2048 + i * 8192 + (moff ^ (u << 5)), a[u]);
        wg_wait<1>();
        if (i > 0) mbar_arrive_if(BAR + (B_EA + i - 1) * 8, lane == 0);
      };
      auto rest = [&](uint32_t (&a)[4][4], int i) {
        wg_fence();
#pragma unroll
        for (int k = 1; k < 4; k++) {
          wgmma_rs_n64<DESC_HI64>(a2, a[k], descBh(RING + 16384) + (i & 3) * 1536 + k * 64, 1);
          wgmma_rs_n128(a1, a[k], descB(RING) + (i & 3) * 1536 + k * 128, 1);
        }
        wg_commit();
      };
      ll_clear<4>(ra);
      keep(ra);
      head(ra, 0); rest(ra, 0);
      ll_get<4>(rb, src + kb_at(1, j) * 128, 32, tag);
      keep(rb);
      PSTAMP(17);
      fetch(rc, 2); fetch(rd, 3);
      head(rb, 1); rest(rb, 1);
      check(rc, rd, 2);
      head(rc, 2); fetch(ra, 4); fetch(rb, 5); rest(rc, 2);
      head(rd, 3); rest(rd, 3);
      check(ra, rb, 4);
      head(ra, 4); fetch(rc, 6); fetch(rd, 7); ll_issue<2>(sv, X->e3s + (xw * 8 + 2 * c) * 8 + r, 8); rest(ra, 4);
      head(rb, 5); rest(rb, 5);
      check(rc, rd, 6);
      head(rc, 6); rest(rc, 6);
      head(rd, 7); rest(rd, 7);
      fence_async_smem();
      ll_wait<2>(sv, X->e3s + (xw * 8 + 2 * c) * 8 + r, 8, tag);
      float s0 = __uint_as_float(sv[0][0]) + __uint_as_float(sv[1][0]), q0 = __uint_as_float(sv[0][1]) + __uint_as_float(sv[1][1]);
      float s1 = __uint_as_float(sv[0][2]) + __uint_as_float(sv[1][2]), q1 = __uint_as_float(sv[0][3]) + __uint_as_float(sv[1][3]);
#pragma unroll
      for (int o = 1; o <= 2; o <<= 1) {
        s0 += __shfl_xor_sync(0xffffffffu, s0, o); q0 += __shfl_xor_sync(0xffffffffu, q0, o);
        s1 += __shfl_xor_sync(0xffffffffu, s1, o); q1 += __shfl_xor_sync(0xffffffffu, q1, o);
      }
      s0 *= 1.f / D_; s1 *= 1.f / D_;
      rs0 = rsqrtf(fmaxf(fmaf(-s0, s0, q0 * (1.f / D_)), 0.f) + 1e-5f);
      rs1 = rsqrtf(fmaxf(fmaf(-s1, s1, q1 * (1.f / D_)), 0.f) + 1e-5f);
      wg_wait<0>();
      keep(a1); keep(a2);
      if (lane == 0) mbar_arrive(BAR + (B_EA + 7) * 8);
      PSTAMP(9);
#pragma unroll
      for (int u = 0; u < 4; u++)
#pragma unroll
        for (int e = 0; e < 4; e++)
          hA[u][e] = swiglu(a1[8 * u + 2 * e], a1[8 * u + 2 * e + 1], a1[32 + 8 * u + 2 * e], a1[33 + 8 * u + 2 * e], (e & 1) ? rs1 : rs0);
#pragma unroll
      for (int u = 0; u < 2; u++)
#pragma unroll
        for (int e = 0; e < 4; e++)
          hA[4 + u][e] = swiglu(a2[8 * u + 2 * e], a2[8 * u + 2 * e + 1], a2[16 + 8 * u + 2 * e], a2[17 + 8 * u + 2 * e], (e & 1) ? rs1 : rs0);
      keep(hA);
      wg_bar(p);
    }
    PSTAMP(10);

    uint32_t hB[8][4];
    {
      float ab[128];
      uint32_t db = descB(RING);
      const uint32_t dAn = descA(H1) - p * 4096;
#pragma unroll 1
      for (int i = 0; i < 8; i++) {
        mbar_wait(BAR + (B_FB + i) * 8);
        const uint32_t da = dAn + i * 512;
        wg_fence();
        wgmma_ss_n256(ab, da, db, i);
#pragma unroll
        for (int k = 1; k < 4; k++) wgmma_ss_n256(ab, da + k * 2, db + k * 128, 1);
        wg_commit();
        wg_wait<1>();
        mbar_arrive_if(BAR + (B_EB + i - 1) * 8, i > 0 && lane == 0);
        db = db == descB(RING + 65536) ? descB(RING) : db + 2048;
      }
      wg_wait<0>();
      keep(ab);
      if (lane == 0) mbar_arrive(BAR + (B_EB + 7) * 8);
      PSTAMP(11);
#pragma unroll
      for (int u = 0; u < 8; u++) {
        const int o = (u >> 2) * 64 + (u & 3) * 8;
#pragma unroll
        for (int e = 0; e < 4; e++)
          hB[u][e] = swiglu(ab[o + 2 * e], ab[o + 2 * e + 1], ab[o + 32 + 2 * e], ab[o + 33 + 2 * e], (e & 1) ? rs1 : rs0);
      }
      keep(hB);
    }
    PSTAMP(12);

    {
      float ya[32], y[32], sum[32];
      const uint32_t offA = (j & 1) ? 256 : 0, offH = (j & 1) ? 0 : 1536;
      uint4* e4 = xb + O_E4 + g * 65536 + warp * 128;
      const uint32_t stg = H0 + p * 131072 + (w >> 1) * 65536 + 28672 + (w & 1) * 2048;
      uint32_t in[4][4], pk[4][4];
      auto insrc = [&](int q) { return e4 + (j * 8 + ((j - 1 - q) & 7)) * 1024; };
      const uint32_t ident = (2 * c == r ? 0x3f80u : 0u) | (2 * c + 1 == r ? 0x3f800000u : 0u);
      auto acc = [&](uint32_t (&in)[4][4]) {
        ll_clear<4>(in);
#pragma unroll
        for (int u = 0; u < 4; u++) {
          mma1688_acc(*reinterpret_cast<float (*)[4]>(&sum[8 * u]), in[u][0], in[u][1], ident);
          mma1688_acc(*reinterpret_cast<float (*)[4]>(&sum[8 * u + 4]), in[u][2], in[u][3], ident);
        }
      };
      uint32_t T;
      auto mm = [&](float (&d)[32], int k0, int k1) {
        wg_fence();
#pragma unroll
        for (int k = k0; k < k1; k++) {
          if (k < 4) wgmma_rs_n64(d, hA[k], T + offA + k * 128, k);
          else if (k < 6) wgmma_rs_n64(d, hA[k], T + offH + (k - 4) * 128, 1);
          else wgmma_rs_n64(d, hB[k - 6], T + offA + 512 + (k - 6) * 128, 1);
        }
        wg_commit();
      };
      auto start = [&](float (&d)[32], float (&dp)[32], int m) {
        const int mt = min(m, 7);
        mbar_wait(BAR + (B_FT + mt) * 8);
        T = descB(0) + (t_addr(mt) >> 4);
        mm(d, 0, 3);
        wg_wait<1>();
        keep(dp);
        mbar_arrive_if(BAR + (B_ET0 + m - 1) * 8, m != 2 && m < 8 && lane == 0);
        if (m < 8) {
          pack32(pk, dp);
          mbar_wait_par(BAR + (B_OE + p) * 8, m & 1);
#pragma unroll
          for (int u = 0; u < 4; u++) { pk[u][0] = (pk[u][0] & ~1u) | tag; sts128(stg + lane * 16 + u * 512, pk[u]); }
          __syncwarp();
          mbar_arrive_if(BAR + (B_OF + p) * 8, lane == 0);
        }
      };
      mbar_wait(BAR + (B_EB + 3 + 3 * p) * 8);
      mbar_wait(BAR + B_FT * 8);
      T = descB(0) + (t_addr(0) >> 4);
      mm(ya, 0, 3);
      unpack32(sum, hf);
      keep(sum);
      wg_wait<0>();
#pragma unroll 1
      for (int m = 0; m < 8; m += 2) {
        mm(ya, 3, 14);
        start(y, ya, m + 1);
        mm(y, 3, 14);
        start(ya, y, m + 2);
        wg_wait<0>();
        if (m == 0) PSTAMP(27);
        if (m == 2) PSTAMP(26);
        if (m == 4) PSTAMP(28);
      }
      PSTAMP(13);
      uint32_t lt[12][4];
      auto fetch3 = [&]() {
#pragma unroll
        for (int q = 0; q < 3; q++)
#pragma unroll
          for (int u = 0; u < 4; u++) ll_ld(lt[4 * q + u], insrc(4 + q) + u * 32);
      };
      fetch3();
      mbar_wait(BAR + B_FIN * 8);
      PSTAMP(24);
#pragma unroll
      for (int q = 0; q < 4; q++) {
#pragma unroll
        for (int u = 0; u < 4; u++) lds128(in[u], t_addr(q + 1) + warp * 2048 + lane * 16 + u * 512);
        if (__builtin_expect(ll_bad<4>(in, tag), 0)) ll_spin<4>(in, insrc(q), 32, tag);
        acc(in);
      }
      PSTAMP(25);
      if (ll_bad<12>(lt, pin(tag, zero))) {
        uint32_t it = 0;
#pragma unroll 1
        do { fetch3(); } while (ll_bad<12>(lt, tag) && ++it < SPIN_LIMIT);
      }
#pragma unroll
      for (int q = 0; q < 3; q++) acc(*reinterpret_cast<uint32_t (*)[4][4]>(&lt[4 * q]));
      PSTAMP(14);
      mbar_wait_par(BAR + (B_OE + p) * 8, 0);
#pragma unroll
      for (int u = 0; u < 4; u++) {
        uint32_t o[4];
#pragma unroll
        for (int e = 0; e < 4; e++) o[e] = pack2(sum[8 * u + 2 * e] + y[8 * u + 2 * e], sum[8 * u + 2 * e + 1] + y[8 * u + 2 * e + 1]);
        stsm4(stg + (moff ^ (u << 5)), o);
      }
      fence_async_smem();
      __syncwarp();
      if (elect_one()) {
        tma3d_store(&P.out, stg, 64 * j, p, g * 64 + 16 * w);
        asm volatile("cp.async.bulk.commit_group;" ::: "memory");
        asm volatile("cp.async.bulk.wait_group.read 0;" ::: "memory");
      }
      PSTAMP(15);
    }
  }
}

typedef CUresult (*EncodeFn)(CUtensorMap*, CUtensorMapDataType, cuuint32_t, void*, const cuuint64_t*, const cuuint64_t*,
                             const cuuint32_t*, const cuuint32_t*, CUtensorMapInterleave, CUtensorMapSwizzle,
                             CUtensorMapL2promotion, CUtensorMapFloatOOBfill);

void enc2d(EncodeFn f, CUtensorMap* m, const void* base, uint64_t cols, uint64_t rows, uint32_t bc, uint32_t br, CUtensorMapSwizzle sw) {
  cuuint64_t gd[2] = {cols, rows}, gs[1] = {cols * 2};
  cuuint32_t bd[2] = {bc, br}, es[2] = {1, 1};
  f(m, CU_TENSOR_MAP_DATA_TYPE_BFLOAT16, 2, const_cast<void*>(base), gd, gs, bd, es, CU_TENSOR_MAP_INTERLEAVE_NONE, sw,
    CU_TENSOR_MAP_L2_PROMOTION_L2_128B, CU_TENSOR_MAP_FLOAT_OOB_FILL_NONE);
}
void enc_par(EncodeFn f, CUtensorMap* m, const void* base, uint32_t pairs) {
  cuuint64_t gd[3] = {(cuuint64_t)D_, 2, (cuuint64_t)S_ / 2}, gs[2] = {D_ * 2, D_ * 4};
  cuuint32_t bd[3] = {64, 1, pairs}, es[3] = {1, 1, 1};
  f(m, CU_TENSOR_MAP_DATA_TYPE_BFLOAT16, 3, const_cast<void*>(base), gd, gs, bd, es, CU_TENSOR_MAP_INTERLEAVE_NONE,
    CU_TENSOR_MAP_SWIZZLE_128B, CU_TENSOR_MAP_L2_PROMOTION_L2_128B, CU_TENSOR_MAP_FLOAT_OOB_FILL_NONE);
}

}

extern "C" void kernel_launch(void* const* d_in, const int* in_sizes, int n_in, void* d_out, int out_size) {
  (void)in_sizes; (void)n_in; (void)out_size;
  static EncodeFn enc = nullptr;
  static Scratch* scratch = nullptr;
  if (!enc) {
    void* fn = nullptr;
    cudaDriverEntryPointQueryResult q;
    cudaGetDriverEntryPoint("cuTensorMapEncodeTiled", &fn, cudaEnableDefault, &q);
    enc = (EncodeFn)fn;
    cudaGetSymbolAddress((void**)&scratch, g_scratch);
    cudaFuncSetAttribute(fused_block_kernel, cudaFuncAttributeMaxDynamicSharedMemorySize, SMEM_BYTES);
  }
  Params P;
  const __nv_bfloat16* xp = (const __nv_bfloat16*)d_in[0];
  const __nv_bfloat16* wqkvp = (const __nv_bfloat16*)d_in[1];
  const __nv_bfloat16* wop = (const __nv_bfloat16*)d_in[2];
  P.w1p = (const __nv_bfloat16*)d_in[4];
  P.w3p = (const __nv_bfloat16*)d_in[5];
  P.w2p = (const __nv_bfloat16*)d_in[6];
  enc_par(enc, &P.x, xp, 64);
  enc_par(enc, &P.out, d_out, 16);
  enc2d(enc, &P.wqkv, wqkvp, 3 * D_, D_, 64, 64, CU_TENSOR_MAP_SWIZZLE_128B);
  enc2d(enc, &P.wo, wop, D_, D_, 64, 64, CU_TENSOR_MAP_SWIZZLE_128B);
  enc2d(enc, &P.w1, P.w1p, F_, D_, 64, 64, CU_TENSOR_MAP_SWIZZLE_128B);
  enc2d(enc, &P.w3, P.w3p, F_, D_, 64, 64, CU_TENSOR_MAP_SWIZZLE_128B);
  enc2d(enc, &P.w1h, P.w1p, F_, D_, 32, 64, CU_TENSOR_MAP_SWIZZLE_64B);
  enc2d(enc, &P.w3h, P.w3p, F_, D_, 32, 64, CU_TENSOR_MAP_SWIZZLE_64B);
  enc2d(enc, &P.w2, P.w2p, D_, F_, 64, 224, CU_TENSOR_MAP_SWIZZLE_128B);

  cudaLaunchConfig_t cfg = {};
  cfg.gridDim = dim3(128);
  cfg.blockDim = dim3(384);
  cfg.dynamicSmemBytes = SMEM_BYTES;
  cfg.stream = cudaStreamPerThread;
  cudaLaunchAttribute at[1];
  at[0].id = cudaLaunchAttributeCooperative;
  at[0].val.cooperative = 1;
  cfg.attrs = at;
  cfg.numAttrs = 1;
  cudaLaunchKernelEx(&cfg, fused_block_kernel, scratch, xp, wqkvp, wop, 0u, P);
}
```

```cpp
#include <cuda_runtime.h>
#include <cuda.h>
#include <cuda_bf16.h>
#include <stdint.h>
#include <stddef.h>

namespace {

constexpr int S_ = 2048, D_ = 512, F_ = 1792;
#define LAG_KB 3
#define E4_FIRST 7
#define PP_AHEAD 1
#define SIDE_KB 0
#define CLR_MODE 0
#define W2_HEAD 3
#define CLR_SLEEP 400
#define XO_DELAY 2

constexpr uint32_t SPIN_LIMIT = 1u << 18;

struct Scratch {
  uint4 e4[16 * 2 * 4 * 8 * 8 * 4 * 32];
  uint4 e2[16 * 2 * 4 * 32 * 32];
  uint4 e3h[16 * 2 * 4 * 32 * 32];
  uint4 e1[16 * 8 * 2 * 4 * 32];
  uint4 e2s[16 * 2 * 4 * 8 * 8];
  uint4 e3s[16 * 2 * 4 * 8 * 8];
  uint4 e0c[8 * 3 * 16 * 16];
  uint4 e0s[2048];
  uint4 e0w[8 * 64];
  unsigned sent[16 * 8 * 8 * 2];
  unsigned epoch[128];
};
__device__ Scratch g_scratch;
#define PSTAMP(i)
#define PSTAMPW(slot, i)
#define W2STAMP(i)

struct alignas(64) Params {
  CUtensorMap x, out, wqkv, wo, w1, w3, w1h, w3h, w2;
  const __nv_bfloat16 *w1p, *w3p, *w2p;
};

constexpr uint32_t SB = 1024;
constexpr uint32_t H0 = SB;
constexpr uint32_t H1 = SB + 65536;
constexpr uint32_t RING = SB + 131072;
constexpr uint32_t BAR = SB + 229376;
constexpr uint32_t TAGS = BAR + 1016;
constexpr uint32_t CS = BAR + 1024;
constexpr uint32_t ST = CS + 768;
constexpr uint32_t WB = ST + 1024;
constexpr uint32_t SMEM_BYTES = 232448;
static_assert(WB + 256 <= SB + SMEM_BYTES, "smem");

enum : int {
  B_FX = 0,
  B_FKV = 16, B_FQ = 24, B_FWO = 32, B_FA = 40, B_FB = 48, B_FT = 56,
  B_EKV = 64, B_EQ = 72, B_EA = 80, B_EB = 88, B_ET0 = 96,
  B_WODONE = 103,
  B_FIN = 33,
  B_EX = 104,
  B_LAG = 112, B_READY = 113, B_PUB = 114, B_CLR = 115, B_CLR0 = 116, B_TAG = 117,
  B_OE = 118, B_OF = 120
};

__device__ __forceinline__ uint32_t smem_u32(const void* p) { return (uint32_t)__cvta_generic_to_shared(p); }
__device__ __forceinline__ void mbar_init(uint32_t b, uint32_t c) { asm volatile("mbarrier.init.shared::cta.b64 [%0], %1;" ::"r"(b), "r"(c) : "memory"); }
__device__ __forceinline__ void mbar_expect_tx(uint32_t b, uint32_t bytes) { asm volatile("mbarrier.arrive.expect_tx.shared::cta.b64 _, [%0], %1;" ::"r"(b), "r"(bytes) : "memory"); }
__device__ __forceinline__ void mbar_arrive(uint32_t b) { asm volatile("mbarrier.arrive.shared::cta.b64 _, [%0];" ::"r"(b) : "memory"); }
__device__ __forceinline__ void mbar_wait(uint32_t b) {
  asm volatile("{\n.reg .pred p;\n.reg .u32 c;\nmov.u32 c, 0;\nLW:\n.pragma \"nounroll\";\n"
               "mbarrier.try_wait.parity.shared::cta.b64 p, [%0], 0;\nadd.u32 c, c, 1;\nsetp.gt.or.u32 p, c, %1, p;\n@!p bra LW;\n}\n"
               ::"r"(b), "n"(SPIN_LIMIT) : "memory");
}
__device__ __forceinline__ void mbar_wait_par(uint32_t b, uint32_t parity) {
  asm volatile("{\n.reg .pred p;\n.reg .u32 c;\nmov.u32 c, 0;\nLW:\n.pragma \"nounroll\";\n"
               "mbarrier.try_wait.parity.shared::cta.b64 p, [%0], %2;\nadd.u32 c, c, 1;\nsetp.gt.or.u32 p, c, %1, p;\n@!p bra LW;\n}\n"
               ::"r"(b), "n"(SPIN_LIMIT), "r"(parity) : "memory");
}
__device__ __forceinline__ bool elect_one() {
  uint32_t p;
  asm volatile("{\n.reg .pred P;\nelect.sync _|P, 0xffffffff;\nselp.u32 %0, 1, 0, P;\n}\n" : "=r"(p));
  return p;
}
__device__ __forceinline__ void tma2d(uint32_t dst, const CUtensorMap* m, int c0, int c1, uint32_t bar) {
  asm volatile("cp.async.bulk.tensor.2d.shared::cluster.global.mbarrier::complete_tx::bytes [%0], [%1, {%3, %4}], [%2];"
               ::"r"(dst), "l"(m), "r"(bar), "r"(c0), "r"(c1) : "memory");
}
__device__ __forceinline__ void tma3d(uint32_t dst, const CUtensorMap* m, int c0, int c1, int c2, uint32_t bar) {
  asm volatile("cp.async.bulk.tensor.3d.shared::cluster.global.mbarrier::complete_tx::bytes [%0], [%1, {%3, %4, %5}], [%2];"
               ::"r"(dst), "l"(m), "r"(bar), "r"(c0), "r"(c1), "r"(c2) : "memory");
}
__device__ __forceinline__ void tma3d_store(const CUtensorMap* m, uint32_t src, int c0, int c1, int c2) {
  asm volatile("cp.async.bulk.tensor.3d.global.shared::cta.bulk_group [%0, {%2, %3, %4}], [%1];"
               ::"l"(m), "r"(src), "r"(c0), "r"(c1), "r"(c2) : "memory");
}
__device__ __forceinline__ void l2_prefetch(const void* p, uint32_t bytes) {
  asm volatile("cp.async.bulk.prefetch.L2.global [%0], %1;" ::"l"(p), "r"(bytes) : "memory");
}
__device__ __forceinline__ void prefetch_map(const CUtensorMap* m) { asm volatile("prefetch.tensormap [%0];" ::"l"(m) : "memory"); }
__device__ __forceinline__ void fence_async_smem() { asm volatile("fence.proxy.async.shared::cta;" ::: "memory"); }
__device__ __forceinline__ void wg_fence() { asm volatile("wgmma.fence.sync.aligned;" ::: "memory"); }
__device__ __forceinline__ void wg_commit() { asm volatile("wgmma.commit_group.sync.aligned;" ::: "memory"); }
template <int N> __device__ __forceinline__ void wg_wait() { asm volatile("wgmma.wait_group.sync.aligned %0;" ::"n"(N) : "memory"); }
__device__ __forceinline__ void wg_bar(int p) {
  if (p == 0) asm volatile("bar.sync 1, 128;" ::: "memory"); else asm volatile("bar.sync 2, 128;" ::: "memory");
}
constexpr uint32_t DESC_HI128 = (1024 >> 4) | (1u << 30);
constexpr uint32_t DESC_HI64 = (512 >> 4) | (2u << 30);
__device__ __forceinline__ constexpr uint32_t descA(uint32_t addr) { return (addr >> 4) | (1u << 16); }
__device__ __forceinline__ constexpr uint32_t descB(uint32_t addr) { return (addr >> 4) | ((8192u >> 4) << 16); }
__device__ __forceinline__ constexpr uint32_t descBh(uint32_t addr) { return (addr >> 4) | ((4096u >> 4) << 16); }

__device__ __forceinline__ void wgmma_ss_n64(float (&d)[32], uint32_t da, uint32_t db, int sc) {
  asm volatile("{\n.reg .pred p;\n.reg .b64 da, db;\nsetp.ne.b32 p, %34, 0;\nmov.b64 da, {%32, %35};\nmov.b64 db, {%33, %35};\n"
    "wgmma.mma_async.sync.aligned.m64n64k16.f32.bf16.bf16 {%0, %1, %2, %3, %4, %5, %6, %7, %8, %9, %10, %11, %12, %13, %14, %15, %16, %17, %18, %19, %20, %21, %22, %23, %24, %25, %26, %27, %28, %29, %30, %31}, da, db, p, 1, 1, 0, 1;\n}\n"
    : "+f"(d[0]), "+f"(d[1]), "+f"(d[2]), "+f"(d[3]), "+f"(d[4]), "+f"(d[5]), "+f"(d[6]), "+f"(d[7]),
      "+f"(d[8]), "+f"(d[9]), "+f"(d[10]), "+f"(d[11]), "+f"(d[12]), "+f"(d[13]), "+f"(d[14]), "+f"(d[15]),
      "+f"(d[16]), "+f"(d[17]), "+f"(d[18]), "+f"(d[19]), "+f"(d[20]), "+f"(d[21]), "+f"(d[22]), "+f"(d[23]),
      "+f"(d[24]), "+f"(d[25]), "+f"(d[26]), "+f"(d[27]), "+f"(d[28]), "+f"(d[29]), "+f"(d[30]), "+f"(d[31])
    : "r"(da), "r"(db), "r"(sc), "n"(DESC_HI128));
}
__device__ __forceinline__ void wgmma_ss_n128(float (&d)[64], uint32_t da, uint32_t db, int sc) {
  asm volatile("{\n.reg .pred p;\n.reg .b64 da, db;\nsetp.ne.b32 p, %66, 0;\nmov.b64 da, {%64, %67};\nmov.b64 db, {%65, %67};\n"
    "wgmma.mma_async.sync.aligned.m64n128k16.f32.bf16.bf16 {%0, %1, %2, %3, %4, %5, %6, %7, %8, %9, %10, %11, %12, %13, %14, %15, %16, %17, %18, %19, %20, %21, %22, %23, %24, %25, %26, %27, %28, %29, %30, %31, %32, %33, %34, %35, %36, %37, %38, %39, %40, %41, %42, %43, %44, %45, %46, %47, %48, %49, %50, %51, %52, %53, %54, %55, %56, %57, %58, %59, %60, %61, %62, %63}, da, db, p, 1, 1, 0, 1;\n}\n"
    : "+f"(d[0]), "+f"(d[1]), "+f"(d[2]), "+f"(d[3]), "+f"(d[4]), "+f"(d[5]), "+f"(d[6]), "+f"(d[7]),
      "+f"(d[8]), "+f"(d[9]), "+f"(d[10]), "+f"(d[11]), "+f"(d[12]), "+f"(d[13]), "+f"(d[14]), "+f"(d[15]),
      "+f"(d[16]), "+f"(d[17]), "+f"(d[18]), "+f"(d[19]), "+f"(d[20]), "+f"(d[21]), "+f"(d[22]), "+f"(d[23]),
      "+f"(d[24]), "+f"(d[25]), "+f"(d[26]), "+f"(d[27]), "+f"(d[28]), "+f"(d[29]), "+f"(d[30]), "+f"(d[31]),
      "+f"(d[32]), "+f"(d[33]), "+f"(d[34]), "+f"(d[35]), "+f"(d[36]), "+f"(d[37]), "+f"(d[38]), "+f"(d[39]),
      "+f"(d[40]), "+f"(d[41]), "+f"(d[42]), "+f"(d[43]), "+f"(d[44]), "+f"(d[45]), "+f"(d[46]), "+f"(d[47]),
      "+f"(d[48]), "+f"(d[49]), "+f"(d[50]), "+f"(d[51]), "+f"(d[52]), "+f"(d[53]), "+f"(d[54]), "+f"(d[55]),
      "+f"(d[56]), "+f"(d[57]), "+f"(d[58]), "+f"(d[59]), "+f"(d[60]), "+f"(d[61]), "+f"(d[62]), "+f"(d[63])
    : "r"(da), "r"(db), "r"(sc), "n"(DESC_HI128));
}
__device__ __forceinline__ void wgmma_ss_n256(float (&d)[128], uint32_t da, uint32_t db, int sc) {
  asm volatile("{\n.reg .pred p;\n.reg .b64 da, db;\nsetp.ne.b32 p, %130, 0;\nmov.b64 da, {%128, %131};\nmov.b64 db, {%129, %131};\n"
    "wgmma.mma_async.sync.aligned.m64n256k16.f32.bf16.bf16 {%0, %1, %2, %3, %4, %5, %6, %7, %8, %9, %10, %11, %12, %13, %14, %15, %16, %17, %18, %19, %20, %21, %22, %23, %24, %25, %26, %27, %28, %29, %30, %31, %32, %33, %34, %35, %36, %37, %38, %39, %40, %41, %42, %43, %44, %45, %46, %47, %48, %49, %50, %51, %52, %53, %54, %55, %56, %57, %58, %59, %60, %61, %62, %63, %64, %65, %66, %67, %68, %69, %70, %71, %72, %73, %74, %75, %76, %77, %78, %79, %80, %81, %82, %83, %84, %85, %86, %87, %88, %89, %90, %91, %92, %93, %94, %95, %96, %97, %98, %99, %100, %101, %102, %103, %104, %105, %106, %107, %108, %109, %110, %111, %112, %113, %114, %115, %116, %117, %118, %119, %120, %121, %122, %123, %124, %125, %126, %127}, da, db, p, 1, 1, 0, 1;\n}\n"
    : "+f"(d[0]), "+f"(d[1]), "+f"(d[2]), "+f"(d[3]), "+f"(d[4]), "+f"(d[5]), "+f"(d[6]), "+f"(d[7]),
      "+f"(d[8]), "+f"(d[9]), "+f"(d[10]), "+f"(d[11]), "+f"(d[12]), "+f"(d[13]), "+f"(d[14]), "+f"(d[15]),
      "+f"(d[16]), "+f"(d[17]), "+f"(d[18]), "+f"(d[19]), "+f"(d[20]), "+f"(d[21]), "+f"(d[22]), "+f"(d[23]),
      "+f"(d[24]), "+f"(d[25]), "+f"(d[26]), "+f"(d[27]), "+f"(d[28]), "+f"(d[29]), "+f"(d[30]), "+f"(d[31]),
      "+f"(d[32]), "+f"(d[33]), "+f"(d[34]), "+f"(d[35]), "+f"(d[36]), "+f"(d[37]), "+f"(d[38]), "+f"(d[39]),
      "+f"(d[40]), "+f"(d[41]), "+f"(d[42]), "+f"(d[43]), "+f"(d[44]), "+f"(d[45]), "+f"(d[46]), "+f"(d[47]),
      "+f"(d[48]), "+f"(d[49]), "+f"(d[50]), "+f"(d[51]), "+f"(d[52]), "+f"(d[53]), "+f"(d[54]), "+f"(d[55]),
      "+f"(d[56]), "+f"(d[57]), "+f"(d[58]), "+f"(d[59]), "+f"(d[60]), "+f"(d[61]), "+f"(d[62]), "+f"(d[63]),
      "+f"(d[64]), "+f"(d[65]), "+f"(d[66]), "+f"(d[67]), "+f"(d[68]), "+f"(d[69]), "+f"(d[70]), "+f"(d[71]),
      "+f"(d[72]), "+f"(d[73]), "+f"(d[74]), "+f"(d[75]), "+f"(d[76]), "+f"(d[77]), "+f"(d[78]), "+f"(d[79]),
      "+f"(d[80]), "+f"(d[81]), "+f"(d[82]), "+f"(d[83]), "+f"(d[84]), "+f"(d[85]), "+f"(d[86]), "+f"(d[87]),
      "+f"(d[88]), "+f"(d[89]), "+f"(d[90]), "+f"(d[91]), "+f"(d[92]), "+f"(d[93]), "+f"(d[94]), "+f"(d[95]),
      "+f"(d[96]), "+f"(d[97]), "+f"(d[98]), "+f"(d[99]), "+f"(d[100]), "+f"(d[101]), "+f"(d[102]), "+f"(d[103]),
      "+f"(d[104]), "+f"(d[105]), "+f"(d[106]), "+f"(d[107]), "+f"(d[108]), "+f"(d[109]), "+f"(d[110]), "+f"(d[111]),
      "+f"(d[112]), "+f"(d[113]), "+f"(d[114]), "+f"(d[115]), "+f"(d[116]), "+f"(d[117]), "+f"(d[118]), "+f"(d[119]),
      "+f"(d[120]), "+f"(d[121]), "+f"(d[122]), "+f"(d[123]), "+f"(d[124]), "+f"(d[125]), "+f"(d[126]), "+f"(d[127])
    : "r"(da), "r"(db), "r"(sc), "n"(DESC_HI128));
}
template <uint32_t HI = DESC_HI128>
__device__ __forceinline__ void wgmma_rs_n64(float (&d)[32], const uint32_t (&a)[4], uint32_t db, int sc) {
  asm volatile("{\n.reg .pred p;\n.reg .b64 db;\nsetp.ne.b32 p, %37, 0;\nmov.b64 db, {%36, %38};\n"
    "wgmma.mma_async.sync.aligned.m64n64k16.f32.bf16.bf16 {%0, %1, %2, %3, %4, %5, %6, %7, %8, %9, %10, %11, %12, %13, %14, %15, %16, %17, %18, %19, %20, %21, %22, %23, %24, %25, %26, %27, %28, %29, %30, %31}, {%32, %33, %34, %35}, db, p, 1, 1, 1;\n}\n"
    : "+f"(d[0]), "+f"(d[1]), "+f"(d[2]), "+f"(d[3]), "+f"(d[4]), "+f"(d[5]), "+f"(d[6]), "+f"(d[7]),
      "+f"(d[8]), "+f"(d[9]), "+f"(d[10]), "+f"(d[11]), "+f"(d[12]), "+f"(d[13]), "+f"(d[14]), "+f"(d[15]),
      "+f"(d[16]), "+f"(d[17]), "+f"(d[18]), "+f"(d[19]), "+f"(d[20]), "+f"(d[21]), "+f"(d[22]), "+f"(d[23]),
      "+f"(d[24]), "+f"(d[25]), "+f"(d[26]), "+f"(d[27]), "+f"(d[28]), "+f"(d[29]), "+f"(d[30]), "+f"(d[31])
    : "r"(a[0]), "r"(a[1]), "r"(a[2]), "r"(a[3]), "r"(db), "r"(sc), "n"(HI));
}
template <uint32_t HI = DESC_HI128>
__device__ __forceinline__ void wgmma_rs_n128(float (&d)[64], const uint32_t (&a)[4], uint32_t db, int sc) {
  asm volatile("{\n.reg .pred p;\n.reg .b64 db;\nsetp.ne.b32 p, %69, 0;\nmov.b64 db, {%68, %70};\n"
    "wgmma.mma_async.sync.aligned.m64n128k16.f32.bf16.bf16 {%0, %1, %2, %3, %4, %5, %6, %7, %8, %9, %10, %11, %12, %13, %14, %15, %16, %17, %18, %19, %20, %21, %22, %23, %24, %25, %26, %27, %28, %29, %30, %31, %32, %33, %34, %35, %36, %37, %38, %39, %40, %41, %42, %43, %44, %45, %46, %47, %48, %49, %50, %51, %52, %53, %54, %55, %56, %57, %58, %59, %60, %61, %62, %63}, {%64, %65, %66, %67}, db, p, 1, 1, 1;\n}\n"
    : "+f"(d[0]), "+f"(d[1]), "+f"(d[2]), "+f"(d[3]), "+f"(d[4]), "+f"(d[5]), "+f"(d[6]), "+f"(d[7]),
      "+f"(d[8]), "+f"(d[9]), "+f"(d[10]), "+f"(d[11]), "+f"(d[12]), "+f"(d[13]), "+f"(d[14]), "+f"(d[15]),
      "+f"(d[16]), "+f"(d[17]), "+f"(d[18]), "+f"(d[19]), "+f"(d[20]), "+f"(d[21]), "+f"(d[22]), "+f"(d[23]),
      "+f"(d[24]), "+f"(d[25]), "+f"(d[26]), "+f"(d[27]), "+f"(d[28]), "+f"(d[29]), "+f"(d[30]), "+f"(d[31]),
      "+f"(d[32]), "+f"(d[33]), "+f"(d[34]), "+f"(d[35]), "+f"(d[36]), "+f"(d[37]), "+f"(d[38]), "+f"(d[39]),
      "+f"(d[40]), "+f"(d[41]), "+f"(d[42]), "+f"(d[43]), "+f"(d[44]), "+f"(d[45]), "+f"(d[46]), "+f"(d[47]),
      "+f"(d[48]), "+f"(d[49]), "+f"(d[50]), "+f"(d[51]), "+f"(d[52]), "+f"(d[53]), "+f"(d[54]), "+f"(d[55]),
      "+f"(d[56]), "+f"(d[57]), "+f"(d[58]), "+f"(d[59]), "+f"(d[60]), "+f"(d[61]), "+f"(d[62]), "+f"(d[63])
    : "r"(a[0]), "r"(a[1]), "r"(a[2]), "r"(a[3]), "r"(db), "r"(sc), "n"(HI));
}

template <int N> __device__ __forceinline__ void keep(float (&d)[N]) {
#pragma unroll
  for (int i = 0; i < N; i++) asm volatile("" : "+f"(d[i])::"memory");
}

__device__ __forceinline__ void keep(uint32_t (&d)[4]) { asm volatile("" : "+r"(d[0]), "+r"(d[1]), "+r"(d[2]), "+r"(d[3])::"memory"); }
template <int N> __device__ __forceinline__ void keep(uint32_t (&d)[N][4]) {
#pragma unroll
  for (int i = 0; i < N; i++) asm volatile("" : "+r"(d[i][0]), "+r"(d[i][1]), "+r"(d[i][2]), "+r"(d[i][3])::"memory");
}

__device__ __forceinline__ uint32_t pack2(float lo, float hi) {
  uint32_t r;
  asm("cvt.rn.bf16x2.f32 %0, %1, %2;" : "=r"(r) : "f"(hi), "f"(lo));
  return r;
}
__device__ __forceinline__ float bf_lo(uint32_t v) { return __uint_as_float(v << 16); }
__device__ __forceinline__ float bf_hi(uint32_t v) { return __uint_as_float(v & 0xffff0000u); }
__device__ __forceinline__ uint32_t hsub2(uint32_t a, uint32_t b) {
  uint32_t r;
  asm("sub.rn.bf16x2 %0, %1, %2;" : "=r"(r) : "r"(a), "r"(b));
  return r;
}
__device__ __forceinline__ uint32_t movm(uint32_t a) {
  uint32_t r;
  asm volatile("movmatrix.sync.aligned.m8n8.trans.b16 %0, %1;" : "=r"(r) : "r"(a));
  return r;
}
__device__ __forceinline__ void ldsm4(uint32_t (&v)[4], uint32_t a) {
  asm volatile("ldmatrix.sync.aligned.m8n8.x4.shared.b16 {%0,%1,%2,%3}, [%4];" : "=r"(v[0]), "=r"(v[1]), "=r"(v[2]), "=r"(v[3]) : "r"(a) : "memory");
}
__device__ __forceinline__ void stsm4(uint32_t a, const uint32_t (&v)[4]) {
  asm volatile("stmatrix.sync.aligned.m8n8.x4.shared.b16 [%0], {%1,%2,%3,%4};" ::"r"(a), "r"(v[0]), "r"(v[1]), "r"(v[2]), "r"(v[3]) : "memory");
}
__device__ __forceinline__ void mma16816(float (&d)[4], const uint32_t (&a)[4], uint32_t b0, uint32_t b1) {
  asm volatile("mma.sync.aligned.m16n8k16.row.col.f32.bf16.bf16.f32 {%0,%1,%2,%3}, {%4,%5,%6,%7}, {%8,%9}, {%10,%10,%10,%10};"
               : "=f"(d[0]), "=f"(d[1]), "=f"(d[2]), "=f"(d[3])
               : "r"(a[0]), "r"(a[1]), "r"(a[2]), "r"(a[3]), "r"(b0), "r"(b1), "f"(0.f));
}
__device__ __forceinline__ void mma1688_acc(float (&d)[4], uint32_t a0, uint32_t a1, uint32_t b0) {
  asm volatile("mma.sync.aligned.m16n8k8.row.col.f32.bf16.bf16.f32 {%0,%1,%2,%3}, {%4,%5}, {%6}, {%0,%1,%2,%3};"
               : "+f"(d[0]), "+f"(d[1]), "+f"(d[2]), "+f"(d[3]) : "r"(a0), "r"(a1), "r"(b0));
}
__device__ __forceinline__ float ex2(float x) { float y; asm("ex2.approx.ftz.f32 %0, %1;" : "=f"(y) : "f"(x)); return y; }
__device__ __forceinline__ float rcp(float x) { float y; asm("rcp.approx.ftz.f32 %0, %1;" : "=f"(y) : "f"(x)); return y; }
__device__ __forceinline__ float tanhf_hw(float x) { float y; asm("tanh.approx.f32 %0, %1;" : "=f"(y) : "f"(x)); return y; }
__device__ __forceinline__ uint32_t lds32(uint32_t a) { uint32_t v; asm volatile("ld.shared.u32 %0, [%1];" : "=r"(v) : "r"(a) : "memory"); return v; }
__device__ __forceinline__ float2 lds64(uint32_t a) { float2 v; asm volatile("ld.shared.v2.f32 {%0,%1}, [%2];" : "=f"(v.x), "=f"(v.y) : "r"(a) : "memory"); return v; }
__device__ __forceinline__ void lds128(uint32_t (&v)[4], uint32_t a) { asm volatile("ld.shared.v4.u32 {%0,%1,%2,%3}, [%4];" : "=r"(v[0]), "=r"(v[1]), "=r"(v[2]), "=r"(v[3]) : "r"(a) : "memory"); }
__device__ __forceinline__ void sts128(uint32_t a, const uint32_t (&v)[4]) { asm volatile("st.shared.v4.u32 [%0], {%1,%2,%3,%4};" ::"r"(a), "r"(v[0]), "r"(v[1]), "r"(v[2]), "r"(v[3]) : "memory"); }
__device__ __forceinline__ void ldg128_nc(uint32_t (&v)[4], const void* p) {
  asm volatile("ld.global.nc.L1::no_allocate.v4.u32 {%0,%1,%2,%3}, [%4];" : "=r"(v[0]), "=r"(v[1]), "=r"(v[2]), "=r"(v[3]) : "l"(p));
}
__device__ __forceinline__ uint32_t pin(uint32_t v, uint32_t zero) {
  asm volatile("{\n.reg .pred p;\n.reg .u32 c;\nmov.u32 c, %1;\nLP:\n.pragma \"nounroll\";\nsetp.eq.u32 p, c, 0;\n@p bra LD;\n"
               "nanosleep.u32 c;\nadd.u32 %0, %0, c;\nsub.u32 c, c, 1;\nbra LP;\nLD:\n}\n" : "+r"(v) : "r"(zero) : "memory");
  return v;
}
__device__ __forceinline__ void mbar_arrive_if(uint32_t b, bool cond) {
  asm volatile("{\n.reg .pred p;\nsetp.ne.u32 p, %1, 0;\n@p mbarrier.arrive.shared::cta.b64 _, [%0];\n}\n" ::"r"(b), "r"((uint32_t)cond) : "memory");
}
__device__ __forceinline__ uint32_t ld_epoch(const unsigned* p) {
  uint32_t v;
  asm volatile("ld.relaxed.gpu.global.u32 %0, [%1];" : "=r"(v) : "l"(p) : "memory");
  return v;
}
__device__ __forceinline__ void ll_st(uint4* p, uint32_t a, uint32_t b, uint32_t c, uint32_t d, uint32_t tag) {
  asm volatile("st.relaxed.gpu.global.v4.b32 [%0], {%1, %2, %3, %4};" ::"l"(p), "r"((a & ~1u) | tag), "r"(b), "r"(c), "r"(d) : "memory");
}
__device__ __forceinline__ void ll_ld(uint32_t (&v)[4], const uint4* p) {
  asm volatile("{\n.reg .b128 t;\n.reg .b64 lo, hi;\nld.relaxed.gpu.global.b128 t, [%4];\nmov.b128 {lo, hi}, t;\n"
               "mov.b64 {%0, %1}, lo;\nmov.b64 {%2, %3}, hi;\n}\n"
               : "=r"(v[0]), "=r"(v[1]), "=r"(v[2]), "=r"(v[3]) : "l"(p) : "memory");
}
template <int N> __device__ __forceinline__ void ll_issue(uint32_t (&v)[N][4], const uint4* p, int stride) {
#pragma unroll
  for (int i = 0; i < N; i++) ll_ld(v[i], p + i * stride);
}
template <int N> __device__ __forceinline__ uint32_t ll_acc(const uint32_t (&v)[N][4], uint32_t tag, uint32_t acc = 0) {
#pragma unroll
  for (int i = 0; i < N; i++) asm("lop3.b32 %0, %1, %2, %0, 0xBE;" : "+r"(acc) : "r"(v[i][0]), "r"(tag));
  return acc;
}
__device__ __forceinline__ bool ll_any(uint32_t acc) { return __any_sync(0xffffffffu, acc & 1u); }
template <int N> __device__ __forceinline__ bool ll_bad(const uint32_t (&v)[N][4], uint32_t tag) { return ll_any(ll_acc<N>(v, tag)); }
template <int N> __device__ __forceinline__ void ll_clear(uint32_t (&v)[N][4]) {
#pragma unroll
  for (int i = 0; i < N; i++) v[i][0] &= ~1u;
}
template <int N> __device__ __forceinline__ void ll_spin(uint32_t (&v)[N][4], const uint4* p, int stride, uint32_t tag) {
  uint32_t it = 0;
#pragma unroll 1
  do { ll_issue<N>(v, p, stride); } while (ll_bad<N>(v, tag) && ++it < SPIN_LIMIT);
}
template <int N> __device__ __forceinline__ void ll_get(uint32_t (&v)[N][4], const uint4* p, int stride, uint32_t tag) {
  ll_spin<N>(v, p, stride, tag);
  ll_clear<N>(v);
}
template <int N> __device__ __forceinline__ void ll_wait(uint32_t (&v)[N][4], const uint4* p, int stride, uint32_t tag) {
  if (__builtin_expect(ll_bad<N>(v, tag), 0)) ll_spin<N>(v, p, stride, tag);
  ll_clear<N>(v);
}
__device__ __forceinline__ void unpack32(float (&d)[32], const uint32_t (&v)[4][4]) {
#pragma unroll
  for (int u = 0; u < 4; u++)
#pragma unroll
    for (int e = 0; e < 4; e++) { d[8 * u + 2 * e] = bf_lo(v[u][e]); d[8 * u + 2 * e + 1] = bf_hi(v[u][e]); }
}
__device__ __forceinline__ void pack32(uint32_t (&v)[4][4], const float (&d)[32]) {
#pragma unroll
  for (int u = 0; u < 4; u++)
#pragma unroll
    for (int e = 0; e < 4; e++) v[u][e] = pack2(d[8 * u + 2 * e], d[8 * u + 2 * e + 1]);
}
__device__ __forceinline__ uint32_t t_addr(int m) { return SB + ((0x03514620u >> (4 * m)) & 7u) * 32768u; }

__device__ __forceinline__ int kb_at(int i, int j) { return i == 0 ? j : (i - 1 + (i - 1 >= j ? 1 : 0)); }

__device__ __forceinline__ void init_bars(int set) {
  if (set >= 0 && elect_one()) {
    const uint32_t cnt = set < 5 ? 1 : 8;
#pragma unroll
    for (int i = 0; i < 8; i++) mbar_init(BAR + (24 + 8 * set + i) * 8, cnt);
    if (set == 9) {
#pragma unroll
      for (int i = 0; i < 9; i++) mbar_init(BAR + (B_EX + i) * 8, 4);
#pragma unroll
      for (int i = 0; i < 4; i++) mbar_init(BAR + (B_READY + i) * 8, i == 1 ? 7 : 3);
#pragma unroll
      for (int i = 0; i < 5; i++) mbar_init(BAR + (B_TAG + i) * 8, i < 3 ? 1 : 4);
    }
    asm volatile("fence.mbarrier_init.release.cluster;" ::: "memory");
  }
  __syncwarp();
  asm volatile("bar.arrive 4, 384;" ::: "memory");
  asm volatile("bar.sync 3, 384;" ::: "memory");
}

__device__ __forceinline__ uint32_t in_addr(int q, int p) { return q < 5 ? t_addr(q + 1) + p * 8192 : t_addr(p + 1) + 16384; }
__device__ __forceinline__ void receive_partials(Scratch* X, int g, int j, int p) {
  const uint32_t tag = lds32(TAGS);
  mbar_expect_tx(BAR + (B_FIN + p) * 8, 6 * 8192);
#pragma unroll 1
  for (int q = 0; q < 6; q++) {
    const int slot = (g * 8 + j) * 8 + ((j - 1 - q) & 7);
    uint32_t it = 0;
#pragma unroll 1
    while (ld_epoch(X->sent + slot * 2 + p) != tag && ++it < SPIN_LIMIT) {}
    mbar_wait(BAR + (B_ET0 + min(q + 1, 5)) * 8);
    asm volatile("cp.async.bulk.shared::cluster.global.mbarrier::complete_tx::bytes [%0], [%1], 8192, [%2];"
                 ::"r"(in_addr(q, p)), "l"(X->e4 + slot * 1024 + p * 512), "r"(BAR + (B_FIN + p) * 8) : "memory");
  }
}

__global__ void __launch_bounds__(384, 1) fused_block_kernel(Scratch* __restrict__ X, const __nv_bfloat16* __restrict__ xp,
                                                             const __nv_bfloat16* __restrict__ wqkvp, const __nv_bfloat16* __restrict__ wop, const uint32_t zero,
                                                             const __grid_constant__ Params P) {
  extern __shared__ __align__(1024) uint8_t smem_raw[];
  if (smem_u32(smem_raw) != SB) return;
  const int tid = threadIdx.x;
  const int warp = __shfl_sync(0xffffffffu, tid >> 5, 0);
  const int lane = tid & 31;
  const int cta = blockIdx.x;
  const int j = (cta >> 6) * 4 + (cta & 3);
  const int g = (cta & 63) >> 2;

  if (warp >= 8) {
    asm volatile("setmaxnreg.dec.sync.aligned.u32 56;");
    if (warp == 8) {
      PSTAMPW(2, 0);
      const bool leader = elect_one();
      if (leader) {
        prefetch_map(&P.x); prefetch_map(&P.wqkv);
#pragma unroll
        for (int i = 0; i < 24; i++) mbar_init(BAR + i * 8, 1);
        asm volatile("fence.mbarrier_init.release.cluster;" ::: "memory");
      }
      __syncwarp();
      asm volatile("bar.arrive 3, 384;" ::: "memory");
      PSTAMPW(2, 20);
      auto ldx = [&](int p, int kb) {
        const uint32_t b = BAR + (B_FX + p * 8 + kb) * 8;
        mbar_expect_tx(b, 8192);
        tma3d(H0 + p * 65536 + kb * 8192, &P.x, kb * 64, p, g * 64, b);
      };
      auto ldkv = [&](int kb, int slot) {
        const uint32_t b = BAR + (B_FKV + kb) * 8, d = RING + slot * 16384;
        mbar_expect_tx(b, 16384);
        tma2d(d, &P.wqkv, 512 + 64 * j, kb * 64, b);
        tma2d(d + 8192, &P.wqkv, 1024 + 64 * j, kb * 64, b);
      };
      if (leader) {
#pragma unroll 1
        for (int i = 0; i < 8 + XO_DELAY; i++) {
          if (i < 8) ldx(0, i);
          if (i < 6) ldkv(i, i);
          if (i >= XO_DELAY) ldx(1, i - XO_DELAY);
          if (i == 0) PSTAMPW(2, 21);
        }
        PSTAMPW(2, 2);
      }
      __syncwarp();
      asm volatile("bar.sync 4, 384;" ::: "memory");
      if (leader) {
        const int f0 = 224 * j + ((j & 1) ? 32 : 0);
        const int fh = 224 * j + ((j & 1) ? 0 : 192);
        prefetch_map(&P.wo); prefetch_map(&P.w1); prefetch_map(&P.w3); prefetch_map(&P.w1h);
        prefetch_map(&P.w3h); prefetch_map(&P.w2); prefetch_map(&P.out);
#pragma unroll 1
        for (int i = 0; i < 2; i++) { mbar_wait(BAR + (B_EKV + i) * 8); ldkv(6 + i, i); }
#pragma unroll 1
        for (int i = 0; i < 8; i++) {
          const uint32_t b = BAR + (B_FQ + i) * 8;
          mbar_wait(BAR + (B_EKV + 2 + (i >> 1)) * 8);
          mbar_expect_tx(b, 8192);
          tma2d(RING + (4 + i) * 8192, &P.wqkv, 64 * j, i * 64, b);
        }
        mbar_expect_tx(BAR + B_FWO * 8, 65536);
#pragma unroll 1
        for (int i = 0; i < 8; i++) {
          const int kb = (i + 1) & 7;
          mbar_wait(BAR + (B_EX + i) * 8);
          tma2d(H0 + kb * 8192, &P.wo, 64 * j, kb * 64, BAR + B_FWO * 8);
          PSTAMPW(2, 4 + i);
        }
#pragma unroll 1
        for (int i = 0; i < 8; i++) {
          const uint32_t b = BAR + (B_FA + i) * 8, d = RING + (i & 3) * 24576;
          const int k0 = kb_at(i, j) * 64;
          mbar_wait(BAR + (B_EKV + 7 + ((0xCBA98520u >> (4 * i)) & 15)) * 8);
          mbar_expect_tx(b, 24576);
          tma2d(d, &P.w1, f0, k0, b);
          tma2d(d + 8192, &P.w3, f0, k0, b);
          tma2d(d + 16384, &P.w1h, fh, k0, b);
          tma2d(d + 20480, &P.w3h, fh, k0, b);
          PSTAMPW(2, 12 + i);
        }
        uint32_t d = RING;
#pragma unroll 1
        for (int i = 0; i < 8; i++) {
          const uint32_t b = BAR + (B_FB + i) * 8;
          const int k0 = kb_at(i, j) * 64;
          mbar_wait(BAR + (B_EA + 5 + i) * 8);
          mbar_expect_tx(b, 32768);
          tma2d(d, &P.w1, f0 + 64, k0, b);
          tma2d(d + 8192, &P.w3, f0 + 64, k0, b);
          tma2d(d + 16384, &P.w1, f0 + 128, k0, b);
          tma2d(d + 24576, &P.w3, f0 + 128, k0, b);
          d = d == RING + 65536 ? RING : d + 32768;
        }
#pragma unroll 1
        for (int m = 0; m < 8; m++) {
          const uint32_t b = BAR + (B_FT + m) * 8;
          mbar_wait(BAR + (B_EB + (m == 7 ? 8 : min(m + 3, 7))) * 8);
          mbar_expect_tx(b, 28672);
          tma2d(t_addr(m), &P.w2, 64 * ((j + 1 + m) & 7), 224 * j, b);
          if (m >= 4) PSTAMPW(2, 23 + m);
        }
        receive_partials(X, g, j, 1);
        X->epoch[cta] = X->epoch[cta] + 1;
      }
    } else {
      const int part = warp - 9;
      uint32_t tag;
      if (part == 2) {
        tag = ld_epoch(X->epoch + cta);
        init_bars(-1);
        tag = (tag + 1) & 1;
        if (lane == 0) {
          asm volatile("st.shared.u32 [%0], %1;" ::"r"(TAGS), "r"(tag) : "memory");
          mbar_arrive(BAR + B_TAG * 8);
        }
      } else {
        init_bars(warp - 1);
        mbar_wait(BAR + B_TAG * 8);
        tag = lds32(TAGS);
      }
      PSTAMPW(3, 16 + part);
      const int xw0 = g * 8;
      auto clear8 = [&](uint4* p, int stride) {
#pragma unroll
        for (int i = 0; i < 8; i++) ll_st(p + i * stride + lane, 0, 0, 0, 0, tag ^ 1);
      };
      auto clear_front = [&]() {
#pragma unroll 1
      for (int u = part; u < 8; u += 3) clear8((u < 4 ? X->e2 : X->e3h) + (xw0 * 32 + 4 * j + (u & 3)) * 32, 1024);
      if (part == 2) {
        clear8(X->e1 + (g * 8 + j) * 256, 32);
#pragma unroll
        for (int i = 0; i < 4; i++)
          ll_st((i < 2 ? X->e2s : X->e3s) + ((xw0 + (i & 1) * 4 + (lane >> 3)) * 8 + j) * 8 + (lane & 7), 0, 0, 0, 0, tag ^ 1);
      }
      };
      if (CLR_MODE == 1) clear_front();
      PSTAMPW(3, 20 + part);
      uint32_t v[8][4];
      if (part < 2) {
        float s[4] = {0.f, 0.f, 0.f, 0.f}, q[4] = {0.f, 0.f, 0.f, 0.f}, piv = 0.f;
        const uint32_t xa = H0 + part * 65536 + (8 * j + (lane >> 2)) * 128 + (lane & 3) * 16 + (lane & 4) * 16;
#pragma unroll 1
        for (int kb = 0; kb < 8; kb++) {
          mbar_wait(BAR + (B_FX + part * 8 + kb) * 8);
          lds128(v[0], xa + kb * 8192); lds128(v[1], (xa + kb * 8192) ^ 64);
          if (kb == 0) piv = __shfl_sync(0xffffffffu, bf_lo(v[0][0]), lane & 28);
#pragma unroll
          for (int e = 0; e < 8; e++) {
            const float a = bf_lo(v[e >> 2][e & 3]) - piv, b = bf_hi(v[e >> 2][e & 3]) - piv;
            s[e & 3] += a + b; q[e & 3] = fmaf(a, a, q[e & 3]); q[e & 3] = fmaf(b, b, q[e & 3]);
          }
        }
        float ss = (s[0] + s[1]) + (s[2] + s[3]), qq = (q[0] + q[1]) + (q[2] + q[3]);
#pragma unroll
        for (int o = 1; o <= 2; o <<= 1) { ss += __shfl_xor_sync(0xffffffffu, ss, o); qq += __shfl_xor_sync(0xffffffffu, qq, o); }
        const float dm = ss * (1.f / D_);
        const float rs = rsqrtf(fmaxf(fmaf(-dm, dm, qq * (1.f / D_)), 0.f) + 1e-5f);
        if ((lane & 3) == 0) ll_st(X->e0s + g * 128 + 2 * (8 * j + (lane >> 2)) + part, __float_as_uint(piv + dm), __float_as_uint(rs), 0, 0, tag);
      } else {
        mbar_wait(BAR + (B_FKV + SIDE_KB) * 8);
        const __nv_bfloat16* wr = wop + (size_t)(j * 64 + g * 4 + (lane >> 3)) * D_ + (lane & 7) * 8;
#pragma unroll
        for (int i = 0; i < 8; i++) ldg128_nc(v[i], wr + i * 64);
        float s[4];
#pragma unroll
        for (int e = 0; e < 4; e++) {
          s[e] = 0.f;
#pragma unroll
          for (int i = 0; i < 8; i++) s[e] += bf_lo(v[i][e]) + bf_hi(v[i][e]);
        }
        float ss = (s[0] + s[1]) + (s[2] + s[3]);
#pragma unroll
        for (int o = 1; o <= 4; o <<= 1) ss += __shfl_xor_sync(0xffffffffu, ss, o);
        if ((lane & 7) == 0) ll_st(X->e0w + j * 64 + g * 4 + (lane >> 3), __float_as_uint(ss * (1.f / D_)), 0, 0, 0, tag);
      }
      __syncwarp();
      if (lane == 0) mbar_arrive(BAR + B_PUB * 8);
      PSTAMPW(3, part * 4 + 2);
      mbar_wait(BAR + B_PUB * 8);
      PSTAMPW(3, part * 4 + 0);
      {
        uint32_t u[2][4];
        const uint4* us = (part == 2 ? X->e0w + j * 64 : X->e0s + g * 128 + part * 64) + lane;
        const uint4* vs = X->e0c + ((j * 3 + part) * 16 + (lane >> 4) * 8) * 16 + (lane & 15);
        uint32_t it = 0;
#pragma unroll 1
        do { ll_issue<2>(u, us, 32); ll_issue<8>(v, vs, 16); } while (ll_any(ll_acc<8>(v, tag, ll_acc<2>(u, tag))) && ++it < SPIN_LIMIT);
        ll_clear<2>(u); ll_clear<8>(v);
#pragma unroll
        for (int i = 0; i < 2; i++) {
          if (part == 2) asm volatile("st.shared.u32 [%0], %1;" ::"r"(WB + (i * 32 + lane) * 4), "r"(u[i][0]) : "memory");
          else asm volatile("st.shared.v2.u32 [%0], {%1,%2};" ::"r"(ST + (part * 64 + i * 32 + lane) * 8), "r"(u[i][0]), "r"(u[i][1]) : "memory");
        }
      }
      uint32_t o[4];
#pragma unroll
      for (int e = 0; e < 4; e++) {
        float s = 0.f;
#pragma unroll
        for (int i = 0; i < 8; i++) s += __uint_as_float(v[i][e]);
        o[e] = __float_as_uint(s + __shfl_xor_sync(0xffffffffu, s, 16));
      }
      if (lane < 16) sts128(CS + (part * 64 + lane * 4) * 4, o);
      __syncwarp();
      if (lane == 0) mbar_arrive(BAR + B_READY * 8);
      PSTAMPW(3, part * 4 + 1);
      if (CLR_MODE == 2) clear_front();
      __syncwarp();
      if (lane == 0) mbar_arrive(BAR + B_CLR0 * 8);
      PSTAMPW(3, 24 + part);
      if (lane == 0) l2_prefetch(part == 0 ? P.w1p + (size_t)cta * 4 * F_ : part == 1 ? P.w3p + (size_t)cta * 4 * F_ : P.w2p + (size_t)cta * 14 * D_, 14336);
      mbar_wait(BAR + (B_EA + 7) * 8);
#pragma unroll 1
      for (int u = 4 * E4_FIRST + part; u < 28; u += 3) {
        clear8(X->e4 + ((g * 8 + ((j + 1 + (u >> 2)) & 7)) * 8 + j) * 1024 + (u & 3) * 32, 128);
        __nanosleep(CLR_SLEEP);
      }
      PSTAMPW(3, part * 4 + 3);
      asm volatile("bar.sync 5, 96;" ::: "memory");
      if (elect_one()) {
        if (part < 2) {
          asm volatile("fence.proxy.async.global;" ::: "memory");
#pragma unroll 1
          for (int m = 0; m < 6; m++) {
            mbar_wait_par(BAR + (B_OF + part) * 8, m & 1);
            fence_async_smem();
            const int slot = (g * 8 + ((j + 1 + m) & 7)) * 8 + j;
#pragma unroll
            for (int i = 0; i < 2; i++)
              asm volatile("cp.async.bulk.global.shared::cta.bulk_group [%0], [%1], 4096;"
                           ::"l"(X->e4 + slot * 1024 + part * 512 + i * 256), "r"(H0 + part * 131072 + i * 65536 + 28672) : "memory");
            asm volatile("cp.async.bulk.commit_group;" ::: "memory");
            asm volatile("cp.async.bulk.wait_group 0;" ::: "memory");
            mbar_arrive(BAR + (B_OE + part) * 8);
            asm volatile("st.relaxed.gpu.global.u32 [%0], %1;" ::"l"(X->sent + slot * 2 + part), "r"(tag) : "memory");
          }
        } else {
          mbar_wait(BAR + B_ET0 * 8);
          receive_partials(X, g, j, 0);
        }
      }
    }
  } else {
    const int p = warp >> 2, w = warp & 3;
    const int r = lane >> 2, c = lane & 3;
    init_bars(warp);
    asm volatile("setmaxnreg.inc.sync.aligned.u32 224;");
    PSTAMP(0);
    const uint32_t dAx = descA(H0) + p * 4096;
    const uint32_t Hn = H1 - p * 65536;
    const uint32_t moff = ((lane & 7) + ((lane >> 3) & 1) * 8) * 128 + (((lane >> 4) ^ (lane & 7)) << 4);
    const uint32_t Xw = H0 + p * 65536 + w * 2048;
    const int xw = (g * 2 + p) * 4 + w;
    if (p == 1) {
      uint32_t v[8][4];
      mbar_wait(BAR + (B_FKV + SIDE_KB) * 8);
      const int wp = w < 3 ? w : 0;
      const __nv_bfloat16* wr = wqkvp + (size_t)(g * 32 + (lane >> 3) * 8) * (3 * D_) + wp * D_ + j * 64 + (lane & 7) * 8;
#pragma unroll
      for (int i = 0; i < 8; i++) ldg128_nc(v[i], wr + (size_t)i * 3 * D_);
      mbar_wait(BAR + B_TAG * 8);
      const uint32_t tg = lds32(TAGS);
      float cs[8];
#pragma unroll
      for (int e = 0; e < 4; e++) {
        float a = 0.f, b = 0.f;
#pragma unroll
        for (int i = 0; i < 8; i++) { a += bf_lo(v[i][e]); b += bf_hi(v[i][e]); }
        cs[2 * e] = a; cs[2 * e + 1] = b;
      }
      const bool up = lane & 8;
#pragma unroll
      for (int e = 0; e < 4; e++) {
        const float keepv = up ? cs[4 + e] : cs[e], give = up ? cs[e] : cs[4 + e];
        cs[e] = keepv + __shfl_xor_sync(0xffffffffu, give, 8);
        cs[e] += __shfl_xor_sync(0xffffffffu, cs[e], 16);
      }
      if (lane < 16 && w < 3)
        ll_st(X->e0c + ((j * 3 + w) * 16 + g) * 16 + (lane & 7) * 2 + (lane >> 3), __float_as_uint(cs[0]), __float_as_uint(cs[1]),
              __float_as_uint(cs[2]), __float_as_uint(cs[3]), tg);
      __syncwarp();
      mbar_arrive_if(BAR + B_PUB * 8, lane == 0);
      PSTAMP(1);
      mbar_wait(BAR + B_LAG * 8);
    }

    float akv[64];
#pragma unroll 1
    for (int kb = 0; kb < 8; kb++) {
      mbar_wait(BAR + (B_FX + p * 8 + kb) * 8);
      mbar_wait(BAR + (B_FKV + kb) * 8);
      if (kb == 0) PSTAMP(2);
      const uint32_t da = dAx + kb * 512, db = descB(RING) + (kb < 6 ? kb : kb - 6) * 1024;
      wg_fence();
      wgmma_ss_n128(akv, da, db, kb);
#pragma unroll
      for (int k = 1; k < 4; k++) wgmma_ss_n128(akv, da + k * 2, db + k * 128, 1);
      wg_commit();
      mbar_arrive_if(BAR + B_LAG * 8, kb == LAG_KB - 1 && p == 0 && lane == 0);
      wg_wait<1>();
      mbar_arrive_if(BAR + (B_EKV + kb - 1) * 8, kb > 0 && lane == 0);
    }
    uint32_t xres[4][4];
#pragma unroll
    for (int u = 0; u < 4; u++) ldsm4(xres[u], Xw + j * 8192 + (moff ^ (u << 5)));

    float aq[32];
    auto qstep = [&](int kb) {
      mbar_wait(BAR + (B_FQ + kb) * 8);
      const uint32_t da = dAx + kb * 512, db = descB(RING + 32768) + kb * 512;
      wg_fence();
      wgmma_ss_n64(aq, da, db, kb);
#pragma unroll
      for (int k = 1; k < 4; k++) wgmma_ss_n64(aq, da + k * 2, db + k * 128, 1);
      wg_commit();
      wg_wait<1>();
      mbar_arrive_if(BAR + (B_EQ + kb - 1) * 8, lane == 0);
      mbar_arrive_if(BAR + (B_EX + kb - 2) * 8, lane == 0 && p == 0 && kb >= 2);
    };
    qstep(0);
    keep(akv);
    PSTAMP(3);
    qstep(1);
    mbar_wait(BAR + B_READY * 8);
    PSTAMP(19);
    const uint32_t tag = lds32(TAGS);
    uint4* const xb = reinterpret_cast<uint4*>(X) + lane + (tag >> 1);
    constexpr int O_E4 = offsetof(Scratch, e4) / 16, O_E2 = offsetof(Scratch, e2) / 16, O_E3H = offsetof(Scratch, e3h) / 16;
    const float2 st0 = lds64(ST + (2 * (16 * w + r) + p) * 8);
    const float2 st1 = lds64(ST + (2 * (16 * w + r + 8) + p) * 8);
    uint32_t hi[4][4], lo[4][4];
    {
      float2 cs[16];
      auto cvt = [&](uint32_t (&d)[4][4], int b0, int ofs, const float2& st) {
#pragma unroll
        for (int b = b0; b < b0 + 8; b++) {
          if (ofs == 2) cs[b] = lds64(CS + (64 + b * 8 + 2 * c) * 4);
          const uint32_t v = pack2(fmaf(-st.x, cs[b].x, akv[4 * b + ofs]) * st.y, fmaf(-st.x, cs[b].y, akv[4 * b + ofs + 1]) * st.y);
          d[b >> 2][b & 3] = b < 8 ? v : movm(v);
        }
      };
      cvt(hi, 0, 2, st1);
      keep(hi[0]); keep(hi[1]);
      qstep(2);
      cvt(hi, 8, 2, st1);
      mbar_wait(BAR + B_CLR0 * 8);
      if (w == 3 && g < 15) {
        uint4* dst = X->e1 + ((g * 8 + j) * 2 + p) * 128 + lane;
#pragma unroll
        for (int i = 0; i < 4; i++) ll_st(dst + i * 32, hi[i][0], hi[i][1], hi[i][2], hi[i][3], tag);
      }
      PSTAMP(20);
      wg_bar(p);
#pragma unroll
      for (int i = 0; i < 4; i++) sts128(Xw + lane * 16 + i * 512, hi[i]);
      qstep(3);
      cvt(lo, 0, 0, st0);
      keep(lo[0]); keep(lo[1]);
      qstep(4);
      cvt(lo, 8, 0, st0);
    }
    PSTAMP(21);
    wg_bar(p);
    uint32_t prev[4][4];
    if (w > 0) {
#pragma unroll
      for (int i = 0; i < 4; i++) lds128(prev[i], Xw - 2048 + lane * 16 + i * 512);
    }
    if (p == 0) {
      asm volatile("fence.proxy.async.shared::cta;" ::: "memory");
      __syncwarp();
      if (lane == 0) mbar_arrive(BAR + (B_EX + 7) * 8);
    }
    PSTAMP(22);
    const uint4* halo = X->e1 + (((g - 1) * 8 + j) * 2 + p) * 128 + lane;
    const bool use_halo = w == 0 && g > 0;
    qstep(5);
    if (use_halo) ll_issue<4>(prev, halo, 32);
    qstep(6);
    qstep(7);
    PSTAMP(23);
    if (w == 0) {
      if (g > 0) {
        if (__builtin_expect(ll_bad<4>(prev, pin(tag, zero)), 0)) ll_spin<4>(prev, halo, 32, tag);
        ll_clear<4>(prev);
      } else {
#pragma unroll
        for (int i = 0; i < 4; i++)
#pragma unroll
          for (int e = 0; e < 4; e++) prev[i][e] = 0;
      }
    }
    wg_wait<0>();
    keep(aq);
    mbar_arrive_if(BAR + (B_EQ + 7) * 8, lane == 0);
    mbar_arrive_if(BAR + (B_EX + 6) * 8, lane == 0 && p == 0);
    PSTAMP(4);

    uint32_t of[4][4];
    {
      const float sc = 0.25f * 1.4426950408889634f;
      const float nohalo = (g == 0 && w == 0) ? -INFINITY : 0.f;
      const bool up0 = 2 * c > r, up1 = 2 * c + 1 > r;
      const uint32_t mup = (up0 ? 0xffffu : 0u) | (up1 ? 0xffff0000u : 0u);
      uint4* dst = xb + O_E2 + (xw * 32 + 4 * j) * 32;
      float d0 = 0.f, d1 = 0.f;
#pragma unroll 1
      for (int hp = 0; hp < 2; hp++) {
#pragma unroll
        for (int e = 0; e < 4; e++) { of[0][e] = of[2][e]; of[1][e] = of[3][e]; }
#pragma unroll
        for (int h = 0; h < 2; h++) {
          uint32_t qf[4];
          const uint32_t co = (32 * hp + 16 * h + 2 * c) * 4;
          {
            const float2 ca = lds64(CS + co), cb = lds64(CS + co + 32);
            qf[0] = pack2(fmaf(-st0.x, ca.x, aq[8 * h + 0]) * st0.y, fmaf(-st0.x, ca.y, aq[8 * h + 1]) * st0.y);
            qf[1] = pack2(fmaf(-st1.x, ca.x, aq[8 * h + 2]) * st1.y, fmaf(-st1.x, ca.y, aq[8 * h + 3]) * st1.y);
            qf[2] = pack2(fmaf(-st0.x, cb.x, aq[8 * h + 4]) * st0.y, fmaf(-st0.x, cb.y, aq[8 * h + 5]) * st0.y);
            qf[3] = pack2(fmaf(-st1.x, cb.x, aq[8 * h + 6]) * st1.y, fmaf(-st1.x, cb.y, aq[8 * h + 7]) * st1.y);
          }
          const int e0 = 2 * h;
          float sp[4], sl[4], sh[4];
          mma16816(sp, qf, prev[0][e0], prev[0][e0 + 1]);
          mma16816(sl, qf, lo[0][e0], lo[0][e0 + 1]);
          mma16816(sh, qf, hi[0][e0], hi[0][e0 + 1]);
          float a0 = up0 ? sp[0] + nohalo : sl[0], a1 = up1 ? sp[1] + nohalo : sl[1];
          float b0 = up0 ? sl[2] : sh[2], b1 = up1 ? sl[3] : sh[3];
          float ma = fmaxf(a0, a1), mb = fmaxf(b0, b1);
          ma = fmaxf(ma, __shfl_xor_sync(0xffffffffu, ma, 1)); mb = fmaxf(mb, __shfl_xor_sync(0xffffffffu, mb, 1));
          ma = fmaxf(ma, __shfl_xor_sync(0xffffffffu, ma, 2)); mb = fmaxf(mb, __shfl_xor_sync(0xffffffffu, mb, 2));
          a0 = ex2((a0 - ma) * sc); a1 = ex2((a1 - ma) * sc); b0 = ex2((b0 - mb) * sc); b1 = ex2((b1 - mb) * sc);
          float sa = a0 + a1, sbb = b0 + b1;
          sa += __shfl_xor_sync(0xffffffffu, sa, 1); sbb += __shfl_xor_sync(0xffffffffu, sbb, 1);
          sa += __shfl_xor_sync(0xffffffffu, sa, 2); sbb += __shfl_xor_sync(0xffffffffu, sbb, 2);
          const float ia = rcp(sa), ib = rcp(sbb);
          const uint32_t pa = pack2(a0 * ia, a1 * ia), pb = pack2(b0 * ib, b1 * ib);
          const uint32_t pf[4] = {pa & mup, 0u, pa & ~mup, pb & mup};
          const uint32_t ph = pb & ~mup;
          float o0[4], o1[4];
          mma16816(o0, pf, prev[2][e0], lo[2][e0]);
          mma16816(o1, pf, prev[2][e0 + 1], lo[2][e0 + 1]);
          mma1688_acc(o0, 0u, ph, hi[2][e0]);
          mma1688_acc(o1, 0u, ph, hi[2][e0 + 1]);
          of[2 + h][0] = pack2(o0[0], o0[1]); of[2 + h][1] = pack2(o0[2], o0[3]);
          of[2 + h][2] = pack2(o1[0], o1[1]); of[2 + h][3] = pack2(o1[2], o1[3]);
          ll_st(dst + (2 * hp + h) * 32, of[2 + h][0], of[2 + h][1], of[2 + h][2], of[2 + h][3], tag);
          const float2 wa = lds64(WB + co), wb = lds64(WB + co + 32);
          d0 = fmaf(o0[0], wa.x, d0); d0 = fmaf(o0[1], wa.y, d0); d0 = fmaf(o1[0], wb.x, d0); d0 = fmaf(o1[1], wb.y, d0);
          d1 = fmaf(o0[2], wa.x, d1); d1 = fmaf(o0[3], wa.y, d1); d1 = fmaf(o1[2], wb.x, d1); d1 = fmaf(o1[3], wb.y, d1);
        }
#pragma unroll
        for (int e = 0; e < 16; e++) aq[e] = aq[16 + e];
#pragma unroll
        for (int e = 0; e < 4; e++) {
          prev[0][e] = prev[1][e]; prev[2][e] = prev[3][e];
          lo[0][e] = lo[1][e]; lo[2][e] = lo[3][e];
          hi[0][e] = hi[1][e]; hi[2][e] = hi[3][e];
        }
      }
#pragma unroll
      for (int o = 1; o <= 2; o <<= 1) { d0 += __shfl_xor_sync(0xffffffffu, d0, o); d1 += __shfl_xor_sync(0xffffffffu, d1, o); }
      if (c == 0) ll_st(X->e2s + (xw * 8 + j) * 8 + r, __float_as_uint(d0), __float_as_uint(d1), 0, 0, tag);
    }
    PSTAMP(5);

    float ah[32];
    uint32_t sv[2][4];
    unpack32(ah, xres);
    {
      uint32_t og[2][14][4];
      const uint4* osrc[7];
#pragma unroll
      for (int i = 0; i < 7; i++) osrc[i] = xb + O_E2 + (xw * 32 + 4 * kb_at(i + 1, j)) * 32;
      const uint4* ssrc = X->e2s + (xw * 8 + 2 * c) * 8 + r;
      auto oissue = [&](int hp) {
#pragma unroll
        for (int i = 0; i < 14; i++) ll_ld(og[hp][i], osrc[i >> 1] + (2 * hp + (i & 1)) * 32);
        if (hp == 1) ll_issue<2>(sv, ssrc, 8);
      };
      auto omma = [&](int hp) {
        ll_clear<14>(og[hp]);
        keep(og[hp]);
        wg_fence();
#pragma unroll
        for (int i = 0; i < 14; i++) wgmma_rs_n64(ah, og[hp][i], descB(H0) + kb_at((i >> 1) + 1, j) * 512 + (2 * hp + (i & 1)) * 128, 1);
        wg_commit();
      };
      mbar_wait(BAR + B_FWO * 8);
      keep(ah); keep(of);
      wg_fence();
#pragma unroll
      for (int k = 0; k < 4; k++) wgmma_rs_n64(ah, of[k], descB(H0) + j * 512 + k * 128, 1);
      wg_commit();
      uint32_t it = 0;
#pragma unroll 1
      do { oissue(0); } while (ll_bad<14>(og[0], tag) && ++it < SPIN_LIMIT);
      PSTAMP(6);
      oissue(1);
      omma(0);
      const uint32_t tg = pin(tag, zero);
      if (__builtin_expect(ll_any(ll_acc<14>(og[1], tg, ll_acc<2>(sv, tg))), 0)) {
#pragma unroll 1
        do { oissue(1); } while (ll_any(ll_acc<14>(og[1], tag, ll_acc<2>(sv, tag))) && ++it < SPIN_LIMIT);
      }
      PSTAMP(16);
      omma(1);
      ll_clear<2>(sv);
    }
    float m0 = __uint_as_float(sv[0][0]) + __uint_as_float(sv[1][0]), m1 = __uint_as_float(sv[0][1]) + __uint_as_float(sv[1][1]);
#pragma unroll
    for (int o = 1; o <= 2; o <<= 1) { m0 += __shfl_xor_sync(0xffffffffu, m0, o); m1 += __shfl_xor_sync(0xffffffffu, m1, o); }
    const uint32_t mu0 = pack2(m0 + st0.x, m0 + st0.x), mu1 = pack2(m1 + st1.x, m1 + st1.x);
    wg_wait<0>();
    keep(ah);
    if (lane == 0) mbar_arrive(BAR + B_WODONE * 8);
    PSTAMP(7);

    uint32_t hf[4][4], ra[4][4];
    pack32(hf, ah);
    {
      uint4* dst = xb + O_E3H + (xw * 32 + 4 * j) * 32;
#pragma unroll
      for (int u = 0; u < 4; u++) {
        ra[u][0] = hsub2(hf[u][0], mu0); ra[u][1] = hsub2(hf[u][1], mu1);
        ra[u][2] = hsub2(hf[u][2], mu0); ra[u][3] = hsub2(hf[u][3], mu1);
        ll_st(dst + u * 32, ra[u][0], ra[u][1], ra[u][2], ra[u][3], tag);
      }
      float s0 = 0.f, q0 = 0.f, s1 = 0.f, q1 = 0.f;
#pragma unroll
      for (int b = 0; b < 8; b++) {
        s0 += ah[4 * b] + ah[4 * b + 1]; s1 += ah[4 * b + 2] + ah[4 * b + 3];
        q0 = fmaf(ah[4 * b], ah[4 * b], q0); q0 = fmaf(ah[4 * b + 1], ah[4 * b + 1], q0);
        q1 = fmaf(ah[4 * b + 2], ah[4 * b + 2], q1); q1 = fmaf(ah[4 * b + 3], ah[4 * b + 3], q1);
      }
#pragma unroll
      for (int o = 1; o <= 2; o <<= 1) {
        s0 += __shfl_xor_sync(0xffffffffu, s0, o); q0 += __shfl_xor_sync(0xffffffffu, q0, o);
        s1 += __shfl_xor_sync(0xffffffffu, s1, o); q1 += __shfl_xor_sync(0xffffffffu, q1, o);
      }
      if (c == 0) ll_st(X->e3s + (xw * 8 + j) * 8 + r, __float_as_uint(s0), __float_as_uint(q0), __float_as_uint(s1), __float_as_uint(q1), tag);
      mbar_wait(BAR + (p == 0 ? B_EQ + 7 : B_WODONE) * 8);
    }
    PSTAMP(8);

    float rs0, rs1;
    auto swiglu = [&](float g0, float g1, float u0, float u1, float rs) -> uint32_t {
      const float hr = 0.5f * rs;
      const float x0 = g0 * hr, x1 = g1 * hr;
      const float t0 = tanhf_hw(x0), t1 = tanhf_hw(x1);
      return pack2(fmaf(x0, t0, x0) * (u0 * rs), fmaf(x1, t1, x1) * (u1 * rs));
    };
    uint32_t hA[6][4];
    {
      float a1[64], a2[32];
      const uint4* src = xb + O_E3H + xw * 32 * 32;
      uint32_t rb[4][4], rc[4][4], rd[4][4];
      auto fetch = [&](uint32_t (&a)[4][4], int i) { ll_issue<4>(a, src + kb_at(i, j) * 128, 32); };
      auto check = [&](uint32_t (&a)[4][4], uint32_t (&b)[4][4], int i) {
        const uint32_t tg = pin(tag, zero);
        if (__builtin_expect(ll_any(ll_acc<4>(a, tg, ll_acc<4>(b, tg))), 0)) {
          uint32_t it = 0;
#pragma unroll 1
          do { fetch(a, i); fetch(b, i + 1); } while (ll_any(ll_acc<4>(a, tag, ll_acc<4>(b, tag))) && ++it < SPIN_LIMIT);
        }
        ll_clear<4>(a); ll_clear<4>(b);
        keep(a); keep(b);
      };
      auto head = [&](uint32_t (&a)[4][4], int i) {
        mbar_wait(BAR + (B_FA + i) * 8);
        wg_fence();
        wgmma_rs_n64<DESC_HI64>(a2, a[0], descBh(RING + 16384) + (i & 3) * 1536, i);
        wgmma_rs_n128(a1, a[0], descB(RING) + (i & 3) * 1536, i);
        wg_commit();
#pragma unroll
        for (int u = 0; u < 4; u++) stsm4(Hn + w * 2048 + i * 8192 + (moff ^ (u << 5)), a[u]);
        wg_wait<1>();
        if (i > 0) mbar_arrive_if(BAR + (B_EA + i - 1) * 8, lane == 0);
      };
      auto rest = [&](uint32_t (&a)[4][4], int i) {
        wg_fence();
#pragma unroll
        for (int k = 1; k < 4; k++) {
          wgmma_rs_n64<DESC_HI64>(a2, a[k], descBh(RING + 16384) + (i & 3) * 1536 + k * 64, 1);
          wgmma_rs_n128(a1, a[k], descB(RING) + (i & 3) * 1536 + k * 128, 1);
        }
        wg_commit();
      };
      ll_clear<4>(ra);
      keep(ra);
      head(ra, 0); rest(ra, 0);
      ll_get<4>(rb, src + kb_at(1, j) * 128, 32, tag);
      keep(rb);
      PSTAMP(17);
      fetch(rc, 2); fetch(rd, 3);
      head(rb, 1); rest(rb, 1);
      check(rc, rd, 2);
      head(rc, 2); fetch(ra, 4); fetch(rb, 5); rest(rc, 2);
      head(rd, 3); rest(rd, 3);
      check(ra, rb, 4);
      head(ra, 4); fetch(rc, 6); fetch(rd, 7); ll_issue<2>(sv, X->e3s + (xw * 8 + 2 * c) * 8 + r, 8); rest(ra, 4);
      head(rb, 5); rest(rb, 5);
      check(rc, rd, 6);
      head(rc, 6); rest(rc, 6);
      head(rd, 7); rest(rd, 7);
      fence_async_smem();
      ll_wait<2>(sv, X->e3s + (xw * 8 + 2 * c) * 8 + r, 8, tag);
      float s0 = __uint_as_float(sv[0][0]) + __uint_as_float(sv[1][0]), q0 = __uint_as_float(sv[0][1]) + __uint_as_float(sv[1][1]);
      float s1 = __uint_as_float(sv[0][2]) + __uint_as_float(sv[1][2]), q1 = __uint_as_float(sv[0][3]) + __uint_as_float(sv[1][3]);
#pragma unroll
      for (int o = 1; o <= 2; o <<= 1) {
        s0 += __shfl_xor_sync(0xffffffffu, s0, o); q0 += __shfl_xor_sync(0xffffffffu, q0, o);
        s1 += __shfl_xor_sync(0xffffffffu, s1, o); q1 += __shfl_xor_sync(0xffffffffu, q1, o);
      }
      s0 *= 1.f / D_; s1 *= 1.f / D_;
      rs0 = rsqrtf(fmaxf(fmaf(-s0, s0, q0 * (1.f / D_)), 0.f) + 1e-5f);
      rs1 = rsqrtf(fmaxf(fmaf(-s1, s1, q1 * (1.f / D_)), 0.f) + 1e-5f);
      wg_wait<0>();
      keep(a1); keep(a2);
      if (lane == 0) mbar_arrive(BAR + (B_EA + 7) * 8);
      PSTAMP(9);
#pragma unroll
      for (int u = 0; u < 4; u++)
#pragma unroll
        for (int e = 0; e < 4; e++)
          hA[u][e] = swiglu(a1[8 * u + 2 * e], a1[8 * u + 2 * e + 1], a1[32 + 8 * u + 2 * e], a1[33 + 8 * u + 2 * e], (e & 1) ? rs1 : rs0);
#pragma unroll
      for (int u = 0; u < 2; u++)
#pragma unroll
        for (int e = 0; e < 4; e++)
          hA[4 + u][e] = swiglu(a2[8 * u + 2 * e], a2[8 * u + 2 * e + 1], a2[16 + 8 * u + 2 * e], a2[17 + 8 * u + 2 * e], (e & 1) ? rs1 : rs0);
      keep(hA);
      wg_bar(p);
    }
    PSTAMP(10);

    uint32_t hB[8][4];
    {
      float ab[128];
      uint32_t db = descB(RING);
      const uint32_t dAn = descA(H1) - p * 4096;
#pragma unroll 1
      for (int i = 0; i < 8; i++) {
        mbar_wait(BAR + (B_FB + i) * 8);
        const uint32_t da = dAn + i * 512;
        wg_fence();
        wgmma_ss_n256(ab, da, db, i);
#pragma unroll
        for (int k = 1; k < 4; k++) wgmma_ss_n256(ab, da + k * 2, db + k * 128, 1);
        wg_commit();
        wg_wait<1>();
        mbar_arrive_if(BAR + (B_EB + i - 1) * 8, i > 0 && lane == 0);
        db = db == descB(RING + 65536) ? descB(RING) : db + 2048;
      }
      wg_wait<0>();
      keep(ab);
      if (lane == 0) mbar_arrive(BAR + (B_EB + 7) * 8);
      PSTAMP(11);
#pragma unroll
      for (int u = 0; u < 8; u++) {
        const int o = (u >> 2) * 64 + (u & 3) * 8;
#pragma unroll
        for (int e = 0; e < 4; e++)
          hB[u][e] = swiglu(ab[o + 2 * e], ab[o + 2 * e + 1], ab[o + 32 + 2 * e], ab[o + 33 + 2 * e], (e & 1) ? rs1 : rs0);
      }
      keep(hB);
    }
    PSTAMP(12);

    {
      float ya[32], y[32], sum[32];
      const uint32_t offA = (j & 1) ? 256 : 0, offH = (j & 1) ? 0 : 1536;
      uint4* e4 = xb + O_E4 + g * 65536 + warp * 128;
      const uint32_t stg = H0 + p * 131072 + (w >> 1) * 65536 + 28672 + (w & 1) * 2048;
      uint32_t in[4][4], pk[4][4];
      auto insrc = [&](int q) { return e4 + (j * 8 + ((j - 1 - q) & 7)) * 1024; };
      const uint32_t ident = (2 * c == r ? 0x3f80u : 0u) | (2 * c + 1 == r ? 0x3f800000u : 0u);
      auto acc = [&](uint32_t (&in)[4][4]) {
        ll_clear<4>(in);
#pragma unroll
        for (int u = 0; u < 4; u++) {
          mma1688_acc(*reinterpret_cast<float (*)[4]>(&sum[8 * u]), in[u][0], in[u][1], ident);
          mma1688_acc(*reinterpret_cast<float (*)[4]>(&sum[8 * u + 4]), in[u][2], in[u][3], ident);
        }
      };
      uint32_t T;
      auto mm = [&](float (&d)[32], int k0, int k1) {
        wg_fence();
#pragma unroll
        for (int k = k0; k < k1; k++) {
          if (k < 4) wgmma_rs_n64(d, hA[k], T + offA + k * 128, k);
          else if (k < 6) wgmma_rs_n64(d, hA[k], T + offH + (k - 4) * 128, 1);
          else wgmma_rs_n64(d, hB[k - 6], T + offA + 512 + (k - 6) * 128, 1);
        }
        wg_commit();
      };
      auto start = [&](float (&d)[32], float (&dp)[32], int m, const bool ODD) {
        const int mt = min(m, 7);
        mbar_wait(BAR + (B_FT + mt) * 8);
        T = descB(0) + (t_addr(mt) >> 4);
        mm(d, 0, 3);
        wg_wait<1>();
        keep(dp);
        mbar_arrive_if(BAR + (B_ET0 + m - 1) * 8, m < 8 && lane == 0);
        pack32(pk, dp);
        if (ODD && m == 7) {
          uint4* dst = e4 + (((j + 7) & 7) * 8 + j) * 1024;
#pragma unroll
          for (int u = 0; u < 4; u++) ll_st(dst + u * 32, pk[u][0], pk[u][1], pk[u][2], pk[u][3], tag);
          mbar_wait(BAR + (B_ET0 + 6) * 8);
        } else if (m < 7) {
          mbar_wait_par(BAR + (B_OE + p) * 8, m & 1);
#pragma unroll
          for (int u = 0; u < 4; u++) { pk[u][0] = (pk[u][0] & ~1u) | tag; sts128(stg + lane * 16 + u * 512, pk[u]); }
          __syncwarp();
          mbar_arrive_if(BAR + (B_OF + p) * 8, lane == 0);
        }
      };
      mbar_wait(BAR + (B_EB + 3 + 3 * p) * 8);
      mbar_wait(BAR + B_FT * 8);
      T = descB(0) + (t_addr(0) >> 4);
      mm(ya, 0, 3);
      unpack32(sum, hf);
      keep(sum);
      wg_wait<0>();
#pragma unroll 1
      for (int m = 0; m < 8; m += 2) {
        mm(ya, 3, 14);
        start(y, ya, m + 1, true);
        mm(y, 3, 14);
        start(ya, y, m + 2, false);
        wg_wait<0>();
        if (m == 0) PSTAMP(27);
        if (m == 2) PSTAMP(26);
        if (m == 4) PSTAMP(28);
      }
      PSTAMP(13);
      uint32_t lt[4][4];
      ll_issue<4>(lt, insrc(6), 32);
      mbar_wait(BAR + (B_FIN + p) * 8);
      PSTAMP(24);
#pragma unroll
      for (int q = 0; q < 6; q++) {
#pragma unroll
        for (int u = 0; u < 4; u++) lds128(in[u], in_addr(q, p) + w * 2048 + lane * 16 + u * 512);
        if (__builtin_expect(ll_bad<4>(in, tag), 0)) ll_spin<4>(in, insrc(q), 32, tag);
        acc(in);
      }
      PSTAMP(25);
      if (ll_bad<4>(lt, pin(tag, zero))) {
        ll_spin<4>(lt, insrc(6), 32, tag);
      }
      acc(lt);
      PSTAMP(14);
      mbar_wait_par(BAR + (B_OE + p) * 8, 1);
#pragma unroll
      for (int u = 0; u < 4; u++) {
        uint32_t o[4];
#pragma unroll
        for (int e = 0; e < 4; e++) o[e] = pack2(sum[8 * u + 2 * e] + y[8 * u + 2 * e], sum[8 * u + 2 * e + 1] + y[8 * u + 2 * e + 1]);
        stsm4(stg + (moff ^ (u << 5)), o);
      }
      fence_async_smem();
      __syncwarp();
      if (elect_one()) {
        tma3d_store(&P.out, stg, 64 * j, p, g * 64 + 16 * w);
        asm volatile("cp.async.bulk.commit_group;" ::: "memory");
        asm volatile("cp.async.bulk.wait_group.read 0;" ::: "memory");
      }
      PSTAMP(15);
    }
  }
}

typedef CUresult (*EncodeFn)(CUtensorMap*, CUtensorMapDataType, cuuint32_t, void*, const cuuint64_t*, const cuuint64_t*,
                             const cuuint32_t*, const cuuint32_t*, CUtensorMapInterleave, CUtensorMapSwizzle,
                             CUtensorMapL2promotion, CUtensorMapFloatOOBfill);

void enc2d(EncodeFn f, CUtensorMap* m, const void* base, uint64_t cols, uint64_t rows, uint32_t bc, uint32_t br, CUtensorMapSwizzle sw) {
  cuuint64_t gd[2] = {cols, rows}, gs[1] = {cols * 2};
  cuuint32_t bd[2] = {bc, br}, es[2] = {1, 1};
  f(m, CU_TENSOR_MAP_DATA_TYPE_BFLOAT16, 2, const_cast<void*>(base), gd, gs, bd, es, CU_TENSOR_MAP_INTERLEAVE_NONE, sw,
    CU_TENSOR_MAP_L2_PROMOTION_L2_128B, CU_TENSOR_MAP_FLOAT_OOB_FILL_NONE);
}
void enc_par(EncodeFn f, CUtensorMap* m, const void* base, uint32_t pairs) {
  cuuint64_t gd[3] = {(cuuint64_t)D_, 2, (cuuint64_t)S_ / 2}, gs[2] = {D_ * 2, D_ * 4};
  cuuint32_t bd[3] = {64, 1, pairs}, es[3] = {1, 1, 1};
  f(m, CU_TENSOR_MAP_DATA_TYPE_BFLOAT16, 3, const_cast<void*>(base), gd, gs, bd, es, CU_TENSOR_MAP_INTERLEAVE_NONE,
    CU_TENSOR_MAP_SWIZZLE_128B, CU_TENSOR_MAP_L2_PROMOTION_L2_128B, CU_TENSOR_MAP_FLOAT_OOB_FILL_NONE);
}

}

extern "C" void kernel_launch(void* const* d_in, const int* in_sizes, int n_in, void* d_out, int out_size) {
  (void)in_sizes; (void)n_in; (void)out_size;
  static EncodeFn enc = nullptr;
  static Scratch* scratch = nullptr;
  if (!enc) {
    void* fn = nullptr;
    cudaDriverEntryPointQueryResult q;
    cudaGetDriverEntryPoint("cuTensorMapEncodeTiled", &fn, cudaEnableDefault, &q);
    enc = (EncodeFn)fn;
    cudaGetSymbolAddress((void**)&scratch, g_scratch);
    cudaFuncSetAttribute(fused_block_kernel, cudaFuncAttributeMaxDynamicSharedMemorySize, SMEM_BYTES);
  }
  Params P;
  const __nv_bfloat16* xp = (const __nv_bfloat16*)d_in[0];
  const __nv_bfloat16* wqkvp = (const __nv_bfloat16*)d_in[1];
  const __nv_bfloat16* wop = (const __nv_bfloat16*)d_in[2];
  P.w1p = (const __nv_bfloat16*)d_in[4];
  P.w3p = (const __nv_bfloat16*)d_in[5];
  P.w2p = (const __nv_bfloat16*)d_in[6];
  enc_par(enc, &P.x, xp, 64);
  enc_par(enc, &P.out, d_out, 16);
  enc2d(enc, &P.wqkv, wqkvp, 3 * D_, D_, 64, 64, CU_TENSOR_MAP_SWIZZLE_128B);
  enc2d(enc, &P.wo, wop, D_, D_, 64, 64, CU_TENSOR_MAP_SWIZZLE_128B);
  enc2d(enc, &P.w1, P.w1p, F_, D_, 64, 64, CU_TENSOR_MAP_SWIZZLE_128B);
  enc2d(enc, &P.w3, P.w3p, F_, D_, 64, 64, CU_TENSOR_MAP_SWIZZLE_128B);
  enc2d(enc, &P.w1h, P.w1p, F_, D_, 32, 64, CU_TENSOR_MAP_SWIZZLE_64B);
  enc2d(enc, &P.w3h, P.w3p, F_, D_, 32, 64, CU_TENSOR_MAP_SWIZZLE_64B);
  enc2d(enc, &P.w2, P.w2p, D_, F_, 64, 224, CU_TENSOR_MAP_SWIZZLE_128B);

  cudaLaunchConfig_t cfg = {};
  cfg.gridDim = dim3(128);
  cfg.blockDim = dim3(384);
  cfg.dynamicSmemBytes = SMEM_BYTES;
  cfg.stream = cudaStreamPerThread;
  cudaLaunchAttribute at[1];
  at[0].id = cudaLaunchAttributeCooperative;
  at[0].val.cooperative = 1;
  cfg.attrs = at;
  cfg.numAttrs = 1;
  cudaLaunchKernelEx(&cfg, fused_block_kernel, scratch, xp, wqkvp, wop, 0u, P);
}
```

```cpp
#include <cuda_runtime.h>
#include <cuda.h>
#include <cuda_bf16.h>
#include <stdint.h>
#include <stddef.h>

namespace {

constexpr int S_ = 2048, D_ = 512, F_ = 1792;
#define LAG_KB 3
#define E4_FIRST 7
#define PP_AHEAD 1
#define SIDE_KB 0
#define CLR_MODE 0
#define W2_HEAD 3
#define CLR_SLEEP 400
#define CMAP 2
#define XO_DELAY 2

constexpr uint32_t SPIN_LIMIT = 1u << 18;

struct Scratch {
  uint4 e4[16 * 8 * 3 * 8 * 4 * 32];
  uint4 e2[16 * 2 * 4 * 32 * 32];
  uint4 e3h[16 * 2 * 4 * 32 * 32];
  uint4 e1[16 * 8 * 2 * 4 * 32];
  uint4 e2s[16 * 2 * 4 * 8 * 8];
  uint4 e3s[16 * 2 * 4 * 8 * 8];
  uint4 e0c[8 * 3 * 16 * 16];
  uint4 e0s[2048];
  uint4 e0w[8 * 64];
  unsigned epoch[128];
};
__device__ Scratch g_scratch;
#define PSTAMP(i)
#define PSTAMPW(slot, i)
#define W2STAMP(i)

struct alignas(64) Params {
  CUtensorMap x, out, wqkv, wo, w1, w3, w1h, w3h, w2;
  const __nv_bfloat16 *w1p, *w3p, *w2p;
};

constexpr uint32_t SB = 1024;
constexpr uint32_t H0 = SB;
constexpr uint32_t H1 = SB + 65536;
constexpr uint32_t RING = SB + 131072;
constexpr uint32_t BAR = SB + 229376;
constexpr uint32_t TAGS = BAR + 1016;
constexpr uint32_t CS = BAR + 1024;
constexpr uint32_t ST = CS + 768;
constexpr uint32_t WB = ST + 1024;
constexpr uint32_t SMEM_BYTES = 232448;
static_assert(WB + 256 <= SB + SMEM_BYTES, "smem");

enum : int {
  B_FX = 0,
  B_FKV = 16, B_FQ = 24, B_FWO = 32, B_FA = 40, B_FB = 48, B_FT = 56,
  B_EKV = 64, B_EQ = 72, B_EA = 80, B_EB = 88, B_ET0 = 96,
  B_WODONE = 103,
  B_FIN = 33,
  B_EX = 104,
  B_LAG = 112, B_READY = 113, B_PUB = 114, B_CLR = 115, B_CLR0 = 116, B_TAG = 117,
  B_HX = 118,
  B_PF = 120,
  B_HC = 122
};

__device__ __forceinline__ uint32_t smem_u32(const void* p) { return (uint32_t)__cvta_generic_to_shared(p); }
__device__ __forceinline__ uint32_t own() { return (blockIdx.x & 1) << 24; }
__device__ __forceinline__ uint32_t peer() { return (~blockIdx.x & 1) << 24; }
__device__ __forceinline__ void mbar_init(uint32_t b, uint32_t c) { asm volatile("mbarrier.init.shared::cta.b64 [%0], %1;" ::"r"(b + own()), "r"(c) : "memory"); }
__device__ __forceinline__ void mbar_expect_tx(uint32_t b, uint32_t bytes) { asm volatile("mbarrier.arrive.expect_tx.shared::cta.b64 _, [%0], %1;" ::"r"(b + own()), "r"(bytes) : "memory"); }
__device__ __forceinline__ void mbar_arrive(uint32_t b) { asm volatile("mbarrier.arrive.shared::cta.b64 _, [%0];" ::"r"(b + own()) : "memory"); }
__device__ __forceinline__ void mbar_wait(uint32_t b) {
  asm volatile("{\n.reg .pred p;\n.reg .u32 c;\nmov.u32 c, 0;\nLW:\n.pragma \"nounroll\";\n"
               "mbarrier.try_wait.parity.shared::cta.b64 p, [%0], 0;\nadd.u32 c, c, 1;\nsetp.gt.or.u32 p, c, %1, p;\n@!p bra LW;\n}\n"
               ::"r"(b + own()), "n"(SPIN_LIMIT) : "memory");
}
__device__ __forceinline__ void mbar_wait_cluster(uint32_t b) {
  asm volatile("{\n.reg .pred p;\n.reg .u32 c;\nmov.u32 c, 0;\nLW:\n.pragma \"nounroll\";\n"
               "mbarrier.try_wait.parity.acquire.cluster.shared::cta.b64 p, [%0], 0;\nadd.u32 c, c, 1;\nsetp.gt.or.u32 p, c, %1, p;\n@!p bra LW;\n}\n"
               ::"r"(b + own()), "n"(SPIN_LIMIT) : "memory");
}
__device__ __forceinline__ bool elect_one() {
  uint32_t p;
  asm volatile("{\n.reg .pred P;\nelect.sync _|P, 0xffffffff;\nselp.u32 %0, 1, 0, P;\n}\n" : "=r"(p));
  return p;
}
__device__ __forceinline__ void tma2d(uint32_t dst, const CUtensorMap* m, int c0, int c1, uint32_t bar) {
  dst += own(); bar += own();
  asm volatile("cp.async.bulk.tensor.2d.shared::cluster.global.mbarrier::complete_tx::bytes [%0], [%1, {%3, %4}], [%2];"
               ::"r"(dst), "l"(m), "r"(bar), "r"(c0), "r"(c1) : "memory");
}
__device__ __forceinline__ void tma3d(uint32_t dst, const CUtensorMap* m, int c0, int c1, int c2, uint32_t bar) {
  dst += own(); bar += own();
  asm volatile("cp.async.bulk.tensor.3d.shared::cluster.global.mbarrier::complete_tx::bytes [%0], [%1, {%3, %4, %5}], [%2];"
               ::"r"(dst), "l"(m), "r"(bar), "r"(c0), "r"(c1), "r"(c2) : "memory");
}
__device__ __forceinline__ void tma3d_store(const CUtensorMap* m, uint32_t src, int c0, int c1, int c2) {
  asm volatile("cp.async.bulk.tensor.3d.global.shared::cta.bulk_group [%0, {%2, %3, %4}], [%1];"
               ::"l"(m), "r"(src + own()), "r"(c0), "r"(c1), "r"(c2) : "memory");
}
__device__ __forceinline__ void l2_prefetch(const void* p, uint32_t bytes) {
  asm volatile("cp.async.bulk.prefetch.L2.global [%0], %1;" ::"l"(p), "r"(bytes) : "memory");
}
__device__ __forceinline__ void prefetch_map(const CUtensorMap* m) { asm volatile("prefetch.tensormap [%0];" ::"l"(m) : "memory"); }
__device__ __forceinline__ void fence_async_smem() { asm volatile("fence.proxy.async.shared::cta;" ::: "memory"); }
__device__ __forceinline__ void wg_fence() { asm volatile("wgmma.fence.sync.aligned;" ::: "memory"); }
__device__ __forceinline__ void wg_commit() { asm volatile("wgmma.commit_group.sync.aligned;" ::: "memory"); }
template <int N> __device__ __forceinline__ void wg_wait() { asm volatile("wgmma.wait_group.sync.aligned %0;" ::"n"(N) : "memory"); }
__device__ __forceinline__ void wg_bar(int p) {
  if (p == 0) asm volatile("bar.sync 1, 128;" ::: "memory"); else asm volatile("bar.sync 2, 128;" ::: "memory");
}
constexpr uint32_t DESC_HI128 = (1024 >> 4) | (1u << 30);
constexpr uint32_t DESC_HI64 = (512 >> 4) | (2u << 30);
__device__ __forceinline__ constexpr uint32_t descA(uint32_t addr) { return (addr >> 4) | (1u << 16); }
__device__ __forceinline__ constexpr uint32_t descB(uint32_t addr) { return (addr >> 4) | ((8192u >> 4) << 16); }
__device__ __forceinline__ constexpr uint32_t descBh(uint32_t addr) { return (addr >> 4) | ((4096u >> 4) << 16); }

__device__ __forceinline__ void wgmma_ss_n64(float (&d)[32], uint32_t da, uint32_t db, int sc) {
  asm volatile("{\n.reg .pred p;\n.reg .b64 da, db;\nsetp.ne.b32 p, %34, 0;\nmov.b64 da, {%32, %35};\nmov.b64 db, {%33, %35};\n"
    "wgmma.mma_async.sync.aligned.m64n64k16.f32.bf16.bf16 {%0, %1, %2, %3, %4, %5, %6, %7, %8, %9, %10, %11, %12, %13, %14, %15, %16, %17, %18, %19, %20, %21, %22, %23, %24, %25, %26, %27, %28, %29, %30, %31}, da, db, p, 1, 1, 0, 1;\n}\n"
    : "+f"(d[0]), "+f"(d[1]), "+f"(d[2]), "+f"(d[3]), "+f"(d[4]), "+f"(d[5]), "+f"(d[6]), "+f"(d[7]),
      "+f"(d[8]), "+f"(d[9]), "+f"(d[10]), "+f"(d[11]), "+f"(d[12]), "+f"(d[13]), "+f"(d[14]), "+f"(d[15]),
      "+f"(d[16]), "+f"(d[17]), "+f"(d[18]), "+f"(d[19]), "+f"(d[20]), "+f"(d[21]), "+f"(d[22]), "+f"(d[23]),
      "+f"(d[24]), "+f"(d[25]), "+f"(d[26]), "+f"(d[27]), "+f"(d[28]), "+f"(d[29]), "+f"(d[30]), "+f"(d[31])
    : "r"(da), "r"(db), "r"(sc), "n"(DESC_HI128));
}
__device__ __forceinline__ void wgmma_ss_n128(float (&d)[64], uint32_t da, uint32_t db, int sc) {
  asm volatile("{\n.reg .pred p;\n.reg .b64 da, db;\nsetp.ne.b32 p, %66, 0;\nmov.b64 da, {%64, %67};\nmov.b64 db, {%65, %67};\n"
    "wgmma.mma_async.sync.aligned.m64n128k16.f32.bf16.bf16 {%0, %1, %2, %3, %4, %5, %6, %7, %8, %9, %10, %11, %12, %13, %14, %15, %16, %17, %18, %19, %20, %21, %22, %23, %24, %25, %26, %27, %28, %29, %30, %31, %32, %33, %34, %35, %36, %37, %38, %39, %40, %41, %42, %43, %44, %45, %46, %47, %48, %49, %50, %51, %52, %53, %54, %55, %56, %57, %58, %59, %60, %61, %62, %63}, da, db, p, 1, 1, 0, 1;\n}\n"
    : "+f"(d[0]), "+f"(d[1]), "+f"(d[2]), "+f"(d[3]), "+f"(d[4]), "+f"(d[5]), "+f"(d[6]), "+f"(d[7]),
      "+f"(d[8]), "+f"(d[9]), "+f"(d[10]), "+f"(d[11]), "+f"(d[12]), "+f"(d[13]), "+f"(d[14]), "+f"(d[15]),
      "+f"(d[16]), "+f"(d[17]), "+f"(d[18]), "+f"(d[19]), "+f"(d[20]), "+f"(d[21]), "+f"(d[22]), "+f"(d[23]),
      "+f"(d[24]), "+f"(d[25]), "+f"(d[26]), "+f"(d[27]), "+f"(d[28]), "+f"(d[29]), "+f"(d[30]), "+f"(d[31]),
      "+f"(d[32]), "+f"(d[33]), "+f"(d[34]), "+f"(d[35]), "+f"(d[36]), "+f"(d[37]), "+f"(d[38]), "+f"(d[39]),
      "+f"(d[40]), "+f"(d[41]), "+f"(d[42]), "+f"(d[43]), "+f"(d[44]), "+f"(d[45]), "+f"(d[46]), "+f"(d[47]),
      "+f"(d[48]), "+f"(d[49]), "+f"(d[50]), "+f"(d[51]), "+f"(d[52]), "+f"(d[53]), "+f"(d[54]), "+f"(d[55]),
      "+f"(d[56]), "+f"(d[57]), "+f"(d[58]), "+f"(d[59]), "+f"(d[60]), "+f"(d[61]), "+f"(d[62]), "+f"(d[63])
    : "r"(da), "r"(db), "r"(sc), "n"(DESC_HI128));
}
__device__ __forceinline__ void wgmma_ss_n256(float (&d)[128], uint32_t da, uint32_t db, int sc) {
  asm volatile("{\n.reg .pred p;\n.reg .b64 da, db;\nsetp.ne.b32 p, %130, 0;\nmov.b64 da, {%128, %131};\nmov.b64 db, {%129, %131};\n"
    "wgmma.mma_async.sync.aligned.m64n256k16.f32.bf16.bf16 {%0, %1, %2, %3, %4, %5, %6, %7, %8, %9, %10, %11, %12, %13, %14, %15, %16, %17, %18, %19, %20, %21, %22, %23, %24, %25, %26, %27, %28, %29, %30, %31, %32, %33, %34, %35, %36, %37, %38, %39, %40, %41, %42, %43, %44, %45, %46, %47, %48, %49, %50, %51, %52, %53, %54, %55, %56, %57, %58, %59, %60, %61, %62, %63, %64, %65, %66, %67, %68, %69, %70, %71, %72, %73, %74, %75, %76, %77, %78, %79, %80, %81, %82, %83, %84, %85, %86, %87, %88, %89, %90, %91, %92, %93, %94, %95, %96, %97, %98, %99, %100, %101, %102, %103, %104, %105, %106, %107, %108, %109, %110, %111, %112, %113, %114, %115, %116, %117, %118, %119, %120, %121, %122, %123, %124, %125, %126, %127}, da, db, p, 1, 1, 0, 1;\n}\n"
    : "+f"(d[0]), "+f"(d[1]), "+f"(d[2]), "+f"(d[3]), "+f"(d[4]), "+f"(d[5]), "+f"(d[6]), "+f"(d[7]),
      "+f"(d[8]), "+f"(d[9]), "+f"(d[10]), "+f"(d[11]), "+f"(d[12]), "+f"(d[13]), "+f"(d[14]), "+f"(d[15]),
      "+f"(d[16]), "+f"(d[17]), "+f"(d[18]), "+f"(d[19]), "+f"(d[20]), "+f"(d[21]), "+f"(d[22]), "+f"(d[23]),
      "+f"(d[24]), "+f"(d[25]), "+f"(d[26]), "+f"(d[27]), "+f"(d[28]), "+f"(d[29]), "+f"(d[30]), "+f"(d[31]),
      "+f"(d[32]), "+f"(d[33]), "+f"(d[34]), "+f"(d[35]), "+f"(d[36]), "+f"(d[37]), "+f"(d[38]), "+f"(d[39]),
      "+f"(d[40]), "+f"(d[41]), "+f"(d[42]), "+f"(d[43]), "+f"(d[44]), "+f"(d[45]), "+f"(d[46]), "+f"(d[47]),
      "+f"(d[48]), "+f"(d[49]), "+f"(d[50]), "+f"(d[51]), "+f"(d[52]), "+f"(d[53]), "+f"(d[54]), "+f"(d[55]),
      "+f"(d[56]), "+f"(d[57]), "+f"(d[58]), "+f"(d[59]), "+f"(d[60]), "+f"(d[61]), "+f"(d[62]), "+f"(d[63]),
      "+f"(d[64]), "+f"(d[65]), "+f"(d[66]), "+f"(d[67]), "+f"(d[68]), "+f"(d[69]), "+f"(d[70]), "+f"(d[71]),
      "+f"(d[72]), "+f"(d[73]), "+f"(d[74]), "+f"(d[75]), "+f"(d[76]), "+f"(d[77]), "+f"(d[78]), "+f"(d[79]),
      "+f"(d[80]), "+f"(d[81]), "+f"(d[82]), "+f"(d[83]), "+f"(d[84]), "+f"(d[85]), "+f"(d[86]), "+f"(d[87]),
      "+f"(d[88]), "+f"(d[89]), "+f"(d[90]), "+f"(d[91]), "+f"(d[92]), "+f"(d[93]), "+f"(d[94]), "+f"(d[95]),
      "+f"(d[96]), "+f"(d[97]), "+f"(d[98]), "+f"(d[99]), "+f"(d[100]), "+f"(d[101]), "+f"(d[102]), "+f"(d[103]),
      "+f"(d[104]), "+f"(d[105]), "+f"(d[106]), "+f"(d[107]), "+f"(d[108]), "+f"(d[109]), "+f"(d[110]), "+f"(d[111]),
      "+f"(d[112]), "+f"(d[113]), "+f"(d[114]), "+f"(d[115]), "+f"(d[116]), "+f"(d[117]), "+f"(d[118]), "+f"(d[119]),
      "+f"(d[120]), "+f"(d[121]), "+f"(d[122]), "+f"(d[123]), "+f"(d[124]), "+f"(d[125]), "+f"(d[126]), "+f"(d[127])
    : "r"(da), "r"(db), "r"(sc), "n"(DESC_HI128));
}
template <uint32_t HI = DESC_HI128>
__device__ __forceinline__ void wgmma_rs_n64(float (&d)[32], const uint32_t (&a)[4], uint32_t db, int sc) {
  asm volatile("{\n.reg .pred p;\n.reg .b64 db;\nsetp.ne.b32 p, %37, 0;\nmov.b64 db, {%36, %38};\n"
    "wgmma.mma_async.sync.aligned.m64n64k16.f32.bf16.bf16 {%0, %1, %2, %3, %4, %5, %6, %7, %8, %9, %10, %11, %12, %13, %14, %15, %16, %17, %18, %19, %20, %21, %22, %23, %24, %25, %26, %27, %28, %29, %30, %31}, {%32, %33, %34, %35}, db, p, 1, 1, 1;\n}\n"
    : "+f"(d[0]), "+f"(d[1]), "+f"(d[2]), "+f"(d[3]), "+f"(d[4]), "+f"(d[5]), "+f"(d[6]), "+f"(d[7]),
      "+f"(d[8]), "+f"(d[9]), "+f"(d[10]), "+f"(d[11]), "+f"(d[12]), "+f"(d[13]), "+f"(d[14]), "+f"(d[15]),
      "+f"(d[16]), "+f"(d[17]), "+f"(d[18]), "+f"(d[19]), "+f"(d[20]), "+f"(d[21]), "+f"(d[22]), "+f"(d[23]),
      "+f"(d[24]), "+f"(d[25]), "+f"(d[26]), "+f"(d[27]), "+f"(d[28]), "+f"(d[29]), "+f"(d[30]), "+f"(d[31])
    : "r"(a[0]), "r"(a[1]), "r"(a[2]), "r"(a[3]), "r"(db), "r"(sc), "n"(HI));
}
template <uint32_t HI = DESC_HI128>
__device__ __forceinline__ void wgmma_rs_n128(float (&d)[64], const uint32_t (&a)[4], uint32_t db, int sc) {
  asm volatile("{\n.reg .pred p;\n.reg .b64 db;\nsetp.ne.b32 p, %69, 0;\nmov.b64 db, {%68, %70};\n"
    "wgmma.mma_async.sync.aligned.m64n128k16.f32.bf16.bf16 {%0, %1, %2, %3, %4, %5, %6, %7, %8, %9, %10, %11, %12, %13, %14, %15, %16, %17, %18, %19, %20, %21, %22, %23, %24, %25, %26, %27, %28, %29, %30, %31, %32, %33, %34, %35, %36, %37, %38, %39, %40, %41, %42, %43, %44, %45, %46, %47, %48, %49, %50, %51, %52, %53, %54, %55, %56, %57, %58, %59, %60, %61, %62, %63}, {%64, %65, %66, %67}, db, p, 1, 1, 1;\n}\n"
    : "+f"(d[0]), "+f"(d[1]), "+f"(d[2]), "+f"(d[3]), "+f"(d[4]), "+f"(d[5]), "+f"(d[6]), "+f"(d[7]),
      "+f"(d[8]), "+f"(d[9]), "+f"(d[10]), "+f"(d[11]), "+f"(d[12]), "+f"(d[13]), "+f"(d[14]), "+f"(d[15]),
      "+f"(d[16]), "+f"(d[17]), "+f"(d[18]), "+f"(d[19]), "+f"(d[20]), "+f"(d[21]), "+f"(d[22]), "+f"(d[23]),
      "+f"(d[24]), "+f"(d[25]), "+f"(d[26]), "+f"(d[27]), "+f"(d[28]), "+f"(d[29]), "+f"(d[30]), "+f"(d[31]),
      "+f"(d[32]), "+f"(d[33]), "+f"(d[34]), "+f"(d[35]), "+f"(d[36]), "+f"(d[37]), "+f"(d[38]), "+f"(d[39]),
      "+f"(d[40]), "+f"(d[41]), "+f"(d[42]), "+f"(d[43]), "+f"(d[44]), "+f"(d[45]), "+f"(d[46]), "+f"(d[47]),
      "+f"(d[48]), "+f"(d[49]), "+f"(d[50]), "+f"(d[51]), "+f"(d[52]), "+f"(d[53]), "+f"(d[54]), "+f"(d[55]),
      "+f"(d[56]), "+f"(d[57]), "+f"(d[58]), "+f"(d[59]), "+f"(d[60]), "+f"(d[61]), "+f"(d[62]), "+f"(d[63])
    : "r"(a[0]), "r"(a[1]), "r"(a[2]), "r"(a[3]), "r"(db), "r"(sc), "n"(HI));
}

template <int N> __device__ __forceinline__ void keep(float (&d)[N]) {
#pragma unroll
  for (int i = 0; i < N; i++) asm volatile("" : "+f"(d[i])::"memory");
}

__device__ __forceinline__ void keep(uint32_t (&d)[4]) { asm volatile("" : "+r"(d[0]), "+r"(d[1]), "+r"(d[2]), "+r"(d[3])::"memory"); }
template <int N> __device__ __forceinline__ void keep(uint32_t (&d)[N][4]) {
#pragma unroll
  for (int i = 0; i < N; i++) asm volatile("" : "+r"(d[i][0]), "+r"(d[i][1]), "+r"(d[i][2]), "+r"(d[i][3])::"memory");
}

__device__ __forceinline__ uint32_t pack2(float lo, float hi) {
  uint32_t r;
  asm("cvt.rn.bf16x2.f32 %0, %1, %2;" : "=r"(r) : "f"(hi), "f"(lo));
  return r;
}
__device__ __forceinline__ float bf_lo(uint32_t v) { return __uint_as_float(v << 16); }
__device__ __forceinline__ float bf_hi(uint32_t v) { return __uint_as_float(v & 0xffff0000u); }
__device__ __forceinline__ uint32_t hsub2(uint32_t a, uint32_t b) {
  uint32_t r;
  asm("sub.rn.bf16x2 %0, %1, %2;" : "=r"(r) : "r"(a), "r"(b));
  return r;
}
__device__ __forceinline__ uint32_t movm(uint32_t a) {
  uint32_t r;
  asm volatile("movmatrix.sync.aligned.m8n8.trans.b16 %0, %1;" : "=r"(r) : "r"(a));
  return r;
}
__device__ __forceinline__ void ldsm4(uint32_t (&v)[4], uint32_t a) {
  asm volatile("ldmatrix.sync.aligned.m8n8.x4.shared.b16 {%0,%1,%2,%3}, [%4];" : "=r"(v[0]), "=r"(v[1]), "=r"(v[2]), "=r"(v[3]) : "r"(a + own()) : "memory");
}
__device__ __forceinline__ void stsm4(uint32_t a, const uint32_t (&v)[4]) {
  asm volatile("stmatrix.sync.aligned.m8n8.x4.shared.b16 [%0], {%1,%2,%3,%4};" ::"r"(a + own()), "r"(v[0]), "r"(v[1]), "r"(v[2]), "r"(v[3]) : "memory");
}
__device__ __forceinline__ void mma16816(float (&d)[4], const uint32_t (&a)[4], uint32_t b0, uint32_t b1) {
  asm volatile("mma.sync.aligned.m16n8k16.row.col.f32.bf16.bf16.f32 {%0,%1,%2,%3}, {%4,%5,%6,%7}, {%8,%9}, {%10,%10,%10,%10};"
               : "=f"(d[0]), "=f"(d[1]), "=f"(d[2]), "=f"(d[3])
               : "r"(a[0]), "r"(a[1]), "r"(a[2]), "r"(a[3]), "r"(b0), "r"(b1), "f"(0.f));
}
__device__ __forceinline__ void mma1688_acc(float (&d)[4], uint32_t a0, uint32_t a1, uint32_t b0) {
  asm volatile("mma.sync.aligned.m16n8k8.row.col.f32.bf16.bf16.f32 {%0,%1,%2,%3}, {%4,%5}, {%6}, {%0,%1,%2,%3};"
               : "+f"(d[0]), "+f"(d[1]), "+f"(d[2]), "+f"(d[3]) : "r"(a0), "r"(a1), "r"(b0));
}
__device__ __forceinline__ float ex2(float x) { float y; asm("ex2.approx.ftz.f32 %0, %1;" : "=f"(y) : "f"(x)); return y; }
__device__ __forceinline__ float rcp(float x) { float y; asm("rcp.approx.ftz.f32 %0, %1;" : "=f"(y) : "f"(x)); return y; }
__device__ __forceinline__ float tanhf_hw(float x) { float y; asm("tanh.approx.f32 %0, %1;" : "=f"(y) : "f"(x)); return y; }
__device__ __forceinline__ uint32_t lds32(uint32_t a) { uint32_t v; asm volatile("ld.shared.u32 %0, [%1];" : "=r"(v) : "r"(a + own()) : "memory"); return v; }
__device__ __forceinline__ float2 lds64(uint32_t a) { float2 v; asm volatile("ld.shared.v2.f32 {%0,%1}, [%2];" : "=f"(v.x), "=f"(v.y) : "r"(a + own()) : "memory"); return v; }
__device__ __forceinline__ void lds128(uint32_t (&v)[4], uint32_t a) { asm volatile("ld.shared.v4.u32 {%0,%1,%2,%3}, [%4];" : "=r"(v[0]), "=r"(v[1]), "=r"(v[2]), "=r"(v[3]) : "r"(a + own()) : "memory"); }
__device__ __forceinline__ void sts128(uint32_t a, const uint32_t (&v)[4]) { asm volatile("st.shared.v4.u32 [%0], {%1,%2,%3,%4};" ::"r"(a + own()), "r"(v[0]), "r"(v[1]), "r"(v[2]), "r"(v[3]) : "memory"); }
__device__ __forceinline__ void ldg128_nc(uint32_t (&v)[4], const void* p) {
  asm volatile("ld.global.nc.L1::no_allocate.v4.u32 {%0,%1,%2,%3}, [%4];" : "=r"(v[0]), "=r"(v[1]), "=r"(v[2]), "=r"(v[3]) : "l"(p));
}
__device__ __forceinline__ uint32_t pin(uint32_t v, uint32_t zero) {
  asm volatile("{\n.reg .pred p;\n.reg .u32 c;\nmov.u32 c, %1;\nLP:\n.pragma \"nounroll\";\nsetp.eq.u32 p, c, 0;\n@p bra LD;\n"
               "nanosleep.u32 c;\nadd.u32 %0, %0, c;\nsub.u32 c, c, 1;\nbra LP;\nLD:\n}\n" : "+r"(v) : "r"(zero) : "memory");
  return v;
}
__device__ __forceinline__ void mbar_arrive_if(uint32_t b, bool cond) {
  asm volatile("{\n.reg .pred p;\nsetp.ne.u32 p, %1, 0;\n@p mbarrier.arrive.shared::cta.b64 _, [%0];\n}\n" ::"r"(b + own()), "r"((uint32_t)cond) : "memory");
}
__device__ __forceinline__ uint32_t ld_epoch(const unsigned* p) {
  uint32_t v;
  asm volatile("ld.relaxed.gpu.global.u32 %0, [%1];" : "=r"(v) : "l"(p) : "memory");
  return v;
}
__device__ __forceinline__ void ll_st(uint4* p, uint32_t a, uint32_t b, uint32_t c, uint32_t d, uint32_t tag) {
  asm volatile("st.relaxed.gpu.global.v4.b32 [%0], {%1, %2, %3, %4};" ::"l"(p), "r"((a & ~1u) | tag), "r"(b), "r"(c), "r"(d) : "memory");
}
__device__ __forceinline__ void ll_ld(uint32_t (&v)[4], const uint4* p) {
  asm volatile("{\n.reg .b128 t;\n.reg .b64 lo, hi;\nld.relaxed.gpu.global.b128 t, [%4];\nmov.b128 {lo, hi}, t;\n"
               "mov.b64 {%0, %1}, lo;\nmov.b64 {%2, %3}, hi;\n}\n"
               : "=r"(v[0]), "=r"(v[1]), "=r"(v[2]), "=r"(v[3]) : "l"(p) : "memory");
}
template <int N> __device__ __forceinline__ void ll_issue(uint32_t (&v)[N][4], const uint4* p, int stride) {
#pragma unroll
  for (int i = 0; i < N; i++) ll_ld(v[i], p + i * stride);
}
template <int N> __device__ __forceinline__ uint32_t ll_acc(const uint32_t (&v)[N][4], uint32_t tag, uint32_t acc = 0) {
#pragma unroll
  for (int i = 0; i < N; i++) asm("lop3.b32 %0, %1, %2, %0, 0xBE;" : "+r"(acc) : "r"(v[i][0]), "r"(tag));
  return acc;
}
__device__ __forceinline__ bool ll_any(uint32_t acc) { return __any_sync(0xffffffffu, acc & 1u); }
template <int N> __device__ __forceinline__ bool ll_bad(const uint32_t (&v)[N][4], uint32_t tag) { return ll_any(ll_acc<N>(v, tag)); }
template <int N> __device__ __forceinline__ void ll_clear(uint32_t (&v)[N][4]) {
#pragma unroll
  for (int i = 0; i < N; i++) v[i][0] &= ~1u;
}
template <int N> __device__ __forceinline__ void ll_spin(uint32_t (&v)[N][4], const uint4* p, int stride, uint32_t tag) {
  uint32_t it = 0;
#pragma unroll 1
  do { ll_issue<N>(v, p, stride); } while (ll_bad<N>(v, tag) && ++it < SPIN_LIMIT);
}
template <int N> __device__ __forceinline__ void ll_get(uint32_t (&v)[N][4], const uint4* p, int stride, uint32_t tag) {
  ll_spin<N>(v, p, stride, tag);
  ll_clear<N>(v);
}
template <int N> __device__ __forceinline__ void ll_wait(uint32_t (&v)[N][4], const uint4* p, int stride, uint32_t tag) {
  if (__builtin_expect(ll_bad<N>(v, tag), 0)) ll_spin<N>(v, p, stride, tag);
  ll_clear<N>(v);
}
__device__ __forceinline__ void unpack32(float (&d)[32], const uint32_t (&v)[4][4]) {
#pragma unroll
  for (int u = 0; u < 4; u++)
#pragma unroll
    for (int e = 0; e < 4; e++) { d[8 * u + 2 * e] = bf_lo(v[u][e]); d[8 * u + 2 * e + 1] = bf_hi(v[u][e]); }
}
__device__ __forceinline__ void pack32(uint32_t (&v)[4][4], const float (&d)[32]) {
#pragma unroll
  for (int u = 0; u < 4; u++)
#pragma unroll
    for (int e = 0; e < 4; e++) v[u][e] = pack2(d[8 * u + 2 * e], d[8 * u + 2 * e + 1]);
}
__device__ __forceinline__ uint32_t t_addr(int m) { return SB + ((0x01534620u >> (4 * m)) & 7u) * 32768u; }

__device__ __forceinline__ int kb_at(int i, int j) { return i == 0 ? j : (i - 1 + (i - 1 >= j ? 1 : 0)); }

__device__ __forceinline__ void init_bars(int set) {
  if (set >= 0 && elect_one()) {
    const uint32_t cnt = set < 5 ? 1 : 8;
#pragma unroll
    for (int i = 0; i < 8; i++) mbar_init(BAR + (24 + 8 * set + i) * 8, cnt);
    if (set == 9) {
#pragma unroll
      for (int i = 0; i < 9; i++) mbar_init(BAR + (B_EX + i) * 8, 4);
#pragma unroll
      for (int i = 0; i < 4; i++) mbar_init(BAR + (B_READY + i) * 8, i == 1 ? 7 : 3);
#pragma unroll
      for (int i = 0; i < 7; i++) mbar_init(BAR + (B_TAG + i) * 8, i < 3 ? 1 : 4);
    }
    asm volatile("fence.mbarrier_init.release.cluster;" ::: "memory");
  }
  __syncwarp();
  asm volatile("barrier.cluster.arrive.release.aligned;" ::: "memory");
  asm volatile("bar.arrive 4, 384;" ::: "memory");
  asm volatile("bar.sync 3, 384;" ::: "memory");
}

__global__ void __launch_bounds__(384, 1) fused_block_kernel(Scratch* __restrict__ X, const __nv_bfloat16* __restrict__ xp,
                                                             const __nv_bfloat16* __restrict__ wqkvp, const __nv_bfloat16* __restrict__ wop, const uint32_t zero,
                                                             const __grid_constant__ Params P) {
  extern __shared__ __align__(1024) uint8_t smem_raw[];
  if (smem_u32(smem_raw) != SB + own()) return;
  const int tid = threadIdx.x;
  const int warp = __shfl_sync(0xffffffffu, tid >> 5, 0);
  const int lane = tid & 31;
  const int cta = blockIdx.x;
  const int j = ((cta >> 1) & 1) * 4 + ((cta >> 4) & 1) * 2 + (cta & 1);
  const int g = ((cta >> 2) & 3) * 4 + (cta >> 5);

  if (warp >= 8) {
    asm volatile("setmaxnreg.dec.sync.aligned.u32 56;");
    if (warp == 8) {
      PSTAMPW(2, 0);
      const bool leader = elect_one();
      if (leader) {
        prefetch_map(&P.x); prefetch_map(&P.wqkv);
#pragma unroll
        for (int i = 0; i < 24; i++) mbar_init(BAR + i * 8, 1);
        asm volatile("fence.mbarrier_init.release.cluster;" ::: "memory");
      }
      __syncwarp();
      asm volatile("bar.arrive 3, 384;" ::: "memory");
      asm volatile("barrier.cluster.arrive.release.aligned;" ::: "memory");
      auto ldx = [&](int p, int kb) {
        const uint32_t b = BAR + (B_FX + p * 8 + kb) * 8;
        mbar_expect_tx(b, 8192);
        tma3d(H0 + p * 65536 + kb * 8192, &P.x, kb * 64, p, g * 64, b);
      };
      auto ldkv = [&](int kb, int slot) {
        const uint32_t b = BAR + (B_FKV + kb) * 8, d = RING + slot * 16384;
        mbar_expect_tx(b, 16384);
        tma2d(d, &P.wqkv, 512 + 64 * j, kb * 64, b);
        tma2d(d + 8192, &P.wqkv, 1024 + 64 * j, kb * 64, b);
      };
      if (leader) {
#pragma unroll 1
        for (int i = 0; i < 8 + XO_DELAY; i++) {
          if (i < 8) ldx(0, i);
          if (i < 6) ldkv(i, i);
          if (i >= XO_DELAY) ldx(1, i - XO_DELAY);
        }
        PSTAMPW(2, 2);
      }
      __syncwarp();
      asm volatile("bar.sync 4, 384;" ::: "memory");
      if (leader) {
        const int f0 = 224 * j + ((j & 1) ? 32 : 0);
        const int fh = 224 * j + ((j & 1) ? 0 : 192);
        prefetch_map(&P.wo); prefetch_map(&P.w1); prefetch_map(&P.w3); prefetch_map(&P.w1h);
        prefetch_map(&P.w3h); prefetch_map(&P.w2); prefetch_map(&P.out);
#pragma unroll 1
        for (int i = 0; i < 2; i++) { mbar_wait(BAR + (B_EKV + i) * 8); ldkv(6 + i, i); }
#pragma unroll 1
        for (int i = 0; i < 8; i++) {
          const uint32_t b = BAR + (B_FQ + i) * 8;
          mbar_wait(BAR + (B_EKV + 2 + (i >> 1)) * 8);
          mbar_expect_tx(b, 8192);
          tma2d(RING + (4 + i) * 8192, &P.wqkv, 64 * j, i * 64, b);
        }
        mbar_expect_tx(BAR + B_FWO * 8, 65536);
#pragma unroll 1
        for (int i = 0; i < 8; i++) {
          const int kb = (i + 1) & 7;
          mbar_wait(BAR + (B_EX + i) * 8);
          tma2d(H0 + kb * 8192, &P.wo, 64 * j, kb * 64, BAR + B_FWO * 8);
        }
#pragma unroll 1
        for (int i = 0; i < 8; i++) {
          const uint32_t b = BAR + (B_FA + i) * 8, d = RING + (i & 3) * 24576;
          const int k0 = kb_at(i, j) * 64;
          mbar_wait(BAR + (B_EKV + 7 + ((0xCBA98520u >> (4 * i)) & 15)) * 8);
          mbar_expect_tx(b, 24576);
          tma2d(d, &P.w1, f0, k0, b);
          tma2d(d + 8192, &P.w3, f0, k0, b);
          tma2d(d + 16384, &P.w1h, fh, k0, b);
          tma2d(d + 20480, &P.w3h, fh, k0, b);
        }
        uint32_t d = RING;
#pragma unroll 1
        for (int i = 0; i < 8; i++) {
          const uint32_t b = BAR + (B_FB + i) * 8;
          const int k0 = kb_at(i, j) * 64;
          mbar_wait(BAR + (B_EA + 5 + i) * 8);
          mbar_expect_tx(b, 32768);
          tma2d(d, &P.w1, f0 + 64, k0, b);
          tma2d(d + 8192, &P.w3, f0 + 64, k0, b);
          tma2d(d + 16384, &P.w1, f0 + 128, k0, b);
          tma2d(d + 24576, &P.w3, f0 + 128, k0, b);
          d = d == RING + 65536 ? RING : d + 32768;
        }
#pragma unroll 1
        for (int i = 0; i < 8; i++) {
          const int m = (0x76453210u >> (4 * i)) & 7;
          const uint32_t b = BAR + (B_FT + m) * 8;
          mbar_wait(BAR + (i < 5 ? B_EB + 3 + i : i < 7 ? B_HC - 5 + i : B_ET0) * 8);
          mbar_expect_tx(b, 28672);
          tma2d(t_addr(m), &P.w2, 64 * ((j + 2 + (m & 6)) & 7), 224 * (j ^ (m & 1)), b);
        }
        mbar_expect_tx(BAR + B_FIN * 8, 2 * 16384);
#pragma unroll 1
        for (int q = 0; q < 2; q++) {
          mbar_wait(BAR + (B_ET0 + 2 + q) * 8);
          asm volatile("cp.async.bulk.shared::cluster.global.mbarrier::complete_tx::bytes [%0], [%1], 16384, [%2];"
                       ::"r"(t_addr(q + 1) + own()), "l"(X->e4 + ((g * 8 + j) * 3 + q) * 1024), "r"(BAR + B_FIN * 8 + own()) : "memory");
        }
        X->epoch[cta] = X->epoch[cta] + 1;
      }
    } else {
      const int part = warp - 9;
      uint32_t tag;
      if (part == 2) {
        tag = ld_epoch(X->epoch + cta);
        init_bars(-1);
        tag = (tag + 1) & 1;
        if (lane == 0) {
          asm volatile("st.shared.u32 [%0], %1;" ::"r"(TAGS + own()), "r"(tag) : "memory");
          mbar_arrive(BAR + B_TAG * 8);
        }
      } else {
        init_bars(warp - 1);
        mbar_wait(BAR + B_TAG * 8);
        tag = lds32(TAGS);
      }
      PSTAMPW(3, 16 + part);
      const int xw0 = g * 8;
      auto clear8 = [&](uint4* p, int stride) {
#pragma unroll
        for (int i = 0; i < 8; i++) ll_st(p + i * stride + lane, 0, 0, 0, 0, tag ^ 1);
      };
      auto clear_front = [&]() {
#pragma unroll 1
      for (int u = part; u < 8; u += 3) clear8((u < 4 ? X->e2 : X->e3h) + (xw0 * 32 + 4 * j + (u & 3)) * 32, 1024);
      if (part == 2) {
        clear8(X->e1 + (g * 8 + j) * 256, 32);
#pragma unroll
        for (int i = 0; i < 4; i++)
          ll_st((i < 2 ? X->e2s : X->e3s) + ((xw0 + (i & 1) * 4 + (lane >> 3)) * 8 + j) * 8 + (lane & 7), 0, 0, 0, 0, tag ^ 1);
      }
      };
      if (CLR_MODE == 1) clear_front();
      PSTAMPW(3, 20 + part);
      uint32_t v[8][4];
      if (part < 2) {
        float s[4] = {0.f, 0.f, 0.f, 0.f}, q[4] = {0.f, 0.f, 0.f, 0.f}, piv = 0.f;
        const uint32_t xa = H0 + part * 65536 + (8 * j + (lane >> 2)) * 128 + (lane & 3) * 16 + (lane & 4) * 16;
#pragma unroll 1
        for (int kb = 0; kb < 8; kb++) {
          mbar_wait(BAR + (B_FX + part * 8 + kb) * 8);
          lds128(v[0], xa + kb * 8192); lds128(v[1], (xa + kb * 8192) ^ 64);
          if (kb == 0) piv = __shfl_sync(0xffffffffu, bf_lo(v[0][0]), lane & 28);
#pragma unroll
          for (int e = 0; e < 8; e++) {
            const float a = bf_lo(v[e >> 2][e & 3]) - piv, b = bf_hi(v[e >> 2][e & 3]) - piv;
            s[e & 3] += a + b; q[e & 3] = fmaf(a, a, q[e & 3]); q[e & 3] = fmaf(b, b, q[e & 3]);
          }
        }
        float ss = (s[0] + s[1]) + (s[2] + s[3]), qq = (q[0] + q[1]) + (q[2] + q[3]);
#pragma unroll
        for (int o = 1; o <= 2; o <<= 1) { ss += __shfl_xor_sync(0xffffffffu, ss, o); qq += __shfl_xor_sync(0xffffffffu, qq, o); }
        const float dm = ss * (1.f / D_);
        const float rs = rsqrtf(fmaxf(fmaf(-dm, dm, qq * (1.f / D_)), 0.f) + 1e-5f);
        if ((lane & 3) == 0) ll_st(X->e0s + g * 128 + 2 * (8 * j + (lane >> 2)) + part, __float_as_uint(piv + dm), __float_as_uint(rs), 0, 0, tag);
      } else {
        mbar_wait(BAR + (B_FKV + SIDE_KB) * 8);
        const __nv_bfloat16* wr = wop + (size_t)(j * 64 + g * 4 + (lane >> 3)) * D_ + (lane & 7) * 8;
#pragma unroll
        for (int i = 0; i < 8; i++) ldg128_nc(v[i], wr + i * 64);
        float s[4];
#pragma unroll
        for (int e = 0; e < 4; e++) {
          s[e] = 0.f;
#pragma unroll
          for (int i = 0; i < 8; i++) s[e] += bf_lo(v[i][e]) + bf_hi(v[i][e]);
        }
        float ss = (s[0] + s[1]) + (s[2] + s[3]);
#pragma unroll
        for (int o = 1; o <= 4; o <<= 1) ss += __shfl_xor_sync(0xffffffffu, ss, o);
        if ((lane & 7) == 0) ll_st(X->e0w + j * 64 + g * 4 + (lane >> 3), __float_as_uint(ss * (1.f / D_)), 0, 0, 0, tag);
      }
      __syncwarp();
      if (lane == 0) mbar_arrive(BAR + B_PUB * 8);
      PSTAMPW(3, part * 4 + 2);
      mbar_wait(BAR + B_PUB * 8);
      PSTAMPW(3, part * 4 + 0);
      {
        uint32_t u[2][4];
        const uint4* us = (part == 2 ? X->e0w + j * 64 : X->e0s + g * 128 + part * 64) + lane;
        const uint4* vs = X->e0c + ((j * 3 + part) * 16 + (lane >> 4) * 8) * 16 + (lane & 15);
        uint32_t it = 0;
#pragma unroll 1
        do { ll_issue<2>(u, us, 32); ll_issue<8>(v, vs, 16); } while (ll_any(ll_acc<8>(v, tag, ll_acc<2>(u, tag))) && ++it < SPIN_LIMIT);
        ll_clear<2>(u); ll_clear<8>(v);
#pragma unroll
        for (int i = 0; i < 2; i++) {
          if (part == 2) asm volatile("st.shared.u32 [%0], %1;" ::"r"(WB + own() + (i * 32 + lane) * 4), "r"(u[i][0]) : "memory");
          else asm volatile("st.shared.v2.u32 [%0], {%1,%2};" ::"r"(ST + own() + (part * 64 + i * 32 + lane) * 8), "r"(u[i][0]), "r"(u[i][1]) : "memory");
        }
      }
      uint32_t o[4];
#pragma unroll
      for (int e = 0; e < 4; e++) {
        float s = 0.f;
#pragma unroll
        for (int i = 0; i < 8; i++) s += __uint_as_float(v[i][e]);
        o[e] = __float_as_uint(s + __shfl_xor_sync(0xffffffffu, s, 16));
      }
      if (lane < 16) sts128(CS + (part * 64 + lane * 4) * 4, o);
      __syncwarp();
      if (lane == 0) mbar_arrive(BAR + B_READY * 8);
      PSTAMPW(3, part * 4 + 1);
      if (CLR_MODE == 2) clear_front();
      __syncwarp();
      if (lane == 0) mbar_arrive(BAR + B_CLR0 * 8);
      PSTAMPW(3, 24 + part);
      if (lane == 0) l2_prefetch(part == 0 ? P.w1p + (size_t)cta * 4 * F_ : part == 1 ? P.w3p + (size_t)cta * 4 * F_ : P.w2p + (size_t)cta * 14 * D_, 14336);
    }
  } else {
    const int p = warp >> 2, w = warp & 3;
    const int r = lane >> 2, c = lane & 3;
    init_bars(warp);
    asm volatile("setmaxnreg.inc.sync.aligned.u32 224;");
    PSTAMP(0);
    const uint32_t dAx = descA(H0) + p * 4096;
    const uint32_t Hn = H1 - p * 65536;
    const uint32_t moff = ((lane & 7) + ((lane >> 3) & 1) * 8) * 128 + (((lane >> 4) ^ (lane & 7)) << 4);
    const uint32_t Xw = H0 + p * 65536 + w * 2048;
    const int xw = (g * 2 + p) * 4 + w;
    if (p == 1) {
      uint32_t v[8][4];
      mbar_wait(BAR + (B_FKV + SIDE_KB) * 8);
      const int wp = w < 3 ? w : 0;
      const __nv_bfloat16* wr = wqkvp + (size_t)(g * 32 + (lane >> 3) * 8) * (3 * D_) + wp * D_ + j * 64 + (lane & 7) * 8;
#pragma unroll
      for (int i = 0; i < 8; i++) ldg128_nc(v[i], wr + (size_t)i * 3 * D_);
      mbar_wait(BAR + B_TAG * 8);
      const uint32_t tg = lds32(TAGS);
      float cs[8];
#pragma unroll
      for (int e = 0; e < 4; e++) {
        float a = 0.f, b = 0.f;
#pragma unroll
        for (int i = 0; i < 8; i++) { a += bf_lo(v[i][e]); b += bf_hi(v[i][e]); }
        cs[2 * e] = a; cs[2 * e + 1] = b;
      }
      const bool up = lane & 8;
#pragma unroll
      for (int e = 0; e < 4; e++) {
        const float keepv = up ? cs[4 + e] : cs[e], give = up ? cs[e] : cs[4 + e];
        cs[e] = keepv + __shfl_xor_sync(0xffffffffu, give, 8);
        cs[e] += __shfl_xor_sync(0xffffffffu, cs[e], 16);
      }
      if (lane < 16 && w < 3)
        ll_st(X->e0c + ((j * 3 + w) * 16 + g) * 16 + (lane & 7) * 2 + (lane >> 3), __float_as_uint(cs[0]), __float_as_uint(cs[1]),
              __float_as_uint(cs[2]), __float_as_uint(cs[3]), tg);
      __syncwarp();
      mbar_arrive_if(BAR + B_PUB * 8, lane == 0);
      PSTAMP(1);
      mbar_wait(BAR + B_LAG * 8);
    }

    float akv[64];
#pragma unroll 1
    for (int kb = 0; kb < 8; kb++) {
      mbar_wait(BAR + (B_FX + p * 8 + kb) * 8);
      mbar_wait(BAR + (B_FKV + kb) * 8);
      if (kb == 0) PSTAMP(2);
      const uint32_t da = dAx + kb * 512, db = descB(RING) + (kb < 6 ? kb : kb - 6) * 1024;
      wg_fence();
      wgmma_ss_n128(akv, da, db, kb);
#pragma unroll
      for (int k = 1; k < 4; k++) wgmma_ss_n128(akv, da + k * 2, db + k * 128, 1);
      wg_commit();
      mbar_arrive_if(BAR + B_LAG * 8, kb == LAG_KB - 1 && p == 0 && lane == 0);
      wg_wait<1>();
      mbar_arrive_if(BAR + (B_EKV + kb - 1) * 8, kb > 0 && lane == 0);
    }
    uint32_t xres[4][4];
#pragma unroll
    for (int u = 0; u < 4; u++) ldsm4(xres[u], Xw + j * 8192 + (moff ^ (u << 5)));

    float aq[32];
    auto qstep = [&](int kb) {
      mbar_wait(BAR + (B_FQ + kb) * 8);
      const uint32_t da = dAx + kb * 512, db = descB(RING + 32768) + kb * 512;
      wg_fence();
      wgmma_ss_n64(aq, da, db, kb);
#pragma unroll
      for (int k = 1; k < 4; k++) wgmma_ss_n64(aq, da + k * 2, db + k * 128, 1);
      wg_commit();
      wg_wait<1>();
      mbar_arrive_if(BAR + (B_EQ + kb - 1) * 8, lane == 0);
      mbar_arrive_if(BAR + (B_EX + kb - 2) * 8, lane == 0 && p == 0 && kb >= 2);
    };
    qstep(0);
    keep(akv);
    PSTAMP(3);
    qstep(1);
    mbar_wait(BAR + B_READY * 8);
    PSTAMP(19);
    const uint32_t tag = lds32(TAGS);
    uint4* const xb = reinterpret_cast<uint4*>(X) + lane + (tag >> 1);
    constexpr int O_E4 = offsetof(Scratch, e4) / 16, O_E2 = offsetof(Scratch, e2) / 16, O_E3H = offsetof(Scratch, e3h) / 16;
    const float2 st0 = lds64(ST + (2 * (16 * w + r) + p) * 8);
    const float2 st1 = lds64(ST + (2 * (16 * w + r + 8) + p) * 8);
    uint32_t hi[4][4], lo[4][4];
    {
      float2 cs[16];
      auto cvt = [&](uint32_t (&d)[4][4], int b0, int ofs, const float2& st) {
#pragma unroll
        for (int b = b0; b < b0 + 8; b++) {
          if (ofs == 2) cs[b] = lds64(CS + (64 + b * 8 + 2 * c) * 4);
          const uint32_t v = pack2(fmaf(-st.x, cs[b].x, akv[4 * b + ofs]) * st.y, fmaf(-st.x, cs[b].y, akv[4 * b + ofs + 1]) * st.y);
          d[b >> 2][b & 3] = b < 8 ? v : movm(v);
        }
      };
      cvt(hi, 0, 2, st1);
      keep(hi[0]); keep(hi[1]);
      qstep(2);
      cvt(hi, 8, 2, st1);
      mbar_wait(BAR + B_CLR0 * 8);
      if (w == 3 && g < 15) {
        uint4* dst = X->e1 + ((g * 8 + j) * 2 + p) * 128 + lane;
#pragma unroll
        for (int i = 0; i < 4; i++) ll_st(dst + i * 32, hi[i][0], hi[i][1], hi[i][2], hi[i][3], tag);
      }
      PSTAMP(20);
      wg_bar(p);
#pragma unroll
      for (int i = 0; i < 4; i++) sts128(Xw + lane * 16 + i * 512, hi[i]);
      qstep(3);
      cvt(lo, 0, 0, st0);
      keep(lo[0]); keep(lo[1]);
      qstep(4);
      cvt(lo, 8, 0, st0);
    }
    PSTAMP(21);
    wg_bar(p);
    uint32_t prev[4][4];
    if (w > 0) {
#pragma unroll
      for (int i = 0; i < 4; i++) lds128(prev[i], Xw - 2048 + lane * 16 + i * 512);
    }
    if (p == 0) {
      asm volatile("fence.proxy.async.shared::cta;" ::: "memory");
      __syncwarp();
      if (lane == 0) mbar_arrive(BAR + (B_EX + 7) * 8);
    }
    PSTAMP(22);
    const uint4* halo = X->e1 + (((g - 1) * 8 + j) * 2 + p) * 128 + lane;
    const bool use_halo = w == 0 && g > 0;
    qstep(5);
    if (use_halo) ll_issue<4>(prev, halo, 32);
    qstep(6);
    qstep(7);
    PSTAMP(23);
    if (w == 0) {
      if (g > 0) {
        if (__builtin_expect(ll_bad<4>(prev, pin(tag, zero)), 0)) ll_spin<4>(prev, halo, 32, tag);
        ll_clear<4>(prev);
      } else {
#pragma unroll
        for (int i = 0; i < 4; i++)
#pragma unroll
          for (int e = 0; e < 4; e++) prev[i][e] = 0;
      }
    }
    wg_wait<0>();
    keep(aq);
    mbar_arrive_if(BAR + (B_EQ + 7) * 8, lane == 0);
    mbar_arrive_if(BAR + (B_EX + 6) * 8, lane == 0 && p == 0);
    PSTAMP(4);

    uint32_t of[4][4];
    {
      const float sc = 0.25f * 1.4426950408889634f;
      const float nohalo = (g == 0 && w == 0) ? -INFINITY : 0.f;
      const bool up0 = 2 * c > r, up1 = 2 * c + 1 > r;
      const uint32_t mup = (up0 ? 0xffffu : 0u) | (up1 ? 0xffff0000u : 0u);
      uint4* dst = xb + O_E2 + (xw * 32 + 4 * j) * 32;
      float d0 = 0.f, d1 = 0.f;
#pragma unroll 1
      for (int hp = 0; hp < 2; hp++) {
#pragma unroll
        for (int e = 0; e < 4; e++) { of[0][e] = of[2][e]; of[1][e] = of[3][e]; }
#pragma unroll
        for (int h = 0; h < 2; h++) {
          uint32_t qf[4];
          const uint32_t co = (32 * hp + 16 * h + 2 * c) * 4;
          {
            const float2 ca = lds64(CS + co), cb = lds64(CS + co + 32);
            qf[0] = pack2(fmaf(-st0.x, ca.x, aq[8 * h + 0]) * st0.y, fmaf(-st0.x, ca.y, aq[8 * h + 1]) * st0.y);
            qf[1] = pack2(fmaf(-st1.x, ca.x, aq[8 * h + 2]) * st1.y, fmaf(-st1.x, ca.y, aq[8 * h + 3]) * st1.y);
            qf[2] = pack2(fmaf(-st0.x, cb.x, aq[8 * h + 4]) * st0.y, fmaf(-st0.x, cb.y, aq[8 * h + 5]) * st0.y);
            qf[3] = pack2(fmaf(-st1.x, cb.x, aq[8 * h + 6]) * st1.y, fmaf(-st1.x, cb.y, aq[8 * h + 7]) * st1.y);
          }
          const int e0 = 2 * h;
          float sp[4], sl[4], sh[4];
          mma16816(sp, qf, prev[0][e0], prev[0][e0 + 1]);
          mma16816(sl, qf, lo[0][e0], lo[0][e0 + 1]);
          mma16816(sh, qf, hi[0][e0], hi[0][e0 + 1]);
          float a0 = up0 ? sp[0] + nohalo : sl[0], a1 = up1 ? sp[1] + nohalo : sl[1];
          float b0 = up0 ? sl[2] : sh[2], b1 = up1 ? sl[3] : sh[3];
          float ma = fmaxf(a0, a1), mb = fmaxf(b0, b1);
          ma = fmaxf(ma, __shfl_xor_sync(0xffffffffu, ma, 1)); mb = fmaxf(mb, __shfl_xor_sync(0xffffffffu, mb, 1));
          ma = fmaxf(ma, __shfl_xor_sync(0xffffffffu, ma, 2)); mb = fmaxf(mb, __shfl_xor_sync(0xffffffffu, mb, 2));
          a0 = ex2((a0 - ma) * sc); a1 = ex2((a1 - ma) * sc); b0 = ex2((b0 - mb) * sc); b1 = ex2((b1 - mb) * sc);
          float sa = a0 + a1, sbb = b0 + b1;
          sa += __shfl_xor_sync(0xffffffffu, sa, 1); sbb += __shfl_xor_sync(0xffffffffu, sbb, 1);
          sa += __shfl_xor_sync(0xffffffffu, sa, 2); sbb += __shfl_xor_sync(0xffffffffu, sbb, 2);
          const float ia = rcp(sa), ib = rcp(sbb);
          const uint32_t pa = pack2(a0 * ia, a1 * ia), pb = pack2(b0 * ib, b1 * ib);
          const uint32_t pf[4] = {pa & mup, 0u, pa & ~mup, pb & mup};
          const uint32_t ph = pb & ~mup;
          float o0[4], o1[4];
          mma16816(o0, pf, prev[2][e0], lo[2][e0]);
          mma16816(o1, pf, prev[2][e0 + 1], lo[2][e0 + 1]);
          mma1688_acc(o0, 0u, ph, hi[2][e0]);
          mma1688_acc(o1, 0u, ph, hi[2][e0 + 1]);
          of[2 + h][0] = pack2(o0[0], o0[1]); of[2 + h][1] = pack2(o0[2], o0[3]);
          of[2 + h][2] = pack2(o1[0], o1[1]); of[2 + h][3] = pack2(o1[2], o1[3]);
          ll_st(dst + (2 * hp + h) * 32, of[2 + h][0], of[2 + h][1], of[2 + h][2], of[2 + h][3], tag);
          const float2 wa = lds64(WB + co), wb = lds64(WB + co + 32);
          d0 = fmaf(o0[0], wa.x, d0); d0 = fmaf(o0[1], wa.y, d0); d0 = fmaf(o1[0], wb.x, d0); d0 = fmaf(o1[1], wb.y, d0);
          d1 = fmaf(o0[2], wa.x, d1); d1 = fmaf(o0[3], wa.y, d1); d1 = fmaf(o1[2], wb.x, d1); d1 = fmaf(o1[3], wb.y, d1);
        }
#pragma unroll
        for (int e = 0; e < 16; e++) aq[e] = aq[16 + e];
#pragma unroll
        for (int e = 0; e < 4; e++) {
          prev[0][e] = prev[1][e]; prev[2][e] = prev[3][e];
          lo[0][e] = lo[1][e]; lo[2][e] = lo[3][e];
          hi[0][e] = hi[1][e]; hi[2][e] = hi[3][e];
        }
      }
#pragma unroll
      for (int o = 1; o <= 2; o <<= 1) { d0 += __shfl_xor_sync(0xffffffffu, d0, o); d1 += __shfl_xor_sync(0xffffffffu, d1, o); }
      if (c == 0) ll_st(X->e2s + (xw * 8 + j) * 8 + r, __float_as_uint(d0), __float_as_uint(d1), 0, 0, tag);
    }
    PSTAMP(5);

    float ah[32];
    uint32_t sv[2][4];
    unpack32(ah, xres);
    {
      uint32_t og[2][14][4];
      const uint4* osrc[7];
#pragma unroll
      for (int i = 0; i < 7; i++) osrc[i] = xb + O_E2 + (xw * 32 + 4 * kb_at(i + 1, j)) * 32;
      const uint4* ssrc = X->e2s + (xw * 8 + 2 * c) * 8 + r;
      auto oissue = [&](int hp) {
#pragma unroll
        for (int i = 0; i < 14; i++) ll_ld(og[hp][i], osrc[i >> 1] + (2 * hp + (i & 1)) * 32);
        if (hp == 1) ll_issue<2>(sv, ssrc, 8);
      };
      auto omma = [&](int hp) {
        ll_clear<14>(og[hp]);
        keep(og[hp]);
        wg_fence();
#pragma unroll
        for (int i = 0; i < 14; i++) wgmma_rs_n64(ah, og[hp][i], descB(H0) + kb_at((i >> 1) + 1, j) * 512 + (2 * hp + (i & 1)) * 128, 1);
        wg_commit();
      };
      mbar_wait(BAR + B_FWO * 8);
      keep(ah); keep(of);
      wg_fence();
#pragma unroll
      for (int k = 0; k < 4; k++) wgmma_rs_n64(ah, of[k], descB(H0) + j * 512 + k * 128, 1);
      wg_commit();
      uint32_t it = 0;
#pragma unroll 1
      do { oissue(0); } while (ll_bad<14>(og[0], tag) && ++it < SPIN_LIMIT);
      PSTAMP(6);
      oissue(1);
      omma(0);
      const uint32_t tg = pin(tag, zero);
      if (__builtin_expect(ll_any(ll_acc<14>(og[1], tg, ll_acc<2>(sv, tg))), 0)) {
#pragma unroll 1
        do { oissue(1); } while (ll_any(ll_acc<14>(og[1], tag, ll_acc<2>(sv, tag))) && ++it < SPIN_LIMIT);
      }
      PSTAMP(16);
      omma(1);
      ll_clear<2>(sv);
    }
    float m0 = __uint_as_float(sv[0][0]) + __uint_as_float(sv[1][0]), m1 = __uint_as_float(sv[0][1]) + __uint_as_float(sv[1][1]);
#pragma unroll
    for (int o = 1; o <= 2; o <<= 1) { m0 += __shfl_xor_sync(0xffffffffu, m0, o); m1 += __shfl_xor_sync(0xffffffffu, m1, o); }
    const uint32_t mu0 = pack2(m0 + st0.x, m0 + st0.x), mu1 = pack2(m1 + st1.x, m1 + st1.x);
    wg_wait<0>();
    keep(ah);
    if (lane == 0) mbar_arrive(BAR + B_WODONE * 8);
    PSTAMP(7);

    uint32_t hf[4][4], ra[4][4];
    pack32(hf, ah);
    {
      uint4* dst = xb + O_E3H + (xw * 32 + 4 * j) * 32;
#pragma unroll
      for (int u = 0; u < 4; u++) {
        ra[u][0] = hsub2(hf[u][0], mu0); ra[u][1] = hsub2(hf[u][1], mu1);
        ra[u][2] = hsub2(hf[u][2], mu0); ra[u][3] = hsub2(hf[u][3], mu1);
        ll_st(dst + u * 32, ra[u][0], ra[u][1], ra[u][2], ra[u][3], tag);
      }
      float s0 = 0.f, q0 = 0.f, s1 = 0.f, q1 = 0.f;
#pragma unroll
      for (int b = 0; b < 8; b++) {
        s0 += ah[4 * b] + ah[4 * b + 1]; s1 += ah[4 * b + 2] + ah[4 * b + 3];
        q0 = fmaf(ah[4 * b], ah[4 * b], q0); q0 = fmaf(ah[4 * b + 1], ah[4 * b + 1], q0);
        q1 = fmaf(ah[4 * b + 2], ah[4 * b + 2], q1); q1 = fmaf(ah[4 * b + 3], ah[4 * b + 3], q1);
      }
#pragma unroll
      for (int o = 1; o <= 2; o <<= 1) {
        s0 += __shfl_xor_sync(0xffffffffu, s0, o); q0 += __shfl_xor_sync(0xffffffffu, q0, o);
        s1 += __shfl_xor_sync(0xffffffffu, s1, o); q1 += __shfl_xor_sync(0xffffffffu, q1, o);
      }
      if (c == 0) ll_st(X->e3s + (xw * 8 + j) * 8 + r, __float_as_uint(s0), __float_as_uint(q0), __float_as_uint(s1), __float_as_uint(q1), tag);
      mbar_wait(BAR + (p == 0 ? B_EQ + 7 : B_WODONE) * 8);
    }
    PSTAMP(8);

    float rs0, rs1;
    auto swiglu = [&](float g0, float g1, float u0, float u1, float rs) -> uint32_t {
      const float hr = 0.5f * rs;
      const float x0 = g0 * hr, x1 = g1 * hr;
      const float t0 = tanhf_hw(x0), t1 = tanhf_hw(x1);
      return pack2(fmaf(x0, t0, x0) * (u0 * rs), fmaf(x1, t1, x1) * (u1 * rs));
    };
    uint32_t hA[6][4];
    {
      float a1[64], a2[32];
      const uint4* src = xb + O_E3H + xw * 32 * 32;
      uint32_t rb[4][4], rc[4][4], rd[4][4];
      auto fetch = [&](uint32_t (&a)[4][4], int i) { ll_issue<4>(a, src + kb_at(i, j) * 128, 32); };
      auto check = [&](uint32_t (&a)[4][4], uint32_t (&b)[4][4], int i) {
        const uint32_t tg = pin(tag, zero);
        if (__builtin_expect(ll_any(ll_acc<4>(a, tg, ll_acc<4>(b, tg))), 0)) {
          uint32_t it = 0;
#pragma unroll 1
          do { fetch(a, i); fetch(b, i + 1); } while (ll_any(ll_acc<4>(a, tag, ll_acc<4>(b, tag))) && ++it < SPIN_LIMIT);
        }
        ll_clear<4>(a); ll_clear<4>(b);
        keep(a); keep(b);
      };
      auto head = [&](uint32_t (&a)[4][4], int i) {
        mbar_wait(BAR + (B_FA + i) * 8);
        wg_fence();
        wgmma_rs_n64<DESC_HI64>(a2, a[0], descBh(RING + 16384) + (i & 3) * 1536, i);
        wgmma_rs_n128(a1, a[0], descB(RING) + (i & 3) * 1536, i);
        wg_commit();
#pragma unroll
        for (int u = 0; u < 4; u++) stsm4(Hn + w * 2048 + i * 8192 + (moff ^ (u << 5)), a[u]);
        wg_wait<1>();
        if (i > 0) mbar_arrive_if(BAR + (B_EA + i - 1) * 8, lane == 0);
      };
      auto rest = [&](uint32_t (&a)[4][4], int i) {
        wg_fence();
#pragma unroll
        for (int k = 1; k < 4; k++) {
          wgmma_rs_n64<DESC_HI64>(a2, a[k], descBh(RING + 16384) + (i & 3) * 1536 + k * 64, 1);
          wgmma_rs_n128(a1, a[k], descB(RING) + (i & 3) * 1536 + k * 128, 1);
        }
        wg_commit();
      };
      ll_clear<4>(ra);
      keep(ra);
      head(ra, 0); rest(ra, 0);
      ll_get<4>(rb, src + kb_at(1, j) * 128, 32, tag);
      keep(rb);
      PSTAMP(17);
      fetch(rc, 2); fetch(rd, 3);
      head(rb, 1); rest(rb, 1);
      check(rc, rd, 2);
      head(rc, 2); fetch(ra, 4); fetch(rb, 5); rest(rc, 2);
      head(rd, 3); rest(rd, 3);
      check(ra, rb, 4);
      head(ra, 4); fetch(rc, 6); fetch(rd, 7); ll_issue<2>(sv, X->e3s + (xw * 8 + 2 * c) * 8 + r, 8); rest(ra, 4);
      head(rb, 5); rest(rb, 5);
      check(rc, rd, 6);
      head(rc, 6); rest(rc, 6);
      head(rd, 7); rest(rd, 7);
      fence_async_smem();
      ll_wait<2>(sv, X->e3s + (xw * 8 + 2 * c) * 8 + r, 8, tag);
      float s0 = __uint_as_float(sv[0][0]) + __uint_as_float(sv[1][0]), q0 = __uint_as_float(sv[0][1]) + __uint_as_float(sv[1][1]);
      float s1 = __uint_as_float(sv[0][2]) + __uint_as_float(sv[1][2]), q1 = __uint_as_float(sv[0][3]) + __uint_as_float(sv[1][3]);
#pragma unroll
      for (int o = 1; o <= 2; o <<= 1) {
        s0 += __shfl_xor_sync(0xffffffffu, s0, o); q0 += __shfl_xor_sync(0xffffffffu, q0, o);
        s1 += __shfl_xor_sync(0xffffffffu, s1, o); q1 += __shfl_xor_sync(0xffffffffu, q1, o);
      }
      s0 *= 1.f / D_; s1 *= 1.f / D_;
      rs0 = rsqrtf(fmaxf(fmaf(-s0, s0, q0 * (1.f / D_)), 0.f) + 1e-5f);
      rs1 = rsqrtf(fmaxf(fmaf(-s1, s1, q1 * (1.f / D_)), 0.f) + 1e-5f);
      wg_wait<0>();
      keep(a1); keep(a2);
      if (lane == 0) mbar_arrive(BAR + (B_EA + 7) * 8);
      PSTAMP(9);
#pragma unroll
      for (int u = 0; u < 4; u++)
#pragma unroll
        for (int e = 0; e < 4; e++)
          hA[u][e] = swiglu(a1[8 * u + 2 * e], a1[8 * u + 2 * e + 1], a1[32 + 8 * u + 2 * e], a1[33 + 8 * u + 2 * e], (e & 1) ? rs1 : rs0);
#pragma unroll
      for (int u = 0; u < 2; u++)
#pragma unroll
        for (int e = 0; e < 4; e++)
          hA[4 + u][e] = swiglu(a2[8 * u + 2 * e], a2[8 * u + 2 * e + 1], a2[16 + 8 * u + 2 * e], a2[17 + 8 * u + 2 * e], (e & 1) ? rs1 : rs0);
      keep(hA);
      wg_bar(p);
    }
    PSTAMP(10);

    uint32_t hB[8][4];
    {
      float ab[128];
      uint32_t db = descB(RING);
      const uint32_t dAn = descA(H1) - p * 4096;
#pragma unroll 1
      for (int i = 0; i < 8; i++) {
        mbar_wait(BAR + (B_FB + i) * 8);
        const uint32_t da = dAn + i * 512;
        wg_fence();
        wgmma_ss_n256(ab, da, db, i);
#pragma unroll
        for (int k = 1; k < 4; k++) wgmma_ss_n256(ab, da + k * 2, db + k * 128, 1);
        wg_commit();
        wg_wait<1>();
        mbar_arrive_if(BAR + (B_EB + i - 1) * 8, i > 0 && lane == 0);
        db = db == descB(RING + 65536) ? descB(RING) : db + 2048;
      }
      wg_wait<0>();
      keep(ab);
      mbar_arrive_if(BAR + (B_EB + 7) * 8, lane == 0);
      asm volatile("barrier.cluster.wait.acquire.aligned;" ::: "memory");
      if (lane == 0) {
        asm volatile("mbarrier.arrive.release.cluster.shared::cluster.b64 _, [%0];" ::"r"(BAR + (B_PF + p) * 8 + peer()) : "memory");
        if (w == 0) mbar_expect_tx(BAR + (B_HX + p) * 8, 28672);
      }
      PSTAMP(11);
      auto send = [&](const uint32_t (&v)[4], int k) {
        asm volatile("st.async.weak.shared::cluster.mbarrier::complete_tx::bytes.v4.b32 [%0], {%1,%2,%3,%4}, [%5];"
                     ::"r"(Hn + 32768 + w * 7168 + k * 512 + lane * 16 + peer()), "r"(v[0]), "r"(v[1]), "r"(v[2]), "r"(v[3]),
                       "r"(BAR + (B_HX + p) * 8 + peer()) : "memory");
      };
#pragma unroll
      for (int u = 0; u < 8; u++) {
        const int o = (u >> 2) * 64 + (u & 3) * 8;
#pragma unroll
        for (int e = 0; e < 4; e++)
          hB[u][e] = swiglu(ab[o + 2 * e], ab[o + 2 * e + 1], ab[o + 32 + 2 * e], ab[o + 33 + 2 * e], (e & 1) ? rs1 : rs0);
        if (u == 1) {
          mbar_wait_cluster(BAR + (B_PF + p) * 8);
#pragma unroll
          for (int k = 0; k < 6; k++) send(hA[k], k);
          send(hB[0], 6);
        }
        if (u >= 1) send(hB[u], 6 + u);
      }
      keep(hB);
    }
    PSTAMP(12);

    {
      float ya[32], y[32];
      uint32_t hP[14][4];
      const uint32_t offA = (j & 1) ? 256 : 0, offH = (j & 1) ? 0 : 1536;
      uint4* e4 = xb + O_E4 + g * 24576 + warp * 128;
      const uint32_t stg = H0 + p * 65536 + 28672 + (w >> 1) * 32768 + (w & 1) * 2048;
      auto mm = [&](float (&d)[32], int m, int k0, int k1) {
        if (k0 == 0) mbar_wait(BAR + (B_FT + m) * 8);
        const uint32_t T = descB(0) + (t_addr(m) >> 4);
        const uint32_t oA = (m & 1) ? 256 - offA : offA, oH = (m & 1) ? 1536 - offH : offH;
        wg_fence();
#pragma unroll
        for (int k = k0; k < k1; k++) {
          const uint32_t db = T + (k < 4 ? oA + k * 128 : k < 6 ? oH + (k - 4) * 128 : oA + 512 + (k - 6) * 128);
          if (m & 1) wgmma_rs_n64(d, hP[k], db, 1);
          else if (k < 6) wgmma_rs_n64(d, hA[k], db, k);
          else wgmma_rs_n64(d, hB[k - 6], db, 1);
        }
        wg_commit();
      };
      auto next = [&](float (&d)[32], float (&dp)[32], int q) {
        mm(d, 2 * q + 2, 0, 3);
        wg_wait<1>();
        keep(dp);
        mbar_arrive_if(BAR + (B_ET0 + 1 + q) * 8, lane == 0);
        uint4* dst = e4 + (((j + 2 + 2 * q) & 7) * 3 + q) * 1024;
#pragma unroll
        for (int u = 0; u < 4; u++)
          ll_st(dst + u * 32, pack2(dp[8 * u], dp[8 * u + 1]), pack2(dp[8 * u + 2], dp[8 * u + 3]),
                pack2(dp[8 * u + 4], dp[8 * u + 5]), pack2(dp[8 * u + 6], dp[8 * u + 7]), tag);
        if (q == 2) mbar_wait(BAR + (B_ET0 + 3) * 8);
        mm(d, 2 * q + 2, 3, 14);
      };
      mm(ya, 0, 0, 8);
      mbar_wait_cluster(BAR + (B_HX + p) * 8);
#pragma unroll
      for (int k = 0; k < 14; k++) lds128(hP[k], Hn + 32768 + w * 7168 + k * 512 + lane * 16);
      mm(ya, 0, 8, 14);
      keep(hP);
      mbar_arrive_if(BAR + (B_HC + p) * 8, lane == 0);
      mm(ya, 1, 0, 3);
      wg_wait<1>();
      mbar_arrive_if(BAR + B_ET0 * 8, lane == 0);
      mm(ya, 1, 3, 14);
      next(y, ya, 0);
      PSTAMP(27);
      mm(y, 3, 0, 14);
      next(ya, y, 1);
      PSTAMP(26);
      mm(ya, 5, 0, 14);
      next(y, ya, 2);
      PSTAMP(28);
      uint32_t in[4][4], lt[4][4];
      const uint4* insrc = e4 + j * 3 * 1024;
      mm(y, 7, 0, 7);
      ll_issue<4>(lt, insrc + 2048, 32);
      mm(y, 7, 7, 14);
      mbar_wait(BAR + B_FIN * 8);
      wg_wait<0>();
      keep(y);
      PSTAMP(13);
      const uint32_t ident = (2 * c == r ? 0x3f80u : 0u) | (2 * c + 1 == r ? 0x3f800000u : 0u);
      auto acc = [&](const uint32_t (&v)[4][4]) {
#pragma unroll
        for (int u = 0; u < 4; u++) {
          mma1688_acc(*reinterpret_cast<float (*)[4]>(&y[8 * u]), v[u][0], v[u][1], ident);
          mma1688_acc(*reinterpret_cast<float (*)[4]>(&y[8 * u + 4]), v[u][2], v[u][3], ident);
        }
      };
      acc(hf);
#pragma unroll
      for (int q = 0; q < 2; q++) {
#pragma unroll
        for (int u = 0; u < 4; u++) lds128(in[u], t_addr(q + 1) + warp * 2048 + lane * 16 + u * 512);
        ll_wait<4>(in, insrc + q * 1024, 32, tag);
        acc(in);
      }
      PSTAMP(25);
      if (ll_bad<4>(lt, pin(tag, zero))) {
        ll_spin<4>(lt, insrc + 2048, 32, tag);
      }
      ll_clear<4>(lt);
      acc(lt);
      PSTAMP(14);
#pragma unroll
      for (int u = 0; u < 4; u++) {
        uint32_t o[4];
#pragma unroll
        for (int e = 0; e < 4; e++) o[e] = pack2(y[8 * u + 2 * e], y[8 * u + 2 * e + 1]);
        stsm4(stg + (moff ^ (u << 5)), o);
      }
      fence_async_smem();
      __syncwarp();
      if (elect_one()) {
        tma3d_store(&P.out, stg, 64 * j, p, g * 64 + 16 * w);
        asm volatile("cp.async.bulk.commit_group;" ::: "memory");
        asm volatile("cp.async.bulk.wait_group.read 0;" ::: "memory");
      }
      PSTAMP(15);
    }
  }
}

typedef CUresult (*EncodeFn)(CUtensorMap*, CUtensorMapDataType, cuuint32_t, void*, const cuuint64_t*, const cuuint64_t*,
                             const cuuint32_t*, const cuuint32_t*, CUtensorMapInterleave, CUtensorMapSwizzle,
                             CUtensorMapL2promotion, CUtensorMapFloatOOBfill);

void enc2d(EncodeFn f, CUtensorMap* m, const void* base, uint64_t cols, uint64_t rows, uint32_t bc, uint32_t br, CUtensorMapSwizzle sw) {
  cuuint64_t gd[2] = {cols, rows}, gs[1] = {cols * 2};
  cuuint32_t bd[2] = {bc, br}, es[2] = {1, 1};
  f(m, CU_TENSOR_MAP_DATA_TYPE_BFLOAT16, 2, const_cast<void*>(base), gd, gs, bd, es, CU_TENSOR_MAP_INTERLEAVE_NONE, sw,
    CU_TENSOR_MAP_L2_PROMOTION_L2_128B, CU_TENSOR_MAP_FLOAT_OOB_FILL_NONE);
}
void enc_par(EncodeFn f, CUtensorMap* m, const void* base, uint32_t pairs) {
  cuuint64_t gd[3] = {(cuuint64_t)D_, 2, (cuuint64_t)S_ / 2}, gs[2] = {D_ * 2, D_ * 4};
  cuuint32_t bd[3] = {64, 1, pairs}, es[3] = {1, 1, 1};
  f(m, CU_TENSOR_MAP_DATA_TYPE_BFLOAT16, 3, const_cast<void*>(base), gd, gs, bd, es, CU_TENSOR_MAP_INTERLEAVE_NONE,
    CU_TENSOR_MAP_SWIZZLE_128B, CU_TENSOR_MAP_L2_PROMOTION_L2_128B, CU_TENSOR_MAP_FLOAT_OOB_FILL_NONE);
}

}

extern "C" void kernel_launch(void* const* d_in, const int* in_sizes, int n_in, void* d_out, int out_size) {
  (void)in_sizes; (void)n_in; (void)out_size;
  static EncodeFn enc = nullptr;
  static Scratch* scratch = nullptr;
  if (!enc) {
    void* fn = nullptr;
    cudaDriverEntryPointQueryResult q;
    cudaGetDriverEntryPoint("cuTensorMapEncodeTiled", &fn, cudaEnableDefault, &q);
    enc = (EncodeFn)fn;
    cudaGetSymbolAddress((void**)&scratch, g_scratch);
    cudaFuncSetAttribute(fused_block_kernel, cudaFuncAttributeMaxDynamicSharedMemorySize, SMEM_BYTES);
  }
  Params P;
  const __nv_bfloat16* xp = (const __nv_bfloat16*)d_in[0];
  const __nv_bfloat16* wqkvp = (const __nv_bfloat16*)d_in[1];
  const __nv_bfloat16* wop = (const __nv_bfloat16*)d_in[2];
  P.w1p = (const __nv_bfloat16*)d_in[4];
  P.w3p = (const __nv_bfloat16*)d_in[5];
  P.w2p = (const __nv_bfloat16*)d_in[6];
  enc_par(enc, &P.x, xp, 64);
  enc_par(enc, &P.out, d_out, 16);
  enc2d(enc, &P.wqkv, wqkvp, 3 * D_, D_, 64, 64, CU_TENSOR_MAP_SWIZZLE_128B);
  enc2d(enc, &P.wo, wop, D_, D_, 64, 64, CU_TENSOR_MAP_SWIZZLE_128B);
  enc2d(enc, &P.w1, P.w1p, F_, D_, 64, 64, CU_TENSOR_MAP_SWIZZLE_128B);
  enc2d(enc, &P.w3, P.w3p, F_, D_, 64, 64, CU_TENSOR_MAP_SWIZZLE_128B);
  enc2d(enc, &P.w1h, P.w1p, F_, D_, 32, 64, CU_TENSOR_MAP_SWIZZLE_64B);
  enc2d(enc, &P.w3h, P.w3p, F_, D_, 32, 64, CU_TENSOR_MAP_SWIZZLE_64B);
  enc2d(enc, &P.w2, P.w2p, D_, F_, 64, 224, CU_TENSOR_MAP_SWIZZLE_128B);

  cudaLaunchConfig_t cfg = {};
  cfg.gridDim = dim3(128);
  cfg.blockDim = dim3(384);
  cfg.dynamicSmemBytes = SMEM_BYTES;
  cfg.stream = cudaStreamPerThread;
  cudaLaunchAttribute at[2];
  at[0].id = cudaLaunchAttributeCooperative;
  at[0].val.cooperative = 1;
  cfg.attrs = at;
  cfg.numAttrs = 1;
  at[1].id = cudaLaunchAttributeClusterDimension;
  at[1].val.clusterDim.x = 2; at[1].val.clusterDim.y = 1; at[1].val.clusterDim.z = 1;
  cfg.numAttrs = 2;
  cudaLaunchKernelEx(&cfg, fused_block_kernel, scratch, xp, wqkvp, wop, 0u, P);
}
```

```cpp
#include <cuda_runtime.h>
#include <cuda.h>
#include <cuda_bf16.h>
#include <stdint.h>
#include <stddef.h>

namespace {

constexpr int S_ = 2048, D_ = 512, F_ = 1792;
#define LAG_KB 3
#define E4_FIRST 7
#define PP_AHEAD 1
#define SIDE_KB 0
#define CLR_MODE 0
#define W2_HEAD 3
#define CLR_SLEEP 400
#define CMAP 2
#define E4_ON 1
#define E4_WHEN B_READY
#define XO_DELAY 2

constexpr uint32_t SPIN_LIMIT = 1u << 18;

struct Scratch {
  uint4 e4[16 * 8 * 3 * 8 * 4 * 32];
  uint4 e2[16 * 2 * 4 * 32 * 32];
  uint4 e3h[16 * 2 * 4 * 32 * 32];
  uint4 e1[16 * 8 * 2 * 4 * 32];
  uint4 e2s[16 * 2 * 4 * 8 * 8];
  uint4 e3s[16 * 2 * 4 * 8 * 8];
  uint4 e0c[8 * 3 * 16 * 16];
  uint4 e0s[2048];
  uint4 e0w[8 * 64];
  unsigned epoch[128];
};
__device__ Scratch g_scratch;
#define PSTAMP(i)
#define PSTAMPW(slot, i)
#define W2STAMP(i)

struct alignas(64) Params {
  CUtensorMap x, out, wqkv, wo, w1, w3, w1h, w3h, w2;
  const __nv_bfloat16 *w1p, *w3p, *w2p;
};

constexpr uint32_t SB = 1024;
constexpr uint32_t H0 = SB;
constexpr uint32_t H1 = SB + 65536;
constexpr uint32_t RING = SB + 131072;
constexpr uint32_t BAR = SB + 229376;
constexpr uint32_t TAGS = BAR + 1016;
constexpr uint32_t CS = BAR + 1024;
constexpr uint32_t ST = CS + 768;
constexpr uint32_t WB = ST + 1024;
constexpr uint32_t SMEM_BYTES = 232448;
static_assert(WB + 256 <= SB + SMEM_BYTES, "smem");

enum : int {
  B_FX = 0,
  B_FKV = 16, B_FQ = 24, B_FWO = 32, B_FA = 40, B_FB = 48, B_FT = 56,
  B_EKV = 64, B_EQ = 72, B_EA = 80, B_EB = 88, B_ET0 = 96,
  B_WODONE = 103,
  B_FIN = 33,
  B_EX = 104,
  B_LAG = 112, B_READY = 113, B_PUB = 114, B_CLR = 115, B_CLR0 = 116, B_TAG = 117,
  B_HX = 118,
  B_PF = 120,
  B_HC = 122
};

__device__ __forceinline__ uint32_t smem_u32(const void* p) { return (uint32_t)__cvta_generic_to_shared(p); }
__device__ __forceinline__ uint32_t own() { return (blockIdx.x & 1) << 24; }
__device__ __forceinline__ uint32_t peer() { return (~blockIdx.x & 1) << 24; }
__device__ __forceinline__ void mbar_init(uint32_t b, uint32_t c) { asm volatile("mbarrier.init.shared::cta.b64 [%0], %1;" ::"r"(b + own()), "r"(c) : "memory"); }
__device__ __forceinline__ void mbar_expect_tx(uint32_t b, uint32_t bytes) { asm volatile("mbarrier.arrive.expect_tx.shared::cta.b64 _, [%0], %1;" ::"r"(b + own()), "r"(bytes) : "memory"); }
__device__ __forceinline__ void mbar_arrive(uint32_t b) { asm volatile("mbarrier.arrive.shared::cta.b64 _, [%0];" ::"r"(b + own()) : "memory"); }
__device__ __forceinline__ void mbar_wait(uint32_t b) {
  asm volatile("{\n.reg .pred p;\n.reg .u32 c;\nmov.u32 c, 0;\nLW:\n.pragma \"nounroll\";\n"
               "mbarrier.try_wait.parity.shared::cta.b64 p, [%0], 0;\nadd.u32 c, c, 1;\nsetp.gt.or.u32 p, c, %1, p;\n@!p bra LW;\n}\n"
               ::"r"(b + own()), "n"(SPIN_LIMIT) : "memory");
}
__device__ __forceinline__ void mbar_wait_cluster(uint32_t b) {
  asm volatile("{\n.reg .pred p;\n.reg .u32 c;\nmov.u32 c, 0;\nLW:\n.pragma \"nounroll\";\n"
               "mbarrier.try_wait.parity.acquire.cluster.shared::cta.b64 p, [%0], 0;\nadd.u32 c, c, 1;\nsetp.gt.or.u32 p, c, %1, p;\n@!p bra LW;\n}\n"
               ::"r"(b + own()), "n"(SPIN_LIMIT) : "memory");
}
__device__ __forceinline__ bool elect_one() {
  uint32_t p;
  asm volatile("{\n.reg .pred P;\nelect.sync _|P, 0xffffffff;\nselp.u32 %0, 1, 0, P;\n}\n" : "=r"(p));
  return p;
}
__device__ __forceinline__ void tma2d(uint32_t dst, const CUtensorMap* m, int c0, int c1, uint32_t bar) {
  dst += own(); bar += own();
  asm volatile("cp.async.bulk.tensor.2d.shared::cluster.global.mbarrier::complete_tx::bytes [%0], [%1, {%3, %4}], [%2];"
               ::"r"(dst), "l"(m), "r"(bar), "r"(c0), "r"(c1) : "memory");
}
__device__ __forceinline__ void tma3d(uint32_t dst, const CUtensorMap* m, int c0, int c1, int c2, uint32_t bar) {
  dst += own(); bar += own();
  asm volatile("cp.async.bulk.tensor.3d.shared::cluster.global.mbarrier::complete_tx::bytes [%0], [%1, {%3, %4, %5}], [%2];"
               ::"r"(dst), "l"(m), "r"(bar), "r"(c0), "r"(c1), "r"(c2) : "memory");
}
__device__ __forceinline__ void tma3d_store(const CUtensorMap* m, uint32_t src, int c0, int c1, int c2) {
  asm volatile("cp.async.bulk.tensor.3d.global.shared::cta.bulk_group [%0, {%2, %3, %4}], [%1];"
               ::"l"(m), "r"(src + own()), "r"(c0), "r"(c1), "r"(c2) : "memory");
}
__device__ __forceinline__ void l2_prefetch(const void* p, uint32_t bytes) {
  asm volatile("cp.async.bulk.prefetch.L2.global [%0], %1;" ::"l"(p), "r"(bytes) : "memory");
}
__device__ __forceinline__ void prefetch_map(const CUtensorMap* m) { asm volatile("prefetch.tensormap [%0];" ::"l"(m) : "memory"); }
__device__ __forceinline__ void fence_async_smem() { asm volatile("fence.proxy.async.shared::cta;" ::: "memory"); }
__device__ __forceinline__ void wg_fence() { asm volatile("wgmma.fence.sync.aligned;" ::: "memory"); }
__device__ __forceinline__ void wg_commit() { asm volatile("wgmma.commit_group.sync.aligned;" ::: "memory"); }
template <int N> __device__ __forceinline__ void wg_wait() { asm volatile("wgmma.wait_group.sync.aligned %0;" ::"n"(N) : "memory"); }
__device__ __forceinline__ void wg_bar(int p) {
  if (p == 0) asm volatile("bar.sync 1, 128;" ::: "memory"); else asm volatile("bar.sync 2, 128;" ::: "memory");
}
constexpr uint32_t DESC_HI128 = (1024 >> 4) | (1u << 30);
constexpr uint32_t DESC_HI64 = (512 >> 4) | (2u << 30);
__device__ __forceinline__ constexpr uint32_t descA(uint32_t addr) { return (addr >> 4) | (1u << 16); }
__device__ __forceinline__ constexpr uint32_t descB(uint32_t addr) { return (addr >> 4) | ((8192u >> 4) << 16); }
__device__ __forceinline__ constexpr uint32_t descBh(uint32_t addr) { return (addr >> 4) | ((4096u >> 4) << 16); }

__device__ __forceinline__ void wgmma_ss_n64(float (&d)[32], uint32_t da, uint32_t db, int sc) {
  asm volatile("{\n.reg .pred p;\n.reg .b64 da, db;\nsetp.ne.b32 p, %34, 0;\nmov.b64 da, {%32, %35};\nmov.b64 db, {%33, %35};\n"
    "wgmma.mma_async.sync.aligned.m64n64k16.f32.bf16.bf16 {%0, %1, %2, %3, %4, %5, %6, %7, %8, %9, %10, %11, %12, %13, %14, %15, %16, %17, %18, %19, %20, %21, %22, %23, %24, %25, %26, %27, %28, %29, %30, %31}, da, db, p, 1, 1, 0, 1;\n}\n"
    : "+f"(d[0]), "+f"(d[1]), "+f"(d[2]), "+f"(d[3]), "+f"(d[4]), "+f"(d[5]), "+f"(d[6]), "+f"(d[7]),
      "+f"(d[8]), "+f"(d[9]), "+f"(d[10]), "+f"(d[11]), "+f"(d[12]), "+f"(d[13]), "+f"(d[14]), "+f"(d[15]),
      "+f"(d[16]), "+f"(d[17]), "+f"(d[18]), "+f"(d[19]), "+f"(d[20]), "+f"(d[21]), "+f"(d[22]), "+f"(d[23]),
      "+f"(d[24]), "+f"(d[25]), "+f"(d[26]), "+f"(d[27]), "+f"(d[28]), "+f"(d[29]), "+f"(d[30]), "+f"(d[31])
    : "r"(da), "r"(db), "r"(sc), "n"(DESC_HI128));
}
__device__ __forceinline__ void wgmma_ss_n128(float (&d)[64], uint32_t da, uint32_t db, int sc) {
  asm volatile("{\n.reg .pred p;\n.reg .b64 da, db;\nsetp.ne.b32 p, %66, 0;\nmov.b64 da, {%64, %67};\nmov.b64 db, {%65, %67};\n"
    "wgmma.mma_async.sync.aligned.m64n128k16.f32.bf16.bf16 {%0, %1, %2, %3, %4, %5, %6, %7, %8, %9, %10, %11, %12, %13, %14, %15, %16, %17, %18, %19, %20, %21, %22, %23, %24, %25, %26, %27, %28, %29, %30, %31, %32, %33, %34, %35, %36, %37, %38, %39, %40, %41, %42, %43, %44, %45, %46, %47, %48, %49, %50, %51, %52, %53, %54, %55, %56, %57, %58, %59, %60, %61, %62, %63}, da, db, p, 1, 1, 0, 1;\n}\n"
    : "+f"(d[0]), "+f"(d[1]), "+f"(d[2]), "+f"(d[3]), "+f"(d[4]), "+f"(d[5]), "+f"(d[6]), "+f"(d[7]),
      "+f"(d[8]), "+f"(d[9]), "+f"(d[10]), "+f"(d[11]), "+f"(d[12]), "+f"(d[13]), "+f"(d[14]), "+f"(d[15]),
      "+f"(d[16]), "+f"(d[17]), "+f"(d[18]), "+f"(d[19]), "+f"(d[20]), "+f"(d[21]), "+f"(d[22]), "+f"(d[23]),
      "+f"(d[24]), "+f"(d[25]), "+f"(d[26]), "+f"(d[27]), "+f"(d[28]), "+f"(d[29]), "+f"(d[30]), "+f"(d[31]),
      "+f"(d[32]), "+f"(d[33]), "+f"(d[34]), "+f"(d[35]), "+f"(d[36]), "+f"(d[37]), "+f"(d[38]), "+f"(d[39]),
      "+f"(d[40]), "+f"(d[41]), "+f"(d[42]), "+f"(d[43]), "+f"(d[44]), "+f"(d[45]), "+f"(d[46]), "+f"(d[47]),
      "+f"(d[48]), "+f"(d[49]), "+f"(d[50]), "+f"(d[51]), "+f"(d[52]), "+f"(d[53]), "+f"(d[54]), "+f"(d[55]),
      "+f"(d[56]), "+f"(d[57]), "+f"(d[58]), "+f"(d[59]), "+f"(d[60]), "+f"(d[61]), "+f"(d[62]), "+f"(d[63])
    : "r"(da), "r"(db), "r"(sc), "n"(DESC_HI128));
}
__device__ __forceinline__ void wgmma_ss_n256(float (&d)[128], uint32_t da, uint32_t db, int sc) {
  asm volatile("{\n.reg .pred p;\n.reg .b64 da, db;\nsetp.ne.b32 p, %130, 0;\nmov.b64 da, {%128, %131};\nmov.b64 db, {%129, %131};\n"
    "wgmma.mma_async.sync.aligned.m64n256k16.f32.bf16.bf16 {%0, %1, %2, %3, %4, %5, %6, %7, %8, %9, %10, %11, %12, %13, %14, %15, %16, %17, %18, %19, %20, %21, %22, %23, %24, %25, %26, %27, %28, %29, %30, %31, %32, %33, %34, %35, %36, %37, %38, %39, %40, %41, %42, %43, %44, %45, %46, %47, %48, %49, %50, %51, %52, %53, %54, %55, %56, %57, %58, %59, %60, %61, %62, %63, %64, %65, %66, %67, %68, %69, %70, %71, %72, %73, %74, %75, %76, %77, %78, %79, %80, %81, %82, %83, %84, %85, %86, %87, %88, %89, %90, %91, %92, %93, %94, %95, %96, %97, %98, %99, %100, %101, %102, %103, %104, %105, %106, %107, %108, %109, %110, %111, %112, %113, %114, %115, %116, %117, %118, %119, %120, %121, %122, %123, %124, %125, %126, %127}, da, db, p, 1, 1, 0, 1;\n}\n"
    : "+f"(d[0]), "+f"(d[1]), "+f"(d[2]), "+f"(d[3]), "+f"(d[4]), "+f"(d[5]), "+f"(d[6]), "+f"(d[7]),
      "+f"(d[8]), "+f"(d[9]), "+f"(d[10]), "+f"(d[11]), "+f"(d[12]), "+f"(d[13]), "+f"(d[14]), "+f"(d[15]),
      "+f"(d[16]), "+f"(d[17]), "+f"(d[18]), "+f"(d[19]), "+f"(d[20]), "+f"(d[21]), "+f"(d[22]), "+f"(d[23]),
      "+f"(d[24]), "+f"(d[25]), "+f"(d[26]), "+f"(d[27]), "+f"(d[28]), "+f"(d[29]), "+f"(d[30]), "+f"(d[31]),
      "+f"(d[32]), "+f"(d[33]), "+f"(d[34]), "+f"(d[35]), "+f"(d[36]), "+f"(d[37]), "+f"(d[38]), "+f"(d[39]),
      "+f"(d[40]), "+f"(d[41]), "+f"(d[42]), "+f"(d[43]), "+f"(d[44]), "+f"(d[45]), "+f"(d[46]), "+f"(d[47]),
      "+f"(d[48]), "+f"(d[49]), "+f"(d[50]), "+f"(d[51]), "+f"(d[52]), "+f"(d[53]), "+f"(d[54]), "+f"(d[55]),
      "+f"(d[56]), "+f"(d[57]), "+f"(d[58]), "+f"(d[59]), "+f"(d[60]), "+f"(d[61]), "+f"(d[62]), "+f"(d[63]),
      "+f"(d[64]), "+f"(d[65]), "+f"(d[66]), "+f"(d[67]), "+f"(d[68]), "+f"(d[69]), "+f"(d[70]), "+f"(d[71]),
      "+f"(d[72]), "+f"(d[73]), "+f"(d[74]), "+f"(d[75]), "+f"(d[76]), "+f"(d[77]), "+f"(d[78]), "+f"(d[79]),
      "+f"(d[80]), "+f"(d[81]), "+f"(d[82]), "+f"(d[83]), "+f"(d[84]), "+f"(d[85]), "+f"(d[86]), "+f"(d[87]),
      "+f"(d[88]), "+f"(d[89]), "+f"(d[90]), "+f"(d[91]), "+f"(d[92]), "+f"(d[93]), "+f"(d[94]), "+f"(d[95]),
      "+f"(d[96]), "+f"(d[97]), "+f"(d[98]), "+f"(d[99]), "+f"(d[100]), "+f"(d[101]), "+f"(d[102]), "+f"(d[103]),
      "+f"(d[104]), "+f"(d[105]), "+f"(d[106]), "+f"(d[107]), "+f"(d[108]), "+f"(d[109]), "+f"(d[110]), "+f"(d[111]),
      "+f"(d[112]), "+f"(d[113]), "+f"(d[114]), "+f"(d[115]), "+f"(d[116]), "+f"(d[117]), "+f"(d[118]), "+f"(d[119]),
      "+f"(d[120]), "+f"(d[121]), "+f"(d[122]), "+f"(d[123]), "+f"(d[124]), "+f"(d[125]), "+f"(d[126]), "+f"(d[127])
    : "r"(da), "r"(db), "r"(sc), "n"(DESC_HI128));
}
template <uint32_t HI = DESC_HI128>
__device__ __forceinline__ void wgmma_rs_n64(float (&d)[32], const uint32_t (&a)[4], uint32_t db, int sc) {
  asm volatile("{\n.reg .pred p;\n.reg .b64 db;\nsetp.ne.b32 p, %37, 0;\nmov.b64 db, {%36, %38};\n"
    "wgmma.mma_async.sync.aligned.m64n64k16.f32.bf16.bf16 {%0, %1, %2, %3, %4, %5, %6, %7, %8, %9, %10, %11, %12, %13, %14, %15, %16, %17, %18, %19, %20, %21, %22, %23, %24, %25, %26, %27, %28, %29, %30, %31}, {%32, %33, %34, %35}, db, p, 1, 1, 1;\n}\n"
    : "+f"(d[0]), "+f"(d[1]), "+f"(d[2]), "+f"(d[3]), "+f"(d[4]), "+f"(d[5]), "+f"(d[6]), "+f"(d[7]),
      "+f"(d[8]), "+f"(d[9]), "+f"(d[10]), "+f"(d[11]), "+f"(d[12]), "+f"(d[13]), "+f"(d[14]), "+f"(d[15]),
      "+f"(d[16]), "+f"(d[17]), "+f"(d[18]), "+f"(d[19]), "+f"(d[20]), "+f"(d[21]), "+f"(d[22]), "+f"(d[23]),
      "+f"(d[24]), "+f"(d[25]), "+f"(d[26]), "+f"(d[27]), "+f"(d[28]), "+f"(d[29]), "+f"(d[30]), "+f"(d[31])
    : "r"(a[0]), "r"(a[1]), "r"(a[2]), "r"(a[3]), "r"(db), "r"(sc), "n"(HI));
}
template <uint32_t HI = DESC_HI128>
__device__ __forceinline__ void wgmma_rs_n128(float (&d)[64], const uint32_t (&a)[4], uint32_t db, int sc) {
  asm volatile("{\n.reg .pred p;\n.reg .b64 db;\nsetp.ne.b32 p, %69, 0;\nmov.b64 db, {%68, %70};\n"
    "wgmma.mma_async.sync.aligned.m64n128k16.f32.bf16.bf16 {%0, %1, %2, %3, %4, %5, %6, %7, %8, %9, %10, %11, %12, %13, %14, %15, %16, %17, %18, %19, %20, %21, %22, %23, %24, %25, %26, %27, %28, %29, %30, %31, %32, %33, %34, %35, %36, %37, %38, %39, %40, %41, %42, %43, %44, %45, %46, %47, %48, %49, %50, %51, %52, %53, %54, %55, %56, %57, %58, %59, %60, %61, %62, %63}, {%64, %65, %66, %67}, db, p, 1, 1, 1;\n}\n"
    : "+f"(d[0]), "+f"(d[1]), "+f"(d[2]), "+f"(d[3]), "+f"(d[4]), "+f"(d[5]), "+f"(d[6]), "+f"(d[7]),
      "+f"(d[8]), "+f"(d[9]), "+f"(d[10]), "+f"(d[11]), "+f"(d[12]), "+f"(d[13]), "+f"(d[14]), "+f"(d[15]),
      "+f"(d[16]), "+f"(d[17]), "+f"(d[18]), "+f"(d[19]), "+f"(d[20]), "+f"(d[21]), "+f"(d[22]), "+f"(d[23]),
      "+f"(d[24]), "+f"(d[25]), "+f"(d[26]), "+f"(d[27]), "+f"(d[28]), "+f"(d[29]), "+f"(d[30]), "+f"(d[31]),
      "+f"(d[32]), "+f"(d[33]), "+f"(d[34]), "+f"(d[35]), "+f"(d[36]), "+f"(d[37]), "+f"(d[38]), "+f"(d[39]),
      "+f"(d[40]), "+f"(d[41]), "+f"(d[42]), "+f"(d[43]), "+f"(d[44]), "+f"(d[45]), "+f"(d[46]), "+f"(d[47]),
      "+f"(d[48]), "+f"(d[49]), "+f"(d[50]), "+f"(d[51]), "+f"(d[52]), "+f"(d[53]), "+f"(d[54]), "+f"(d[55]),
      "+f"(d[56]), "+f"(d[57]), "+f"(d[58]), "+f"(d[59]), "+f"(d[60]), "+f"(d[61]), "+f"(d[62]), "+f"(d[63])
    : "r"(a[0]), "r"(a[1]), "r"(a[2]), "r"(a[3]), "r"(db), "r"(sc), "n"(HI));
}

template <int N> __device__ __forceinline__ void keep(float (&d)[N]) {
#pragma unroll
  for (int i = 0; i < N; i++) asm volatile("" : "+f"(d[i])::"memory");
}

__device__ __forceinline__ void keep(uint32_t (&d)[4]) { asm volatile("" : "+r"(d[0]), "+r"(d[1]), "+r"(d[2]), "+r"(d[3])::"memory"); }
template <int N> __device__ __forceinline__ void keep(uint32_t (&d)[N][4]) {
#pragma unroll
  for (int i = 0; i < N; i++) asm volatile("" : "+r"(d[i][0]), "+r"(d[i][1]), "+r"(d[i][2]), "+r"(d[i][3])::"memory");
}

__device__ __forceinline__ uint32_t pack2(float lo, float hi) {
  uint32_t r;
  asm("cvt.rn.bf16x2.f32 %0, %1, %2;" : "=r"(r) : "f"(hi), "f"(lo));
  return r;
}
__device__ __forceinline__ float bf_lo(uint32_t v) { return __uint_as_float(v << 16); }
__device__ __forceinline__ float bf_hi(uint32_t v) { return __uint_as_float(v & 0xffff0000u); }
__device__ __forceinline__ uint32_t hsub2(uint32_t a, uint32_t b) {
  uint32_t r;
  asm("sub.rn.bf16x2 %0, %1, %2;" : "=r"(r) : "r"(a), "r"(b));
  return r;
}
__device__ __forceinline__ uint32_t movm(uint32_t a) {
  uint32_t r;
  asm volatile("movmatrix.sync.aligned.m8n8.trans.b16 %0, %1;" : "=r"(r) : "r"(a));
  return r;
}
__device__ __forceinline__ void ldsm4(uint32_t (&v)[4], uint32_t a) {
  asm volatile("ldmatrix.sync.aligned.m8n8.x4.shared.b16 {%0,%1,%2,%3}, [%4];" : "=r"(v[0]), "=r"(v[1]), "=r"(v[2]), "=r"(v[3]) : "r"(a + own()) : "memory");
}
__device__ __forceinline__ void stsm4(uint32_t a, const uint32_t (&v)[4]) {
  asm volatile("stmatrix.sync.aligned.m8n8.x4.shared.b16 [%0], {%1,%2,%3,%4};" ::"r"(a + own()), "r"(v[0]), "r"(v[1]), "r"(v[2]), "r"(v[3]) : "memory");
}
__device__ __forceinline__ void mma16816(float (&d)[4], const uint32_t (&a)[4], uint32_t b0, uint32_t b1) {
  asm volatile("mma.sync.aligned.m16n8k16.row.col.f32.bf16.bf16.f32 {%0,%1,%2,%3}, {%4,%5,%6,%7}, {%8,%9}, {%10,%10,%10,%10};"
               : "=f"(d[0]), "=f"(d[1]), "=f"(d[2]), "=f"(d[3])
               : "r"(a[0]), "r"(a[1]), "r"(a[2]), "r"(a[3]), "r"(b0), "r"(b1), "f"(0.f));
}
__device__ __forceinline__ void mma1688_acc(float (&d)[4], uint32_t a0, uint32_t a1, uint32_t b0) {
  asm volatile("mma.sync.aligned.m16n8k8.row.col.f32.bf16.bf16.f32 {%0,%1,%2,%3}, {%4,%5}, {%6}, {%0,%1,%2,%3};"
               : "+f"(d[0]), "+f"(d[1]), "+f"(d[2]), "+f"(d[3]) : "r"(a0), "r"(a1), "r"(b0));
}
__device__ __forceinline__ float ex2(float x) { float y; asm("ex2.approx.ftz.f32 %0, %1;" : "=f"(y) : "f"(x)); return y; }
__device__ __forceinline__ float rcp(float x) { float y; asm("rcp.approx.ftz.f32 %0, %1;" : "=f"(y) : "f"(x)); return y; }
__device__ __forceinline__ float tanhf_hw(float x) { float y; asm("tanh.approx.f32 %0, %1;" : "=f"(y) : "f"(x)); return y; }
__device__ __forceinline__ uint32_t lds32(uint32_t a) { uint32_t v; asm volatile("ld.shared.u32 %0, [%1];" : "=r"(v) : "r"(a + own()) : "memory"); return v; }
__device__ __forceinline__ float2 lds64(uint32_t a) { float2 v; asm volatile("ld.shared.v2.f32 {%0,%1}, [%2];" : "=f"(v.x), "=f"(v.y) : "r"(a + own()) : "memory"); return v; }
__device__ __forceinline__ void lds128(uint32_t (&v)[4], uint32_t a) { asm volatile("ld.shared.v4.u32 {%0,%1,%2,%3}, [%4];" : "=r"(v[0]), "=r"(v[1]), "=r"(v[2]), "=r"(v[3]) : "r"(a + own()) : "memory"); }
__device__ __forceinline__ void sts128(uint32_t a, const uint32_t (&v)[4]) { asm volatile("st.shared.v4.u32 [%0], {%1,%2,%3,%4};" ::"r"(a + own()), "r"(v[0]), "r"(v[1]), "r"(v[2]), "r"(v[3]) : "memory"); }
__device__ __forceinline__ void ldg128_nc(uint32_t (&v)[4], const void* p) {
  asm volatile("ld.global.nc.L1::no_allocate.v4.u32 {%0,%1,%2,%3}, [%4];" : "=r"(v[0]), "=r"(v[1]), "=r"(v[2]), "=r"(v[3]) : "l"(p));
}
__device__ __forceinline__ uint32_t pin(uint32_t v, uint32_t zero) {
  asm volatile("{\n.reg .pred p;\n.reg .u32 c;\nmov.u32 c, %1;\nLP:\n.pragma \"nounroll\";\nsetp.eq.u32 p, c, 0;\n@p bra LD;\n"
               "nanosleep.u32 c;\nadd.u32 %0, %0, c;\nsub.u32 c, c, 1;\nbra LP;\nLD:\n}\n" : "+r"(v) : "r"(zero) : "memory");
  return v;
}
__device__ __forceinline__ void mbar_arrive_if(uint32_t b, bool cond) {
  asm volatile("{\n.reg .pred p;\nsetp.ne.u32 p, %1, 0;\n@p mbarrier.arrive.shared::cta.b64 _, [%0];\n}\n" ::"r"(b + own()), "r"((uint32_t)cond) : "memory");
}
__device__ __forceinline__ uint32_t ld_epoch(const unsigned* p) {
  uint32_t v;
  asm volatile("ld.relaxed.gpu.global.u32 %0, [%1];" : "=r"(v) : "l"(p) : "memory");
  return v;
}
__device__ __forceinline__ void ll_st(uint4* p, uint32_t a, uint32_t b, uint32_t c, uint32_t d, uint32_t tag) {
  asm volatile("st.relaxed.gpu.global.v4.b32 [%0], {%1, %2, %3, %4};" ::"l"(p), "r"((a & ~1u) | tag), "r"(b), "r"(c), "r"(d) : "memory");
}
__device__ __forceinline__ void ll_ld(uint32_t (&v)[4], const uint4* p) {
  asm volatile("{\n.reg .b128 t;\n.reg .b64 lo, hi;\nld.relaxed.gpu.global.b128 t, [%4];\nmov.b128 {lo, hi}, t;\n"
               "mov.b64 {%0, %1}, lo;\nmov.b64 {%2, %3}, hi;\n}\n"
               : "=r"(v[0]), "=r"(v[1]), "=r"(v[2]), "=r"(v[3]) : "l"(p) : "memory");
}
template <int N> __device__ __forceinline__ void ll_issue(uint32_t (&v)[N][4], const uint4* p, int stride) {
#pragma unroll
  for (int i = 0; i < N; i++) ll_ld(v[i], p + i * stride);
}
template <int N> __device__ __forceinline__ uint32_t ll_acc(const uint32_t (&v)[N][4], uint32_t tag, uint32_t acc = 0) {
#pragma unroll
  for (int i = 0; i < N; i++) asm("lop3.b32 %0, %1, %2, %0, 0xBE;" : "+r"(acc) : "r"(v[i][0]), "r"(tag));
  return acc;
}
__device__ __forceinline__ bool ll_any(uint32_t acc) { return __any_sync(0xffffffffu, acc & 1u); }
template <int N> __device__ __forceinline__ bool ll_bad(const uint32_t (&v)[N][4], uint32_t tag) { return ll_any(ll_acc<N>(v, tag)); }
template <int N> __device__ __forceinline__ void ll_clear(uint32_t (&v)[N][4]) {
#pragma unroll
  for (int i = 0; i < N; i++) v[i][0] &= ~1u;
}
template <int N> __device__ __forceinline__ void ll_spin(uint32_t (&v)[N][4], const uint4* p, int stride, uint32_t tag) {
  uint32_t it = 0;
#pragma unroll 1
  do { ll_issue<N>(v, p, stride); } while (ll_bad<N>(v, tag) && ++it < SPIN_LIMIT);
}
template <int N> __device__ __forceinline__ void ll_get(uint32_t (&v)[N][4], const uint4* p, int stride, uint32_t tag) {
  ll_spin<N>(v, p, stride, tag);
  ll_clear<N>(v);
}
template <int N> __device__ __forceinline__ void ll_wait(uint32_t (&v)[N][4], const uint4* p, int stride, uint32_t tag) {
  if (__builtin_expect(ll_bad<N>(v, tag), 0)) ll_spin<N>(v, p, stride, tag);
  ll_clear<N>(v);
}
__device__ __forceinline__ void unpack32(float (&d)[32], const uint32_t (&v)[4][4]) {
#pragma unroll
  for (int u = 0; u < 4; u++)
#pragma unroll
    for (int e = 0; e < 4; e++) { d[8 * u + 2 * e] = bf_lo(v[u][e]); d[8 * u + 2 * e + 1] = bf_hi(v[u][e]); }
}
__device__ __forceinline__ void pack32(uint32_t (&v)[4][4], const float (&d)[32]) {
#pragma unroll
  for (int u = 0; u < 4; u++)
#pragma unroll
    for (int e = 0; e < 4; e++) v[u][e] = pack2(d[8 * u + 2 * e], d[8 * u + 2 * e + 1]);
}
__device__ __forceinline__ uint32_t t_addr(int m) { return SB + ((0x01534620u >> (4 * m)) & 7u) * 32768u; }

__device__ __forceinline__ constexpr int w2_pass(int m) { return m < 4 ? m & 1 : m >> 1; }
__device__ __forceinline__ constexpr int w2_peer(int m) { return m < 4 ? m >> 1 : m & 1; }

__device__ __forceinline__ int kb_at(int i, int j) { return i == 0 ? j : (i - 1 + (i - 1 >= j ? 1 : 0)); }

__device__ __forceinline__ void init_bars(int set) {
  if (set >= 0 && elect_one()) {
    const uint32_t cnt = set < 5 ? 1 : 8;
#pragma unroll
    for (int i = 0; i < 8; i++) mbar_init(BAR + (24 + 8 * set + i) * 8, cnt);
    if (set == 9) {
#pragma unroll
      for (int i = 0; i < 9; i++) mbar_init(BAR + (B_EX + i) * 8, 4);
#pragma unroll
      for (int i = 0; i < 4; i++) mbar_init(BAR + (B_READY + i) * 8, i == 1 ? 7 : 3);
#pragma unroll
      for (int i = 0; i < 7; i++) mbar_init(BAR + (B_TAG + i) * 8, i < 3 ? 1 : 4);
    }
    asm volatile("fence.mbarrier_init.release.cluster;" ::: "memory");
  }
  __syncwarp();
  asm volatile("barrier.cluster.arrive.relaxed.aligned;" ::: "memory");
  asm volatile("bar.arrive 4, 384;" ::: "memory");
  asm volatile("bar.sync 3, 384;" ::: "memory");
}

__global__ void __launch_bounds__(384, 1) fused_block_kernel(Scratch* __restrict__ X, const __nv_bfloat16* __restrict__ xp,
                                                             const __nv_bfloat16* __restrict__ wqkvp, const __nv_bfloat16* __restrict__ wop, const uint32_t zero,
                                                             const __grid_constant__ Params P) {
  extern __shared__ __align__(1024) uint8_t smem_raw[];
  if (smem_u32(smem_raw) != SB + own()) return;
  const int tid = threadIdx.x;
  const int warp = __shfl_sync(0xffffffffu, tid >> 5, 0);
  const int lane = tid & 31;
  const int cta = blockIdx.x;
  const int j = ((cta >> 1) & 1) * 4 + ((cta >> 4) & 1) * 2 + (cta & 1);
  const int g = ((cta >> 2) & 3) * 4 + (cta >> 5);

  if (warp >= 8) {
    asm volatile("setmaxnreg.dec.sync.aligned.u32 56;");
    if (warp == 8) {
      PSTAMPW(2, 0);
      const bool leader = elect_one();
      if (leader) {
        prefetch_map(&P.x); prefetch_map(&P.wqkv);
#pragma unroll
        for (int i = 0; i < 24; i++) mbar_init(BAR + i * 8, 1);
        asm volatile("fence.mbarrier_init.release.cluster;" ::: "memory");
      }
      __syncwarp();
      asm volatile("bar.arrive 3, 384;" ::: "memory");
      asm volatile("barrier.cluster.arrive.relaxed.aligned;" ::: "memory");
      auto ldx = [&](int p, int kb) {
        const uint32_t b = BAR + (B_FX + p * 8 + kb) * 8;
        mbar_expect_tx(b, 8192);
        tma3d(H0 + p * 65536 + kb * 8192, &P.x, kb * 64, p, g * 64, b);
      };
      auto ldkv = [&](int kb, int slot) {
        const uint32_t b = BAR + (B_FKV + kb) * 8, d = RING + slot * 16384;
        mbar_expect_tx(b, 16384);
        tma2d(d, &P.wqkv, 512 + 64 * j, kb * 64, b);
        tma2d(d + 8192, &P.wqkv, 1024 + 64 * j, kb * 64, b);
      };
      if (leader) {
#pragma unroll 1
        for (int i = 0; i < 8 + XO_DELAY; i++) {
          if (i < 8) ldx(0, i);
          if (i < 6) ldkv(i, i);
          if (i >= XO_DELAY) ldx(1, i - XO_DELAY);
        }
        PSTAMPW(2, 2);
      }
      __syncwarp();
      asm volatile("bar.sync 4, 384;" ::: "memory");
      if (leader) {
        const int f0 = 224 * j + ((j & 1) ? 32 : 0);
        const int fh = 224 * j + ((j & 1) ? 0 : 192);
        prefetch_map(&P.wo); prefetch_map(&P.w1); prefetch_map(&P.w3); prefetch_map(&P.w1h);
        prefetch_map(&P.w3h); prefetch_map(&P.w2); prefetch_map(&P.out);
#pragma unroll 1
        for (int i = 0; i < 2; i++) { mbar_wait(BAR + (B_EKV + i) * 8); ldkv(6 + i, i); }
#pragma unroll 1
        for (int i = 0; i < 8; i++) {
          const uint32_t b = BAR + (B_FQ + i) * 8;
          mbar_wait(BAR + (B_EKV + 2 + (i >> 1)) * 8);
          mbar_expect_tx(b, 8192);
          tma2d(RING + (4 + i) * 8192, &P.wqkv, 64 * j, i * 64, b);
        }
        mbar_expect_tx(BAR + B_FWO * 8, 65536);
#pragma unroll 1
        for (int i = 0; i < 8; i++) {
          const int kb = (i + 1) & 7;
          mbar_wait(BAR + (B_EX + i) * 8);
          tma2d(H0 + kb * 8192, &P.wo, 64 * j, kb * 64, BAR + B_FWO * 8);
        }
#pragma unroll 1
        for (int i = 0; i < 8; i++) {
          const uint32_t b = BAR + (B_FA + i) * 8, d = RING + (i & 3) * 24576;
          const int k0 = kb_at(i, j) * 64;
          mbar_wait(BAR + (B_EKV + 7 + ((0xCBA98520u >> (4 * i)) & 15)) * 8);
          mbar_expect_tx(b, 24576);
          tma2d(d, &P.w1, f0, k0, b);
          tma2d(d + 8192, &P.w3, f0, k0, b);
          tma2d(d + 16384, &P.w1h, fh, k0, b);
          tma2d(d + 20480, &P.w3h, fh, k0, b);
        }
        uint32_t d = RING;
#pragma unroll 1
        for (int i = 0; i < 8; i++) {
          const uint32_t b = BAR + (B_FB + i) * 8;
          const int k0 = kb_at(i, j) * 64;
          mbar_wait(BAR + (B_EA + 5 + i) * 8);
          mbar_expect_tx(b, 32768);
          tma2d(d, &P.w1, f0 + 64, k0, b);
          tma2d(d + 8192, &P.w3, f0 + 64, k0, b);
          tma2d(d + 16384, &P.w1, f0 + 128, k0, b);
          tma2d(d + 24576, &P.w3, f0 + 128, k0, b);
          d = d == RING + 65536 ? RING : d + 32768;
        }
#pragma unroll 1
        for (int i = 0; i < 8; i++) {
          const int m = (0x76453210u >> (4 * i)) & 7;
          const uint32_t b = BAR + (B_FT + m) * 8;
          mbar_wait(BAR + (i < 5 ? B_EB + 3 + i : i < 7 ? B_HC - 5 + i : B_ET0) * 8);
          mbar_expect_tx(b, 28672);
          tma2d(t_addr(m), &P.w2, 64 * ((j + 2 + 2 * w2_pass(m)) & 7), 224 * (j ^ w2_peer(m)), b);
          PSTAMPW(2, 4 + i);
        }
#pragma unroll 1
        for (int q = 0; q < 2; q++) {
          mbar_expect_tx(BAR + (B_FIN + q) * 8, 16384);
          mbar_wait(BAR + (B_ET0 + 3 - q) * 8);
          PSTAMPW(2, 24 + q);
          asm volatile("cp.async.bulk.shared::cluster.global.mbarrier::complete_tx::bytes [%0], [%1], 16384, [%2];"
                       ::"r"(t_addr(q + 1) + own()), "l"(X->e4 + ((g * 8 + j) * 3 + q) * 1024), "r"(BAR + (B_FIN + q) * 8 + own()) : "memory");
        }
        X->epoch[cta] = X->epoch[cta] + 1;
      }
    } else {
      const int part = warp - 9;
      uint32_t tag;
      if (part == 2) {
        tag = ld_epoch(X->epoch + cta);
        init_bars(-1);
        tag = (tag + 1) & 1;
        if (lane == 0) {
          asm volatile("st.shared.u32 [%0], %1;" ::"r"(TAGS + own()), "r"(tag) : "memory");
          mbar_arrive(BAR + B_TAG * 8);
        }
      } else {
        init_bars(warp - 1);
        mbar_wait(BAR + B_TAG * 8);
        tag = lds32(TAGS);
      }
      PSTAMPW(3, 16 + part);
      const int xw0 = g * 8;
      auto clear8 = [&](uint4* p, int stride) {
#pragma unroll
        for (int i = 0; i < 8; i++) ll_st(p + i * stride + lane, 0, 0, 0, 0, tag ^ 1);
      };
      auto clear_front = [&]() {
#pragma unroll 1
      for (int u = part; u < 8; u += 3) clear8((u < 4 ? X->e2 : X->e3h) + (xw0 * 32 + 4 * j + (u & 3)) * 32, 1024);
      if (part == 2) {
        clear8(X->e1 + (g * 8 + j) * 256, 32);
#pragma unroll
        for (int i = 0; i < 4; i++)
          ll_st((i < 2 ? X->e2s : X->e3s) + ((xw0 + (i & 1) * 4 + (lane >> 3)) * 8 + j) * 8 + (lane & 7), 0, 0, 0, 0, tag ^ 1);
      }
      };
      if (CLR_MODE == 1) clear_front();
      PSTAMPW(3, 20 + part);
      uint32_t v[8][4];
      if (part < 2) {
        float s[4] = {0.f, 0.f, 0.f, 0.f}, q[4] = {0.f, 0.f, 0.f, 0.f}, piv = 0.f;
        const uint32_t xa = H0 + part * 65536 + (8 * j + (lane >> 2)) * 128 + (lane & 3) * 16 + (lane & 4) * 16;
#pragma unroll 1
        for (int kb = 0; kb < 8; kb++) {
          mbar_wait(BAR + (B_FX + part * 8 + kb) * 8);
          lds128(v[0], xa + kb * 8192); lds128(v[1], (xa + kb * 8192) ^ 64);
          if (kb == 0) piv = __shfl_sync(0xffffffffu, bf_lo(v[0][0]), lane & 28);
#pragma unroll
          for (int e = 0; e < 8; e++) {
            const float a = bf_lo(v[e >> 2][e & 3]) - piv, b = bf_hi(v[e >> 2][e & 3]) - piv;
            s[e & 3] += a + b; q[e & 3] = fmaf(a, a, q[e & 3]); q[e & 3] = fmaf(b, b, q[e & 3]);
          }
        }
        float ss = (s[0] + s[1]) + (s[2] + s[3]), qq = (q[0] + q[1]) + (q[2] + q[3]);
#pragma unroll
        for (int o = 1; o <= 2; o <<= 1) { ss += __shfl_xor_sync(0xffffffffu, ss, o); qq += __shfl_xor_sync(0xffffffffu, qq, o); }
        const float dm = ss * (1.f / D_);
        const float rs = rsqrtf(fmaxf(fmaf(-dm, dm, qq * (1.f / D_)), 0.f) + 1e-5f);
        if ((lane & 3) == 0) ll_st(X->e0s + g * 128 + 2 * (8 * j + (lane >> 2)) + part, __float_as_uint(piv + dm), __float_as_uint(rs), 0, 0, tag);
      } else {
        mbar_wait(BAR + (B_FKV + SIDE_KB) * 8);
        const __nv_bfloat16* wr = wop + (size_t)(j * 64 + g * 4 + (lane >> 3)) * D_ + (lane & 7) * 8;
#pragma unroll
        for (int i = 0; i < 8; i++) ldg128_nc(v[i], wr + i * 64);
        float s[4];
#pragma unroll
        for (int e = 0; e < 4; e++) {
          s[e] = 0.f;
#pragma unroll
          for (int i = 0; i < 8; i++) s[e] += bf_lo(v[i][e]) + bf_hi(v[i][e]);
        }
        float ss = (s[0] + s[1]) + (s[2] + s[3]);
#pragma unroll
        for (int o = 1; o <= 4; o <<= 1) ss += __shfl_xor_sync(0xffffffffu, ss, o);
        if ((lane & 7) == 0) ll_st(X->e0w + j * 64 + g * 4 + (lane >> 3), __float_as_uint(ss * (1.f / D_)), 0, 0, 0, tag);
      }
      __syncwarp();
      if (lane == 0) mbar_arrive(BAR + B_PUB * 8);
      PSTAMPW(3, part * 4 + 2);
      mbar_wait(BAR + B_PUB * 8);
      PSTAMPW(3, part * 4 + 0);
      {
        uint32_t u[2][4];
        const uint4* us = (part == 2 ? X->e0w + j * 64 : X->e0s + g * 128 + part * 64) + lane;
        const uint4* vs = X->e0c + ((j * 3 + part) * 16 + (lane >> 4) * 8) * 16 + (lane & 15);
        uint32_t it = 0;
#pragma unroll 1
        do { ll_issue<2>(u, us, 32); ll_issue<8>(v, vs, 16); } while (ll_any(ll_acc<8>(v, tag, ll_acc<2>(u, tag))) && ++it < SPIN_LIMIT);
        ll_clear<2>(u); ll_clear<8>(v);
#pragma unroll
        for (int i = 0; i < 2; i++) {
          if (part == 2) asm volatile("st.shared.u32 [%0], %1;" ::"r"(WB + own() + (i * 32 + lane) * 4), "r"(u[i][0]) : "memory");
          else asm volatile("st.shared.v2.u32 [%0], {%1,%2};" ::"r"(ST + own() + (part * 64 + i * 32 + lane) * 8), "r"(u[i][0]), "r"(u[i][1]) : "memory");
        }
      }
      uint32_t o[4];
#pragma unroll
      for (int e = 0; e < 4; e++) {
        float s = 0.f;
#pragma unroll
        for (int i = 0; i < 8; i++) s += __uint_as_float(v[i][e]);
        o[e] = __float_as_uint(s + __shfl_xor_sync(0xffffffffu, s, 16));
      }
      if (lane < 16) sts128(CS + (part * 64 + lane * 4) * 4, o);
      __syncwarp();
      if (lane == 0) mbar_arrive(BAR + B_READY * 8);
      PSTAMPW(3, part * 4 + 1);
      if (CLR_MODE == 2) clear_front();
      __syncwarp();
      if (lane == 0) mbar_arrive(BAR + B_CLR0 * 8);
      PSTAMPW(3, 24 + part);
      if (lane == 0) l2_prefetch(part == 0 ? P.w1p + (size_t)cta * 4 * F_ : part == 1 ? P.w3p + (size_t)cta * 4 * F_ : P.w2p + (size_t)cta * 14 * D_, 14336);
      mbar_wait(BAR + (E4_WHEN) * 8);
#pragma unroll 1
      for (int u = 0; u < 4 * E4_ON; u++) {
        clear8(X->e4 + ((g * 8 + ((j + 2 + 2 * part) & 7)) * 3 + part) * 1024 + u * 32, 128);
        __nanosleep(CLR_SLEEP);
      }
      __syncwarp();
      if (lane == 0) mbar_arrive(BAR + B_CLR * 8);
      PSTAMPW(3, part * 4 + 3);
    }
  } else {
    const int p = warp >> 2, w = warp & 3;
    const int r = lane >> 2, c = lane & 3;
    init_bars(warp);
    asm volatile("setmaxnreg.inc.sync.aligned.u32 224;");
    PSTAMP(0);
    const uint32_t dAx = descA(H0) + p * 4096;
    const uint32_t Hn = H1 - p * 65536;
    const uint32_t moff = ((lane & 7) + ((lane >> 3) & 1) * 8) * 128 + (((lane >> 4) ^ (lane & 7)) << 4);
    const uint32_t Xw = H0 + p * 65536 + w * 2048;
    const int xw = (g * 2 + p) * 4 + w;
    if (p == 1) {
      uint32_t v[8][4];
      mbar_wait(BAR + (B_FKV + SIDE_KB) * 8);
      const int wp = w < 3 ? w : 0;
      const __nv_bfloat16* wr = wqkvp + (size_t)(g * 32 + (lane >> 3) * 8) * (3 * D_) + wp * D_ + j * 64 + (lane & 7) * 8;
#pragma unroll
      for (int i = 0; i < 8; i++) ldg128_nc(v[i], wr + (size_t)i * 3 * D_);
      mbar_wait(BAR + B_TAG * 8);
      const uint32_t tg = lds32(TAGS);
      float cs[8];
#pragma unroll
      for (int e = 0; e < 4; e++) {
        float a = 0.f, b = 0.f;
#pragma unroll
        for (int i = 0; i < 8; i++) { a += bf_lo(v[i][e]); b += bf_hi(v[i][e]); }
        cs[2 * e] = a; cs[2 * e + 1] = b;
      }
      const bool up = lane & 8;
#pragma unroll
      for (int e = 0; e < 4; e++) {
        const float keepv = up ? cs[4 + e] : cs[e], give = up ? cs[e] : cs[4 + e];
        cs[e] = keepv + __shfl_xor_sync(0xffffffffu, give, 8);
        cs[e] += __shfl_xor_sync(0xffffffffu, cs[e], 16);
      }
      if (lane < 16 && w < 3)
        ll_st(X->e0c + ((j * 3 + w) * 16 + g) * 16 + (lane & 7) * 2 + (lane >> 3), __float_as_uint(cs[0]), __float_as_uint(cs[1]),
              __float_as_uint(cs[2]), __float_as_uint(cs[3]), tg);
      __syncwarp();
      mbar_arrive_if(BAR + B_PUB * 8, lane == 0);
      PSTAMP(1);
      mbar_wait(BAR + B_LAG * 8);
    }

    float akv[64];
#pragma unroll 1
    for (int kb = 0; kb < 8; kb++) {
      mbar_wait(BAR + (B_FX + p * 8 + kb) * 8);
      mbar_wait(BAR + (B_FKV + kb) * 8);
      if (kb == 0) PSTAMP(2);
      const uint32_t da = dAx + kb * 512, db = descB(RING) + (kb < 6 ? kb : kb - 6) * 1024;
      wg_fence();
      wgmma_ss_n128(akv, da, db, kb);
#pragma unroll
      for (int k = 1; k < 4; k++) wgmma_ss_n128(akv, da + k * 2, db + k * 128, 1);
      wg_commit();
      mbar_arrive_if(BAR + B_LAG * 8, kb == LAG_KB - 1 && p == 0 && lane == 0);
      wg_wait<1>();
      mbar_arrive_if(BAR + (B_EKV + kb - 1) * 8, kb > 0 && lane == 0);
    }
    asm volatile("barrier.cluster.wait.aligned;" ::: "memory");
    uint32_t xres[4][4];
#pragma unroll
    for (int u = 0; u < 4; u++) ldsm4(xres[u], Xw + j * 8192 + (moff ^ (u << 5)));

    float aq[32];
    auto qstep = [&](int kb) {
      mbar_wait(BAR + (B_FQ + kb) * 8);
      const uint32_t da = dAx + kb * 512, db = descB(RING + 32768) + kb * 512;
      wg_fence();
      wgmma_ss_n64(aq, da, db, kb);
#pragma unroll
      for (int k = 1; k < 4; k++) wgmma_ss_n64(aq, da + k * 2, db + k * 128, 1);
      wg_commit();
      wg_wait<1>();
      mbar_arrive_if(BAR + (B_EQ + kb - 1) * 8, lane == 0);
      mbar_arrive_if(BAR + (B_EX + kb - 2) * 8, lane == 0 && p == 0 && kb >= 2);
    };
    qstep(0);
    keep(akv);
    PSTAMP(3);
    qstep(1);
    mbar_wait(BAR + B_READY * 8);
    PSTAMP(19);
    const uint32_t tag = lds32(TAGS);
    uint4* const xb = reinterpret_cast<uint4*>(X) + lane + (tag >> 1);
    constexpr int O_E4 = offsetof(Scratch, e4) / 16, O_E2 = offsetof(Scratch, e2) / 16, O_E3H = offsetof(Scratch, e3h) / 16;
    const float2 st0 = lds64(ST + (2 * (16 * w + r) + p) * 8);
    const float2 st1 = lds64(ST + (2 * (16 * w + r + 8) + p) * 8);
    uint32_t hi[4][4], lo[4][4];
    {
      float2 cs[16];
      auto cvt = [&](uint32_t (&d)[4][4], int b0, int ofs, const float2& st) {
#pragma unroll
        for (int b = b0; b < b0 + 8; b++) {
          if (ofs == 2) cs[b] = lds64(CS + (64 + b * 8 + 2 * c) * 4);
          const uint32_t v = pack2(fmaf(-st.x, cs[b].x, akv[4 * b + ofs]) * st.y, fmaf(-st.x, cs[b].y, akv[4 * b + ofs + 1]) * st.y);
          d[b >> 2][b & 3] = b < 8 ? v : movm(v);
        }
      };
      cvt(hi, 0, 2, st1);
      keep(hi[0]); keep(hi[1]);
      qstep(2);
      cvt(hi, 8, 2, st1);
      mbar_wait(BAR + B_CLR0 * 8);
      if (w == 3 && g < 15) {
        uint4* dst = X->e1 + ((g * 8 + j) * 2 + p) * 128 + lane;
#pragma unroll
        for (int i = 0; i < 4; i++) ll_st(dst + i * 32, hi[i][0], hi[i][1], hi[i][2], hi[i][3], tag);
      }
      PSTAMP(20);
      wg_bar(p);
#pragma unroll
      for (int i = 0; i < 4; i++) sts128(Xw + lane * 16 + i * 512, hi[i]);
      qstep(3);
      cvt(lo, 0, 0, st0);
      keep(lo[0]); keep(lo[1]);
      qstep(4);
      cvt(lo, 8, 0, st0);
    }
    PSTAMP(21);
    wg_bar(p);
    uint32_t prev[4][4];
    if (w > 0) {
#pragma unroll
      for (int i = 0; i < 4; i++) lds128(prev[i], Xw - 2048 + lane * 16 + i * 512);
    }
    if (p == 0) {
      asm volatile("fence.proxy.async.shared::cta;" ::: "memory");
      __syncwarp();
      if (lane == 0) mbar_arrive(BAR + (B_EX + 7) * 8);
    }
    PSTAMP(22);
    const uint4* halo = X->e1 + (((g - 1) * 8 + j) * 2 + p) * 128 + lane;
    const bool use_halo = w == 0 && g > 0;
    qstep(5);
    if (use_halo) ll_issue<4>(prev, halo, 32);
    qstep(6);
    qstep(7);
    PSTAMP(23);
    if (w == 0) {
      if (g > 0) {
        if (__builtin_expect(ll_bad<4>(prev, pin(tag, zero)), 0)) ll_spin<4>(prev, halo, 32, tag);
        ll_clear<4>(prev);
      } else {
#pragma unroll
        for (int i = 0; i < 4; i++)
#pragma unroll
          for (int e = 0; e < 4; e++) prev[i][e] = 0;
      }
    }
    wg_wait<0>();
    keep(aq);
    mbar_arrive_if(BAR + (B_EQ + 7) * 8, lane == 0);
    mbar_arrive_if(BAR + (B_EX + 6) * 8, lane == 0 && p == 0);
    PSTAMP(4);

    uint32_t of[4][4];
    {
      const float sc = 0.25f * 1.4426950408889634f;
      const float nohalo = (g == 0 && w == 0) ? -INFINITY : 0.f;
      const bool up0 = 2 * c > r, up1 = 2 * c + 1 > r;
      const uint32_t mup = (up0 ? 0xffffu : 0u) | (up1 ? 0xffff0000u : 0u);
      uint4* dst = xb + O_E2 + (xw * 32 + 4 * j) * 32;
      float d0 = 0.f, d1 = 0.f;
#pragma unroll 1
      for (int hp = 0; hp < 2; hp++) {
#pragma unroll
        for (int e = 0; e < 4; e++) { of[0][e] = of[2][e]; of[1][e] = of[3][e]; }
#pragma unroll
        for (int h = 0; h < 2; h++) {
          uint32_t qf[4];
          const uint32_t co = (32 * hp + 16 * h + 2 * c) * 4;
          {
            const float2 ca = lds64(CS + co), cb = lds64(CS + co + 32);
            qf[0] = pack2(fmaf(-st0.x, ca.x, aq[8 * h + 0]) * st0.y, fmaf(-st0.x, ca.y, aq[8 * h + 1]) * st0.y);
            qf[1] = pack2(fmaf(-st1.x, ca.x, aq[8 * h + 2]) * st1.y, fmaf(-st1.x, ca.y, aq[8 * h + 3]) * st1.y);
            qf[2] = pack2(fmaf(-st0.x, cb.x, aq[8 * h + 4]) * st0.y, fmaf(-st0.x, cb.y, aq[8 * h + 5]) * st0.y);
            qf[3] = pack2(fmaf(-st1.x, cb.x, aq[8 * h + 6]) * st1.y, fmaf(-st1.x, cb.y, aq[8 * h + 7]) * st1.y);
          }
          const int e0 = 2 * h;
          float sp[4], sl[4], sh[4];
          mma16816(sp, qf, prev[0][e0], prev[0][e0 + 1]);
          mma16816(sl, qf, lo[0][e0], lo[0][e0 + 1]);
          mma16816(sh, qf, hi[0][e0], hi[0][e0 + 1]);
          float a0 = up0 ? sp[0] + nohalo : sl[0], a1 = up1 ? sp[1] + nohalo : sl[1];
          float b0 = up0 ? sl[2] : sh[2], b1 = up1 ? sl[3] : sh[3];
          float ma = fmaxf(a0, a1), mb = fmaxf(b0, b1);
          ma = fmaxf(ma, __shfl_xor_sync(0xffffffffu, ma, 1)); mb = fmaxf(mb, __shfl_xor_sync(0xffffffffu, mb, 1));
          ma = fmaxf(ma, __shfl_xor_sync(0xffffffffu, ma, 2)); mb = fmaxf(mb, __shfl_xor_sync(0xffffffffu, mb, 2));
          a0 = ex2((a0 - ma) * sc); a1 = ex2((a1 - ma) * sc); b0 = ex2((b0 - mb) * sc); b1 = ex2((b1 - mb) * sc);
          float sa = a0 + a1, sbb = b0 + b1;
          sa += __shfl_xor_sync(0xffffffffu, sa, 1); sbb += __shfl_xor_sync(0xffffffffu, sbb, 1);
          sa += __shfl_xor_sync(0xffffffffu, sa, 2); sbb += __shfl_xor_sync(0xffffffffu, sbb, 2);
          const float ia = rcp(sa), ib = rcp(sbb);
          const uint32_t pa = pack2(a0 * ia, a1 * ia), pb = pack2(b0 * ib, b1 * ib);
          const uint32_t pf[4] = {pa & mup, 0u, pa & ~mup, pb & mup};
          const uint32_t ph = pb & ~mup;
          float o0[4], o1[4];
          mma16816(o0, pf, prev[2][e0], lo[2][e0]);
          mma16816(o1, pf, prev[2][e0 + 1], lo[2][e0 + 1]);
          mma1688_acc(o0, 0u, ph, hi[2][e0]);
          mma1688_acc(o1, 0u, ph, hi[2][e0 + 1]);
          of[2 + h][0] = pack2(o0[0], o0[1]); of[2 + h][1] = pack2(o0[2], o0[3]);
          of[2 + h][2] = pack2(o1[0], o1[1]); of[2 + h][3] = pack2(o1[2], o1[3]);
          ll_st(dst + (2 * hp + h) * 32, of[2 + h][0], of[2 + h][1], of[2 + h][2], of[2 + h][3], tag);
          const float2 wa = lds64(WB + co), wb = lds64(WB + co + 32);
          d0 = fmaf(o0[0], wa.x, d0); d0 = fmaf(o0[1], wa.y, d0); d0 = fmaf(o1[0], wb.x, d0); d0 = fmaf(o1[1], wb.y, d0);
          d1 = fmaf(o0[2], wa.x, d1); d1 = fmaf(o0[3], wa.y, d1); d1 = fmaf(o1[2], wb.x, d1); d1 = fmaf(o1[3], wb.y, d1);
        }
#pragma unroll
        for (int e = 0; e < 16; e++) aq[e] = aq[16 + e];
#pragma unroll
        for (int e = 0; e < 4; e++) {
          prev[0][e] = prev[1][e]; prev[2][e] = prev[3][e];
          lo[0][e] = lo[1][e]; lo[2][e] = lo[3][e];
          hi[0][e] = hi[1][e]; hi[2][e] = hi[3][e];
        }
      }
#pragma unroll
      for (int o = 1; o <= 2; o <<= 1) { d0 += __shfl_xor_sync(0xffffffffu, d0, o); d1 += __shfl_xor_sync(0xffffffffu, d1, o); }
      if (c == 0) ll_st(X->e2s + (xw * 8 + j) * 8 + r, __float_as_uint(d0), __float_as_uint(d1), 0, 0, tag);
    }
    PSTAMP(5);

    float ah[32];
    uint32_t sv[2][4];
    unpack32(ah, xres);
    {
      uint32_t og[2][14][4];
      const uint4* osrc[7];
#pragma unroll
      for (int i = 0; i < 7; i++) osrc[i] = xb + O_E2 + (xw * 32 + 4 * kb_at(i + 1, j)) * 32;
      const uint4* ssrc = X->e2s + (xw * 8 + 2 * c) * 8 + r;
      auto oissue = [&](int hp) {
#pragma unroll
        for (int i = 0; i < 14; i++) ll_ld(og[hp][i], osrc[i >> 1] + (2 * hp + (i & 1)) * 32);
        if (hp == 1) ll_issue<2>(sv, ssrc, 8);
      };
      auto omma = [&](int hp) {
        ll_clear<14>(og[hp]);
        keep(og[hp]);
        wg_fence();
#pragma unroll
        for (int i = 0; i < 14; i++) wgmma_rs_n64(ah, og[hp][i], descB(H0) + kb_at((i >> 1) + 1, j) * 512 + (2 * hp + (i & 1)) * 128, 1);
        wg_commit();
      };
      mbar_wait(BAR + B_FWO * 8);
      keep(ah); keep(of);
      wg_fence();
#pragma unroll
      for (int k = 0; k < 4; k++) wgmma_rs_n64(ah, of[k], descB(H0) + j * 512 + k * 128, 1);
      wg_commit();
      uint32_t it = 0;
#pragma unroll 1
      do { oissue(0); } while (ll_bad<14>(og[0], tag) && ++it < SPIN_LIMIT);
      PSTAMP(6);
      oissue(1);
      omma(0);
      const uint32_t tg = pin(tag, zero);
      if (__builtin_expect(ll_any(ll_acc<14>(og[1], tg, ll_acc<2>(sv, tg))), 0)) {
#pragma unroll 1
        do { oissue(1); } while (ll_any(ll_acc<14>(og[1], tag, ll_acc<2>(sv, tag))) && ++it < SPIN_LIMIT);
      }
      PSTAMP(16);
      omma(1);
      ll_clear<2>(sv);
    }
    float m0 = __uint_as_float(sv[0][0]) + __uint_as_float(sv[1][0]), m1 = __uint_as_float(sv[0][1]) + __uint_as_float(sv[1][1]);
#pragma unroll
    for (int o = 1; o <= 2; o <<= 1) { m0 += __shfl_xor_sync(0xffffffffu, m0, o); m1 += __shfl_xor_sync(0xffffffffu, m1, o); }
    const uint32_t mu0 = pack2(m0 + st0.x, m0 + st0.x), mu1 = pack2(m1 + st1.x, m1 + st1.x);
    wg_wait<0>();
    keep(ah);
    if (lane == 0) mbar_arrive(BAR + B_WODONE * 8);
    PSTAMP(7);

    uint32_t hf[4][4], ra[4][4];
    pack32(hf, ah);
    {
      uint4* dst = xb + O_E3H + (xw * 32 + 4 * j) * 32;
#pragma unroll
      for (int u = 0; u < 4; u++) {
        ra[u][0] = hsub2(hf[u][0], mu0); ra[u][1] = hsub2(hf[u][1], mu1);
        ra[u][2] = hsub2(hf[u][2], mu0); ra[u][3] = hsub2(hf[u][3], mu1);
        ll_st(dst + u * 32, ra[u][0], ra[u][1], ra[u][2], ra[u][3], tag);
      }
      float s0 = 0.f, q0 = 0.f, s1 = 0.f, q1 = 0.f;
#pragma unroll
      for (int b = 0; b < 8; b++) {
        s0 += ah[4 * b] + ah[4 * b + 1]; s1 += ah[4 * b + 2] + ah[4 * b + 3];
        q0 = fmaf(ah[4 * b], ah[4 * b], q0); q0 = fmaf(ah[4 * b + 1], ah[4 * b + 1], q0);
        q1 = fmaf(ah[4 * b + 2], ah[4 * b + 2], q1); q1 = fmaf(ah[4 * b + 3], ah[4 * b + 3], q1);
      }
#pragma unroll
      for (int o = 1; o <= 2; o <<= 1) {
        s0 += __shfl_xor_sync(0xffffffffu, s0, o); q0 += __shfl_xor_sync(0xffffffffu, q0, o);
        s1 += __shfl_xor_sync(0xffffffffu, s1, o); q1 += __shfl_xor_sync(0xffffffffu, q1, o);
      }
      if (c == 0) ll_st(X->e3s + (xw * 8 + j) * 8 + r, __float_as_uint(s0), __float_as_uint(q0), __float_as_uint(s1), __float_as_uint(q1), tag);
      mbar_wait(BAR + (p == 0 ? B_EQ + 7 : B_WODONE) * 8);
    }
    PSTAMP(8);

    float rs0, rs1;
    auto swiglu = [&](float g0, float g1, float u0, float u1, float rs) -> uint32_t {
      const float hr = 0.5f * rs;
      const float x0 = g0 * hr, x1 = g1 * hr;
      const float t0 = tanhf_hw(x0), t1 = tanhf_hw(x1);
      return pack2(fmaf(x0, t0, x0) * (u0 * rs), fmaf(x1, t1, x1) * (u1 * rs));
    };
    uint32_t hA[6][4];
    {
      float a1[64], a2[32];
      const uint4* src = xb + O_E3H + xw * 32 * 32;
      uint32_t rb[4][4], rc[4][4], rd[4][4];
      auto fetch = [&](uint32_t (&a)[4][4], int i) { ll_issue<4>(a, src + kb_at(i, j) * 128, 32); };
      auto check = [&](uint32_t (&a)[4][4], uint32_t (&b)[4][4], int i) {
        const uint32_t tg = pin(tag, zero);
        if (__builtin_expect(ll_any(ll_acc<4>(a, tg, ll_acc<4>(b, tg))), 0)) {
          uint32_t it = 0;
#pragma unroll 1
          do { fetch(a, i); fetch(b, i + 1); } while (ll_any(ll_acc<4>(a, tag, ll_acc<4>(b, tag))) && ++it < SPIN_LIMIT);
        }
        ll_clear<4>(a); ll_clear<4>(b);
        keep(a); keep(b);
      };
      auto head = [&](uint32_t (&a)[4][4], int i) {
        mbar_wait(BAR + (B_FA + i) * 8);
        wg_fence();
        wgmma_rs_n64<DESC_HI64>(a2, a[0], descBh(RING + 16384) + (i & 3) * 1536, i);
        wgmma_rs_n128(a1, a[0], descB(RING) + (i & 3) * 1536, i);
        wg_commit();
#pragma unroll
        for (int u = 0; u < 4; u++) stsm4(Hn + w * 2048 + i * 8192 + (moff ^ (u << 5)), a[u]);
        wg_wait<1>();
        if (i > 0) mbar_arrive_if(BAR + (B_EA + i - 1) * 8, lane == 0);
      };
      auto rest = [&](uint32_t (&a)[4][4], int i) {
        wg_fence();
#pragma unroll
        for (int k = 1; k < 4; k++) {
          wgmma_rs_n64<DESC_HI64>(a2, a[k], descBh(RING + 16384) + (i & 3) * 1536 + k * 64, 1);
          wgmma_rs_n128(a1, a[k], descB(RING) + (i & 3) * 1536 + k * 128, 1);
        }
        wg_commit();
      };
      ll_clear<4>(ra);
      keep(ra);
      head(ra, 0); rest(ra, 0);
      ll_get<4>(rb, src + kb_at(1, j) * 128, 32, tag);
      keep(rb);
      PSTAMP(17);
      fetch(rc, 2); fetch(rd, 3);
      head(rb, 1); rest(rb, 1);
      check(rc, rd, 2);
      head(rc, 2); fetch(ra, 4); fetch(rb, 5); rest(rc, 2);
      head(rd, 3); rest(rd, 3);
      check(ra, rb, 4);
      head(ra, 4); fetch(rc, 6); fetch(rd, 7); ll_issue<2>(sv, X->e3s + (xw * 8 + 2 * c) * 8 + r, 8); rest(ra, 4);
      head(rb, 5); rest(rb, 5);
      check(rc, rd, 6);
      head(rc, 6); rest(rc, 6);
      head(rd, 7); rest(rd, 7);
      fence_async_smem();
      ll_wait<2>(sv, X->e3s + (xw * 8 + 2 * c) * 8 + r, 8, tag);
      float s0 = __uint_as_float(sv[0][0]) + __uint_as_float(sv[1][0]), q0 = __uint_as_float(sv[0][1]) + __uint_as_float(sv[1][1]);
      float s1 = __uint_as_float(sv[0][2]) + __uint_as_float(sv[1][2]), q1 = __uint_as_float(sv[0][3]) + __uint_as_float(sv[1][3]);
#pragma unroll
      for (int o = 1; o <= 2; o <<= 1) {
        s0 += __shfl_xor_sync(0xffffffffu, s0, o); q0 += __shfl_xor_sync(0xffffffffu, q0, o);
        s1 += __shfl_xor_sync(0xffffffffu, s1, o); q1 += __shfl_xor_sync(0xffffffffu, q1, o);
      }
      s0 *= 1.f / D_; s1 *= 1.f / D_;
      rs0 = rsqrtf(fmaxf(fmaf(-s0, s0, q0 * (1.f / D_)), 0.f) + 1e-5f);
      rs1 = rsqrtf(fmaxf(fmaf(-s1, s1, q1 * (1.f / D_)), 0.f) + 1e-5f);
      wg_wait<0>();
      keep(a1); keep(a2);
      if (lane == 0) mbar_arrive(BAR + (B_EA + 7) * 8);
      PSTAMP(9);
#pragma unroll
      for (int u = 0; u < 4; u++)
#pragma unroll
        for (int e = 0; e < 4; e++)
          hA[u][e] = swiglu(a1[8 * u + 2 * e], a1[8 * u + 2 * e + 1], a1[32 + 8 * u + 2 * e], a1[33 + 8 * u + 2 * e], (e & 1) ? rs1 : rs0);
#pragma unroll
      for (int u = 0; u < 2; u++)
#pragma unroll
        for (int e = 0; e < 4; e++)
          hA[4 + u][e] = swiglu(a2[8 * u + 2 * e], a2[8 * u + 2 * e + 1], a2[16 + 8 * u + 2 * e], a2[17 + 8 * u + 2 * e], (e & 1) ? rs1 : rs0);
      keep(hA);
      wg_bar(p);
    }
    PSTAMP(10);

    uint32_t hB[8][4];
    {
      float ab[128];
      uint32_t db = descB(RING);
      const uint32_t dAn = descA(H1) - p * 4096;
#pragma unroll 1
      for (int i = 0; i < 8; i++) {
        mbar_wait(BAR + (B_FB + i) * 8);
        const uint32_t da = dAn + i * 512;
        wg_fence();
        wgmma_ss_n256(ab, da, db, i);
#pragma unroll
        for (int k = 1; k < 4; k++) wgmma_ss_n256(ab, da + k * 2, db + k * 128, 1);
        wg_commit();
        wg_wait<1>();
        mbar_arrive_if(BAR + (B_EB + i - 1) * 8, i > 0 && lane == 0);
        db = db == descB(RING + 65536) ? descB(RING) : db + 2048;
      }
      wg_wait<0>();
      keep(ab);
      mbar_arrive_if(BAR + (B_EB + 7) * 8, lane == 0);
      if (lane == 0) {
        asm volatile("mbarrier.arrive.relaxed.cluster.shared::cluster.b64 _, [%0];" ::"r"(BAR + (B_PF + p) * 8 + peer()) : "memory");
        if (w == 0) mbar_expect_tx(BAR + (B_HX + p) * 8, 28672);
      }
      PSTAMP(11);
#pragma unroll
      for (int u = 0; u < 8; u++) {
        const int o = (u >> 2) * 64 + (u & 3) * 8;
#pragma unroll
        for (int e = 0; e < 4; e++)
          hB[u][e] = swiglu(ab[o + 2 * e], ab[o + 2 * e + 1], ab[o + 32 + 2 * e], ab[o + 33 + 2 * e], (e & 1) ? rs1 : rs0);
      }
      keep(hB);
    }
    PSTAMP(12);

    {
      float ya[32], y[32];
      uint32_t hP[14][4];
      const uint32_t offA = (j & 1) ? 256 : 0, offH = (j & 1) ? 0 : 1536;
      uint4* e4 = xb + O_E4 + g * 24576 + warp * 128;
      const uint32_t stg = H0 + p * 65536 + 28672 + (w >> 1) * 32768 + (w & 1) * 2048;
      auto mm = [&](float (&d)[32], int m, int k0, int k1) {
        if (k0 == 0) mbar_wait(BAR + (B_FT + m) * 8);
        const uint32_t T = descB(0) + (t_addr(m) >> 4);
        const uint32_t oA = w2_peer(m) ? 256 - offA : offA, oH = w2_peer(m) ? 1536 - offH : offH;
        wg_fence();
#pragma unroll
        for (int k = k0; k < k1; k++) {
          const uint32_t db = T + (k < 4 ? oA + k * 128 : k < 6 ? oH + (k - 4) * 128 : oA + 512 + (k - 6) * 128);
          if (w2_peer(m)) wgmma_rs_n64(d, hP[k], db, 1);
          else if (k < 6) wgmma_rs_n64(d, hA[k], db, k);
          else wgmma_rs_n64(d, hB[k - 6], db, 1);
        }
        wg_commit();
      };
      auto next = [&](float (&d)[32], int m, float (&dp)[32], int q) {
        mm(d, m, 0, 3);
        wg_wait<1>();
        keep(dp);
        mbar_arrive_if(BAR + (B_ET0 + q) * 8, lane == 0);
        uint4* dst = e4 + (((j + 2 + 2 * q) & 7) * 3 + q) * 1024;
#pragma unroll
        for (int u = 0; u < 4; u++)
          ll_st(dst + u * 32, pack2(dp[8 * u], dp[8 * u + 1]), pack2(dp[8 * u + 2], dp[8 * u + 3]),
                pack2(dp[8 * u + 4], dp[8 * u + 5]), pack2(dp[8 * u + 6], dp[8 * u + 7]), tag);
        if (q == 2) mbar_wait(BAR + (B_ET0 + 2) * 8);
        mm(d, m, 3, 14);
      };
      mbar_wait_cluster(BAR + (B_PF + p) * 8);
      const uint32_t mbx = Hn + 32768 + w * 7168 + lane * 16;
#pragma unroll
      for (int i = 0; i < 7; i++) {
        const uint32_t a = (i ? pin(mbx, zero) : mbx) + peer();
#pragma unroll
        for (int k = 2 * i; k < 2 * i + 2; k++) {
          const uint32_t (&v)[4] = k < 6 ? hA[k < 6 ? k : 0] : hB[k < 6 ? 0 : k - 6];
          asm volatile("st.async.weak.shared::cluster.mbarrier::complete_tx::bytes.v4.b32 [%0], {%1,%2,%3,%4}, [%5];"
                       ::"r"(a + k * 512), "r"(v[0]), "r"(v[1]), "r"(v[2]), "r"(v[3]), "r"(BAR + (B_HX + p) * 8 + peer()) : "memory");
        }
        if (i < 4) mm(ya, 0, 4 * i - (i > 2 ? 2 * (i - 2) : 0) , i < 3 ? 4 * i + 4 - (i > 1 ? 2 : 0) : 14);
        else mm(y, 1, 3 * (i - 4), 3 * (i - 3));
      }
      PSTAMP(18);
      mbar_wait_cluster(BAR + (B_HX + p) * 8);
      PSTAMP(24);
#pragma unroll
      for (int k = 0; k < 14; k++) lds128(hP[k], mbx + k * 512);
      mm(y, 1, 9, 14);
      keep(hP);
      mbar_arrive_if(BAR + (B_HC + p) * 8, lane == 0);
      mm(ya, 2, 0, 14);
      mbar_wait(BAR + B_CLR * 8);
      next(y, 3, ya, 0);
      PSTAMP(27);
      next(ya, 4, y, 1);
      mbar_arrive_if(BAR + (B_ET0 + 3) * 8, lane == 0);
      mm(ya, 5, 0, 14);
      PSTAMP(26);
      next(y, 6, ya, 2);
      PSTAMP(28);
      uint32_t in[4][4], lt[4][4];
      const uint4* insrc = e4 + j * 3 * 1024;
      mm(y, 7, 0, 7);
      ll_issue<4>(lt, insrc + 2048, 32);
      mm(y, 7, 7, 14);
      mbar_wait(BAR + B_FIN * 8);
      mbar_wait(BAR + (B_FIN + 1) * 8);
      wg_wait<0>();
      keep(y);
      PSTAMP(13);
      const uint32_t ident = (2 * c == r ? 0x3f80u : 0u) | (2 * c + 1 == r ? 0x3f800000u : 0u);
      auto acc = [&](const uint32_t (&v)[4][4]) {
#pragma unroll
        for (int u = 0; u < 4; u++) {
          mma1688_acc(*reinterpret_cast<float (*)[4]>(&y[8 * u]), v[u][0], v[u][1], ident);
          mma1688_acc(*reinterpret_cast<float (*)[4]>(&y[8 * u + 4]), v[u][2], v[u][3], ident);
        }
      };
      acc(hf);
#pragma unroll
      for (int q = 0; q < 2; q++) {
#pragma unroll
        for (int u = 0; u < 4; u++) lds128(in[u], t_addr(q + 1) + warp * 2048 + lane * 16 + u * 512);
        ll_wait<4>(in, insrc + q * 1024, 32, tag);
        acc(in);
      }
      PSTAMP(25);
      if (ll_bad<4>(lt, pin(tag, zero))) {
        ll_spin<4>(lt, insrc + 2048, 32, tag);
      }
      ll_clear<4>(lt);
      acc(lt);
      PSTAMP(14);
#pragma unroll
      for (int u = 0; u < 4; u++) {
        uint32_t o[4];
#pragma unroll
        for (int e = 0; e < 4; e++) o[e] = pack2(y[8 * u + 2 * e], y[8 * u + 2 * e + 1]);
        stsm4(stg + (moff ^ (u << 5)), o);
      }
      fence_async_smem();
      __syncwarp();
      if (elect_one()) {
        tma3d_store(&P.out, stg, 64 * j, p, g * 64 + 16 * w);
        asm volatile("cp.async.bulk.commit_group;" ::: "memory");
        asm volatile("cp.async.bulk.wait_group.read 0;" ::: "memory");
      }
      PSTAMP(15);
    }
  }
}

typedef CUresult (*EncodeFn)(CUtensorMap*, CUtensorMapDataType, cuuint32_t, void*, const cuuint64_t*, const cuuint64_t*,
                             const cuuint32_t*, const cuuint32_t*, CUtensorMapInterleave, CUtensorMapSwizzle,
                             CUtensorMapL2promotion, CUtensorMapFloatOOBfill);

void enc2d(EncodeFn f, CUtensorMap* m, const void* base, uint64_t cols, uint64_t rows, uint32_t bc, uint32_t br, CUtensorMapSwizzle sw) {
  cuuint64_t gd[2] = {cols, rows}, gs[1] = {cols * 2};
  cuuint32_t bd[2] = {bc, br}, es[2] = {1, 1};
  f(m, CU_TENSOR_MAP_DATA_TYPE_BFLOAT16, 2, const_cast<void*>(base), gd, gs, bd, es, CU_TENSOR_MAP_INTERLEAVE_NONE, sw,
    CU_TENSOR_MAP_L2_PROMOTION_L2_128B, CU_TENSOR_MAP_FLOAT_OOB_FILL_NONE);
}
void enc_par(EncodeFn f, CUtensorMap* m, const void* base, uint32_t pairs) {
  cuuint64_t gd[3] = {(cuuint64_t)D_, 2, (cuuint64_t)S_ / 2}, gs[2] = {D_ * 2, D_ * 4};
  cuuint32_t bd[3] = {64, 1, pairs}, es[3] = {1, 1, 1};
  f(m, CU_TENSOR_MAP_DATA_TYPE_BFLOAT16, 3, const_cast<void*>(base), gd, gs, bd, es, CU_TENSOR_MAP_INTERLEAVE_NONE,
    CU_TENSOR_MAP_SWIZZLE_128B, CU_TENSOR_MAP_L2_PROMOTION_L2_128B, CU_TENSOR_MAP_FLOAT_OOB_FILL_NONE);
}

}

extern "C" void kernel_launch(void* const* d_in, const int* in_sizes, int n_in, void* d_out, int out_size) {
  (void)in_sizes; (void)n_in; (void)out_size;
  static EncodeFn enc = nullptr;
  static Scratch* scratch = nullptr;
  if (!enc) {
    void* fn = nullptr;
    cudaDriverEntryPointQueryResult q;
    cudaGetDriverEntryPoint("cuTensorMapEncodeTiled", &fn, cudaEnableDefault, &q);
    enc = (EncodeFn)fn;
    cudaGetSymbolAddress((void**)&scratch, g_scratch);
    cudaFuncSetAttribute(fused_block_kernel, cudaFuncAttributeMaxDynamicSharedMemorySize, SMEM_BYTES);
  }
  Params P;
  const __nv_bfloat16* xp = (const __nv_bfloat16*)d_in[0];
  const __nv_bfloat16* wqkvp = (const __nv_bfloat16*)d_in[1];
  const __nv_bfloat16* wop = (const __nv_bfloat16*)d_in[2];
  P.w1p = (const __nv_bfloat16*)d_in[4];
  P.w3p = (const __nv_bfloat16*)d_in[5];
  P.w2p = (const __nv_bfloat16*)d_in[6];
  enc_par(enc, &P.x, xp, 64);
  enc_par(enc, &P.out, d_out, 16);
  enc2d(enc, &P.wqkv, wqkvp, 3 * D_, D_, 64, 64, CU_TENSOR_MAP_SWIZZLE_128B);
  enc2d(enc, &P.wo, wop, D_, D_, 64, 64, CU_TENSOR_MAP_SWIZZLE_128B);
  enc2d(enc, &P.w1, P.w1p, F_, D_, 64, 64, CU_TENSOR_MAP_SWIZZLE_128B);
  enc2d(enc, &P.w3, P.w3p, F_, D_, 64, 64, CU_TENSOR_MAP_SWIZZLE_128B);
  enc2d(enc, &P.w1h, P.w1p, F_, D_, 32, 64, CU_TENSOR_MAP_SWIZZLE_64B);
  enc2d(enc, &P.w3h, P.w3p, F_, D_, 32, 64, CU_TENSOR_MAP_SWIZZLE_64B);
  enc2d(enc, &P.w2, P.w2p, D_, F_, 64, 224, CU_TENSOR_MAP_SWIZZLE_128B);

  cudaLaunchConfig_t cfg = {};
  cfg.gridDim = dim3(128);
  cfg.blockDim = dim3(384);
  cfg.dynamicSmemBytes = SMEM_BYTES;
  cfg.stream = cudaStreamPerThread;
  cudaLaunchAttribute at[2];
  at[0].id = cudaLaunchAttributeCooperative;
  at[0].val.cooperative = 1;
  cfg.attrs = at;
  cfg.numAttrs = 1;
  at[1].id = cudaLaunchAttributeClusterDimension;
  at[1].val.clusterDim.x = 2; at[1].val.clusterDim.y = 1; at[1].val.clusterDim.z = 1;
  cfg.numAttrs = 2;
  cudaLaunchKernelEx(&cfg, fused_block_kernel, scratch, xp, wqkvp, wop, 0u, P);
}
```

```cpp
#include <cuda_runtime.h>
#include <cuda.h>
#include <cuda_bf16.h>
#include <stdint.h>
#include <stddef.h>

namespace {

constexpr int S_ = 2048, D_ = 512, F_ = 1792;
#define LAG_KB 3
#define E4_FIRST 7
#define PP_AHEAD 1
#define SIDE_KB 0
#define CLR_MODE 0
#define W2_HEAD 3
#define CLR_SLEEP 400
#define CMAP 2
#define E4_ON 1
#define E4_WHEN (B_EA + 7)
#define SEND_EARLY 2
#define XO_DELAY 2

constexpr uint32_t SPIN_LIMIT = 1u << 18;

struct Scratch {
  uint4 e4[16 * 8 * 3 * 8 * 4 * 32];
  uint4 e2[16 * 2 * 4 * 32 * 32];
  uint4 e3h[16 * 2 * 4 * 32 * 32];
  uint4 e1[16 * 8 * 2 * 4 * 32];
  uint4 e2s[16 * 2 * 4 * 8 * 8];
  uint4 e3s[16 * 2 * 4 * 8 * 8];
  uint4 e0c[8 * 3 * 16 * 16];
  uint4 e0s[2048];
  uint4 e0w[8 * 64];
  unsigned epoch[128];
};
__device__ Scratch g_scratch;
#define PSTAMP(i)
#define PSTAMPW(slot, i)
#define W2STAMP(i)

struct alignas(64) Params {
  CUtensorMap x, out, wqkv, wo, w1, w3, w1h, w3h, w2;
  const __nv_bfloat16 *w1p, *w3p, *w2p;
};

constexpr uint32_t SB = 1024;
constexpr uint32_t H0 = SB;
constexpr uint32_t H1 = SB + 65536;
constexpr uint32_t RING = SB + 131072;
constexpr uint32_t BAR = SB + 229376;
constexpr uint32_t TAGS = BAR + 1016;
constexpr uint32_t CS = BAR + 1024;
constexpr uint32_t ST = CS + 768;
constexpr uint32_t WB = ST + 1024;
constexpr uint32_t SMEM_BYTES = 232448;
static_assert(WB + 256 <= SB + SMEM_BYTES, "smem");

enum : int {
  B_FX = 0,
  B_FKV = 16, B_FQ = 24, B_FWO = 32, B_FA = 40, B_FB = 48, B_FT = 56,
  B_EKV = 64, B_EQ = 72, B_EA = 80, B_EB = 88, B_ET0 = 96,
  B_WODONE = 103,
  B_FIN = 33,
  B_EX = 104,
  B_LAG = 112, B_READY = 113, B_PUB = 114, B_CLR = 115, B_CLR0 = 116, B_TAG = 117,
  B_HX = 35,
  B_PF = 118,
  B_HC = 122
};

__device__ __forceinline__ uint32_t smem_u32(const void* p) { return (uint32_t)__cvta_generic_to_shared(p); }
__device__ __forceinline__ uint32_t own() { return (blockIdx.x & 1) << 24; }
__device__ __forceinline__ uint32_t peer() { return (~blockIdx.x & 1) << 24; }
__device__ __forceinline__ void mbar_init(uint32_t b, uint32_t c) { asm volatile("mbarrier.init.shared::cta.b64 [%0], %1;" ::"r"(b + own()), "r"(c) : "memory"); }
__device__ __forceinline__ void mbar_expect_tx(uint32_t b, uint32_t bytes) { asm volatile("mbarrier.arrive.expect_tx.shared::cta.b64 _, [%0], %1;" ::"r"(b + own()), "r"(bytes) : "memory"); }
__device__ __forceinline__ void mbar_arrive(uint32_t b) { asm volatile("mbarrier.arrive.shared::cta.b64 _, [%0];" ::"r"(b + own()) : "memory"); }
__device__ __forceinline__ void mbar_wait(uint32_t b) {
  asm volatile("{\n.reg .pred p;\n.reg .u32 c;\nmov.u32 c, 0;\nLW:\n.pragma \"nounroll\";\n"
               "mbarrier.try_wait.parity.shared::cta.b64 p, [%0], 0;\nadd.u32 c, c, 1;\nsetp.gt.or.u32 p, c, %1, p;\n@!p bra LW;\n}\n"
               ::"r"(b + own()), "n"(SPIN_LIMIT) : "memory");
}
__device__ __forceinline__ void mbar_arrive_peer(uint32_t b) {
  asm volatile("mbarrier.arrive.relaxed.cluster.shared::cluster.b64 _, [%0];" ::"r"(b + peer()) : "memory");
}
__device__ __forceinline__ void mbar_wait_cluster(uint32_t b) {
  asm volatile("{\n.reg .pred p;\n.reg .u32 c;\nmov.u32 c, 0;\nLW:\n.pragma \"nounroll\";\n"
               "mbarrier.try_wait.parity.acquire.cluster.shared::cta.b64 p, [%0], 0;\nadd.u32 c, c, 1;\nsetp.gt.or.u32 p, c, %1, p;\n@!p bra LW;\n}\n"
               ::"r"(b + own()), "n"(SPIN_LIMIT) : "memory");
}
__device__ __forceinline__ bool elect_one() {
  uint32_t p;
  asm volatile("{\n.reg .pred P;\nelect.sync _|P, 0xffffffff;\nselp.u32 %0, 1, 0, P;\n}\n" : "=r"(p));
  return p;
}
__device__ __forceinline__ void tma2d(uint32_t dst, const CUtensorMap* m, int c0, int c1, uint32_t bar) {
  dst += own(); bar += own();
  asm volatile("cp.async.bulk.tensor.2d.shared::cluster.global.mbarrier::complete_tx::bytes [%0], [%1, {%3, %4}], [%2];"
               ::"r"(dst), "l"(m), "r"(bar), "r"(c0), "r"(c1) : "memory");
}
__device__ __forceinline__ void tma3d(uint32_t dst, const CUtensorMap* m, int c0, int c1, int c2, uint32_t bar) {
  dst += own(); bar += own();
  asm volatile("cp.async.bulk.tensor.3d.shared::cluster.global.mbarrier::complete_tx::bytes [%0], [%1, {%3, %4, %5}], [%2];"
               ::"r"(dst), "l"(m), "r"(bar), "r"(c0), "r"(c1), "r"(c2) : "memory");
}
__device__ __forceinline__ void tma3d_store(const CUtensorMap* m, uint32_t src, int c0, int c1, int c2) {
  asm volatile("cp.async.bulk.tensor.3d.global.shared::cta.bulk_group [%0, {%2, %3, %4}], [%1];"
               ::"l"(m), "r"(src + own()), "r"(c0), "r"(c1), "r"(c2) : "memory");
}
__device__ __forceinline__ void l2_prefetch(const void* p, uint32_t bytes) {
  asm volatile("cp.async.bulk.prefetch.L2.global [%0], %1;" ::"l"(p), "r"(bytes) : "memory");
}
__device__ __forceinline__ void prefetch_map(const CUtensorMap* m) { asm volatile("prefetch.tensormap [%0];" ::"l"(m) : "memory"); }
__device__ __forceinline__ void fence_async_smem() { asm volatile("fence.proxy.async.shared::cta;" ::: "memory"); }
__device__ __forceinline__ void wg_fence() { asm volatile("wgmma.fence.sync.aligned;" ::: "memory"); }
__device__ __forceinline__ void wg_commit() { asm volatile("wgmma.commit_group.sync.aligned;" ::: "memory"); }
template <int N> __device__ __forceinline__ void wg_wait() { asm volatile("wgmma.wait_group.sync.aligned %0;" ::"n"(N) : "memory"); }
__device__ __forceinline__ void wg_bar(int p) {
  if (p == 0) asm volatile("bar.sync 1, 128;" ::: "memory"); else asm volatile("bar.sync 2, 128;" ::: "memory");
}
constexpr uint32_t DESC_HI128 = (1024 >> 4) | (1u << 30);
constexpr uint32_t DESC_HI64 = (512 >> 4) | (2u << 30);
__device__ __forceinline__ constexpr uint32_t descA(uint32_t addr) { return (addr >> 4) | (1u << 16); }
__device__ __forceinline__ constexpr uint32_t descB(uint32_t addr) { return (addr >> 4) | ((8192u >> 4) << 16); }
__device__ __forceinline__ constexpr uint32_t descBh(uint32_t addr) { return (addr >> 4) | ((4096u >> 4) << 16); }

__device__ __forceinline__ void wgmma_ss_n64(float (&d)[32], uint32_t da, uint32_t db, int sc) {
  asm volatile("{\n.reg .pred p;\n.reg .b64 da, db;\nsetp.ne.b32 p, %34, 0;\nmov.b64 da, {%32, %35};\nmov.b64 db, {%33, %35};\n"
    "wgmma.mma_async.sync.aligned.m64n64k16.f32.bf16.bf16 {%0, %1, %2, %3, %4, %5, %6, %7, %8, %9, %10, %11, %12, %13, %14, %15, %16, %17, %18, %19, %20, %21, %22, %23, %24, %25, %26, %27, %28, %29, %30, %31}, da, db, p, 1, 1, 0, 1;\n}\n"
    : "+f"(d[0]), "+f"(d[1]), "+f"(d[2]), "+f"(d[3]), "+f"(d[4]), "+f"(d[5]), "+f"(d[6]), "+f"(d[7]),
      "+f"(d[8]), "+f"(d[9]), "+f"(d[10]), "+f"(d[11]), "+f"(d[12]), "+f"(d[13]), "+f"(d[14]), "+f"(d[15]),
      "+f"(d[16]), "+f"(d[17]), "+f"(d[18]), "+f"(d[19]), "+f"(d[20]), "+f"(d[21]), "+f"(d[22]), "+f"(d[23]),
      "+f"(d[24]), "+f"(d[25]), "+f"(d[26]), "+f"(d[27]), "+f"(d[28]), "+f"(d[29]), "+f"(d[30]), "+f"(d[31])
    : "r"(da), "r"(db), "r"(sc), "n"(DESC_HI128));
}
__device__ __forceinline__ void wgmma_ss_n128(float (&d)[64], uint32_t da, uint32_t db, int sc) {
  asm volatile("{\n.reg .pred p;\n.reg .b64 da, db;\nsetp.ne.b32 p, %66, 0;\nmov.b64 da, {%64, %67};\nmov.b64 db, {%65, %67};\n"
    "wgmma.mma_async.sync.aligned.m64n128k16.f32.bf16.bf16 {%0, %1, %2, %3, %4, %5, %6, %7, %8, %9, %10, %11, %12, %13, %14, %15, %16, %17, %18, %19, %20, %21, %22, %23, %24, %25, %26, %27, %28, %29, %30, %31, %32, %33, %34, %35, %36, %37, %38, %39, %40, %41, %42, %43, %44, %45, %46, %47, %48, %49, %50, %51, %52, %53, %54, %55, %56, %57, %58, %59, %60, %61, %62, %63}, da, db, p, 1, 1, 0, 1;\n}\n"
    : "+f"(d[0]), "+f"(d[1]), "+f"(d[2]), "+f"(d[3]), "+f"(d[4]), "+f"(d[5]), "+f"(d[6]), "+f"(d[7]),
      "+f"(d[8]), "+f"(d[9]), "+f"(d[10]), "+f"(d[11]), "+f"(d[12]), "+f"(d[13]), "+f"(d[14]), "+f"(d[15]),
      "+f"(d[16]), "+f"(d[17]), "+f"(d[18]), "+f"(d[19]), "+f"(d[20]), "+f"(d[21]), "+f"(d[22]), "+f"(d[23]),
      "+f"(d[24]), "+f"(d[25]), "+f"(d[26]), "+f"(d[27]), "+f"(d[28]), "+f"(d[29]), "+f"(d[30]), "+f"(d[31]),
      "+f"(d[32]), "+f"(d[33]), "+f"(d[34]), "+f"(d[35]), "+f"(d[36]), "+f"(d[37]), "+f"(d[38]), "+f"(d[39]),
      "+f"(d[40]), "+f"(d[41]), "+f"(d[42]), "+f"(d[43]), "+f"(d[44]), "+f"(d[45]), "+f"(d[46]), "+f"(d[47]),
      "+f"(d[48]), "+f"(d[49]), "+f"(d[50]), "+f"(d[51]), "+f"(d[52]), "+f"(d[53]), "+f"(d[54]), "+f"(d[55]),
      "+f"(d[56]), "+f"(d[57]), "+f"(d[58]), "+f"(d[59]), "+f"(d[60]), "+f"(d[61]), "+f"(d[62]), "+f"(d[63])
    : "r"(da), "r"(db), "r"(sc), "n"(DESC_HI128));
}
__device__ __forceinline__ void wgmma_ss_n256(float (&d)[128], uint32_t da, uint32_t db, int sc) {
  asm volatile("{\n.reg .pred p;\n.reg .b64 da, db;\nsetp.ne.b32 p, %130, 0;\nmov.b64 da, {%128, %131};\nmov.b64 db, {%129, %131};\n"
    "wgmma.mma_async.sync.aligned.m64n256k16.f32.bf16.bf16 {%0, %1, %2, %3, %4, %5, %6, %7, %8, %9, %10, %11, %12, %13, %14, %15, %16, %17, %18, %19, %20, %21, %22, %23, %24, %25, %26, %27, %28, %29, %30, %31, %32, %33, %34, %35, %36, %37, %38, %39, %40, %41, %42, %43, %44, %45, %46, %47, %48, %49, %50, %51, %52, %53, %54, %55, %56, %57, %58, %59, %60, %61, %62, %63, %64, %65, %66, %67, %68, %69, %70, %71, %72, %73, %74, %75, %76, %77, %78, %79, %80, %81, %82, %83, %84, %85, %86, %87, %88, %89, %90, %91, %92, %93, %94, %95, %96, %97, %98, %99, %100, %101, %102, %103, %104, %105, %106, %107, %108, %109, %110, %111, %112, %113, %114, %115, %116, %117, %118, %119, %120, %121, %122, %123, %124, %125, %126, %127}, da, db, p, 1, 1, 0, 1;\n}\n"
    : "+f"(d[0]), "+f"(d[1]), "+f"(d[2]), "+f"(d[3]), "+f"(d[4]), "+f"(d[5]), "+f"(d[6]), "+f"(d[7]),
      "+f"(d[8]), "+f"(d[9]), "+f"(d[10]), "+f"(d[11]), "+f"(d[12]), "+f"(d[13]), "+f"(d[14]), "+f"(d[15]),
      "+f"(d[16]), "+f"(d[17]), "+f"(d[18]), "+f"(d[19]), "+f"(d[20]), "+f"(d[21]), "+f"(d[22]), "+f"(d[23]),
      "+f"(d[24]), "+f"(d[25]), "+f"(d[26]), "+f"(d[27]), "+f"(d[28]), "+f"(d[29]), "+f"(d[30]), "+f"(d[31]),
      "+f"(d[32]), "+f"(d[33]), "+f"(d[34]), "+f"(d[35]), "+f"(d[36]), "+f"(d[37]), "+f"(d[38]), "+f"(d[39]),
      "+f"(d[40]), "+f"(d[41]), "+f"(d[42]), "+f"(d[43]), "+f"(d[44]), "+f"(d[45]), "+f"(d[46]), "+f"(d[47]),
      "+f"(d[48]), "+f"(d[49]), "+f"(d[50]), "+f"(d[51]), "+f"(d[52]), "+f"(d[53]), "+f"(d[54]), "+f"(d[55]),
      "+f"(d[56]), "+f"(d[57]), "+f"(d[58]), "+f"(d[59]), "+f"(d[60]), "+f"(d[61]), "+f"(d[62]), "+f"(d[63]),
      "+f"(d[64]), "+f"(d[65]), "+f"(d[66]), "+f"(d[67]), "+f"(d[68]), "+f"(d[69]), "+f"(d[70]), "+f"(d[71]),
      "+f"(d[72]), "+f"(d[73]), "+f"(d[74]), "+f"(d[75]), "+f"(d[76]), "+f"(d[77]), "+f"(d[78]), "+f"(d[79]),
      "+f"(d[80]), "+f"(d[81]), "+f"(d[82]), "+f"(d[83]), "+f"(d[84]), "+f"(d[85]), "+f"(d[86]), "+f"(d[87]),
      "+f"(d[88]), "+f"(d[89]), "+f"(d[90]), "+f"(d[91]), "+f"(d[92]), "+f"(d[93]), "+f"(d[94]), "+f"(d[95]),
      "+f"(d[96]), "+f"(d[97]), "+f"(d[98]), "+f"(d[99]), "+f"(d[100]), "+f"(d[101]), "+f"(d[102]), "+f"(d[103]),
      "+f"(d[104]), "+f"(d[105]), "+f"(d[106]), "+f"(d[107]), "+f"(d[108]), "+f"(d[109]), "+f"(d[110]), "+f"(d[111]),
      "+f"(d[112]), "+f"(d[113]), "+f"(d[114]), "+f"(d[115]), "+f"(d[116]), "+f"(d[117]), "+f"(d[118]), "+f"(d[119]),
      "+f"(d[120]), "+f"(d[121]), "+f"(d[122]), "+f"(d[123]), "+f"(d[124]), "+f"(d[125]), "+f"(d[126]), "+f"(d[127])
    : "r"(da), "r"(db), "r"(sc), "n"(DESC_HI128));
}
template <uint32_t HI = DESC_HI128>
__device__ __forceinline__ void wgmma_rs_n64(float (&d)[32], const uint32_t (&a)[4], uint32_t db, int sc) {
  asm volatile("{\n.reg .pred p;\n.reg .b64 db;\nsetp.ne.b32 p, %37, 0;\nmov.b64 db, {%36, %38};\n"
    "wgmma.mma_async.sync.aligned.m64n64k16.f32.bf16.bf16 {%0, %1, %2, %3, %4, %5, %6, %7, %8, %9, %10, %11, %12, %13, %14, %15, %16, %17, %18, %19, %20, %21, %22, %23, %24, %25, %26, %27, %28, %29, %30, %31}, {%32, %33, %34, %35}, db, p, 1, 1, 1;\n}\n"
    : "+f"(d[0]), "+f"(d[1]), "+f"(d[2]), "+f"(d[3]), "+f"(d[4]), "+f"(d[5]), "+f"(d[6]), "+f"(d[7]),
      "+f"(d[8]), "+f"(d[9]), "+f"(d[10]), "+f"(d[11]), "+f"(d[12]), "+f"(d[13]), "+f"(d[14]), "+f"(d[15]),
      "+f"(d[16]), "+f"(d[17]), "+f"(d[18]), "+f"(d[19]), "+f"(d[20]), "+f"(d[21]), "+f"(d[22]), "+f"(d[23]),
      "+f"(d[24]), "+f"(d[25]), "+f"(d[26]), "+f"(d[27]), "+f"(d[28]), "+f"(d[29]), "+f"(d[30]), "+f"(d[31])
    : "r"(a[0]), "r"(a[1]), "r"(a[2]), "r"(a[3]), "r"(db), "r"(sc), "n"(HI));
}
template <uint32_t HI = DESC_HI128>
__device__ __forceinline__ void wgmma_rs_n128(float (&d)[64], const uint32_t (&a)[4], uint32_t db, int sc) {
  asm volatile("{\n.reg .pred p;\n.reg .b64 db;\nsetp.ne.b32 p, %69, 0;\nmov.b64 db, {%68, %70};\n"
    "wgmma.mma_async.sync.aligned.m64n128k16.f32.bf16.bf16 {%0, %1, %2, %3, %4, %5, %6, %7, %8, %9, %10, %11, %12, %13, %14, %15, %16, %17, %18, %19, %20, %21, %22, %23, %24, %25, %26, %27, %28, %29, %30, %31, %32, %33, %34, %35, %36, %37, %38, %39, %40, %41, %42, %43, %44, %45, %46, %47, %48, %49, %50, %51, %52, %53, %54, %55, %56, %57, %58, %59, %60, %61, %62, %63}, {%64, %65, %66, %67}, db, p, 1, 1, 1;\n}\n"
    : "+f"(d[0]), "+f"(d[1]), "+f"(d[2]), "+f"(d[3]), "+f"(d[4]), "+f"(d[5]), "+f"(d[6]), "+f"(d[7]),
      "+f"(d[8]), "+f"(d[9]), "+f"(d[10]), "+f"(d[11]), "+f"(d[12]), "+f"(d[13]), "+f"(d[14]), "+f"(d[15]),
      "+f"(d[16]), "+f"(d[17]), "+f"(d[18]), "+f"(d[19]), "+f"(d[20]), "+f"(d[21]), "+f"(d[22]), "+f"(d[23]),
      "+f"(d[24]), "+f"(d[25]), "+f"(d[26]), "+f"(d[27]), "+f"(d[28]), "+f"(d[29]), "+f"(d[30]), "+f"(d[31]),
      "+f"(d[32]), "+f"(d[33]), "+f"(d[34]), "+f"(d[35]), "+f"(d[36]), "+f"(d[37]), "+f"(d[38]), "+f"(d[39]),
      "+f"(d[40]), "+f"(d[41]), "+f"(d[42]), "+f"(d[43]), "+f"(d[44]), "+f"(d[45]), "+f"(d[46]), "+f"(d[47]),
      "+f"(d[48]), "+f"(d[49]), "+f"(d[50]), "+f"(d[51]), "+f"(d[52]), "+f"(d[53]), "+f"(d[54]), "+f"(d[55]),
      "+f"(d[56]), "+f"(d[57]), "+f"(d[58]), "+f"(d[59]), "+f"(d[60]), "+f"(d[61]), "+f"(d[62]), "+f"(d[63])
    : "r"(a[0]), "r"(a[1]), "r"(a[2]), "r"(a[3]), "r"(db), "r"(sc), "n"(HI));
}

template <int N> __device__ __forceinline__ void keep(float (&d)[N]) {
#pragma unroll
  for (int i = 0; i < N; i++) asm volatile("" : "+f"(d[i])::"memory");
}

__device__ __forceinline__ void keep(uint32_t (&d)[4]) { asm volatile("" : "+r"(d[0]), "+r"(d[1]), "+r"(d[2]), "+r"(d[3])::"memory"); }
template <int N> __device__ __forceinline__ void keep(uint32_t (&d)[N][4]) {
#pragma unroll
  for (int i = 0; i < N; i++) asm volatile("" : "+r"(d[i][0]), "+r"(d[i][1]), "+r"(d[i][2]), "+r"(d[i][3])::"memory");
}

__device__ __forceinline__ uint32_t pack2(float lo, float hi) {
  uint32_t r;
  asm("cvt.rn.bf16x2.f32 %0, %1, %2;" : "=r"(r) : "f"(hi), "f"(lo));
  return r;
}
__device__ __forceinline__ float bf_lo(uint32_t v) { return __uint_as_float(v << 16); }
__device__ __forceinline__ float bf_hi(uint32_t v) { return __uint_as_float(v & 0xffff0000u); }
__device__ __forceinline__ uint32_t hsub2(uint32_t a, uint32_t b) {
  uint32_t r;
  asm("sub.rn.bf16x2 %0, %1, %2;" : "=r"(r) : "r"(a), "r"(b));
  return r;
}
__device__ __forceinline__ uint32_t movm(uint32_t a) {
  uint32_t r;
  asm volatile("movmatrix.sync.aligned.m8n8.trans.b16 %0, %1;" : "=r"(r) : "r"(a));
  return r;
}
__device__ __forceinline__ void ldsm4(uint32_t (&v)[4], uint32_t a) {
  asm volatile("ldmatrix.sync.aligned.m8n8.x4.shared.b16 {%0,%1,%2,%3}, [%4];" : "=r"(v[0]), "=r"(v[1]), "=r"(v[2]), "=r"(v[3]) : "r"(a + own()) : "memory");
}
__device__ __forceinline__ void stsm4(uint32_t a, const uint32_t (&v)[4]) {
  asm volatile("stmatrix.sync.aligned.m8n8.x4.shared.b16 [%0], {%1,%2,%3,%4};" ::"r"(a + own()), "r"(v[0]), "r"(v[1]), "r"(v[2]), "r"(v[3]) : "memory");
}
__device__ __forceinline__ void mma16816(float (&d)[4], const uint32_t (&a)[4], uint32_t b0, uint32_t b1) {
  asm volatile("mma.sync.aligned.m16n8k16.row.col.f32.bf16.bf16.f32 {%0,%1,%2,%3}, {%4,%5,%6,%7}, {%8,%9}, {%10,%10,%10,%10};"
               : "=f"(d[0]), "=f"(d[1]), "=f"(d[2]), "=f"(d[3])
               : "r"(a[0]), "r"(a[1]), "r"(a[2]), "r"(a[3]), "r"(b0), "r"(b1), "f"(0.f));
}
__device__ __forceinline__ void mma1688_acc(float (&d)[4], uint32_t a0, uint32_t a1, uint32_t b0) {
  asm volatile("mma.sync.aligned.m16n8k8.row.col.f32.bf16.bf16.f32 {%0,%1,%2,%3}, {%4,%5}, {%6}, {%0,%1,%2,%3};"
               : "+f"(d[0]), "+f"(d[1]), "+f"(d[2]), "+f"(d[3]) : "r"(a0), "r"(a1), "r"(b0));
}
__device__ __forceinline__ float ex2(float x) { float y; asm("ex2.approx.ftz.f32 %0, %1;" : "=f"(y) : "f"(x)); return y; }
__device__ __forceinline__ float rcp(float x) { float y; asm("rcp.approx.ftz.f32 %0, %1;" : "=f"(y) : "f"(x)); return y; }
__device__ __forceinline__ float tanhf_hw(float x) { float y; asm("tanh.approx.f32 %0, %1;" : "=f"(y) : "f"(x)); return y; }
__device__ __forceinline__ uint32_t lds32(uint32_t a) { uint32_t v; asm volatile("ld.shared.u32 %0, [%1];" : "=r"(v) : "r"(a + own()) : "memory"); return v; }
__device__ __forceinline__ float2 lds64(uint32_t a) { float2 v; asm volatile("ld.shared.v2.f32 {%0,%1}, [%2];" : "=f"(v.x), "=f"(v.y) : "r"(a + own()) : "memory"); return v; }
__device__ __forceinline__ void lds128(uint32_t (&v)[4], uint32_t a) { asm volatile("ld.shared.v4.u32 {%0,%1,%2,%3}, [%4];" : "=r"(v[0]), "=r"(v[1]), "=r"(v[2]), "=r"(v[3]) : "r"(a + own()) : "memory"); }
__device__ __forceinline__ void sts128(uint32_t a, const uint32_t (&v)[4]) { asm volatile("st.shared.v4.u32 [%0], {%1,%2,%3,%4};" ::"r"(a + own()), "r"(v[0]), "r"(v[1]), "r"(v[2]), "r"(v[3]) : "memory"); }
__device__ __forceinline__ void ldg128_nc(uint32_t (&v)[4], const void* p) {
  asm volatile("ld.global.nc.L1::no_allocate.v4.u32 {%0,%1,%2,%3}, [%4];" : "=r"(v[0]), "=r"(v[1]), "=r"(v[2]), "=r"(v[3]) : "l"(p));
}
__device__ __forceinline__ uint32_t pin(uint32_t v, uint32_t zero) {
  asm volatile("{\n.reg .pred p;\n.reg .u32 c;\nmov.u32 c, %1;\nLP:\n.pragma \"nounroll\";\nsetp.eq.u32 p, c, 0;\n@p bra LD;\n"
               "nanosleep.u32 c;\nadd.u32 %0, %0, c;\nsub.u32 c, c, 1;\nbra LP;\nLD:\n}\n" : "+r"(v) : "r"(zero) : "memory");
  return v;
}
__device__ __forceinline__ void mbar_arrive_if(uint32_t b, bool cond) {
  asm volatile("{\n.reg .pred p;\nsetp.ne.u32 p, %1, 0;\n@p mbarrier.arrive.shared::cta.b64 _, [%0];\n}\n" ::"r"(b + own()), "r"((uint32_t)cond) : "memory");
}
__device__ __forceinline__ uint32_t ld_epoch(const unsigned* p) {
  uint32_t v;
  asm volatile("ld.relaxed.gpu.global.u32 %0, [%1];" : "=r"(v) : "l"(p) : "memory");
  return v;
}
__device__ __forceinline__ void ll_st(uint4* p, uint32_t a, uint32_t b, uint32_t c, uint32_t d, uint32_t tag) {
  asm volatile("st.relaxed.gpu.global.v4.b32 [%0], {%1, %2, %3, %4};" ::"l"(p), "r"((a & ~1u) | tag), "r"(b), "r"(c), "r"(d) : "memory");
}
__device__ __forceinline__ void ll_ld(uint32_t (&v)[4], const uint4* p) {
  asm volatile("{\n.reg .b128 t;\n.reg .b64 lo, hi;\nld.relaxed.gpu.global.b128 t, [%4];\nmov.b128 {lo, hi}, t;\n"
               "mov.b64 {%0, %1}, lo;\nmov.b64 {%2, %3}, hi;\n}\n"
               : "=r"(v[0]), "=r"(v[1]), "=r"(v[2]), "=r"(v[3]) : "l"(p) : "memory");
}
template <int N> __device__ __forceinline__ void ll_issue(uint32_t (&v)[N][4], const uint4* p, int stride) {
#pragma unroll
  for (int i = 0; i < N; i++) ll_ld(v[i], p + i * stride);
}
template <int N> __device__ __forceinline__ uint32_t ll_acc(const uint32_t (&v)[N][4], uint32_t tag, uint32_t acc = 0) {
#pragma unroll
  for (int i = 0; i < N; i++) asm("lop3.b32 %0, %1, %2, %0, 0xBE;" : "+r"(acc) : "r"(v[i][0]), "r"(tag));
  return acc;
}
__device__ __forceinline__ bool ll_any(uint32_t acc) { return __any_sync(0xffffffffu, acc & 1u); }
template <int N> __device__ __forceinline__ bool ll_bad(const uint32_t (&v)[N][4], uint32_t tag) { return ll_any(ll_acc<N>(v, tag)); }
template <int N> __device__ __forceinline__ void ll_clear(uint32_t (&v)[N][4]) {
#pragma unroll
  for (int i = 0; i < N; i++) v[i][0] &= ~1u;
}
template <int N> __device__ __forceinline__ void ll_spin(uint32_t (&v)[N][4], const uint4* p, int stride, uint32_t tag) {
  uint32_t it = 0;
#pragma unroll 1
  do { ll_issue<N>(v, p, stride); } while (ll_bad<N>(v, tag) && ++it < SPIN_LIMIT);
}
template <int N> __device__ __forceinline__ void ll_get(uint32_t (&v)[N][4], const uint4* p, int stride, uint32_t tag) {
  ll_spin<N>(v, p, stride, tag);
  ll_clear<N>(v);
}
template <int N> __device__ __forceinline__ void ll_wait(uint32_t (&v)[N][4], const uint4* p, int stride, uint32_t tag) {
  if (__builtin_expect(ll_bad<N>(v, tag), 0)) ll_spin<N>(v, p, stride, tag);
  ll_clear<N>(v);
}
__device__ __forceinline__ void unpack32(float (&d)[32], const uint32_t (&v)[4][4]) {
#pragma unroll
  for (int u = 0; u < 4; u++)
#pragma unroll
    for (int e = 0; e < 4; e++) { d[8 * u + 2 * e] = bf_lo(v[u][e]); d[8 * u + 2 * e + 1] = bf_hi(v[u][e]); }
}
__device__ __forceinline__ void pack32(uint32_t (&v)[4][4], const float (&d)[32]) {
#pragma unroll
  for (int u = 0; u < 4; u++)
#pragma unroll
    for (int e = 0; e < 4; e++) v[u][e] = pack2(d[8 * u + 2 * e], d[8 * u + 2 * e + 1]);
}
__device__ __forceinline__ uint32_t t_addr(int m) { return SB + ((0x01534620u >> (4 * m)) & 7u) * 32768u; }

__device__ __forceinline__ constexpr int w2_pass(int m) { return m < 4 ? m & 1 : m >> 1; }
__device__ __forceinline__ constexpr int w2_peer(int m) { return m < 4 ? m >> 1 : m & 1; }

__device__ __forceinline__ int kb_at(int i, int j) { return i == 0 ? j : (i - 1 + (i - 1 >= j ? 1 : 0)); }

__device__ __forceinline__ void init_bars(int set) {
  if (set >= 0 && elect_one()) {
    const uint32_t cnt = set < 5 ? 1 : 8;
#pragma unroll
    for (int i = 0; i < 8; i++) mbar_init(BAR + (24 + 8 * set + i) * 8, cnt);
    if (set == 9) {
#pragma unroll
      for (int i = 0; i < 9; i++) mbar_init(BAR + (B_EX + i) * 8, 4);
#pragma unroll
      for (int i = 0; i < 4; i++) mbar_init(BAR + (B_READY + i) * 8, i == 1 ? 7 : 3);
#pragma unroll
      for (int i = 0; i < 7; i++) mbar_init(BAR + (B_TAG + i) * 8, i < 1 ? 1 : 4);
    }
    asm volatile("fence.mbarrier_init.release.cluster;" ::: "memory");
  }
  __syncwarp();
  asm volatile("barrier.cluster.arrive.relaxed.aligned;" ::: "memory");
  asm volatile("bar.arrive 4, 384;" ::: "memory");
  asm volatile("bar.sync 3, 384;" ::: "memory");
}

__global__ void __launch_bounds__(384, 1) fused_block_kernel(Scratch* __restrict__ X, const __nv_bfloat16* __restrict__ xp,
                                                             const __nv_bfloat16* __restrict__ wqkvp, const __nv_bfloat16* __restrict__ wop, const uint32_t zero,
                                                             const __grid_constant__ Params P) {
  extern __shared__ __align__(1024) uint8_t smem_raw[];
  if (smem_u32(smem_raw) != SB + own()) return;
  const int tid = threadIdx.x;
  const int warp = __shfl_sync(0xffffffffu, tid >> 5, 0);
  const int lane = tid & 31;
  const int cta = blockIdx.x;
  const int j = ((cta >> 1) & 1) * 4 + ((cta >> 4) & 1) * 2 + (cta & 1);
  const int g = ((cta >> 2) & 3) * 4 + (cta >> 5);

  if (warp >= 8) {
    asm volatile("setmaxnreg.dec.sync.aligned.u32 56;");
    if (warp == 8) {
      PSTAMPW(2, 0);
      const bool leader = elect_one();
      if (leader) {
        prefetch_map(&P.x); prefetch_map(&P.wqkv);
#pragma unroll
        for (int i = 0; i < 24; i++) mbar_init(BAR + i * 8, 1);
        asm volatile("fence.mbarrier_init.release.cluster;" ::: "memory");
      }
      __syncwarp();
      asm volatile("bar.arrive 3, 384;" ::: "memory");
      asm volatile("barrier.cluster.arrive.relaxed.aligned;" ::: "memory");
      auto ldx = [&](int p, int kb) {
        const uint32_t b = BAR + (B_FX + p * 8 + kb) * 8;
        mbar_expect_tx(b, 8192);
        tma3d(H0 + p * 65536 + kb * 8192, &P.x, kb * 64, p, g * 64, b);
      };
      auto ldkv = [&](int kb, int slot) {
        const uint32_t b = BAR + (B_FKV + kb) * 8, d = RING + slot * 16384;
        mbar_expect_tx(b, 16384);
        tma2d(d, &P.wqkv, 512 + 64 * j, kb * 64, b);
        tma2d(d + 8192, &P.wqkv, 1024 + 64 * j, kb * 64, b);
      };
      if (leader) {
#pragma unroll 1
        for (int i = 0; i < 8 + XO_DELAY; i++) {
          if (i < 8) ldx(0, i);
          if (i < 6) ldkv(i, i);
          if (i >= XO_DELAY) ldx(1, i - XO_DELAY);
        }
        PSTAMPW(2, 2);
      }
      __syncwarp();
      asm volatile("bar.sync 4, 384;" ::: "memory");
      if (leader) {
        const int f0 = 224 * j + ((j & 1) ? 32 : 0);
        const int fh = 224 * j + ((j & 1) ? 0 : 192);
        prefetch_map(&P.wo); prefetch_map(&P.w1); prefetch_map(&P.w3); prefetch_map(&P.w1h);
        prefetch_map(&P.w3h); prefetch_map(&P.w2); prefetch_map(&P.out);
#pragma unroll 1
        for (int i = 0; i < 2; i++) { mbar_wait(BAR + (B_EKV + i) * 8); ldkv(6 + i, i); }
#pragma unroll 1
        for (int i = 0; i < 8; i++) {
          const uint32_t b = BAR + (B_FQ + i) * 8;
          mbar_wait(BAR + (B_EKV + 2 + (i >> 1)) * 8);
          mbar_expect_tx(b, 8192);
          tma2d(RING + (4 + i) * 8192, &P.wqkv, 64 * j, i * 64, b);
        }
        mbar_expect_tx(BAR + B_FWO * 8, 65536);
#pragma unroll 1
        for (int i = 0; i < 8; i++) {
          const int kb = (i + 1) & 7;
          mbar_wait(BAR + (B_EX + i) * 8);
          tma2d(H0 + kb * 8192, &P.wo, 64 * j, kb * 64, BAR + B_FWO * 8);
        }
#pragma unroll 1
        for (int i = 0; i < 8; i++) {
          const uint32_t b = BAR + (B_FA + i) * 8, d = RING + (i & 3) * 24576;
          const int k0 = kb_at(i, j) * 64;
          mbar_wait(BAR + (B_EKV + 7 + ((0xCBA98520u >> (4 * i)) & 15)) * 8);
          mbar_expect_tx(b, 24576);
          tma2d(d, &P.w1, f0, k0, b);
          tma2d(d + 8192, &P.w3, f0, k0, b);
          tma2d(d + 16384, &P.w1h, fh, k0, b);
          tma2d(d + 20480, &P.w3h, fh, k0, b);
        }
        uint32_t d = RING;
#pragma unroll 1
        for (int i = 0; i < 8; i++) {
          const uint32_t b = BAR + (B_FB + i) * 8;
          const int k0 = kb_at(i, j) * 64;
          mbar_wait(BAR + (B_EA + 5 + i) * 8);
          mbar_expect_tx(b, 32768);
          tma2d(d, &P.w1, f0 + 64, k0, b);
          tma2d(d + 8192, &P.w3, f0 + 64, k0, b);
          tma2d(d + 16384, &P.w1, f0 + 128, k0, b);
          tma2d(d + 24576, &P.w3, f0 + 128, k0, b);
          d = d == RING + 65536 ? RING : d + 32768;
        }
#pragma unroll 1
        for (int i = 0; i < 8; i++) {
          const int m = (0x76453210u >> (4 * i)) & 7;
          const uint32_t b = BAR + (B_FT + m) * 8;
          mbar_wait(BAR + (i < 5 ? B_EB + 3 + i : i < 7 ? B_HC - 5 + i : B_ET0) * 8);
          mbar_expect_tx(b, 28672);
          tma2d(t_addr(m), &P.w2, 64 * ((j + 2 + 2 * w2_pass(m)) & 7), 224 * (j ^ w2_peer(m)), b);
          PSTAMPW(2, 4 + i);
        }
#pragma unroll 1
        for (int q = 0; q < 2; q++) {
          mbar_expect_tx(BAR + (B_FIN + q) * 8, 16384);
          mbar_wait(BAR + (B_ET0 + 3 - q) * 8);
          PSTAMPW(2, 24 + q);
          asm volatile("cp.async.bulk.shared::cluster.global.mbarrier::complete_tx::bytes [%0], [%1], 16384, [%2];"
                       ::"r"(t_addr(q + 1) + own()), "l"(X->e4 + ((g * 8 + j) * 3 + q) * 1024), "r"(BAR + (B_FIN + q) * 8 + own()) : "memory");
        }
        X->epoch[cta] = X->epoch[cta] + 1;
      }
    } else {
      const int part = warp - 9;
      uint32_t tag;
      if (part == 2) {
        tag = ld_epoch(X->epoch + cta);
        init_bars(-1);
        tag = (tag + 1) & 1;
        if (lane == 0) {
          asm volatile("st.shared.u32 [%0], %1;" ::"r"(TAGS + own()), "r"(tag) : "memory");
          mbar_arrive(BAR + B_TAG * 8);
        }
      } else {
        init_bars(warp - 1);
        mbar_wait(BAR + B_TAG * 8);
        tag = lds32(TAGS);
      }
      PSTAMPW(3, 16 + part);
      const int xw0 = g * 8;
      auto clear8 = [&](uint4* p, int stride) {
#pragma unroll
        for (int i = 0; i < 8; i++) ll_st(p + i * stride + lane, 0, 0, 0, 0, tag ^ 1);
      };
      auto clear_front = [&]() {
#pragma unroll 1
      for (int u = part; u < 8; u += 3) clear8((u < 4 ? X->e2 : X->e3h) + (xw0 * 32 + 4 * j + (u & 3)) * 32, 1024);
      if (part == 2) {
        clear8(X->e1 + (g * 8 + j) * 256, 32);
#pragma unroll
        for (int i = 0; i < 4; i++)
          ll_st((i < 2 ? X->e2s : X->e3s) + ((xw0 + (i & 1) * 4 + (lane >> 3)) * 8 + j) * 8 + (lane & 7), 0, 0, 0, 0, tag ^ 1);
      }
      };
      if (CLR_MODE == 1) clear_front();
      PSTAMPW(3, 20 + part);
      uint32_t v[8][4];
      if (part < 2) {
        float s[4] = {0.f, 0.f, 0.f, 0.f}, q[4] = {0.f, 0.f, 0.f, 0.f}, piv = 0.f;
        const uint32_t xa = H0 + part * 65536 + (8 * j + (lane >> 2)) * 128 + (lane & 3) * 16 + (lane & 4) * 16;
#pragma unroll 1
        for (int kb = 0; kb < 8; kb++) {
          mbar_wait(BAR + (B_FX + part * 8 + kb) * 8);
          lds128(v[0], xa + kb * 8192); lds128(v[1], (xa + kb * 8192) ^ 64);
          if (kb == 0) piv = __shfl_sync(0xffffffffu, bf_lo(v[0][0]), lane & 28);
#pragma unroll
          for (int e = 0; e < 8; e++) {
            const float a = bf_lo(v[e >> 2][e & 3]) - piv, b = bf_hi(v[e >> 2][e & 3]) - piv;
            s[e & 3] += a + b; q[e & 3] = fmaf(a, a, q[e & 3]); q[e & 3] = fmaf(b, b, q[e & 3]);
          }
        }
        float ss = (s[0] + s[1]) + (s[2] + s[3]), qq = (q[0] + q[1]) + (q[2] + q[3]);
#pragma unroll
        for (int o = 1; o <= 2; o <<= 1) { ss += __shfl_xor_sync(0xffffffffu, ss, o); qq += __shfl_xor_sync(0xffffffffu, qq, o); }
        const float dm = ss * (1.f / D_);
        const float rs = rsqrtf(fmaxf(fmaf(-dm, dm, qq * (1.f / D_)), 0.f) + 1e-5f);
        if ((lane & 3) == 0) ll_st(X->e0s + g * 128 + 2 * (8 * j + (lane >> 2)) + part, __float_as_uint(piv + dm), __float_as_uint(rs), 0, 0, tag);
      } else {
        mbar_wait(BAR + (B_FKV + SIDE_KB) * 8);
        const __nv_bfloat16* wr = wop + (size_t)(j * 64 + g * 4 + (lane >> 3)) * D_ + (lane & 7) * 8;
#pragma unroll
        for (int i = 0; i < 8; i++) ldg128_nc(v[i], wr + i * 64);
        float s[4];
#pragma unroll
        for (int e = 0; e < 4; e++) {
          s[e] = 0.f;
#pragma unroll
          for (int i = 0; i < 8; i++) s[e] += bf_lo(v[i][e]) + bf_hi(v[i][e]);
        }
        float ss = (s[0] + s[1]) + (s[2] + s[3]);
#pragma unroll
        for (int o = 1; o <= 4; o <<= 1) ss += __shfl_xor_sync(0xffffffffu, ss, o);
        if ((lane & 7) == 0) ll_st(X->e0w + j * 64 + g * 4 + (lane >> 3), __float_as_uint(ss * (1.f / D_)), 0, 0, 0, tag);
      }
      __syncwarp();
      if (lane == 0) mbar_arrive(BAR + B_PUB * 8);
      PSTAMPW(3, part * 4 + 2);
      mbar_wait(BAR + B_PUB * 8);
      PSTAMPW(3, part * 4 + 0);
      {
        uint32_t u[2][4];
        const uint4* us = (part == 2 ? X->e0w + j * 64 : X->e0s + g * 128 + part * 64) + lane;
        const uint4* vs = X->e0c + ((j * 3 + part) * 16 + (lane >> 4) * 8) * 16 + (lane & 15);
        uint32_t it = 0;
#pragma unroll 1
        do { ll_issue<2>(u, us, 32); ll_issue<8>(v, vs, 16); } while (ll_any(ll_acc<8>(v, tag, ll_acc<2>(u, tag))) && ++it < SPIN_LIMIT);
        ll_clear<2>(u); ll_clear<8>(v);
#pragma unroll
        for (int i = 0; i < 2; i++) {
          if (part == 2) asm volatile("st.shared.u32 [%0], %1;" ::"r"(WB + own() + (i * 32 + lane) * 4), "r"(u[i][0]) : "memory");
          else asm volatile("st.shared.v2.u32 [%0], {%1,%2};" ::"r"(ST + own() + (part * 64 + i * 32 + lane) * 8), "r"(u[i][0]), "r"(u[i][1]) : "memory");
        }
      }
      uint32_t o[4];
#pragma unroll
      for (int e = 0; e < 4; e++) {
        float s = 0.f;
#pragma unroll
        for (int i = 0; i < 8; i++) s += __uint_as_float(v[i][e]);
        o[e] = __float_as_uint(s + __shfl_xor_sync(0xffffffffu, s, 16));
      }
      if (lane < 16) sts128(CS + (part * 64 + lane * 4) * 4, o);
      __syncwarp();
      if (lane == 0) mbar_arrive(BAR + B_READY * 8);
      PSTAMPW(3, part * 4 + 1);
      if (CLR_MODE == 2) clear_front();
      __syncwarp();
      if (lane == 0) mbar_arrive(BAR + B_CLR0 * 8);
      PSTAMPW(3, 24 + part);
      if (lane == 0) l2_prefetch(part == 0 ? P.w1p + (size_t)cta * 4 * F_ : part == 1 ? P.w3p + (size_t)cta * 4 * F_ : P.w2p + (size_t)cta * 14 * D_, 14336);
      mbar_wait(BAR + (E4_WHEN) * 8);
#pragma unroll 1
      for (int u = 0; u < 4 * E4_ON; u++) {
        clear8(X->e4 + ((g * 8 + ((j + 2 + 2 * part) & 7)) * 3 + part) * 1024 + u * 32, 128);
        __nanosleep(CLR_SLEEP);
      }
      __syncwarp();
      if (lane == 0) mbar_arrive(BAR + B_CLR * 8);
      PSTAMPW(3, part * 4 + 3);
    }
  } else {
    const int p = warp >> 2, w = warp & 3;
    const int r = lane >> 2, c = lane & 3;
    init_bars(warp);
    asm volatile("setmaxnreg.inc.sync.aligned.u32 224;");
    PSTAMP(0);
    const uint32_t dAx = descA(H0) + p * 4096;
    const uint32_t Hn = H1 - p * 65536;
    const uint32_t moff = ((lane & 7) + ((lane >> 3) & 1) * 8) * 128 + (((lane >> 4) ^ (lane & 7)) << 4);
    const uint32_t Xw = H0 + p * 65536 + w * 2048;
    const int xw = (g * 2 + p) * 4 + w;
    if (p == 1) {
      uint32_t v[8][4];
      mbar_wait(BAR + (B_FKV + SIDE_KB) * 8);
      const int wp = w < 3 ? w : 0;
      const __nv_bfloat16* wr = wqkvp + (size_t)(g * 32 + (lane >> 3) * 8) * (3 * D_) + wp * D_ + j * 64 + (lane & 7) * 8;
#pragma unroll
      for (int i = 0; i < 8; i++) ldg128_nc(v[i], wr + (size_t)i * 3 * D_);
      mbar_wait(BAR + B_TAG * 8);
      const uint32_t tg = lds32(TAGS);
      float cs[8];
#pragma unroll
      for (int e = 0; e < 4; e++) {
        float a = 0.f, b = 0.f;
#pragma unroll
        for (int i = 0; i < 8; i++) { a += bf_lo(v[i][e]); b += bf_hi(v[i][e]); }
        cs[2 * e] = a; cs[2 * e + 1] = b;
      }
      const bool up = lane & 8;
#pragma unroll
      for (int e = 0; e < 4; e++) {
        const float keepv = up ? cs[4 + e] : cs[e], give = up ? cs[e] : cs[4 + e];
        cs[e] = keepv + __shfl_xor_sync(0xffffffffu, give, 8);
        cs[e] += __shfl_xor_sync(0xffffffffu, cs[e], 16);
      }
      if (lane < 16 && w < 3)
        ll_st(X->e0c + ((j * 3 + w) * 16 + g) * 16 + (lane & 7) * 2 + (lane >> 3), __float_as_uint(cs[0]), __float_as_uint(cs[1]),
              __float_as_uint(cs[2]), __float_as_uint(cs[3]), tg);
      __syncwarp();
      mbar_arrive_if(BAR + B_PUB * 8, lane == 0);
      PSTAMP(1);
      mbar_wait(BAR + B_LAG * 8);
    }

    float akv[64];
#pragma unroll 1
    for (int kb = 0; kb < 8; kb++) {
      mbar_wait(BAR + (B_FX + p * 8 + kb) * 8);
      mbar_wait(BAR + (B_FKV + kb) * 8);
      if (kb == 0) PSTAMP(2);
      const uint32_t da = dAx + kb * 512, db = descB(RING) + (kb < 6 ? kb : kb - 6) * 1024;
      wg_fence();
      wgmma_ss_n128(akv, da, db, kb);
#pragma unroll
      for (int k = 1; k < 4; k++) wgmma_ss_n128(akv, da + k * 2, db + k * 128, 1);
      wg_commit();
      mbar_arrive_if(BAR + B_LAG * 8, kb == LAG_KB - 1 && p == 0 && lane == 0);
      wg_wait<1>();
      mbar_arrive_if(BAR + (B_EKV + kb - 1) * 8, kb > 0 && lane == 0);
    }
    asm volatile("barrier.cluster.wait.aligned;" ::: "memory");
    uint32_t xres[4][4];
#pragma unroll
    for (int u = 0; u < 4; u++) ldsm4(xres[u], Xw + j * 8192 + (moff ^ (u << 5)));

    float aq[32];
    auto qstep = [&](int kb) {
      mbar_wait(BAR + (B_FQ + kb) * 8);
      const uint32_t da = dAx + kb * 512, db = descB(RING + 32768) + kb * 512;
      wg_fence();
      wgmma_ss_n64(aq, da, db, kb);
#pragma unroll
      for (int k = 1; k < 4; k++) wgmma_ss_n64(aq, da + k * 2, db + k * 128, 1);
      wg_commit();
      wg_wait<1>();
      mbar_arrive_if(BAR + (B_EQ + kb - 1) * 8, lane == 0);
      mbar_arrive_if(BAR + (B_EX + kb - 2) * 8, lane == 0 && p == 0 && kb >= 2);
    };
    qstep(0);
    keep(akv);
    PSTAMP(3);
    qstep(1);
    mbar_wait(BAR + B_READY * 8);
    PSTAMP(19);
    const uint32_t tag = lds32(TAGS);
    uint4* const xb = reinterpret_cast<uint4*>(X) + lane + (tag >> 1);
    constexpr int O_E4 = offsetof(Scratch, e4) / 16, O_E2 = offsetof(Scratch, e2) / 16, O_E3H = offsetof(Scratch, e3h) / 16;
    const float2 st0 = lds64(ST + (2 * (16 * w + r) + p) * 8);
    const float2 st1 = lds64(ST + (2 * (16 * w + r + 8) + p) * 8);
    uint32_t hi[4][4], lo[4][4];
    {
      float2 cs[16];
      auto cvt = [&](uint32_t (&d)[4][4], int b0, int ofs, const float2& st) {
#pragma unroll
        for (int b = b0; b < b0 + 8; b++) {
          if (ofs == 2) cs[b] = lds64(CS + (64 + b * 8 + 2 * c) * 4);
          const uint32_t v = pack2(fmaf(-st.x, cs[b].x, akv[4 * b + ofs]) * st.y, fmaf(-st.x, cs[b].y, akv[4 * b + ofs + 1]) * st.y);
          d[b >> 2][b & 3] = b < 8 ? v : movm(v);
        }
      };
      cvt(hi, 0, 2, st1);
      keep(hi[0]); keep(hi[1]);
      qstep(2);
      cvt(hi, 8, 2, st1);
      mbar_wait(BAR + B_CLR0 * 8);
      if (w == 3 && g < 15) {
        uint4* dst = X->e1 + ((g * 8 + j) * 2 + p) * 128 + lane;
#pragma unroll
        for (int i = 0; i < 4; i++) ll_st(dst + i * 32, hi[i][0], hi[i][1], hi[i][2], hi[i][3], tag);
      }
      PSTAMP(20);
      wg_bar(p);
#pragma unroll
      for (int i = 0; i < 4; i++) sts128(Xw + lane * 16 + i * 512, hi[i]);
      qstep(3);
      cvt(lo, 0, 0, st0);
      keep(lo[0]); keep(lo[1]);
      qstep(4);
      cvt(lo, 8, 0, st0);
    }
    PSTAMP(21);
    wg_bar(p);
    uint32_t prev[4][4];
    if (w > 0) {
#pragma unroll
      for (int i = 0; i < 4; i++) lds128(prev[i], Xw - 2048 + lane * 16 + i * 512);
    }
    if (p == 0) {
      asm volatile("fence.proxy.async.shared::cta;" ::: "memory");
      __syncwarp();
      if (lane == 0) mbar_arrive(BAR + (B_EX + 7) * 8);
    }
    PSTAMP(22);
    const uint4* halo = X->e1 + (((g - 1) * 8 + j) * 2 + p) * 128 + lane;
    const bool use_halo = w == 0 && g > 0;
    qstep(5);
    if (use_halo) ll_issue<4>(prev, halo, 32);
    qstep(6);
    qstep(7);
    PSTAMP(23);
    if (w == 0) {
      if (g > 0) {
        if (__builtin_expect(ll_bad<4>(prev, pin(tag, zero)), 0)) ll_spin<4>(prev, halo, 32, tag);
        ll_clear<4>(prev);
      } else {
#pragma unroll
        for (int i = 0; i < 4; i++)
#pragma unroll
          for (int e = 0; e < 4; e++) prev[i][e] = 0;
      }
    }
    wg_wait<0>();
    keep(aq);
    mbar_arrive_if(BAR + (B_EQ + 7) * 8, lane == 0);
    mbar_arrive_if(BAR + (B_EX + 6) * 8, lane == 0 && p == 0);
    PSTAMP(4);

    uint32_t of[4][4];
    {
      const float sc = 0.25f * 1.4426950408889634f;
      const float nohalo = (g == 0 && w == 0) ? -INFINITY : 0.f;
      const bool up0 = 2 * c > r, up1 = 2 * c + 1 > r;
      const uint32_t mup = (up0 ? 0xffffu : 0u) | (up1 ? 0xffff0000u : 0u);
      uint4* dst = xb + O_E2 + (xw * 32 + 4 * j) * 32;
      float d0 = 0.f, d1 = 0.f;
#pragma unroll 1
      for (int hp = 0; hp < 2; hp++) {
#pragma unroll
        for (int e = 0; e < 4; e++) { of[0][e] = of[2][e]; of[1][e] = of[3][e]; }
#pragma unroll
        for (int h = 0; h < 2; h++) {
          uint32_t qf[4];
          const uint32_t co = (32 * hp + 16 * h + 2 * c) * 4;
          {
            const float2 ca = lds64(CS + co), cb = lds64(CS + co + 32);
            qf[0] = pack2(fmaf(-st0.x, ca.x, aq[8 * h + 0]) * st0.y, fmaf(-st0.x, ca.y, aq[8 * h + 1]) * st0.y);
            qf[1] = pack2(fmaf(-st1.x, ca.x, aq[8 * h + 2]) * st1.y, fmaf(-st1.x, ca.y, aq[8 * h + 3]) * st1.y);
            qf[2] = pack2(fmaf(-st0.x, cb.x, aq[8 * h + 4]) * st0.y, fmaf(-st0.x, cb.y, aq[8 * h + 5]) * st0.y);
            qf[3] = pack2(fmaf(-st1.x, cb.x, aq[8 * h + 6]) * st1.y, fmaf(-st1.x, cb.y, aq[8 * h + 7]) * st1.y);
          }
          const int e0 = 2 * h;
          float sp[4], sl[4], sh[4];
          mma16816(sp, qf, prev[0][e0], prev[0][e0 + 1]);
          mma16816(sl, qf, lo[0][e0], lo[0][e0 + 1]);
          mma16816(sh, qf, hi[0][e0], hi[0][e0 + 1]);
          float a0 = up0 ? sp[0] + nohalo : sl[0], a1 = up1 ? sp[1] + nohalo : sl[1];
          float b0 = up0 ? sl[2] : sh[2], b1 = up1 ? sl[3] : sh[3];
          float ma = fmaxf(a0, a1), mb = fmaxf(b0, b1);
          ma = fmaxf(ma, __shfl_xor_sync(0xffffffffu, ma, 1)); mb = fmaxf(mb, __shfl_xor_sync(0xffffffffu, mb, 1));
          ma = fmaxf(ma, __shfl_xor_sync(0xffffffffu, ma, 2)); mb = fmaxf(mb, __shfl_xor_sync(0xffffffffu, mb, 2));
          a0 = ex2((a0 - ma) * sc); a1 = ex2((a1 - ma) * sc); b0 = ex2((b0 - mb) * sc); b1 = ex2((b1 - mb) * sc);
          float sa = a0 + a1, sbb = b0 + b1;
          sa += __shfl_xor_sync(0xffffffffu, sa, 1); sbb += __shfl_xor_sync(0xffffffffu, sbb, 1);
          sa += __shfl_xor_sync(0xffffffffu, sa, 2); sbb += __shfl_xor_sync(0xffffffffu, sbb, 2);
          const float ia = rcp(sa), ib = rcp(sbb);
          const uint32_t pa = pack2(a0 * ia, a1 * ia), pb = pack2(b0 * ib, b1 * ib);
          const uint32_t pf[4] = {pa & mup, 0u, pa & ~mup, pb & mup};
          const uint32_t ph = pb & ~mup;
          float o0[4], o1[4];
          mma16816(o0, pf, prev[2][e0], lo[2][e0]);
          mma16816(o1, pf, prev[2][e0 + 1], lo[2][e0 + 1]);
          mma1688_acc(o0, 0u, ph, hi[2][e0]);
          mma1688_acc(o1, 0u, ph, hi[2][e0 + 1]);
          of[2 + h][0] = pack2(o0[0], o0[1]); of[2 + h][1] = pack2(o0[2], o0[3]);
          of[2 + h][2] = pack2(o1[0], o1[1]); of[2 + h][3] = pack2(o1[2], o1[3]);
          ll_st(dst + (2 * hp + h) * 32, of[2 + h][0], of[2 + h][1], of[2 + h][2], of[2 + h][3], tag);
          const float2 wa = lds64(WB + co), wb = lds64(WB + co + 32);
          d0 = fmaf(o0[0], wa.x, d0); d0 = fmaf(o0[1], wa.y, d0); d0 = fmaf(o1[0], wb.x, d0); d0 = fmaf(o1[1], wb.y, d0);
          d1 = fmaf(o0[2], wa.x, d1); d1 = fmaf(o0[3], wa.y, d1); d1 = fmaf(o1[2], wb.x, d1); d1 = fmaf(o1[3], wb.y, d1);
        }
#pragma unroll
        for (int e = 0; e < 16; e++) aq[e] = aq[16 + e];
#pragma unroll
        for (int e = 0; e < 4; e++) {
          prev[0][e] = prev[1][e]; prev[2][e] = prev[3][e];
          lo[0][e] = lo[1][e]; lo[2][e] = lo[3][e];
          hi[0][e] = hi[1][e]; hi[2][e] = hi[3][e];
        }
      }
#pragma unroll
      for (int o = 1; o <= 2; o <<= 1) { d0 += __shfl_xor_sync(0xffffffffu, d0, o); d1 += __shfl_xor_sync(0xffffffffu, d1, o); }
      if (c == 0) ll_st(X->e2s + (xw * 8 + j) * 8 + r, __float_as_uint(d0), __float_as_uint(d1), 0, 0, tag);
    }
    PSTAMP(5);

    float ah[32];
    uint32_t sv[2][4];
    unpack32(ah, xres);
    {
      uint32_t og[2][14][4];
      const uint4* osrc[7];
#pragma unroll
      for (int i = 0; i < 7; i++) osrc[i] = xb + O_E2 + (xw * 32 + 4 * kb_at(i + 1, j)) * 32;
      const uint4* ssrc = X->e2s + (xw * 8 + 2 * c) * 8 + r;
      auto oissue = [&](int hp) {
#pragma unroll
        for (int i = 0; i < 14; i++) ll_ld(og[hp][i], osrc[i >> 1] + (2 * hp + (i & 1)) * 32);
        if (hp == 1) ll_issue<2>(sv, ssrc, 8);
      };
      auto omma = [&](int hp) {
        ll_clear<14>(og[hp]);
        keep(og[hp]);
        wg_fence();
#pragma unroll
        for (int i = 0; i < 14; i++) wgmma_rs_n64(ah, og[hp][i], descB(H0) + kb_at((i >> 1) + 1, j) * 512 + (2 * hp + (i & 1)) * 128, 1);
        wg_commit();
      };
      mbar_wait(BAR + B_FWO * 8);
      keep(ah); keep(of);
      wg_fence();
#pragma unroll
      for (int k = 0; k < 4; k++) wgmma_rs_n64(ah, of[k], descB(H0) + j * 512 + k * 128, 1);
      wg_commit();
      uint32_t it = 0;
#pragma unroll 1
      do { oissue(0); } while (ll_bad<14>(og[0], tag) && ++it < SPIN_LIMIT);
      PSTAMP(6);
      oissue(1);
      omma(0);
      const uint32_t tg = pin(tag, zero);
      if (__builtin_expect(ll_any(ll_acc<14>(og[1], tg, ll_acc<2>(sv, tg))), 0)) {
#pragma unroll 1
        do { oissue(1); } while (ll_any(ll_acc<14>(og[1], tag, ll_acc<2>(sv, tag))) && ++it < SPIN_LIMIT);
      }
      PSTAMP(16);
      omma(1);
      ll_clear<2>(sv);
    }
    float m0 = __uint_as_float(sv[0][0]) + __uint_as_float(sv[1][0]), m1 = __uint_as_float(sv[0][1]) + __uint_as_float(sv[1][1]);
#pragma unroll
    for (int o = 1; o <= 2; o <<= 1) { m0 += __shfl_xor_sync(0xffffffffu, m0, o); m1 += __shfl_xor_sync(0xffffffffu, m1, o); }
    const uint32_t mu0 = pack2(m0 + st0.x, m0 + st0.x), mu1 = pack2(m1 + st1.x, m1 + st1.x);
    wg_wait<0>();
    keep(ah);
    if (lane == 0) mbar_arrive(BAR + B_WODONE * 8);
    PSTAMP(7);

    uint32_t hf[4][4], ra[4][4];
    pack32(hf, ah);
    {
      uint4* dst = xb + O_E3H + (xw * 32 + 4 * j) * 32;
#pragma unroll
      for (int u = 0; u < 4; u++) {
        ra[u][0] = hsub2(hf[u][0], mu0); ra[u][1] = hsub2(hf[u][1], mu1);
        ra[u][2] = hsub2(hf[u][2], mu0); ra[u][3] = hsub2(hf[u][3], mu1);
        ll_st(dst + u * 32, ra[u][0], ra[u][1], ra[u][2], ra[u][3], tag);
      }
      float s0 = 0.f, q0 = 0.f, s1 = 0.f, q1 = 0.f;
#pragma unroll
      for (int b = 0; b < 8; b++) {
        s0 += ah[4 * b] + ah[4 * b + 1]; s1 += ah[4 * b + 2] + ah[4 * b + 3];
        q0 = fmaf(ah[4 * b], ah[4 * b], q0); q0 = fmaf(ah[4 * b + 1], ah[4 * b + 1], q0);
        q1 = fmaf(ah[4 * b + 2], ah[4 * b + 2], q1); q1 = fmaf(ah[4 * b + 3], ah[4 * b + 3], q1);
      }
#pragma unroll
      for (int o = 1; o <= 2; o <<= 1) {
        s0 += __shfl_xor_sync(0xffffffffu, s0, o); q0 += __shfl_xor_sync(0xffffffffu, q0, o);
        s1 += __shfl_xor_sync(0xffffffffu, s1, o); q1 += __shfl_xor_sync(0xffffffffu, q1, o);
      }
      if (c == 0) ll_st(X->e3s + (xw * 8 + j) * 8 + r, __float_as_uint(s0), __float_as_uint(q0), __float_as_uint(s1), __float_as_uint(q1), tag);
      mbar_wait(BAR + (p == 0 ? B_EQ + 7 : B_WODONE) * 8);
    }
    PSTAMP(8);

    float rs0, rs1;
    auto swiglu = [&](float g0, float g1, float u0, float u1, float rs) -> uint32_t {
      const float hr = 0.5f * rs;
      const float x0 = g0 * hr, x1 = g1 * hr;
      const float t0 = tanhf_hw(x0), t1 = tanhf_hw(x1);
      return pack2(fmaf(x0, t0, x0) * (u0 * rs), fmaf(x1, t1, x1) * (u1 * rs));
    };
    uint32_t hA[6][4];
    {
      float a1[64], a2[32];
      const uint4* src = xb + O_E3H + xw * 32 * 32;
      uint32_t rb[4][4], rc[4][4], rd[4][4];
      auto fetch = [&](uint32_t (&a)[4][4], int i) { ll_issue<4>(a, src + kb_at(i, j) * 128, 32); };
      auto check = [&](uint32_t (&a)[4][4], uint32_t (&b)[4][4], int i) {
        const uint32_t tg = pin(tag, zero);
        if (__builtin_expect(ll_any(ll_acc<4>(a, tg, ll_acc<4>(b, tg))), 0)) {
          uint32_t it = 0;
#pragma unroll 1
          do { fetch(a, i); fetch(b, i + 1); } while (ll_any(ll_acc<4>(a, tag, ll_acc<4>(b, tag))) && ++it < SPIN_LIMIT);
        }
        ll_clear<4>(a); ll_clear<4>(b);
        keep(a); keep(b);
      };
      auto head = [&](uint32_t (&a)[4][4], int i) {
        mbar_wait(BAR + (B_FA + i) * 8);
        wg_fence();
        wgmma_rs_n64<DESC_HI64>(a2, a[0], descBh(RING + 16384) + (i & 3) * 1536, i);
        wgmma_rs_n128(a1, a[0], descB(RING) + (i & 3) * 1536, i);
        wg_commit();
#pragma unroll
        for (int u = 0; u < 4; u++) stsm4(Hn + w * 2048 + i * 8192 + (moff ^ (u << 5)), a[u]);
        wg_wait<1>();
        if (i > 0) mbar_arrive_if(BAR + (B_EA + i - 1) * 8, lane == 0);
      };
      auto rest = [&](uint32_t (&a)[4][4], int i) {
        wg_fence();
#pragma unroll
        for (int k = 1; k < 4; k++) {
          wgmma_rs_n64<DESC_HI64>(a2, a[k], descBh(RING + 16384) + (i & 3) * 1536 + k * 64, 1);
          wgmma_rs_n128(a1, a[k], descB(RING) + (i & 3) * 1536 + k * 128, 1);
        }
        wg_commit();
      };
      ll_clear<4>(ra);
      keep(ra);
      head(ra, 0); rest(ra, 0);
      ll_get<4>(rb, src + kb_at(1, j) * 128, 32, tag);
      keep(rb);
      PSTAMP(17);
      fetch(rc, 2); fetch(rd, 3);
      head(rb, 1); rest(rb, 1);
      check(rc, rd, 2);
      head(rc, 2); fetch(ra, 4); fetch(rb, 5); rest(rc, 2);
      head(rd, 3); rest(rd, 3);
      check(ra, rb, 4);
      head(ra, 4); fetch(rc, 6); fetch(rd, 7); ll_issue<2>(sv, X->e3s + (xw * 8 + 2 * c) * 8 + r, 8); rest(ra, 4);
      head(rb, 5); rest(rb, 5);
      check(rc, rd, 6);
      head(rc, 6); rest(rc, 6);
      head(rd, 7); rest(rd, 7);
      fence_async_smem();
      ll_wait<2>(sv, X->e3s + (xw * 8 + 2 * c) * 8 + r, 8, tag);
      float s0 = __uint_as_float(sv[0][0]) + __uint_as_float(sv[1][0]), q0 = __uint_as_float(sv[0][1]) + __uint_as_float(sv[1][1]);
      float s1 = __uint_as_float(sv[0][2]) + __uint_as_float(sv[1][2]), q1 = __uint_as_float(sv[0][3]) + __uint_as_float(sv[1][3]);
#pragma unroll
      for (int o = 1; o <= 2; o <<= 1) {
        s0 += __shfl_xor_sync(0xffffffffu, s0, o); q0 += __shfl_xor_sync(0xffffffffu, q0, o);
        s1 += __shfl_xor_sync(0xffffffffu, s1, o); q1 += __shfl_xor_sync(0xffffffffu, q1, o);
      }
      s0 *= 1.f / D_; s1 *= 1.f / D_;
      rs0 = rsqrtf(fmaxf(fmaf(-s0, s0, q0 * (1.f / D_)), 0.f) + 1e-5f);
      rs1 = rsqrtf(fmaxf(fmaf(-s1, s1, q1 * (1.f / D_)), 0.f) + 1e-5f);
      wg_wait<0>();
      keep(a1); keep(a2);
      if (lane == 0) mbar_arrive(BAR + (B_EA + 7) * 8);
      PSTAMP(9);
#pragma unroll
      for (int u = 0; u < 4; u++)
#pragma unroll
        for (int e = 0; e < 4; e++)
          hA[u][e] = swiglu(a1[8 * u + 2 * e], a1[8 * u + 2 * e + 1], a1[32 + 8 * u + 2 * e], a1[33 + 8 * u + 2 * e], (e & 1) ? rs1 : rs0);
#pragma unroll
      for (int u = 0; u < 2; u++)
#pragma unroll
        for (int e = 0; e < 4; e++)
          hA[4 + u][e] = swiglu(a2[8 * u + 2 * e], a2[8 * u + 2 * e + 1], a2[16 + 8 * u + 2 * e], a2[17 + 8 * u + 2 * e], (e & 1) ? rs1 : rs0);
      keep(hA);
      wg_bar(p);
    }
    PSTAMP(10);

    const uint32_t mbx = Hn + 32768 + w * 512 + lane * 16;
    auto send = [&](const uint32_t (&v)[4], uint32_t a, int part) {
      asm volatile("st.async.weak.shared::cluster.mbarrier::complete_tx::bytes.v4.b32 [%0], {%1,%2,%3,%4}, [%5];"
                   ::"r"(a + peer()), "r"(v[0]), "r"(v[1]), "r"(v[2]), "r"(v[3]), "r"(BAR + (B_HX + 2 * part + p) * 8 + peer()) : "memory");
    };
    uint32_t hB[8][4];
    {
      float ab[128];
      uint32_t db = descB(RING);
      const uint32_t dAn = descA(H1) - p * 4096;
      if (lane == 0 && w == 0) { mbar_expect_tx(BAR + (B_HX + p) * 8, 12288); mbar_expect_tx(BAR + (B_HX + 2 + p) * 8, 16384); }
#pragma unroll 1
      for (int i = 0; i < 8; i++) {
        mbar_wait(BAR + (B_FB + i) * 8);
        const uint32_t da = dAn + i * 512;
        wg_fence();
        wgmma_ss_n256(ab, da, db, i);
#pragma unroll
        for (int k = 1; k < 4; k++) wgmma_ss_n256(ab, da + k * 2, db + k * 128, 1);
        wg_commit();
        if (i == 7) {
          mbar_wait_cluster(BAR + (B_PF + p) * 8);
#pragma unroll
          for (int k = 0; k < 6; k++) send(hA[k], mbx + k * 2048, 0);
        }
        wg_wait<1>();
        mbar_arrive_if(BAR + (B_EB + i - 1) * 8, i > 0 && lane == 0);
        if (i == 6 && lane == 0) mbar_arrive_peer(BAR + (B_PF + p) * 8);
        db = db == descB(RING + 65536) ? descB(RING) : db + 2048;
      }
      wg_wait<0>();
      keep(ab);
      mbar_arrive_if(BAR + (B_EB + 7) * 8, lane == 0);
      if (lane == 0) mbar_arrive_peer(BAR + (B_PF + 2 + p) * 8);
      PSTAMP(11);
#pragma unroll
      for (int u = 0; u < 8; u++) {
        const int o = (u >> 2) * 64 + (u & 3) * 8;
#pragma unroll
        for (int e = 0; e < 4; e++)
          hB[u][e] = swiglu(ab[o + 2 * e], ab[o + 2 * e + 1], ab[o + 32 + 2 * e], ab[o + 33 + 2 * e], (e & 1) ? rs1 : rs0);
        if (u == 3) mbar_wait_cluster(BAR + (B_PF + 2 + p) * 8);
        if (u >= 4 && u < 4 + SEND_EARLY) send(hB[u - 4], mbx + (2 + u) * 2048, 1);
      }
      keep(hB);
    }
    PSTAMP(12);

    {
      float ya[32], y[32];
      uint32_t hP[14][4];
      const uint32_t offA = (j & 1) ? 256 : 0, offH = (j & 1) ? 0 : 1536;
      uint4* e4 = xb + O_E4 + g * 24576 + warp * 128;
      const uint32_t stg = H0 + p * 65536 + 28672 + (w >> 1) * 32768 + (w & 1) * 2048;
      auto mm = [&](float (&d)[32], int m, int k0, int k1) {
        if (k0 == 0) mbar_wait(BAR + (B_FT + m) * 8);
        const uint32_t T = descB(0) + (t_addr(m) >> 4);
        const uint32_t oA = w2_peer(m) ? 256 - offA : offA, oH = w2_peer(m) ? 1536 - offH : offH;
        wg_fence();
#pragma unroll
        for (int k = k0; k < k1; k++) {
          const uint32_t db = T + (k < 4 ? oA + k * 128 : k < 6 ? oH + (k - 4) * 128 : oA + 512 + (k - 6) * 128);
          if (w2_peer(m)) wgmma_rs_n64(d, hP[k], db, 1);
          else if (k < 6) wgmma_rs_n64(d, hA[k], db, k);
          else wgmma_rs_n64(d, hB[k - 6], db, 1);
        }
        wg_commit();
      };
      auto next = [&](float (&d)[32], int m, float (&dp)[32], int q) {
        mm(d, m, 0, 3);
        wg_wait<1>();
        keep(dp);
        mbar_arrive_if(BAR + (B_ET0 + q) * 8, lane == 0);
        uint4* dst = e4 + (((j + 2 + 2 * q) & 7) * 3 + q) * 1024;
#pragma unroll
        for (int u = 0; u < 4; u++)
          ll_st(dst + u * 32, pack2(dp[8 * u], dp[8 * u + 1]), pack2(dp[8 * u + 2], dp[8 * u + 3]),
                pack2(dp[8 * u + 4], dp[8 * u + 5]), pack2(dp[8 * u + 6], dp[8 * u + 7]), tag);
        if (q == 2) mbar_wait(BAR + (B_ET0 + 2) * 8);
        mm(d, m, 3, 14);
      };
#pragma unroll
      for (int i = 0; i < 4; i++) {
        const uint32_t a = i ? pin(mbx, zero) : mbx;
#pragma unroll
        for (int k = SEND_EARLY + (8 - SEND_EARLY) * i / 4; k < SEND_EARLY + (8 - SEND_EARLY) * (i + 1) / 4; k++) send(hB[k], a + (6 + k) * 2048, 1);
        if (i < 3) mm(ya, 0, 5 * i, i < 2 ? 5 * i + 5 : 14);
        else mm(y, 1, 0, 6);
      }
      mbar_wait_cluster(BAR + (B_HX + p) * 8);
#pragma unroll
      for (int k = 0; k < 6; k++) lds128(hP[k], mbx + k * 2048);
      mm(y, 1, 6, 14);
      keep(hP[0]); keep(hP[1]); keep(hP[2]); keep(hP[3]); keep(hP[4]); keep(hP[5]);
      mm(ya, 2, 0, 3);
      PSTAMP(18);
      mbar_wait_cluster(BAR + (B_HX + 2 + p) * 8);
      PSTAMP(24);
#pragma unroll
      for (int k = 6; k < 14; k++) lds128(hP[k], mbx + k * 2048);
      mm(ya, 2, 3, 6);
      keep(hP);
      mbar_arrive_if(BAR + (B_HC + p) * 8, lane == 0);
      mm(ya, 2, 6, 14);
      mbar_wait(BAR + B_CLR * 8);
      next(y, 3, ya, 0);
      PSTAMP(27);
      next(ya, 4, y, 1);
      mbar_arrive_if(BAR + (B_ET0 + 3) * 8, lane == 0);
      mm(ya, 5, 0, 14);
      PSTAMP(26);
      next(y, 6, ya, 2);
      PSTAMP(28);
      uint32_t in[4][4], lt[4][4];
      const uint4* insrc = e4 + j * 3 * 1024;
      mm(y, 7, 0, 7);
      ll_issue<4>(lt, insrc + 2048, 32);
      mm(y, 7, 7, 14);
      mbar_wait(BAR + B_FIN * 8);
      mbar_wait(BAR + (B_FIN + 1) * 8);
      wg_wait<0>();
      keep(y);
      PSTAMP(13);
      const uint32_t ident = (2 * c == r ? 0x3f80u : 0u) | (2 * c + 1 == r ? 0x3f800000u : 0u);
      auto acc = [&](const uint32_t (&v)[4][4]) {
#pragma unroll
        for (int u = 0; u < 4; u++) {
          mma1688_acc(*reinterpret_cast<float (*)[4]>(&y[8 * u]), v[u][0], v[u][1], ident);
          mma1688_acc(*reinterpret_cast<float (*)[4]>(&y[8 * u + 4]), v[u][2], v[u][3], ident);
        }
      };
      acc(hf);
#pragma unroll
      for (int q = 0; q < 2; q++) {
#pragma unroll
        for (int u = 0; u < 4; u++) lds128(in[u], t_addr(q + 1) + warp * 2048 + lane * 16 + u * 512);
        ll_wait<4>(in, insrc + q * 1024, 32, tag);
        acc(in);
      }
      PSTAMP(25);
      if (ll_bad<4>(lt, pin(tag, zero))) {
        ll_spin<4>(lt, insrc + 2048, 32, tag);
      }
      ll_clear<4>(lt);
      acc(lt);
      PSTAMP(14);
#pragma unroll
      for (int u = 0; u < 4; u++) {
        uint32_t o[4];
#pragma unroll
        for (int e = 0; e < 4; e++) o[e] = pack2(y[8 * u + 2 * e], y[8 * u + 2 * e + 1]);
        stsm4(stg + (moff ^ (u << 5)), o);
      }
      fence_async_smem();
      __syncwarp();
      if (elect_one()) {
        tma3d_store(&P.out, stg, 64 * j, p, g * 64 + 16 * w);
        asm volatile("cp.async.bulk.commit_group;" ::: "memory");
        asm volatile("cp.async.bulk.wait_group.read 0;" ::: "memory");
      }
      PSTAMP(15);
    }
  }
}

typedef CUresult (*EncodeFn)(CUtensorMap*, CUtensorMapDataType, cuuint32_t, void*, const cuuint64_t*, const cuuint64_t*,
                             const cuuint32_t*, const cuuint32_t*, CUtensorMapInterleave, CUtensorMapSwizzle,
                             CUtensorMapL2promotion, CUtensorMapFloatOOBfill);

void enc2d(EncodeFn f, CUtensorMap* m, const void* base, uint64_t cols, uint64_t rows, uint32_t bc, uint32_t br, CUtensorMapSwizzle sw) {
  cuuint64_t gd[2] = {cols, rows}, gs[1] = {cols * 2};
  cuuint32_t bd[2] = {bc, br}, es[2] = {1, 1};
  f(m, CU_TENSOR_MAP_DATA_TYPE_BFLOAT16, 2, const_cast<void*>(base), gd, gs, bd, es, CU_TENSOR_MAP_INTERLEAVE_NONE, sw,
    CU_TENSOR_MAP_L2_PROMOTION_L2_128B, CU_TENSOR_MAP_FLOAT_OOB_FILL_NONE);
}
void enc_par(EncodeFn f, CUtensorMap* m, const void* base, uint32_t pairs) {
  cuuint64_t gd[3] = {(cuuint64_t)D_, 2, (cuuint64_t)S_ / 2}, gs[2] = {D_ * 2, D_ * 4};
  cuuint32_t bd[3] = {64, 1, pairs}, es[3] = {1, 1, 1};
  f(m, CU_TENSOR_MAP_DATA_TYPE_BFLOAT16, 3, const_cast<void*>(base), gd, gs, bd, es, CU_TENSOR_MAP_INTERLEAVE_NONE,
    CU_TENSOR_MAP_SWIZZLE_128B, CU_TENSOR_MAP_L2_PROMOTION_L2_128B, CU_TENSOR_MAP_FLOAT_OOB_FILL_NONE);
}

}

extern "C" void kernel_launch(void* const* d_in, const int* in_sizes, int n_in, void* d_out, int out_size) {
  (void)in_sizes; (void)n_in; (void)out_size;
  static EncodeFn enc = nullptr;
  static Scratch* scratch = nullptr;
  if (!enc) {
    void* fn = nullptr;
    cudaDriverEntryPointQueryResult q;
    cudaGetDriverEntryPoint("cuTensorMapEncodeTiled", &fn, cudaEnableDefault, &q);
    enc = (EncodeFn)fn;
    cudaGetSymbolAddress((void**)&scratch, g_scratch);
    cudaFuncSetAttribute(fused_block_kernel, cudaFuncAttributeMaxDynamicSharedMemorySize, SMEM_BYTES);
  }
  Params P;
  const __nv_bfloat16* xp = (const __nv_bfloat16*)d_in[0];
  const __nv_bfloat16* wqkvp = (const __nv_bfloat16*)d_in[1];
  const __nv_bfloat16* wop = (const __nv_bfloat16*)d_in[2];
  P.w1p = (const __nv_bfloat16*)d_in[4];
  P.w3p = (const __nv_bfloat16*)d_in[5];
  P.w2p = (const __nv_bfloat16*)d_in[6];
  enc_par(enc, &P.x, xp, 64);
  enc_par(enc, &P.out, d_out, 16);
  enc2d(enc, &P.wqkv, wqkvp, 3 * D_, D_, 64, 64, CU_TENSOR_MAP_SWIZZLE_128B);
  enc2d(enc, &P.wo, wop, D_, D_, 64, 64, CU_TENSOR_MAP_SWIZZLE_128B);
  enc2d(enc, &P.w1, P.w1p, F_, D_, 64, 64, CU_TENSOR_MAP_SWIZZLE_128B);
  enc2d(enc, &P.w3, P.w3p, F_, D_, 64, 64, CU_TENSOR_MAP_SWIZZLE_128B);
  enc2d(enc, &P.w1h, P.w1p, F_, D_, 32, 64, CU_TENSOR_MAP_SWIZZLE_64B);
  enc2d(enc, &P.w3h, P.w3p, F_, D_, 32, 64, CU_TENSOR_MAP_SWIZZLE_64B);
  enc2d(enc, &P.w2, P.w2p, D_, F_, 64, 224, CU_TENSOR_MAP_SWIZZLE_128B);

  cudaLaunchConfig_t cfg = {};
  cfg.gridDim = dim3(128);
  cfg.blockDim = dim3(384);
  cfg.dynamicSmemBytes = SMEM_BYTES;
  cfg.stream = cudaStreamPerThread;
  cudaLaunchAttribute at[2];
  at[0].id = cudaLaunchAttributeCooperative;
  at[0].val.cooperative = 1;
  cfg.attrs = at;
  cfg.numAttrs = 1;
  at[1].id = cudaLaunchAttributeClusterDimension;
  at[1].val.clusterDim.x = 2; at[1].val.clusterDim.y = 1; at[1].val.clusterDim.z = 1;
  cfg.numAttrs = 2;
  cudaLaunchKernelEx(&cfg, fused_block_kernel, scratch, xp, wqkvp, wop, 0u, P);
}
```

```cpp
#include <cuda_runtime.h>
#include <cuda.h>
#include <cuda_bf16.h>
#include <stdint.h>
#include <stddef.h>

namespace {

constexpr int S_ = 2048, D_ = 512, F_ = 1792;
#define LAG_KB 3
#define E4_FIRST 7
#define PP_AHEAD 1
#define SIDE_KB 0
#define CLR_MODE 0
#define W2_HEAD 3
#define CLR_SLEEP 400
#define CMAP 2
#define E4_ON 1
#define E4_WHEN (B_EA + 7)
#define SEND_EARLY 2
#define CS_KB 3
#define WO_KB 3
#define GATHER_SLEEP 200
#define XO_DELAY 2

constexpr uint32_t SPIN_LIMIT = 1u << 18;

struct Scratch {
  uint4 e4[16 * 8 * 3 * 8 * 4 * 32];
  uint4 e2[16 * 2 * 4 * 32 * 32];
  uint4 e3h[16 * 2 * 4 * 32 * 32];
  uint4 e1[16 * 8 * 2 * 4 * 32];
  uint4 e2s[16 * 2 * 4 * 8 * 8];
  uint4 e3s[16 * 2 * 4 * 8 * 8];
  uint4 e0c[8 * 3 * 16 * 16];
  uint4 e0s[2048];
  uint4 e0w[8 * 64];
  unsigned epoch[128];
};
__device__ Scratch g_scratch;
#define PSTAMP(i)
#define PSTAMPW(slot, i)
#define W2STAMP(i)

struct alignas(64) Params {
  CUtensorMap x, out, wqkv, wo, w1, w3, w1h, w3h, w2;
  const __nv_bfloat16 *w1p, *w3p, *w2p;
};

constexpr uint32_t SB = 1024;
constexpr uint32_t H0 = SB;
constexpr uint32_t H1 = SB + 65536;
constexpr uint32_t RING = SB + 131072;
constexpr uint32_t BAR = SB + 229376;
constexpr uint32_t TAGS = BAR + 1016;
constexpr uint32_t CS = BAR + 1024;
constexpr uint32_t ST = CS + 768;
constexpr uint32_t WB = ST + 1024;
constexpr uint32_t SMEM_BYTES = 232448;
static_assert(WB + 256 <= SB + SMEM_BYTES, "smem");

enum : int {
  B_FX = 0,
  B_FKV = 16, B_FQ = 24, B_FWO = 32, B_FA = 40, B_FB = 48, B_FT = 56,
  B_EKV = 64, B_EQ = 72, B_EA = 80, B_EB = 88, B_ET0 = 96,
  B_WODONE = 103,
  B_FIN = 33,
  B_EX = 104,
  B_LAG = 112, B_READY = 113, B_PUB = 114, B_CLR = 115, B_CLR0 = 116, B_TAG = 117,
  B_HX = 35,
  B_PF = 118,
  B_HC = 122,
  B_CLR1 = 124
};

__device__ __forceinline__ uint32_t smem_u32(const void* p) { return (uint32_t)__cvta_generic_to_shared(p); }
__device__ __forceinline__ uint32_t own() { return (blockIdx.x & 1) << 24; }
__device__ __forceinline__ uint32_t peer() { return (~blockIdx.x & 1) << 24; }
__device__ __forceinline__ void mbar_init(uint32_t b, uint32_t c) { asm volatile("mbarrier.init.shared::cta.b64 [%0], %1;" ::"r"(b + own()), "r"(c) : "memory"); }
__device__ __forceinline__ void mbar_expect_tx(uint32_t b, uint32_t bytes) { asm volatile("mbarrier.arrive.expect_tx.shared::cta.b64 _, [%0], %1;" ::"r"(b + own()), "r"(bytes) : "memory"); }
__device__ __forceinline__ void mbar_arrive(uint32_t b) { asm volatile("mbarrier.arrive.shared::cta.b64 _, [%0];" ::"r"(b + own()) : "memory"); }
__device__ __forceinline__ void mbar_wait(uint32_t b) {
  asm volatile("{\n.reg .pred p;\n.reg .u32 c;\nmov.u32 c, 0;\nLW:\n.pragma \"nounroll\";\n"
               "mbarrier.try_wait.parity.shared::cta.b64 p, [%0], 0;\nadd.u32 c, c, 1;\nsetp.gt.or.u32 p, c, %1, p;\n@!p bra LW;\n}\n"
               ::"r"(b + own()), "n"(SPIN_LIMIT) : "memory");
}
__device__ __forceinline__ void mbar_arrive_peer(uint32_t b) {
  asm volatile("mbarrier.arrive.relaxed.cluster.shared::cluster.b64 _, [%0];" ::"r"(b + peer()) : "memory");
}
__device__ __forceinline__ void mbar_wait_cluster(uint32_t b) {
  asm volatile("{\n.reg .pred p;\n.reg .u32 c;\nmov.u32 c, 0;\nLW:\n.pragma \"nounroll\";\n"
               "mbarrier.try_wait.parity.acquire.cluster.shared::cta.b64 p, [%0], 0;\nadd.u32 c, c, 1;\nsetp.gt.or.u32 p, c, %1, p;\n@!p bra LW;\n}\n"
               ::"r"(b + own()), "n"(SPIN_LIMIT) : "memory");
}
__device__ __forceinline__ bool elect_one() {
  uint32_t p;
  asm volatile("{\n.reg .pred P;\nelect.sync _|P, 0xffffffff;\nselp.u32 %0, 1, 0, P;\n}\n" : "=r"(p));
  return p;
}
__device__ __forceinline__ void tma2d(uint32_t dst, const CUtensorMap* m, int c0, int c1, uint32_t bar) {
  dst += own(); bar += own();
  asm volatile("cp.async.bulk.tensor.2d.shared::cluster.global.mbarrier::complete_tx::bytes [%0], [%1, {%3, %4}], [%2];"
               ::"r"(dst), "l"(m), "r"(bar), "r"(c0), "r"(c1) : "memory");
}
__device__ __forceinline__ void tma3d(uint32_t dst, const CUtensorMap* m, int c0, int c1, int c2, uint32_t bar) {
  dst += own(); bar += own();
  asm volatile("cp.async.bulk.tensor.3d.shared::cluster.global.mbarrier::complete_tx::bytes [%0], [%1, {%3, %4, %5}], [%2];"
               ::"r"(dst), "l"(m), "r"(bar), "r"(c0), "r"(c1), "r"(c2) : "memory");
}
__device__ __forceinline__ void tma3d_store(const CUtensorMap* m, uint32_t src, int c0, int c1, int c2) {
  asm volatile("cp.async.bulk.tensor.3d.global.shared::cta.bulk_group [%0, {%2, %3, %4}], [%1];"
               ::"l"(m), "r"(src + own()), "r"(c0), "r"(c1), "r"(c2) : "memory");
}
__device__ __forceinline__ void l2_prefetch(const void* p, uint32_t bytes) {
  asm volatile("cp.async.bulk.prefetch.L2.global [%0], %1;" ::"l"(p), "r"(bytes) : "memory");
}
__device__ __forceinline__ void prefetch_map(const CUtensorMap* m) { asm volatile("prefetch.tensormap [%0];" ::"l"(m) : "memory"); }
__device__ __forceinline__ void fence_async_smem() { asm volatile("fence.proxy.async.shared::cta;" ::: "memory"); }
__device__ __forceinline__ void wg_fence() { asm volatile("wgmma.fence.sync.aligned;" ::: "memory"); }
__device__ __forceinline__ void wg_commit() { asm volatile("wgmma.commit_group.sync.aligned;" ::: "memory"); }
template <int N> __device__ __forceinline__ void wg_wait() { asm volatile("wgmma.wait_group.sync.aligned %0;" ::"n"(N) : "memory"); }
__device__ __forceinline__ void wg_bar(int p) {
  if (p == 0) asm volatile("bar.sync 1, 128;" ::: "memory"); else asm volatile("bar.sync 2, 128;" ::: "memory");
}
constexpr uint32_t DESC_HI128 = (1024 >> 4) | (1u << 30);
constexpr uint32_t DESC_HI64 = (512 >> 4) | (2u << 30);
__device__ __forceinline__ constexpr uint32_t descA(uint32_t addr) { return (addr >> 4) | (1u << 16); }
__device__ __forceinline__ constexpr uint32_t descB(uint32_t addr) { return (addr >> 4) | ((8192u >> 4) << 16); }
__device__ __forceinline__ constexpr uint32_t descBh(uint32_t addr) { return (addr >> 4) | ((4096u >> 4) << 16); }

__device__ __forceinline__ void wgmma_ss_n64(float (&d)[32], uint32_t da, uint32_t db, int sc) {
  asm volatile("{\n.reg .pred p;\n.reg .b64 da, db;\nsetp.ne.b32 p, %34, 0;\nmov.b64 da, {%32, %35};\nmov.b64 db, {%33, %35};\n"
    "wgmma.mma_async.sync.aligned.m64n64k16.f32.bf16.bf16 {%0, %1, %2, %3, %4, %5, %6, %7, %8, %9, %10, %11, %12, %13, %14, %15, %16, %17, %18, %19, %20, %21, %22, %23, %24, %25, %26, %27, %28, %29, %30, %31}, da, db, p, 1, 1, 0, 1;\n}\n"
    : "+f"(d[0]), "+f"(d[1]), "+f"(d[2]), "+f"(d[3]), "+f"(d[4]), "+f"(d[5]), "+f"(d[6]), "+f"(d[7]),
      "+f"(d[8]), "+f"(d[9]), "+f"(d[10]), "+f"(d[11]), "+f"(d[12]), "+f"(d[13]), "+f"(d[14]), "+f"(d[15]),
      "+f"(d[16]), "+f"(d[17]), "+f"(d[18]), "+f"(d[19]), "+f"(d[20]), "+f"(d[21]), "+f"(d[22]), "+f"(d[23]),
      "+f"(d[24]), "+f"(d[25]), "+f"(d[26]), "+f"(d[27]), "+f"(d[28]), "+f"(d[29]), "+f"(d[30]), "+f"(d[31])
    : "r"(da), "r"(db), "r"(sc), "n"(DESC_HI128));
}
__device__ __forceinline__ void wgmma_ss_n128(float (&d)[64], uint32_t da, uint32_t db, int sc) {
  asm volatile("{\n.reg .pred p;\n.reg .b64 da, db;\nsetp.ne.b32 p, %66, 0;\nmov.b64 da, {%64, %67};\nmov.b64 db, {%65, %67};\n"
    "wgmma.mma_async.sync.aligned.m64n128k16.f32.bf16.bf16 {%0, %1, %2, %3, %4, %5, %6, %7, %8, %9, %10, %11, %12, %13, %14, %15, %16, %17, %18, %19, %20, %21, %22, %23, %24, %25, %26, %27, %28, %29, %30, %31, %32, %33, %34, %35, %36, %37, %38, %39, %40, %41, %42, %43, %44, %45, %46, %47, %48, %49, %50, %51, %52, %53, %54, %55, %56, %57, %58, %59, %60, %61, %62, %63}, da, db, p, 1, 1, 0, 1;\n}\n"
    : "+f"(d[0]), "+f"(d[1]), "+f"(d[2]), "+f"(d[3]), "+f"(d[4]), "+f"(d[5]), "+f"(d[6]), "+f"(d[7]),
      "+f"(d[8]), "+f"(d[9]), "+f"(d[10]), "+f"(d[11]), "+f"(d[12]), "+f"(d[13]), "+f"(d[14]), "+f"(d[15]),
      "+f"(d[16]), "+f"(d[17]), "+f"(d[18]), "+f"(d[19]), "+f"(d[20]), "+f"(d[21]), "+f"(d[22]), "+f"(d[23]),
      "+f"(d[24]), "+f"(d[25]), "+f"(d[26]), "+f"(d[27]), "+f"(d[28]), "+f"(d[29]), "+f"(d[30]), "+f"(d[31]),
      "+f"(d[32]), "+f"(d[33]), "+f"(d[34]), "+f"(d[35]), "+f"(d[36]), "+f"(d[37]), "+f"(d[38]), "+f"(d[39]),
      "+f"(d[40]), "+f"(d[41]), "+f"(d[42]), "+f"(d[43]), "+f"(d[44]), "+f"(d[45]), "+f"(d[46]), "+f"(d[47]),
      "+f"(d[48]), "+f"(d[49]), "+f"(d[50]), "+f"(d[51]), "+f"(d[52]), "+f"(d[53]), "+f"(d[54]), "+f"(d[55]),
      "+f"(d[56]), "+f"(d[57]), "+f"(d[58]), "+f"(d[59]), "+f"(d[60]), "+f"(d[61]), "+f"(d[62]), "+f"(d[63])
    : "r"(da), "r"(db), "r"(sc), "n"(DESC_HI128));
}
__device__ __forceinline__ void wgmma_ss_n256(float (&d)[128], uint32_t da, uint32_t db, int sc) {
  asm volatile("{\n.reg .pred p;\n.reg .b64 da, db;\nsetp.ne.b32 p, %130, 0;\nmov.b64 da, {%128, %131};\nmov.b64 db, {%129, %131};\n"
    "wgmma.mma_async.sync.aligned.m64n256k16.f32.bf16.bf16 {%0, %1, %2, %3, %4, %5, %6, %7, %8, %9, %10, %11, %12, %13, %14, %15, %16, %17, %18, %19, %20, %21, %22, %23, %24, %25, %26, %27, %28, %29, %30, %31, %32, %33, %34, %35, %36, %37, %38, %39, %40, %41, %42, %43, %44, %45, %46, %47, %48, %49, %50, %51, %52, %53, %54, %55, %56, %57, %58, %59, %60, %61, %62, %63, %64, %65, %66, %67, %68, %69, %70, %71, %72, %73, %74, %75, %76, %77, %78, %79, %80, %81, %82, %83, %84, %85, %86, %87, %88, %89, %90, %91, %92, %93, %94, %95, %96, %97, %98, %99, %100, %101, %102, %103, %104, %105, %106, %107, %108, %109, %110, %111, %112, %113, %114, %115, %116, %117, %118, %119, %120, %121, %122, %123, %124, %125, %126, %127}, da, db, p, 1, 1, 0, 1;\n}\n"
    : "+f"(d[0]), "+f"(d[1]), "+f"(d[2]), "+f"(d[3]), "+f"(d[4]), "+f"(d[5]), "+f"(d[6]), "+f"(d[7]),
      "+f"(d[8]), "+f"(d[9]), "+f"(d[10]), "+f"(d[11]), "+f"(d[12]), "+f"(d[13]), "+f"(d[14]), "+f"(d[15]),
      "+f"(d[16]), "+f"(d[17]), "+f"(d[18]), "+f"(d[19]), "+f"(d[20]), "+f"(d[21]), "+f"(d[22]), "+f"(d[23]),
      "+f"(d[24]), "+f"(d[25]), "+f"(d[26]), "+f"(d[27]), "+f"(d[28]), "+f"(d[29]), "+f"(d[30]), "+f"(d[31]),
      "+f"(d[32]), "+f"(d[33]), "+f"(d[34]), "+f"(d[35]), "+f"(d[36]), "+f"(d[37]), "+f"(d[38]), "+f"(d[39]),
      "+f"(d[40]), "+f"(d[41]), "+f"(d[42]), "+f"(d[43]), "+f"(d[44]), "+f"(d[45]), "+f"(d[46]), "+f"(d[47]),
      "+f"(d[48]), "+f"(d[49]), "+f"(d[50]), "+f"(d[51]), "+f"(d[52]), "+f"(d[53]), "+f"(d[54]), "+f"(d[55]),
      "+f"(d[56]), "+f"(d[57]), "+f"(d[58]), "+f"(d[59]), "+f"(d[60]), "+f"(d[61]), "+f"(d[62]), "+f"(d[63]),
      "+f"(d[64]), "+f"(d[65]), "+f"(d[66]), "+f"(d[67]), "+f"(d[68]), "+f"(d[69]), "+f"(d[70]), "+f"(d[71]),
      "+f"(d[72]), "+f"(d[73]), "+f"(d[74]), "+f"(d[75]), "+f"(d[76]), "+f"(d[77]), "+f"(d[78]), "+f"(d[79]),
      "+f"(d[80]), "+f"(d[81]), "+f"(d[82]), "+f"(d[83]), "+f"(d[84]), "+f"(d[85]), "+f"(d[86]), "+f"(d[87]),
      "+f"(d[88]), "+f"(d[89]), "+f"(d[90]), "+f"(d[91]), "+f"(d[92]), "+f"(d[93]), "+f"(d[94]), "+f"(d[95]),
      "+f"(d[96]), "+f"(d[97]), "+f"(d[98]), "+f"(d[99]), "+f"(d[100]), "+f"(d[101]), "+f"(d[102]), "+f"(d[103]),
      "+f"(d[104]), "+f"(d[105]), "+f"(d[106]), "+f"(d[107]), "+f"(d[108]), "+f"(d[109]), "+f"(d[110]), "+f"(d[111]),
      "+f"(d[112]), "+f"(d[113]), "+f"(d[114]), "+f"(d[115]), "+f"(d[116]), "+f"(d[117]), "+f"(d[118]), "+f"(d[119]),
      "+f"(d[120]), "+f"(d[121]), "+f"(d[122]), "+f"(d[123]), "+f"(d[124]), "+f"(d[125]), "+f"(d[126]), "+f"(d[127])
    : "r"(da), "r"(db), "r"(sc), "n"(DESC_HI128));
}
template <uint32_t HI = DESC_HI128>
__device__ __forceinline__ void wgmma_rs_n64(float (&d)[32], const uint32_t (&a)[4], uint32_t db, int sc) {
  asm volatile("{\n.reg .pred p;\n.reg .b64 db;\nsetp.ne.b32 p, %37, 0;\nmov.b64 db, {%36, %38};\n"
    "wgmma.mma_async.sync.aligned.m64n64k16.f32.bf16.bf16 {%0, %1, %2, %3, %4, %5, %6, %7, %8, %9, %10, %11, %12, %13, %14, %15, %16, %17, %18, %19, %20, %21, %22, %23, %24, %25, %26, %27, %28, %29, %30, %31}, {%32, %33, %34, %35}, db, p, 1, 1, 1;\n}\n"
    : "+f"(d[0]), "+f"(d[1]), "+f"(d[2]), "+f"(d[3]), "+f"(d[4]), "+f"(d[5]), "+f"(d[6]), "+f"(d[7]),
      "+f"(d[8]), "+f"(d[9]), "+f"(d[10]), "+f"(d[11]), "+f"(d[12]), "+f"(d[13]), "+f"(d[14]), "+f"(d[15]),
      "+f"(d[16]), "+f"(d[17]), "+f"(d[18]), "+f"(d[19]), "+f"(d[20]), "+f"(d[21]), "+f"(d[22]), "+f"(d[23]),
      "+f"(d[24]), "+f"(d[25]), "+f"(d[26]), "+f"(d[27]), "+f"(d[28]), "+f"(d[29]), "+f"(d[30]), "+f"(d[31])
    : "r"(a[0]), "r"(a[1]), "r"(a[2]), "r"(a[3]), "r"(db), "r"(sc), "n"(HI));
}
template <uint32_t HI = DESC_HI128>
__device__ __forceinline__ void wgmma_rs_n128(float (&d)[64], const uint32_t (&a)[4], uint32_t db, int sc) {
  asm volatile("{\n.reg .pred p;\n.reg .b64 db;\nsetp.ne.b32 p, %69, 0;\nmov.b64 db, {%68, %70};\n"
    "wgmma.mma_async.sync.aligned.m64n128k16.f32.bf16.bf16 {%0, %1, %2, %3, %4, %5, %6, %7, %8, %9, %10, %11, %12, %13, %14, %15, %16, %17, %18, %19, %20, %21, %22, %23, %24, %25, %26, %27, %28, %29, %30, %31, %32, %33, %34, %35, %36, %37, %38, %39, %40, %41, %42, %43, %44, %45, %46, %47, %48, %49, %50, %51, %52, %53, %54, %55, %56, %57, %58, %59, %60, %61, %62, %63}, {%64, %65, %66, %67}, db, p, 1, 1, 1;\n}\n"
    : "+f"(d[0]), "+f"(d[1]), "+f"(d[2]), "+f"(d[3]), "+f"(d[4]), "+f"(d[5]), "+f"(d[6]), "+f"(d[7]),
      "+f"(d[8]), "+f"(d[9]), "+f"(d[10]), "+f"(d[11]), "+f"(d[12]), "+f"(d[13]), "+f"(d[14]), "+f"(d[15]),
      "+f"(d[16]), "+f"(d[17]), "+f"(d[18]), "+f"(d[19]), "+f"(d[20]), "+f"(d[21]), "+f"(d[22]), "+f"(d[23]),
      "+f"(d[24]), "+f"(d[25]), "+f"(d[26]), "+f"(d[27]), "+f"(d[28]), "+f"(d[29]), "+f"(d[30]), "+f"(d[31]),
      "+f"(d[32]), "+f"(d[33]), "+f"(d[34]), "+f"(d[35]), "+f"(d[36]), "+f"(d[37]), "+f"(d[38]), "+f"(d[39]),
      "+f"(d[40]), "+f"(d[41]), "+f"(d[42]), "+f"(d[43]), "+f"(d[44]), "+f"(d[45]), "+f"(d[46]), "+f"(d[47]),
      "+f"(d[48]), "+f"(d[49]), "+f"(d[50]), "+f"(d[51]), "+f"(d[52]), "+f"(d[53]), "+f"(d[54]), "+f"(d[55]),
      "+f"(d[56]), "+f"(d[57]), "+f"(d[58]), "+f"(d[59]), "+f"(d[60]), "+f"(d[61]), "+f"(d[62]), "+f"(d[63])
    : "r"(a[0]), "r"(a[1]), "r"(a[2]), "r"(a[3]), "r"(db), "r"(sc), "n"(HI));
}

template <int N> __device__ __forceinline__ void keep(float (&d)[N]) {
#pragma unroll
  for (int i = 0; i < N; i++) asm volatile("" : "+f"(d[i])::"memory");
}

__device__ __forceinline__ void keep(uint32_t (&d)[4]) { asm volatile("" : "+r"(d[0]), "+r"(d[1]), "+r"(d[2]), "+r"(d[3])::"memory"); }
template <int N> __device__ __forceinline__ void keep(uint32_t (&d)[N][4]) {
#pragma unroll
  for (int i = 0; i < N; i++) asm volatile("" : "+r"(d[i][0]), "+r"(d[i][1]), "+r"(d[i][2]), "+r"(d[i][3])::"memory");
}

__device__ __forceinline__ uint32_t pack2(float lo, float hi) {
  uint32_t r;
  asm("cvt.rn.bf16x2.f32 %0, %1, %2;" : "=r"(r) : "f"(hi), "f"(lo));
  return r;
}
__device__ __forceinline__ float bf_lo(uint32_t v) { return __uint_as_float(v << 16); }
__device__ __forceinline__ float bf_hi(uint32_t v) { return __uint_as_float(v & 0xffff0000u); }
__device__ __forceinline__ uint32_t hsub2(uint32_t a, uint32_t b) {
  uint32_t r;
  asm("sub.rn.bf16x2 %0, %1, %2;" : "=r"(r) : "r"(a), "r"(b));
  return r;
}
__device__ __forceinline__ uint32_t movm(uint32_t a) {
  uint32_t r;
  asm volatile("movmatrix.sync.aligned.m8n8.trans.b16 %0, %1;" : "=r"(r) : "r"(a));
  return r;
}
__device__ __forceinline__ void ldsm4(uint32_t (&v)[4], uint32_t a) {
  asm volatile("ldmatrix.sync.aligned.m8n8.x4.shared.b16 {%0,%1,%2,%3}, [%4];" : "=r"(v[0]), "=r"(v[1]), "=r"(v[2]), "=r"(v[3]) : "r"(a + own()) : "memory");
}
__device__ __forceinline__ void stsm4(uint32_t a, const uint32_t (&v)[4]) {
  asm volatile("stmatrix.sync.aligned.m8n8.x4.shared.b16 [%0], {%1,%2,%3,%4};" ::"r"(a + own()), "r"(v[0]), "r"(v[1]), "r"(v[2]), "r"(v[3]) : "memory");
}
__device__ __forceinline__ void mma16816(float (&d)[4], const uint32_t (&a)[4], uint32_t b0, uint32_t b1) {
  asm volatile("mma.sync.aligned.m16n8k16.row.col.f32.bf16.bf16.f32 {%0,%1,%2,%3}, {%4,%5,%6,%7}, {%8,%9}, {%10,%10,%10,%10};"
               : "=f"(d[0]), "=f"(d[1]), "=f"(d[2]), "=f"(d[3])
               : "r"(a[0]), "r"(a[1]), "r"(a[2]), "r"(a[3]), "r"(b0), "r"(b1), "f"(0.f));
}
__device__ __forceinline__ void mma1688_acc(float (&d)[4], uint32_t a0, uint32_t a1, uint32_t b0) {
  asm volatile("mma.sync.aligned.m16n8k8.row.col.f32.bf16.bf16.f32 {%0,%1,%2,%3}, {%4,%5}, {%6}, {%0,%1,%2,%3};"
               : "+f"(d[0]), "+f"(d[1]), "+f"(d[2]), "+f"(d[3]) : "r"(a0), "r"(a1), "r"(b0));
}
__device__ __forceinline__ float ex2(float x) { float y; asm("ex2.approx.ftz.f32 %0, %1;" : "=f"(y) : "f"(x)); return y; }
__device__ __forceinline__ float rcp(float x) { float y; asm("rcp.approx.ftz.f32 %0, %1;" : "=f"(y) : "f"(x)); return y; }
__device__ __forceinline__ float tanhf_hw(float x) { float y; asm("tanh.approx.f32 %0, %1;" : "=f"(y) : "f"(x)); return y; }
__device__ __forceinline__ uint32_t lds32(uint32_t a) { uint32_t v; asm volatile("ld.shared.u32 %0, [%1];" : "=r"(v) : "r"(a + own()) : "memory"); return v; }
__device__ __forceinline__ float2 lds64(uint32_t a) { float2 v; asm volatile("ld.shared.v2.f32 {%0,%1}, [%2];" : "=f"(v.x), "=f"(v.y) : "r"(a + own()) : "memory"); return v; }
__device__ __forceinline__ void lds128(uint32_t (&v)[4], uint32_t a) { asm volatile("ld.shared.v4.u32 {%0,%1,%2,%3}, [%4];" : "=r"(v[0]), "=r"(v[1]), "=r"(v[2]), "=r"(v[3]) : "r"(a + own()) : "memory"); }
__device__ __forceinline__ void sts128(uint32_t a, const uint32_t (&v)[4]) { asm volatile("st.shared.v4.u32 [%0], {%1,%2,%3,%4};" ::"r"(a + own()), "r"(v[0]), "r"(v[1]), "r"(v[2]), "r"(v[3]) : "memory"); }
__device__ __forceinline__ void ldg128_nc(uint32_t (&v)[4], const void* p) {
  asm volatile("ld.global.nc.L1::no_allocate.v4.u32 {%0,%1,%2,%3}, [%4];" : "=r"(v[0]), "=r"(v[1]), "=r"(v[2]), "=r"(v[3]) : "l"(p));
}
__device__ __forceinline__ uint32_t pin(uint32_t v, uint32_t zero) {
  asm volatile("{\n.reg .pred p;\n.reg .u32 c;\nmov.u32 c, %1;\nLP:\n.pragma \"nounroll\";\nsetp.eq.u32 p, c, 0;\n@p bra LD;\n"
               "nanosleep.u32 c;\nadd.u32 %0, %0, c;\nsub.u32 c, c, 1;\nbra LP;\nLD:\n}\n" : "+r"(v) : "r"(zero) : "memory");
  return v;
}
__device__ __forceinline__ void mbar_arrive_if(uint32_t b, bool cond) {
  asm volatile("{\n.reg .pred p;\nsetp.ne.u32 p, %1, 0;\n@p mbarrier.arrive.shared::cta.b64 _, [%0];\n}\n" ::"r"(b + own()), "r"((uint32_t)cond) : "memory");
}
__device__ __forceinline__ uint32_t ld_epoch(const unsigned* p) {
  uint32_t v;
  asm volatile("ld.relaxed.gpu.global.u32 %0, [%1];" : "=r"(v) : "l"(p) : "memory");
  return v;
}
__device__ __forceinline__ void ll_st(uint4* p, uint32_t a, uint32_t b, uint32_t c, uint32_t d, uint32_t tag) {
  asm volatile("st.relaxed.gpu.global.v4.b32 [%0], {%1, %2, %3, %4};" ::"l"(p), "r"((a & ~1u) | tag), "r"(b), "r"(c), "r"(d) : "memory");
}
__device__ __forceinline__ void ll_ld(uint32_t (&v)[4], const uint4* p) {
  asm volatile("{\n.reg .b128 t;\n.reg .b64 lo, hi;\nld.relaxed.gpu.global.b128 t, [%4];\nmov.b128 {lo, hi}, t;\n"
               "mov.b64 {%0, %1}, lo;\nmov.b64 {%2, %3}, hi;\n}\n"
               : "=r"(v[0]), "=r"(v[1]), "=r"(v[2]), "=r"(v[3]) : "l"(p) : "memory");
}
template <int N> __device__ __forceinline__ void ll_issue(uint32_t (&v)[N][4], const uint4* p, int stride) {
#pragma unroll
  for (int i = 0; i < N; i++) ll_ld(v[i], p + i * stride);
}
template <int N> __device__ __forceinline__ uint32_t ll_acc(const uint32_t (&v)[N][4], uint32_t tag, uint32_t acc = 0) {
#pragma unroll
  for (int i = 0; i < N; i++) asm("lop3.b32 %0, %1, %2, %0, 0xBE;" : "+r"(acc) : "r"(v[i][0]), "r"(tag));
  return acc;
}
__device__ __forceinline__ bool ll_any(uint32_t acc) { return __any_sync(0xffffffffu, acc & 1u); }
template <int N> __device__ __forceinline__ bool ll_bad(const uint32_t (&v)[N][4], uint32_t tag) { return ll_any(ll_acc<N>(v, tag)); }
template <int N> __device__ __forceinline__ void ll_clear(uint32_t (&v)[N][4]) {
#pragma unroll
  for (int i = 0; i < N; i++) v[i][0] &= ~1u;
}
template <int N> __device__ __forceinline__ void ll_spin(uint32_t (&v)[N][4], const uint4* p, int stride, uint32_t tag) {
  uint32_t it = 0;
#pragma unroll 1
  do { ll_issue<N>(v, p, stride); } while (ll_bad<N>(v, tag) && ++it < SPIN_LIMIT);
}
template <int N> __device__ __forceinline__ void ll_get(uint32_t (&v)[N][4], const uint4* p, int stride, uint32_t tag) {
  ll_spin<N>(v, p, stride, tag);
  ll_clear<N>(v);
}
template <int N> __device__ __forceinline__ void ll_wait(uint32_t (&v)[N][4], const uint4* p, int stride, uint32_t tag) {
  if (__builtin_expect(ll_bad<N>(v, tag), 0)) ll_spin<N>(v, p, stride, tag);
  ll_clear<N>(v);
}
__device__ __forceinline__ void unpack32(float (&d)[32], const uint32_t (&v)[4][4]) {
#pragma unroll
  for (int u = 0; u < 4; u++)
#pragma unroll
    for (int e = 0; e < 4; e++) { d[8 * u + 2 * e] = bf_lo(v[u][e]); d[8 * u + 2 * e + 1] = bf_hi(v[u][e]); }
}
__device__ __forceinline__ void pack32(uint32_t (&v)[4][4], const float (&d)[32]) {
#pragma unroll
  for (int u = 0; u < 4; u++)
#pragma unroll
    for (int e = 0; e < 4; e++) v[u][e] = pack2(d[8 * u + 2 * e], d[8 * u + 2 * e + 1]);
}
__device__ __forceinline__ uint32_t t_addr(int m) { return SB + ((0x01534620u >> (4 * m)) & 7u) * 32768u; }

__device__ __forceinline__ constexpr int w2_pass(int m) { return m < 4 ? m & 1 : m >> 1; }
__device__ __forceinline__ constexpr int w2_peer(int m) { return m < 4 ? m >> 1 : m & 1; }

__device__ __forceinline__ int kb_at(int i, int j) { return i == 0 ? j : (i - 1 + (i - 1 >= j ? 1 : 0)); }

__device__ __forceinline__ void init_bars(int set) {
  if (set >= 0 && elect_one()) {
    const uint32_t cnt = set < 5 ? 1 : 8;
#pragma unroll
    for (int i = 0; i < 8; i++) mbar_init(BAR + (24 + 8 * set + i) * 8, cnt);
    if (set == 9) {
#pragma unroll
      for (int i = 0; i < 9; i++) mbar_init(BAR + (B_EX + i) * 8, 4);
#pragma unroll
      for (int i = 0; i < 4; i++) mbar_init(BAR + (B_READY + i) * 8, i == 1 ? 7 : 3);
#pragma unroll
      for (int i = 0; i < 8; i++) mbar_init(BAR + (B_TAG + i) * 8, i < 1 ? 1 : i < 7 ? 4 : 3);
    }
    asm volatile("fence.mbarrier_init.release.cluster;" ::: "memory");
  }
  __syncwarp();
  asm volatile("barrier.cluster.arrive.relaxed.aligned;" ::: "memory");
  asm volatile("bar.arrive 4, 384;" ::: "memory");
  asm volatile("bar.sync 3, 384;" ::: "memory");
}

__global__ void __launch_bounds__(384, 1) fused_block_kernel(Scratch* __restrict__ X, const __nv_bfloat16* __restrict__ xp,
                                                             const __nv_bfloat16* __restrict__ wqkvp, const __nv_bfloat16* __restrict__ wop, const uint32_t zero,
                                                             const __grid_constant__ Params P) {
  extern __shared__ __align__(1024) uint8_t smem_raw[];
  if (smem_u32(smem_raw) != SB + own()) return;
  const int tid = threadIdx.x;
  const int warp = __shfl_sync(0xffffffffu, tid >> 5, 0);
  const int lane = tid & 31;
  const int cta = blockIdx.x;
  const int j = ((cta >> 1) & 1) * 4 + ((cta >> 4) & 1) * 2 + (cta & 1);
  const int g = ((cta >> 2) & 3) * 4 + (cta >> 5);

  if (warp >= 8) {
    asm volatile("setmaxnreg.dec.sync.aligned.u32 56;");
    if (warp == 8) {
      PSTAMPW(2, 0);
      const bool leader = elect_one();
      if (leader) {
        prefetch_map(&P.x); prefetch_map(&P.wqkv);
#pragma unroll
        for (int i = 0; i < 24; i++) mbar_init(BAR + i * 8, 1);
        asm volatile("fence.mbarrier_init.release.cluster;" ::: "memory");
      }
      __syncwarp();
      asm volatile("bar.arrive 3, 384;" ::: "memory");
      asm volatile("barrier.cluster.arrive.relaxed.aligned;" ::: "memory");
      auto ldx = [&](int p, int kb) {
        const uint32_t b = BAR + (B_FX + p * 8 + kb) * 8;
        mbar_expect_tx(b, 8192);
        tma3d(H0 + p * 65536 + kb * 8192, &P.x, kb * 64, p, g * 64, b);
      };
      auto ldkv = [&](int kb, int slot) {
        const uint32_t b = BAR + (B_FKV + kb) * 8, d = RING + slot * 16384;
        mbar_expect_tx(b, 16384);
        tma2d(d, &P.wqkv, 512 + 64 * j, kb * 64, b);
        tma2d(d + 8192, &P.wqkv, 1024 + 64 * j, kb * 64, b);
      };
      if (leader) {
#pragma unroll 1
        for (int i = 0; i < 8 + XO_DELAY; i++) {
          if (i < 8) ldx(0, i);
          if (i < 6) ldkv(i, i);
          if (i >= XO_DELAY) ldx(1, i - XO_DELAY);
        }
        PSTAMPW(2, 2);
      }
      __syncwarp();
      asm volatile("bar.sync 4, 384;" ::: "memory");
      if (leader) {
        const int f0 = 224 * j + ((j & 1) ? 32 : 0);
        const int fh = 224 * j + ((j & 1) ? 0 : 192);
        prefetch_map(&P.wo); prefetch_map(&P.w1); prefetch_map(&P.w3); prefetch_map(&P.w1h);
        prefetch_map(&P.w3h); prefetch_map(&P.w2); prefetch_map(&P.out);
#pragma unroll 1
        for (int i = 0; i < 2; i++) { mbar_wait(BAR + (B_EKV + i) * 8); ldkv(6 + i, i); }
#pragma unroll 1
        for (int i = 0; i < 8; i++) {
          const uint32_t b = BAR + (B_FQ + i) * 8;
          mbar_wait(BAR + (B_EKV + 2 + (i >> 1)) * 8);
          mbar_expect_tx(b, 8192);
          tma2d(RING + (4 + i) * 8192, &P.wqkv, 64 * j, i * 64, b);
        }
        mbar_expect_tx(BAR + B_FWO * 8, 65536);
#pragma unroll 1
        for (int i = 0; i < 8; i++) {
          const int kb = (i + 1) & 7;
          mbar_wait(BAR + (B_EX + i) * 8);
          tma2d(H0 + kb * 8192, &P.wo, 64 * j, kb * 64, BAR + B_FWO * 8);
        }
#pragma unroll 1
        for (int i = 0; i < 8; i++) {
          const uint32_t b = BAR + (B_FA + i) * 8, d = RING + (i & 3) * 24576;
          const int k0 = kb_at(i, j) * 64;
          mbar_wait(BAR + (B_EKV + 7 + ((0xCBA98520u >> (4 * i)) & 15)) * 8);
          mbar_expect_tx(b, 24576);
          tma2d(d, &P.w1, f0, k0, b);
          tma2d(d + 8192, &P.w3, f0, k0, b);
          tma2d(d + 16384, &P.w1h, fh, k0, b);
          tma2d(d + 20480, &P.w3h, fh, k0, b);
        }
        uint32_t d = RING;
#pragma unroll 1
        for (int i = 0; i < 8; i++) {
          const uint32_t b = BAR + (B_FB + i) * 8;
          const int k0 = kb_at(i, j) * 64;
          mbar_wait(BAR + (B_EA + 5 + i) * 8);
          mbar_expect_tx(b, 32768);
          tma2d(d, &P.w1, f0 + 64, k0, b);
          tma2d(d + 8192, &P.w3, f0 + 64, k0, b);
          tma2d(d + 16384, &P.w1, f0 + 128, k0, b);
          tma2d(d + 24576, &P.w3, f0 + 128, k0, b);
          d = d == RING + 65536 ? RING : d + 32768;
        }
#pragma unroll 1
        for (int i = 0; i < 8; i++) {
          const int m = (0x76453210u >> (4 * i)) & 7;
          const uint32_t b = BAR + (B_FT + m) * 8;
          mbar_wait(BAR + (i < 5 ? B_EB + 3 + i : i < 7 ? B_HC - 5 + i : B_ET0) * 8);
          mbar_expect_tx(b, 28672);
          tma2d(t_addr(m), &P.w2, 64 * ((j + 2 + 2 * w2_pass(m)) & 7), 224 * (j ^ w2_peer(m)), b);
          PSTAMPW(2, 4 + i);
        }
#pragma unroll 1
        for (int q = 0; q < 2; q++) {
          mbar_expect_tx(BAR + (B_FIN + q) * 8, 16384);
          mbar_wait(BAR + (B_ET0 + 3 - q) * 8);
          PSTAMPW(2, 24 + q);
          asm volatile("cp.async.bulk.shared::cluster.global.mbarrier::complete_tx::bytes [%0], [%1], 16384, [%2];"
                       ::"r"(t_addr(q + 1) + own()), "l"(X->e4 + ((g * 8 + j) * 3 + q) * 1024), "r"(BAR + (B_FIN + q) * 8 + own()) : "memory");
        }
        X->epoch[cta] = X->epoch[cta] + 1;
      }
    } else {
      const int part = warp - 9;
      uint32_t tag;
      if (part == 2) {
        tag = ld_epoch(X->epoch + cta);
        init_bars(-1);
        tag = (tag + 1) & 1;
        if (lane == 0) {
          asm volatile("st.shared.u32 [%0], %1;" ::"r"(TAGS + own()), "r"(tag) : "memory");
          mbar_arrive(BAR + B_TAG * 8);
        }
      } else {
        init_bars(warp - 1);
        mbar_wait(BAR + B_TAG * 8);
        tag = lds32(TAGS);
      }
      PSTAMPW(3, 16 + part);
      const int xw0 = g * 8;
      auto clear8 = [&](uint4* p, int stride) {
#pragma unroll
        for (int i = 0; i < 8; i++) ll_st(p + i * stride + lane, 0, 0, 0, 0, tag ^ 1);
      };
      auto clear_front = [&]() {
#pragma unroll 1
      for (int u = part; u < 8; u += 3) clear8((u < 4 ? X->e2 : X->e3h) + (xw0 * 32 + 4 * j + (u & 3)) * 32, 1024);
      if (part == 2) {
        clear8(X->e1 + (g * 8 + j) * 256, 32);
#pragma unroll
        for (int i = 0; i < 4; i++)
          ll_st((i < 2 ? X->e2s : X->e3s) + ((xw0 + (i & 1) * 4 + (lane >> 3)) * 8 + j) * 8 + (lane & 7), 0, 0, 0, 0, tag ^ 1);
      }
      };
      if (CLR_MODE == 1) clear_front();
      PSTAMPW(3, 20 + part);
      if (part == 0 ? lane < 16 : part == 1 ? lane < 4 : false)
        ll_st(part == 0 ? X->e0s + g * 128 + 16 * j + lane : X->e0w + j * 64 + g * 4 + lane, 0, 0, 0, 0, tag ^ 1);
      if (lane < 16) ll_st(X->e0c + ((j * 3 + part) * 16 + g) * 16 + lane, 0, 0, 0, 0, tag ^ 1);
      __syncwarp();
      if (lane == 0) mbar_arrive(BAR + B_CLR1 * 8);
      uint32_t v[8][4];
      {
        float s[4] = {0.f, 0.f, 0.f, 0.f}, q[4] = {0.f, 0.f, 0.f, 0.f};
        const uint32_t xa = H0 + ((lane >> 1) & 1) * 65536 + (8 * j + (lane >> 2)) * 128 + (lane & 1) * 64 + ((lane >> 1) & 3) * 16;
#pragma unroll 1
        for (int kb = part; kb < 8; kb += 3) {
          mbar_wait(BAR + (B_FX + kb) * 8);
          mbar_wait(BAR + (B_FX + 8 + kb) * 8);
#pragma unroll
          for (int i = 0; i < 4; i++) lds128(v[i], (xa + kb * 8192) ^ (i * 16));
#pragma unroll
          for (int e = 0; e < 16; e++) {
            const float a = bf_lo(v[e >> 2][e & 3]), b = bf_hi(v[e >> 2][e & 3]);
            s[e & 3] += a + b; q[e & 3] = fmaf(a, a, q[e & 3]); q[e & 3] = fmaf(b, b, q[e & 3]);
          }
        }
        float ss = (s[0] + s[1]) + (s[2] + s[3]), qq = (q[0] + q[1]) + (q[2] + q[3]);
        ss += __shfl_xor_sync(0xffffffffu, ss, 1); qq += __shfl_xor_sync(0xffffffffu, qq, 1);
        if (part && !(lane & 1))
          asm volatile("st.shared.v2.f32 [%0], {%1,%2};" ::"r"(CS + own() + part * 128 + lane * 4), "f"(ss), "f"(qq) : "memory");
        if (part) asm volatile("bar.arrive 5, 96;" ::: "memory");
        else {
          asm volatile("bar.sync 5, 96;" ::: "memory");
          const float2 t1 = lds64(CS + 128 + (lane >> 1) * 8), t2 = lds64(CS + 256 + (lane >> 1) * 8);
          const float mean = (ss + t1.x + t2.x) * (1.f / D_);
          const float rs = rsqrtf(fmaxf(fmaf(-mean, mean, (qq + t1.y + t2.y) * (1.f / D_)), 0.f) + 1e-5f);
          if (!(lane & 1)) ll_st(X->e0s + g * 128 + 16 * j + (lane >> 1), __float_as_uint(mean), __float_as_uint(rs), 0, 0, tag);
        }
      }
      if (part == 2) {
        const __nv_bfloat16* wr = wop + (size_t)(j * 64 + g * 4 + (lane >> 3)) * D_ + (lane & 7) * 8;
#pragma unroll
        for (int i = 0; i < 8; i++) ldg128_nc(v[i], wr + i * 64);
        float s[4];
#pragma unroll
        for (int e = 0; e < 4; e++) {
          s[e] = 0.f;
#pragma unroll
          for (int i = 0; i < 8; i++) s[e] += bf_lo(v[i][e]) + bf_hi(v[i][e]);
        }
        float ss = (s[0] + s[1]) + (s[2] + s[3]);
#pragma unroll
        for (int o = 1; o <= 4; o <<= 1) ss += __shfl_xor_sync(0xffffffffu, ss, o);
        if ((lane & 7) == 0) ll_st(X->e0w + j * 64 + g * 4 + (lane >> 3), __float_as_uint(ss * (1.f / D_)), 0, 0, 0, tag);
      }
      __syncwarp();
      if (lane == 0) mbar_arrive(BAR + B_PUB * 8);
      PSTAMPW(3, part * 4 + 2);
      mbar_wait(BAR + B_PUB * 8);
      PSTAMPW(3, part * 4 + 0);
      __nanosleep(GATHER_SLEEP);
      {
        uint32_t u[2][4];
        const uint4* us = (part == 2 ? X->e0w + j * 64 : X->e0s + g * 128 + part * 64) + lane;
        const uint4* vs = X->e0c + ((j * 3 + part) * 16 + (lane >> 4) * 8) * 16 + (lane & 15);
        uint32_t it = 0;
#pragma unroll 1
        do { ll_issue<2>(u, us, 32); ll_issue<8>(v, vs, 16); } while (ll_any(ll_acc<8>(v, tag, ll_acc<2>(u, tag))) && ++it < SPIN_LIMIT);
        ll_clear<2>(u); ll_clear<8>(v);
#pragma unroll
        for (int i = 0; i < 2; i++) {
          if (part == 2) asm volatile("st.shared.u32 [%0], %1;" ::"r"(WB + own() + (i * 32 + lane) * 4), "r"(u[i][0]) : "memory");
          else asm volatile("st.shared.v2.u32 [%0], {%1,%2};" ::"r"(ST + own() + (part * 64 + i * 32 + lane) * 8), "r"(u[i][0]), "r"(u[i][1]) : "memory");
        }
      }
      uint32_t o[4];
#pragma unroll
      for (int e = 0; e < 4; e++) {
        float s = 0.f;
#pragma unroll
        for (int i = 0; i < 8; i++) s += __uint_as_float(v[i][e]);
        o[e] = __float_as_uint(s + __shfl_xor_sync(0xffffffffu, s, 16));
      }
      if (lane < 16) sts128(CS + (part * 64 + lane * 4) * 4, o);
      __syncwarp();
      if (lane == 0) mbar_arrive(BAR + B_READY * 8);
      PSTAMPW(3, part * 4 + 1);
      if (CLR_MODE == 2) clear_front();
      __syncwarp();
      if (lane == 0) mbar_arrive(BAR + B_CLR0 * 8);
      PSTAMPW(3, 24 + part);
      if (lane == 0) l2_prefetch(part == 0 ? P.w1p + (size_t)cta * 4 * F_ : part == 1 ? P.w3p + (size_t)cta * 4 * F_ : P.w2p + (size_t)cta * 14 * D_, 14336);
      mbar_wait(BAR + (E4_WHEN) * 8);
#pragma unroll 1
      for (int u = 0; u < 4 * E4_ON; u++) {
        clear8(X->e4 + ((g * 8 + ((j + 2 + 2 * part) & 7)) * 3 + part) * 1024 + u * 32, 128);
        __nanosleep(CLR_SLEEP);
      }
      __syncwarp();
      if (lane == 0) mbar_arrive(BAR + B_CLR * 8);
      PSTAMPW(3, part * 4 + 3);
    }
  } else {
    const int p = warp >> 2, w = warp & 3;
    const int r = lane >> 2, c = lane & 3;
    init_bars(warp);
    asm volatile("setmaxnreg.inc.sync.aligned.u32 224;");
    PSTAMP(0);
    const uint32_t dAx = descA(H0) + p * 4096;
    const uint32_t Hn = H1 - p * 65536;
    const uint32_t moff = ((lane & 7) + ((lane >> 3) & 1) * 8) * 128 + (((lane >> 4) ^ (lane & 7)) << 4);
    const uint32_t Xw = H0 + p * 65536 + w * 2048;
    const int xw = (g * 2 + p) * 4 + w;
    uint32_t cv[8][4];
    if (p == 1) {
      mbar_wait(BAR + (B_FKV + SIDE_KB) * 8);
      const int wp = w < 3 ? w : 0;
      const __nv_bfloat16* wr = wqkvp + (size_t)(g * 32 + (lane >> 3) * 8) * (3 * D_) + wp * D_ + j * 64 + (lane & 7) * 8;
#pragma unroll
      for (int i = 0; i < 8; i++) ldg128_nc(cv[i], wr + (size_t)i * 3 * D_);
      mbar_wait(BAR + B_LAG * 8);
    }

    float akv[64];
    auto kvstep = [&](int kb) {
      mbar_wait(BAR + (B_FX + p * 8 + kb) * 8);
      mbar_wait(BAR + (B_FKV + kb) * 8);
      if (kb == 0) PSTAMP(2);
      const uint32_t da = dAx + kb * 512, db = descB(RING) + (kb < 6 ? kb : kb - 6) * 1024;
      wg_fence();
      wgmma_ss_n128(akv, da, db, kb);
#pragma unroll
      for (int k = 1; k < 4; k++) wgmma_ss_n128(akv, da + k * 2, db + k * 128, 1);
      wg_commit();
      mbar_arrive_if(BAR + B_LAG * 8, kb == LAG_KB - 1 && p == 0 && lane == 0);
      wg_wait<1>();
      mbar_arrive_if(BAR + (B_EKV + kb - 1) * 8, kb > 0 && lane == 0);
    };
#pragma unroll
    for (int kb = 0; kb < CS_KB; kb++) kvstep(kb);
    if (p == 1) {
      PSTAMP(29);
      mbar_wait(BAR + B_CLR1 * 8);
      const uint32_t tg = lds32(TAGS);
      const uint32_t hm = 0xffff0000u | (tg >> 1), sh = 16 + (tg >> 1);
      float cs[8];
#pragma unroll
      for (int e = 0; e < 4; e++) {
        float a = 0.f, b = 0.f;
#pragma unroll
        for (int i = 0; i < 8; i++) { a += __uint_as_float(cv[i][e] << sh); b += __uint_as_float(cv[i][e] & hm); }
        cs[2 * e] = a; cs[2 * e + 1] = b;
      }
      const bool up = lane & 8;
#pragma unroll
      for (int e = 0; e < 4; e++) {
        const float keepv = up ? cs[4 + e] : cs[e], give = up ? cs[e] : cs[4 + e];
        cs[e] = keepv + __shfl_xor_sync(0xffffffffu, give, 8);
        cs[e] += __shfl_xor_sync(0xffffffffu, cs[e], 16);
      }
      if (lane < 16 && w < 3)
        ll_st(X->e0c + ((j * 3 + w) * 16 + g) * 16 + (lane & 7) * 2 + (lane >> 3), __float_as_uint(cs[0]), __float_as_uint(cs[1]),
              __float_as_uint(cs[2]), __float_as_uint(cs[3]), tg);
      __syncwarp();
      mbar_arrive_if(BAR + B_PUB * 8, lane == 0);
      PSTAMP(1);
    }
#pragma unroll 1
    for (int kb = CS_KB; kb < 8; kb++) kvstep(kb);
    asm volatile("barrier.cluster.wait.aligned;" ::: "memory");
    uint32_t xres[4][4];
#pragma unroll
    for (int u = 0; u < 4; u++) ldsm4(xres[u], Xw + j * 8192 + (moff ^ (u << 5)));

    float aq[32];
    auto qstep = [&](int kb) {
      mbar_wait(BAR + (B_FQ + kb) * 8);
      const uint32_t da = dAx + kb * 512, db = descB(RING + 32768) + kb * 512;
      wg_fence();
      wgmma_ss_n64(aq, da, db, kb);
#pragma unroll
      for (int k = 1; k < 4; k++) wgmma_ss_n64(aq, da + k * 2, db + k * 128, 1);
      wg_commit();
      wg_wait<1>();
      mbar_arrive_if(BAR + (B_EQ + kb - 1) * 8, lane == 0);
      mbar_arrive_if(BAR + (B_EX + kb - 2) * 8, lane == 0 && p == 0 && kb >= 2);
    };
    qstep(0);
    keep(akv);
    PSTAMP(3);
    qstep(1);
    mbar_wait(BAR + B_READY * 8);
    PSTAMP(19);
    const uint32_t tag = lds32(TAGS);
    uint4* const xb = reinterpret_cast<uint4*>(X) + lane + (tag >> 1);
    constexpr int O_E4 = offsetof(Scratch, e4) / 16, O_E2 = offsetof(Scratch, e2) / 16, O_E3H = offsetof(Scratch, e3h) / 16;
    const float2 st0 = lds64(ST + (2 * (16 * w + r) + p) * 8);
    const float2 st1 = lds64(ST + (2 * (16 * w + r + 8) + p) * 8);
    uint32_t hi[4][4], lo[4][4];
    {
      float2 cs[16];
      auto cvt = [&](uint32_t (&d)[4][4], int b0, int ofs, const float2& st) {
#pragma unroll
        for (int b = b0; b < b0 + 8; b++) {
          if (ofs == 2) cs[b] = lds64(CS + (64 + b * 8 + 2 * c) * 4);
          const uint32_t v = pack2(fmaf(-st.x, cs[b].x, akv[4 * b + ofs]) * st.y, fmaf(-st.x, cs[b].y, akv[4 * b + ofs + 1]) * st.y);
          d[b >> 2][b & 3] = b < 8 ? v : movm(v);
        }
      };
      cvt(hi, 0, 2, st1);
      keep(hi[0]); keep(hi[1]);
      qstep(2);
      cvt(hi, 8, 2, st1);
      mbar_wait(BAR + B_CLR0 * 8);
      if (w == 3 && g < 15) {
        uint4* dst = X->e1 + ((g * 8 + j) * 2 + p) * 128 + lane;
#pragma unroll
        for (int i = 0; i < 4; i++) ll_st(dst + i * 32, hi[i][0], hi[i][1], hi[i][2], hi[i][3], tag);
      }
      PSTAMP(20);
      wg_bar(p);
#pragma unroll
      for (int i = 0; i < 4; i++) sts128(Xw + lane * 16 + i * 512, hi[i]);
      qstep(3);
      cvt(lo, 0, 0, st0);
      keep(lo[0]); keep(lo[1]);
      qstep(4);
      cvt(lo, 8, 0, st0);
    }
    PSTAMP(21);
    wg_bar(p);
    uint32_t prev[4][4];
    if (w > 0) {
#pragma unroll
      for (int i = 0; i < 4; i++) lds128(prev[i], Xw - 2048 + lane * 16 + i * 512);
    }
    if (p == 0) {
      asm volatile("fence.proxy.async.shared::cta;" ::: "memory");
      __syncwarp();
      if (lane == 0) mbar_arrive(BAR + (B_EX + 7) * 8);
    }
    PSTAMP(22);
    const uint4* halo = X->e1 + (((g - 1) * 8 + j) * 2 + p) * 128 + lane;
    const bool use_halo = w == 0 && g > 0;
    qstep(5);
    if (use_halo) ll_issue<4>(prev, halo, 32);
    qstep(6);
    qstep(7);
    PSTAMP(23);
    if (w == 0) {
      if (g > 0) {
        if (__builtin_expect(ll_bad<4>(prev, pin(tag, zero)), 0)) ll_spin<4>(prev, halo, 32, tag);
        ll_clear<4>(prev);
      } else {
#pragma unroll
        for (int i = 0; i < 4; i++)
#pragma unroll
          for (int e = 0; e < 4; e++) prev[i][e] = 0;
      }
    }
    wg_wait<0>();
    keep(aq);
    mbar_arrive_if(BAR + (B_EQ + 7) * 8, lane == 0);
    mbar_arrive_if(BAR + (B_EX + 6) * 8, lane == 0 && p == 0);
    PSTAMP(4);

    uint32_t of[4][4];
    {
      const float sc = 0.25f * 1.4426950408889634f;
      const float nohalo = (g == 0 && w == 0) ? -INFINITY : 0.f;
      const bool up0 = 2 * c > r, up1 = 2 * c + 1 > r;
      const uint32_t mup = (up0 ? 0xffffu : 0u) | (up1 ? 0xffff0000u : 0u);
      uint4* dst = xb + O_E2 + (xw * 32 + 4 * j) * 32;
      float d0 = 0.f, d1 = 0.f;
#pragma unroll 1
      for (int hp = 0; hp < 2; hp++) {
#pragma unroll
        for (int e = 0; e < 4; e++) { of[0][e] = of[2][e]; of[1][e] = of[3][e]; }
#pragma unroll
        for (int h = 0; h < 2; h++) {
          uint32_t qf[4];
          const uint32_t co = (32 * hp + 16 * h + 2 * c) * 4;
          {
            const float2 ca = lds64(CS + co), cb = lds64(CS + co + 32);
            qf[0] = pack2(fmaf(-st0.x, ca.x, aq[8 * h + 0]) * st0.y, fmaf(-st0.x, ca.y, aq[8 * h + 1]) * st0.y);
            qf[1] = pack2(fmaf(-st1.x, ca.x, aq[8 * h + 2]) * st1.y, fmaf(-st1.x, ca.y, aq[8 * h + 3]) * st1.y);
            qf[2] = pack2(fmaf(-st0.x, cb.x, aq[8 * h + 4]) * st0.y, fmaf(-st0.x, cb.y, aq[8 * h + 5]) * st0.y);
            qf[3] = pack2(fmaf(-st1.x, cb.x, aq[8 * h + 6]) * st1.y, fmaf(-st1.x, cb.y, aq[8 * h + 7]) * st1.y);
          }
          const int e0 = 2 * h;
          float sp[4], sl[4], sh[4];
          mma16816(sp, qf, prev[0][e0], prev[0][e0 + 1]);
          mma16816(sl, qf, lo[0][e0], lo[0][e0 + 1]);
          mma16816(sh, qf, hi[0][e0], hi[0][e0 + 1]);
          float a0 = up0 ? sp[0] + nohalo : sl[0], a1 = up1 ? sp[1] + nohalo : sl[1];
          float b0 = up0 ? sl[2] : sh[2], b1 = up1 ? sl[3] : sh[3];
          float ma = fmaxf(a0, a1), mb = fmaxf(b0, b1);
          ma = fmaxf(ma, __shfl_xor_sync(0xffffffffu, ma, 1)); mb = fmaxf(mb, __shfl_xor_sync(0xffffffffu, mb, 1));
          ma = fmaxf(ma, __shfl_xor_sync(0xffffffffu, ma, 2)); mb = fmaxf(mb, __shfl_xor_sync(0xffffffffu, mb, 2));
          a0 = ex2((a0 - ma) * sc); a1 = ex2((a1 - ma) * sc); b0 = ex2((b0 - mb) * sc); b1 = ex2((b1 - mb) * sc);
          float sa = a0 + a1, sbb = b0 + b1;
          sa += __shfl_xor_sync(0xffffffffu, sa, 1); sbb += __shfl_xor_sync(0xffffffffu, sbb, 1);
          sa += __shfl_xor_sync(0xffffffffu, sa, 2); sbb += __shfl_xor_sync(0xffffffffu, sbb, 2);
          const float ia = rcp(sa), ib = rcp(sbb);
          const uint32_t pa = pack2(a0 * ia, a1 * ia), pb = pack2(b0 * ib, b1 * ib);
          const uint32_t pf[4] = {pa & mup, 0u, pa & ~mup, pb & mup};
          const uint32_t ph = pb & ~mup;
          float o0[4], o1[4];
          mma16816(o0, pf, prev[2][e0], lo[2][e0]);
          mma16816(o1, pf, prev[2][e0 + 1], lo[2][e0 + 1]);
          mma1688_acc(o0, 0u, ph, hi[2][e0]);
          mma1688_acc(o1, 0u, ph, hi[2][e0 + 1]);
          of[2 + h][0] = pack2(o0[0], o0[1]); of[2 + h][1] = pack2(o0[2], o0[3]);
          of[2 + h][2] = pack2(o1[0], o1[1]); of[2 + h][3] = pack2(o1[2], o1[3]);
          ll_st(dst + (2 * hp + h) * 32, of[2 + h][0], of[2 + h][1], of[2 + h][2], of[2 + h][3], tag);
          const float2 wa = lds64(WB + co), wb = lds64(WB + co + 32);
          d0 = fmaf(o0[0], wa.x, d0); d0 = fmaf(o0[1], wa.y, d0); d0 = fmaf(o1[0], wb.x, d0); d0 = fmaf(o1[1], wb.y, d0);
          d1 = fmaf(o0[2], wa.x, d1); d1 = fmaf(o0[3], wa.y, d1); d1 = fmaf(o1[2], wb.x, d1); d1 = fmaf(o1[3], wb.y, d1);
        }
#pragma unroll
        for (int e = 0; e < 16; e++) aq[e] = aq[16 + e];
#pragma unroll
        for (int e = 0; e < 4; e++) {
          prev[0][e] = prev[1][e]; prev[2][e] = prev[3][e];
          lo[0][e] = lo[1][e]; lo[2][e] = lo[3][e];
          hi[0][e] = hi[1][e]; hi[2][e] = hi[3][e];
        }
      }
#pragma unroll
      for (int o = 1; o <= 2; o <<= 1) { d0 += __shfl_xor_sync(0xffffffffu, d0, o); d1 += __shfl_xor_sync(0xffffffffu, d1, o); }
      if (c == 0) ll_st(X->e2s + (xw * 8 + j) * 8 + r, __float_as_uint(d0), __float_as_uint(d1), 0, 0, tag);
    }
    PSTAMP(5);

    float ah[32];
    uint32_t sv[2][4];
    unpack32(ah, xres);
    {
      uint32_t og[2][14][4];
      const uint4* osrc[7];
#pragma unroll
      for (int i = 0; i < 7; i++) osrc[i] = xb + O_E2 + (xw * 32 + 4 * kb_at(i + 1, j)) * 32;
      const uint4* ssrc = X->e2s + (xw * 8 + 2 * c) * 8 + r;
      auto oissue = [&](int hp) {
#pragma unroll
        for (int i = 0; i < 14; i++) ll_ld(og[hp][i], osrc[i >> 1] + (2 * hp + (i & 1)) * 32);
        if (hp == 1) ll_issue<2>(sv, ssrc, 8);
      };
      auto omma = [&](int hp) {
        ll_clear<14>(og[hp]);
        keep(og[hp]);
        wg_fence();
#pragma unroll
        for (int i = 0; i < 14; i++) wgmma_rs_n64(ah, og[hp][i], descB(H0) + kb_at((i >> 1) + 1, j) * 512 + (2 * hp + (i & 1)) * 128, 1);
        wg_commit();
      };
      mbar_wait(BAR + B_FWO * 8);
      keep(ah); keep(of);
      wg_fence();
#pragma unroll
      for (int k = 0; k < 4; k++) wgmma_rs_n64(ah, of[k], descB(H0) + j * 512 + k * 128, 1);
      wg_commit();
      uint32_t it = 0;
#pragma unroll 1
      do { oissue(0); } while (ll_bad<14>(og[0], tag) && ++it < SPIN_LIMIT);
      PSTAMP(6);
      oissue(1);
      omma(0);
      const uint32_t tg = pin(tag, zero);
      if (__builtin_expect(ll_any(ll_acc<14>(og[1], tg, ll_acc<2>(sv, tg))), 0)) {
#pragma unroll 1
        do { oissue(1); } while (ll_any(ll_acc<14>(og[1], tag, ll_acc<2>(sv, tag))) && ++it < SPIN_LIMIT);
      }
      PSTAMP(16);
      omma(1);
      ll_clear<2>(sv);
    }
    float m0 = __uint_as_float(sv[0][0]) + __uint_as_float(sv[1][0]), m1 = __uint_as_float(sv[0][1]) + __uint_as_float(sv[1][1]);
#pragma unroll
    for (int o = 1; o <= 2; o <<= 1) { m0 += __shfl_xor_sync(0xffffffffu, m0, o); m1 += __shfl_xor_sync(0xffffffffu, m1, o); }
    const uint32_t mu0 = pack2(m0 + st0.x, m0 + st0.x), mu1 = pack2(m1 + st1.x, m1 + st1.x);
    wg_wait<0>();
    keep(ah);
    if (lane == 0) mbar_arrive(BAR + B_WODONE * 8);
    PSTAMP(7);

    uint32_t hf[4][4], ra[4][4];
    pack32(hf, ah);
    {
      uint4* dst = xb + O_E3H + (xw * 32 + 4 * j) * 32;
#pragma unroll
      for (int u = 0; u < 4; u++) {
        ra[u][0] = hsub2(hf[u][0], mu0); ra[u][1] = hsub2(hf[u][1], mu1);
        ra[u][2] = hsub2(hf[u][2], mu0); ra[u][3] = hsub2(hf[u][3], mu1);
        ll_st(dst + u * 32, ra[u][0], ra[u][1], ra[u][2], ra[u][3], tag);
      }
      float s0 = 0.f, q0 = 0.f, s1 = 0.f, q1 = 0.f;
#pragma unroll
      for (int b = 0; b < 8; b++) {
        s0 += ah[4 * b] + ah[4 * b + 1]; s1 += ah[4 * b + 2] + ah[4 * b + 3];
        q0 = fmaf(ah[4 * b], ah[4 * b], q0); q0 = fmaf(ah[4 * b + 1], ah[4 * b + 1], q0);
        q1 = fmaf(ah[4 * b + 2], ah[4 * b + 2], q1); q1 = fmaf(ah[4 * b + 3], ah[4 * b + 3], q1);
      }
#pragma unroll
      for (int o = 1; o <= 2; o <<= 1) {
        s0 += __shfl_xor_sync(0xffffffffu, s0, o); q0 += __shfl_xor_sync(0xffffffffu, q0, o);
        s1 += __shfl_xor_sync(0xffffffffu, s1, o); q1 += __shfl_xor_sync(0xffffffffu, q1, o);
      }
      if (c == 0) ll_st(X->e3s + (xw * 8 + j) * 8 + r, __float_as_uint(s0), __float_as_uint(q0), __float_as_uint(s1), __float_as_uint(q1), tag);
      mbar_wait(BAR + (p == 0 ? B_EQ + 7 : B_WODONE) * 8);
    }
    PSTAMP(8);

    float rs0, rs1;
    auto swiglu = [&](float g0, float g1, float u0, float u1, float rs) -> uint32_t {
      const float hr = 0.5f * rs;
      const float x0 = g0 * hr, x1 = g1 * hr;
      const float t0 = tanhf_hw(x0), t1 = tanhf_hw(x1);
      return pack2(fmaf(x0, t0, x0) * (u0 * rs), fmaf(x1, t1, x1) * (u1 * rs));
    };
    uint32_t hA[6][4];
    {
      float a1[64], a2[32];
      const uint4* src = xb + O_E3H + xw * 32 * 32;
      uint32_t rb[4][4], rc[4][4], rd[4][4];
      auto fetch = [&](uint32_t (&a)[4][4], int i) { ll_issue<4>(a, src + kb_at(i, j) * 128, 32); };
      auto check = [&](uint32_t (&a)[4][4], uint32_t (&b)[4][4], int i) {
        const uint32_t tg = pin(tag, zero);
        if (__builtin_expect(ll_any(ll_acc<4>(a, tg, ll_acc<4>(b, tg))), 0)) {
          uint32_t it = 0;
#pragma unroll 1
          do { fetch(a, i); fetch(b, i + 1); } while (ll_any(ll_acc<4>(a, tag, ll_acc<4>(b, tag))) && ++it < SPIN_LIMIT);
        }
        ll_clear<4>(a); ll_clear<4>(b);
        keep(a); keep(b);
      };
      auto head = [&](uint32_t (&a)[4][4], int i) {
        mbar_wait(BAR + (B_FA + i) * 8);
        wg_fence();
        wgmma_rs_n64<DESC_HI64>(a2, a[0], descBh(RING + 16384) + (i & 3) * 1536, i);
        wgmma_rs_n128(a1, a[0], descB(RING) + (i & 3) * 1536, i);
        wg_commit();
#pragma unroll
        for (int u = 0; u < 4; u++) stsm4(Hn + w * 2048 + i * 8192 + (moff ^ (u << 5)), a[u]);
        wg_wait<1>();
        if (i > 0) mbar_arrive_if(BAR + (B_EA + i - 1) * 8, lane == 0);
      };
      auto rest = [&](uint32_t (&a)[4][4], int i) {
        wg_fence();
#pragma unroll
        for (int k = 1; k < 4; k++) {
          wgmma_rs_n64<DESC_HI64>(a2, a[k], descBh(RING + 16384) + (i & 3) * 1536 + k * 64, 1);
          wgmma_rs_n128(a1, a[k], descB(RING) + (i & 3) * 1536 + k * 128, 1);
        }
        wg_commit();
      };
      ll_clear<4>(ra);
      keep(ra);
      head(ra, 0); rest(ra, 0);
      ll_get<4>(rb, src + kb_at(1, j) * 128, 32, tag);
      keep(rb);
      PSTAMP(17);
      fetch(rc, 2); fetch(rd, 3);
      head(rb, 1); rest(rb, 1);
      check(rc, rd, 2);
      head(rc, 2); fetch(ra, 4); fetch(rb, 5); rest(rc, 2);
      head(rd, 3); rest(rd, 3);
      check(ra, rb, 4);
      head(ra, 4); fetch(rc, 6); fetch(rd, 7); ll_issue<2>(sv, X->e3s + (xw * 8 + 2 * c) * 8 + r, 8); rest(ra, 4);
      head(rb, 5); rest(rb, 5);
      check(rc, rd, 6);
      head(rc, 6); rest(rc, 6);
      head(rd, 7); rest(rd, 7);
      fence_async_smem();
      ll_wait<2>(sv, X->e3s + (xw * 8 + 2 * c) * 8 + r, 8, tag);
      float s0 = __uint_as_float(sv[0][0]) + __uint_as_float(sv[1][0]), q0 = __uint_as_float(sv[0][1]) + __uint_as_float(sv[1][1]);
      float s1 = __uint_as_float(sv[0][2]) + __uint_as_float(sv[1][2]), q1 = __uint_as_float(sv[0][3]) + __uint_as_float(sv[1][3]);
#pragma unroll
      for (int o = 1; o <= 2; o <<= 1) {
        s0 += __shfl_xor_sync(0xffffffffu, s0, o); q0 += __shfl_xor_sync(0xffffffffu, q0, o);
        s1 += __shfl_xor_sync(0xffffffffu, s1, o); q1 += __shfl_xor_sync(0xffffffffu, q1, o);
      }
      s0 *= 1.f / D_; s1 *= 1.f / D_;
      rs0 = rsqrtf(fmaxf(fmaf(-s0, s0, q0 * (1.f / D_)), 0.f) + 1e-5f);
      rs1 = rsqrtf(fmaxf(fmaf(-s1, s1, q1 * (1.f / D_)), 0.f) + 1e-5f);
      wg_wait<0>();
      keep(a1); keep(a2);
      if (lane == 0) mbar_arrive(BAR + (B_EA + 7) * 8);
      PSTAMP(9);
#pragma unroll
      for (int u = 0; u < 4; u++)
#pragma unroll
        for (int e = 0; e < 4; e++)
          hA[u][e] = swiglu(a1[8 * u + 2 * e], a1[8 * u + 2 * e + 1], a1[32 + 8 * u + 2 * e], a1[33 + 8 * u + 2 * e], (e & 1) ? rs1 : rs0);
#pragma unroll
      for (int u = 0; u < 2; u++)
#pragma unroll
        for (int e = 0; e < 4; e++)
          hA[4 + u][e] = swiglu(a2[8 * u + 2 * e], a2[8 * u + 2 * e + 1], a2[16 + 8 * u + 2 * e], a2[17 + 8 * u + 2 * e], (e & 1) ? rs1 : rs0);
      keep(hA);
      wg_bar(p);
    }
    PSTAMP(10);

    const uint32_t mbx = Hn + 32768 + w * 512 + lane * 16;
    auto send = [&](const uint32_t (&v)[4], uint32_t a, int part) {
      asm volatile("st.async.weak.shared::cluster.mbarrier::complete_tx::bytes.v4.b32 [%0], {%1,%2,%3,%4}, [%5];"
                   ::"r"(a + peer()), "r"(v[0]), "r"(v[1]), "r"(v[2]), "r"(v[3]), "r"(BAR + (B_HX + 2 * part + p) * 8 + peer()) : "memory");
    };
    uint32_t hB[8][4];
    {
      float ab[128];
      uint32_t db = descB(RING);
      const uint32_t dAn = descA(H1) - p * 4096;
      if (lane == 0 && w == 0) { mbar_expect_tx(BAR + (B_HX + p) * 8, 12288); mbar_expect_tx(BAR + (B_HX + 2 + p) * 8, 16384); }
#pragma unroll 1
      for (int i = 0; i < 8; i++) {
        mbar_wait(BAR + (B_FB + i) * 8);
        const uint32_t da = dAn + i * 512;
        wg_fence();
        wgmma_ss_n256(ab, da, db, i);
#pragma unroll
        for (int k = 1; k < 4; k++) wgmma_ss_n256(ab, da + k * 2, db + k * 128, 1);
        wg_commit();
        if (i == 7) {
          mbar_wait_cluster(BAR + (B_PF + p) * 8);
#pragma unroll
          for (int k = 0; k < 6; k++) send(hA[k], mbx + k * 2048, 0);
        }
        wg_wait<1>();
        mbar_arrive_if(BAR + (B_EB + i - 1) * 8, i > 0 && lane == 0);
        if (i == 6 && lane == 0) mbar_arrive_peer(BAR + (B_PF + p) * 8);
        db = db == descB(RING + 65536) ? descB(RING) : db + 2048;
      }
      wg_wait<0>();
      keep(ab);
      mbar_arrive_if(BAR + (B_EB + 7) * 8, lane == 0);
      if (lane == 0) mbar_arrive_peer(BAR + (B_PF + 2 + p) * 8);
      PSTAMP(11);
#pragma unroll
      for (int u = 0; u < 8; u++) {
        const int o = (u >> 2) * 64 + (u & 3) * 8;
#pragma unroll
        for (int e = 0; e < 4; e++)
          hB[u][e] = swiglu(ab[o + 2 * e], ab[o + 2 * e + 1], ab[o + 32 + 2 * e], ab[o + 33 + 2 * e], (e & 1) ? rs1 : rs0);
        if (u == 3) mbar_wait_cluster(BAR + (B_PF + 2 + p) * 8);
        if (u >= 4 && u < 4 + SEND_EARLY) send(hB[u - 4], mbx + (2 + u) * 2048, 1);
      }
      keep(hB);
    }
    PSTAMP(12);

    {
      float ya[32], y[32];
      uint32_t hP[14][4];
      const uint32_t offA = (j & 1) ? 256 : 0, offH = (j & 1) ? 0 : 1536;
      uint4* e4 = xb + O_E4 + g * 24576 + warp * 128;
      const uint32_t stg = H0 + p * 65536 + 28672 + (w >> 1) * 32768 + (w & 1) * 2048;
      auto mm = [&](float (&d)[32], int m, int k0, int k1) {
        if (k0 == 0) mbar_wait(BAR + (B_FT + m) * 8);
        const uint32_t T = descB(0) + (t_addr(m) >> 4);
        const uint32_t oA = w2_peer(m) ? 256 - offA : offA, oH = w2_peer(m) ? 1536 - offH : offH;
        wg_fence();
#pragma unroll
        for (int k = k0; k < k1; k++) {
          const uint32_t db = T + (k < 4 ? oA + k * 128 : k < 6 ? oH + (k - 4) * 128 : oA + 512 + (k - 6) * 128);
          if (w2_peer(m)) wgmma_rs_n64(d, hP[k], db, 1);
          else if (k < 6) wgmma_rs_n64(d, hA[k], db, k);
          else wgmma_rs_n64(d, hB[k - 6], db, 1);
        }
        wg_commit();
      };
      auto next = [&](float (&d)[32], int m, float (&dp)[32], int q) {
        mm(d, m, 0, 3);
        wg_wait<1>();
        keep(dp);
        mbar_arrive_if(BAR + (B_ET0 + q) * 8, lane == 0);
        uint4* dst = e4 + (((j + 2 + 2 * q) & 7) * 3 + q) * 1024;
#pragma unroll
        for (int u = 0; u < 4; u++)
          ll_st(dst + u * 32, pack2(dp[8 * u], dp[8 * u + 1]), pack2(dp[8 * u + 2], dp[8 * u + 3]),
                pack2(dp[8 * u + 4], dp[8 * u + 5]), pack2(dp[8 * u + 6], dp[8 * u + 7]), tag);
        if (q == 2) mbar_wait(BAR + (B_ET0 + 2) * 8);
        mm(d, m, 3, 14);
      };
#pragma unroll
      for (int i = 0; i < 4; i++) {
        const uint32_t a = i ? pin(mbx, zero) : mbx;
#pragma unroll
        for (int k = SEND_EARLY + (8 - SEND_EARLY) * i / 4; k < SEND_EARLY + (8 - SEND_EARLY) * (i + 1) / 4; k++) send(hB[k], a + (6 + k) * 2048, 1);
        if (i < 3) mm(ya, 0, 5 * i, i < 2 ? 5 * i + 5 : 14);
        else mm(y, 1, 0, 6);
      }
      mbar_wait_cluster(BAR + (B_HX + p) * 8);
#pragma unroll
      for (int k = 0; k < 6; k++) lds128(hP[k], mbx + k * 2048);
      mm(y, 1, 6, 14);
      keep(hP[0]); keep(hP[1]); keep(hP[2]); keep(hP[3]); keep(hP[4]); keep(hP[5]);
      mm(ya, 2, 0, 3);
      PSTAMP(18);
      mbar_wait_cluster(BAR + (B_HX + 2 + p) * 8);
      PSTAMP(24);
#pragma unroll
      for (int k = 6; k < 14; k++) lds128(hP[k], mbx + k * 2048);
      mm(ya, 2, 3, 6);
      keep(hP);
      mbar_arrive_if(BAR + (B_HC + p) * 8, lane == 0);
      mm(ya, 2, 6, 14);
      mbar_wait(BAR + B_CLR * 8);
      next(y, 3, ya, 0);
      PSTAMP(27);
      next(ya, 4, y, 1);
      mbar_arrive_if(BAR + (B_ET0 + 3) * 8, lane == 0);
      mm(ya, 5, 0, 14);
      PSTAMP(26);
      next(y, 6, ya, 2);
      PSTAMP(28);
      uint32_t in[4][4], lt[4][4];
      const uint4* insrc = e4 + j * 3 * 1024;
      mm(y, 7, 0, 7);
      ll_issue<4>(lt, insrc + 2048, 32);
      mm(y, 7, 7, 14);
      mbar_wait(BAR + B_FIN * 8);
      mbar_wait(BAR + (B_FIN + 1) * 8);
      wg_wait<0>();
      keep(y);
      PSTAMP(13);
      const uint32_t ident = (2 * c == r ? 0x3f80u : 0u) | (2 * c + 1 == r ? 0x3f800000u : 0u);
      auto acc = [&](const uint32_t (&v)[4][4]) {
#pragma unroll
        for (int u = 0; u < 4; u++) {
          mma1688_acc(*reinterpret_cast<float (*)[4]>(&y[8 * u]), v[u][0], v[u][1], ident);
          mma1688_acc(*reinterpret_cast<float (*)[4]>(&y[8 * u + 4]), v[u][2], v[u][3], ident);
        }
      };
      acc(hf);
#pragma unroll
      for (int q = 0; q < 2; q++) {
#pragma unroll
        for (int u = 0; u < 4; u++) lds128(in[u], t_addr(q + 1) + warp * 2048 + lane * 16 + u * 512);
        ll_wait<4>(in, insrc + q * 1024, 32, tag);
        acc(in);
      }
      PSTAMP(25);
      if (ll_bad<4>(lt, pin(tag, zero))) {
        ll_spin<4>(lt, insrc + 2048, 32, tag);
      }
      ll_clear<4>(lt);
      acc(lt);
      PSTAMP(14);
#pragma unroll
      for (int u = 0; u < 4; u++) {
        uint32_t o[4];
#pragma unroll
        for (int e = 0; e < 4; e++) o[e] = pack2(y[8 * u + 2 * e], y[8 * u + 2 * e + 1]);
        stsm4(stg + (moff ^ (u << 5)), o);
      }
      fence_async_smem();
      __syncwarp();
      if (elect_one()) {
        tma3d_store(&P.out, stg, 64 * j, p, g * 64 + 16 * w);
        asm volatile("cp.async.bulk.commit_group;" ::: "memory");
        asm volatile("cp.async.bulk.wait_group.read 0;" ::: "memory");
      }
      PSTAMP(15);
    }
  }
}

typedef CUresult (*EncodeFn)(CUtensorMap*, CUtensorMapDataType, cuuint32_t, void*, const cuuint64_t*, const cuuint64_t*,
                             const cuuint32_t*, const cuuint32_t*, CUtensorMapInterleave, CUtensorMapSwizzle,
                             CUtensorMapL2promotion, CUtensorMapFloatOOBfill);

void enc2d(EncodeFn f, CUtensorMap* m, const void* base, uint64_t cols, uint64_t rows, uint32_t bc, uint32_t br, CUtensorMapSwizzle sw) {
  cuuint64_t gd[2] = {cols, rows}, gs[1] = {cols * 2};
  cuuint32_t bd[2] = {bc, br}, es[2] = {1, 1};
  f(m, CU_TENSOR_MAP_DATA_TYPE_BFLOAT16, 2, const_cast<void*>(base), gd, gs, bd, es, CU_TENSOR_MAP_INTERLEAVE_NONE, sw,
    CU_TENSOR_MAP_L2_PROMOTION_L2_128B, CU_TENSOR_MAP_FLOAT_OOB_FILL_NONE);
}
void enc_par(EncodeFn f, CUtensorMap* m, const void* base, uint32_t pairs) {
  cuuint64_t gd[3] = {(cuuint64_t)D_, 2, (cuuint64_t)S_ / 2}, gs[2] = {D_ * 2, D_ * 4};
  cuuint32_t bd[3] = {64, 1, pairs}, es[3] = {1, 1, 1};
  f(m, CU_TENSOR_MAP_DATA_TYPE_BFLOAT16, 3, const_cast<void*>(base), gd, gs, bd, es, CU_TENSOR_MAP_INTERLEAVE_NONE,
    CU_TENSOR_MAP_SWIZZLE_128B, CU_TENSOR_MAP_L2_PROMOTION_L2_128B, CU_TENSOR_MAP_FLOAT_OOB_FILL_NONE);
}

}

extern "C" void kernel_launch(void* const* d_in, const int* in_sizes, int n_in, void* d_out, int out_size) {
  (void)in_sizes; (void)n_in; (void)out_size;
  static EncodeFn enc = nullptr;
  static Scratch* scratch = nullptr;
  if (!enc) {
    void* fn = nullptr;
    cudaDriverEntryPointQueryResult q;
    cudaGetDriverEntryPoint("cuTensorMapEncodeTiled", &fn, cudaEnableDefault, &q);
    enc = (EncodeFn)fn;
    cudaGetSymbolAddress((void**)&scratch, g_scratch);
    cudaFuncSetAttribute(fused_block_kernel, cudaFuncAttributeMaxDynamicSharedMemorySize, SMEM_BYTES);
  }
  Params P;
  const __nv_bfloat16* xp = (const __nv_bfloat16*)d_in[0];
  const __nv_bfloat16* wqkvp = (const __nv_bfloat16*)d_in[1];
  const __nv_bfloat16* wop = (const __nv_bfloat16*)d_in[2];
  P.w1p = (const __nv_bfloat16*)d_in[4];
  P.w3p = (const __nv_bfloat16*)d_in[5];
  P.w2p = (const __nv_bfloat16*)d_in[6];
  enc_par(enc, &P.x, xp, 64);
  enc_par(enc, &P.out, d_out, 16);
  enc2d(enc, &P.wqkv, wqkvp, 3 * D_, D_, 64, 64, CU_TENSOR_MAP_SWIZZLE_128B);
  enc2d(enc, &P.wo, wop, D_, D_, 64, 64, CU_TENSOR_MAP_SWIZZLE_128B);
  enc2d(enc, &P.w1, P.w1p, F_, D_, 64, 64, CU_TENSOR_MAP_SWIZZLE_128B);
  enc2d(enc, &P.w3, P.w3p, F_, D_, 64, 64, CU_TENSOR_MAP_SWIZZLE_128B);
  enc2d(enc, &P.w1h, P.w1p, F_, D_, 32, 64, CU_TENSOR_MAP_SWIZZLE_64B);
  enc2d(enc, &P.w3h, P.w3p, F_, D_, 32, 64, CU_TENSOR_MAP_SWIZZLE_64B);
  enc2d(enc, &P.w2, P.w2p, D_, F_, 64, 224, CU_TENSOR_MAP_SWIZZLE_128B);

  cudaLaunchConfig_t cfg = {};
  cfg.gridDim = dim3(128);
  cfg.blockDim = dim3(384);
  cfg.dynamicSmemBytes = SMEM_BYTES;
  cfg.stream = cudaStreamPerThread;
  cudaLaunchAttribute at[2];
  at[0].id = cudaLaunchAttributeCooperative;
  at[0].val.cooperative = 1;
  cfg.attrs = at;
  cfg.numAttrs = 1;
  at[1].id = cudaLaunchAttributeClusterDimension;
  at[1].val.clusterDim.x = 2; at[1].val.clusterDim.y = 1; at[1].val.clusterDim.z = 1;
  cfg.numAttrs = 2;
  cudaLaunchKernelEx(&cfg, fused_block_kernel, scratch, xp, wqkvp, wop, 0u, P);
}
```

```cpp
#include <cuda_runtime.h>
#include <cuda.h>
#include <cuda_bf16.h>
#include <stdint.h>
#include <stddef.h>

namespace {

constexpr int S_ = 2048, D_ = 512, F_ = 1792;
#define LAG_KB 3
#define E4_FIRST 7
#define PP_AHEAD 1
#define SIDE_KB 0
#define CLR_MODE 0
#define W2_HEAD 3
#define CLR_SLEEP 400
#define CMAP 2
#define E4_ON 1
#define E4_WHEN (B_EA + 7)
#define SEND_EARLY 2
#define CS_KB 3
#define WO_KB 3
#define GATHER_SLEEP 200
#define XO_DELAY 2

constexpr uint32_t SPIN_LIMIT = 1u << 18;

struct Scratch {
  uint4 e4[16 * 8 * 3 * 8 * 4 * 32];
  uint4 e2[16 * 2 * 4 * 32 * 32];
  uint4 e3h[16 * 2 * 4 * 32 * 32];
  uint4 e1[16 * 8 * 2 * 4 * 32];
  uint4 e2s[16 * 2 * 4 * 8 * 8];
  uint4 e3s[16 * 2 * 4 * 8 * 8];
  uint4 e0c[8 * 3 * 16 * 16];
  uint4 e0s[2048];
  uint4 e0w[8 * 64];
  unsigned epoch[128];
};
__device__ Scratch g_scratch;
#define PSTAMP(i)
#define PSTAMPW(slot, i)
#define W2STAMP(i)

struct alignas(64) Params {
  CUtensorMap x, out, wqkv, wo, w1, w3, w1h, w3h, w2;
  const __nv_bfloat16 *w1p, *w3p, *w2p;
};

constexpr uint32_t SB = 1024;
constexpr uint32_t H0 = SB;
constexpr uint32_t H1 = SB + 65536;
constexpr uint32_t RING = SB + 131072;
constexpr uint32_t BAR = SB + 229376;
constexpr uint32_t TAGS = BAR + 1016;
constexpr uint32_t CS = BAR + 1024;
constexpr uint32_t ST = CS + 768;
constexpr uint32_t WB = ST + 1024;
constexpr uint32_t SMEM_BYTES = 232448;
static_assert(WB + 256 <= SB + SMEM_BYTES, "smem");

enum : int {
  B_FX = 0,
  B_FKV = 16, B_FQ = 24, B_FWO = 32, B_FA = 40, B_FB = 48, B_FT = 56,
  B_EKV = 64, B_EQ = 72, B_EA = 80, B_EB = 88, B_ET0 = 96,
  B_WODONE = 103,
  B_WBAR = 39,
  B_FIN = 33,
  B_EX = 104,
  B_LAG = 112, B_READY = 113, B_PUB = 114, B_CLR = 115, B_CLR0 = 116, B_TAG = 117,
  B_HX = 35,
  B_PF = 118,
  B_HC = 122,
  B_CLR1 = 124
};

__device__ __forceinline__ uint32_t smem_u32(const void* p) { return (uint32_t)__cvta_generic_to_shared(p); }
__device__ __forceinline__ uint32_t own() { return (blockIdx.x & 1) << 24; }
__device__ __forceinline__ uint32_t peer() { return (~blockIdx.x & 1) << 24; }
__device__ __forceinline__ void mbar_init(uint32_t b, uint32_t c) { asm volatile("mbarrier.init.shared::cta.b64 [%0], %1;" ::"r"(b + own()), "r"(c) : "memory"); }
__device__ __forceinline__ void mbar_expect_tx(uint32_t b, uint32_t bytes) { asm volatile("mbarrier.arrive.expect_tx.shared::cta.b64 _, [%0], %1;" ::"r"(b + own()), "r"(bytes) : "memory"); }
__device__ __forceinline__ void mbar_arrive(uint32_t b) { asm volatile("mbarrier.arrive.shared::cta.b64 _, [%0];" ::"r"(b + own()) : "memory"); }
__device__ __forceinline__ void mbar_wait(uint32_t b) {
  asm volatile("{\n.reg .pred p;\n.reg .u32 c;\nmov.u32 c, 0;\nLW:\n.pragma \"nounroll\";\n"
               "mbarrier.try_wait.parity.shared::cta.b64 p, [%0], 0;\nadd.u32 c, c, 1;\nsetp.gt.or.u32 p, c, %1, p;\n@!p bra LW;\n}\n"
               ::"r"(b + own()), "n"(SPIN_LIMIT) : "memory");
}
__device__ __forceinline__ void mbar_arrive_peer(uint32_t b) {
  asm volatile("mbarrier.arrive.relaxed.cluster.shared::cluster.b64 _, [%0];" ::"r"(b + peer()) : "memory");
}
__device__ __forceinline__ void mbar_wait_cluster(uint32_t b) {
  asm volatile("{\n.reg .pred p;\n.reg .u32 c;\nmov.u32 c, 0;\nLW:\n.pragma \"nounroll\";\n"
               "mbarrier.try_wait.parity.acquire.cluster.shared::cta.b64 p, [%0], 0;\nadd.u32 c, c, 1;\nsetp.gt.or.u32 p, c, %1, p;\n@!p bra LW;\n}\n"
               ::"r"(b + own()), "n"(SPIN_LIMIT) : "memory");
}
__device__ __forceinline__ bool elect_one() {
  uint32_t p;
  asm volatile("{\n.reg .pred P;\nelect.sync _|P, 0xffffffff;\nselp.u32 %0, 1, 0, P;\n}\n" : "=r"(p));
  return p;
}
__device__ __forceinline__ void tma2d(uint32_t dst, const CUtensorMap* m, int c0, int c1, uint32_t bar) {
  dst += own(); bar += own();
  asm volatile("cp.async.bulk.tensor.2d.shared::cluster.global.mbarrier::complete_tx::bytes [%0], [%1, {%3, %4}], [%2];"
               ::"r"(dst), "l"(m), "r"(bar), "r"(c0), "r"(c1) : "memory");
}
__device__ __forceinline__ void tma3d(uint32_t dst, const CUtensorMap* m, int c0, int c1, int c2, uint32_t bar) {
  dst += own(); bar += own();
  asm volatile("cp.async.bulk.tensor.3d.shared::cluster.global.mbarrier::complete_tx::bytes [%0], [%1, {%3, %4, %5}], [%2];"
               ::"r"(dst), "l"(m), "r"(bar), "r"(c0), "r"(c1), "r"(c2) : "memory");
}
__device__ __forceinline__ void tma3d_store(const CUtensorMap* m, uint32_t src, int c0, int c1, int c2) {
  asm volatile("cp.async.bulk.tensor.3d.global.shared::cta.bulk_group [%0, {%2, %3, %4}], [%1];"
               ::"l"(m), "r"(src + own()), "r"(c0), "r"(c1), "r"(c2) : "memory");
}
__device__ __forceinline__ void l2_prefetch(const void* p, uint32_t bytes) {
  asm volatile("cp.async.bulk.prefetch.L2.global [%0], %1;" ::"l"(p), "r"(bytes) : "memory");
}
__device__ __forceinline__ void prefetch_map(const CUtensorMap* m) { asm volatile("prefetch.tensormap [%0];" ::"l"(m) : "memory"); }
__device__ __forceinline__ void fence_async_smem() { asm volatile("fence.proxy.async.shared::cta;" ::: "memory"); }
__device__ __forceinline__ void wg_fence() { asm volatile("wgmma.fence.sync.aligned;" ::: "memory"); }
__device__ __forceinline__ void wg_commit() { asm volatile("wgmma.commit_group.sync.aligned;" ::: "memory"); }
template <int N> __device__ __forceinline__ void wg_wait() { asm volatile("wgmma.wait_group.sync.aligned %0;" ::"n"(N) : "memory"); }
__device__ __forceinline__ void wg_bar(int p) {
  if (p == 0) asm volatile("bar.sync 1, 128;" ::: "memory"); else asm volatile("bar.sync 2, 128;" ::: "memory");
}
constexpr uint32_t DESC_HI128 = (1024 >> 4) | (1u << 30);
constexpr uint32_t DESC_HI64 = (512 >> 4) | (2u << 30);
__device__ __forceinline__ constexpr uint32_t descA(uint32_t addr) { return (addr >> 4) | (1u << 16); }
__device__ __forceinline__ constexpr uint32_t descB(uint32_t addr) { return (addr >> 4) | ((8192u >> 4) << 16); }
__device__ __forceinline__ constexpr uint32_t descBh(uint32_t addr) { return (addr >> 4) | ((4096u >> 4) << 16); }

__device__ __forceinline__ void wgmma_ss_n64(float (&d)[32], uint32_t da, uint32_t db, int sc) {
  asm volatile("{\n.reg .pred p;\n.reg .b64 da, db;\nsetp.ne.b32 p, %34, 0;\nmov.b64 da, {%32, %35};\nmov.b64 db, {%33, %35};\n"
    "wgmma.mma_async.sync.aligned.m64n64k16.f32.bf16.bf16 {%0, %1, %2, %3, %4, %5, %6, %7, %8, %9, %10, %11, %12, %13, %14, %15, %16, %17, %18, %19, %20, %21, %22, %23, %24, %25, %26, %27, %28, %29, %30, %31}, da, db, p, 1, 1, 0, 1;\n}\n"
    : "+f"(d[0]), "+f"(d[1]), "+f"(d[2]), "+f"(d[3]), "+f"(d[4]), "+f"(d[5]), "+f"(d[6]), "+f"(d[7]),
      "+f"(d[8]), "+f"(d[9]), "+f"(d[10]), "+f"(d[11]), "+f"(d[12]), "+f"(d[13]), "+f"(d[14]), "+f"(d[15]),
      "+f"(d[16]), "+f"(d[17]), "+f"(d[18]), "+f"(d[19]), "+f"(d[20]), "+f"(d[21]), "+f"(d[22]), "+f"(d[23]),
      "+f"(d[24]), "+f"(d[25]), "+f"(d[26]), "+f"(d[27]), "+f"(d[28]), "+f"(d[29]), "+f"(d[30]), "+f"(d[31])
    : "r"(da), "r"(db), "r"(sc), "n"(DESC_HI128));
}
__device__ __forceinline__ void wgmma_ss_n128(float (&d)[64], uint32_t da, uint32_t db, int sc) {
  asm volatile("{\n.reg .pred p;\n.reg .b64 da, db;\nsetp.ne.b32 p, %66, 0;\nmov.b64 da, {%64, %67};\nmov.b64 db, {%65, %67};\n"
    "wgmma.mma_async.sync.aligned.m64n128k16.f32.bf16.bf16 {%0, %1, %2, %3, %4, %5, %6, %7, %8, %9, %10, %11, %12, %13, %14, %15, %16, %17, %18, %19, %20, %21, %22, %23, %24, %25, %26, %27, %28, %29, %30, %31, %32, %33, %34, %35, %36, %37, %38, %39, %40, %41, %42, %43, %44, %45, %46, %47, %48, %49, %50, %51, %52, %53, %54, %55, %56, %57, %58, %59, %60, %61, %62, %63}, da, db, p, 1, 1, 0, 1;\n}\n"
    : "+f"(d[0]), "+f"(d[1]), "+f"(d[2]), "+f"(d[3]), "+f"(d[4]), "+f"(d[5]), "+f"(d[6]), "+f"(d[7]),
      "+f"(d[8]), "+f"(d[9]), "+f"(d[10]), "+f"(d[11]), "+f"(d[12]), "+f"(d[13]), "+f"(d[14]), "+f"(d[15]),
      "+f"(d[16]), "+f"(d[17]), "+f"(d[18]), "+f"(d[19]), "+f"(d[20]), "+f"(d[21]), "+f"(d[22]), "+f"(d[23]),
      "+f"(d[24]), "+f"(d[25]), "+f"(d[26]), "+f"(d[27]), "+f"(d[28]), "+f"(d[29]), "+f"(d[30]), "+f"(d[31]),
      "+f"(d[32]), "+f"(d[33]), "+f"(d[34]), "+f"(d[35]), "+f"(d[36]), "+f"(d[37]), "+f"(d[38]), "+f"(d[39]),
      "+f"(d[40]), "+f"(d[41]), "+f"(d[42]), "+f"(d[43]), "+f"(d[44]), "+f"(d[45]), "+f"(d[46]), "+f"(d[47]),
      "+f"(d[48]), "+f"(d[49]), "+f"(d[50]), "+f"(d[51]), "+f"(d[52]), "+f"(d[53]), "+f"(d[54]), "+f"(d[55]),
      "+f"(d[56]), "+f"(d[57]), "+f"(d[58]), "+f"(d[59]), "+f"(d[60]), "+f"(d[61]), "+f"(d[62]), "+f"(d[63])
    : "r"(da), "r"(db), "r"(sc), "n"(DESC_HI128));
}
__device__ __forceinline__ void wgmma_ss_n256(float (&d)[128], uint32_t da, uint32_t db, int sc) {
  asm volatile("{\n.reg .pred p;\n.reg .b64 da, db;\nsetp.ne.b32 p, %130, 0;\nmov.b64 da, {%128, %131};\nmov.b64 db, {%129, %131};\n"
    "wgmma.mma_async.sync.aligned.m64n256k16.f32.bf16.bf16 {%0, %1, %2, %3, %4, %5, %6, %7, %8, %9, %10, %11, %12, %13, %14, %15, %16, %17, %18, %19, %20, %21, %22, %23, %24, %25, %26, %27, %28, %29, %30, %31, %32, %33, %34, %35, %36, %37, %38, %39, %40, %41, %42, %43, %44, %45, %46, %47, %48, %49, %50, %51, %52, %53, %54, %55, %56, %57, %58, %59, %60, %61, %62, %63, %64, %65, %66, %67, %68, %69, %70, %71, %72, %73, %74, %75, %76, %77, %78, %79, %80, %81, %82, %83, %84, %85, %86, %87, %88, %89, %90, %91, %92, %93, %94, %95, %96, %97, %98, %99, %100, %101, %102, %103, %104, %105, %106, %107, %108, %109, %110, %111, %112, %113, %114, %115, %116, %117, %118, %119, %120, %121, %122, %123, %124, %125, %126, %127}, da, db, p, 1, 1, 0, 1;\n}\n"
    : "+f"(d[0]), "+f"(d[1]), "+f"(d[2]), "+f"(d[3]), "+f"(d[4]), "+f"(d[5]), "+f"(d[6]), "+f"(d[7]),
      "+f"(d[8]), "+f"(d[9]), "+f"(d[10]), "+f"(d[11]), "+f"(d[12]), "+f"(d[13]), "+f"(d[14]), "+f"(d[15]),
      "+f"(d[16]), "+f"(d[17]), "+f"(d[18]), "+f"(d[19]), "+f"(d[20]), "+f"(d[21]), "+f"(d[22]), "+f"(d[23]),
      "+f"(d[24]), "+f"(d[25]), "+f"(d[26]), "+f"(d[27]), "+f"(d[28]), "+f"(d[29]), "+f"(d[30]), "+f"(d[31]),
      "+f"(d[32]), "+f"(d[33]), "+f"(d[34]), "+f"(d[35]), "+f"(d[36]), "+f"(d[37]), "+f"(d[38]), "+f"(d[39]),
      "+f"(d[40]), "+f"(d[41]), "+f"(d[42]), "+f"(d[43]), "+f"(d[44]), "+f"(d[45]), "+f"(d[46]), "+f"(d[47]),
      "+f"(d[48]), "+f"(d[49]), "+f"(d[50]), "+f"(d[51]), "+f"(d[52]), "+f"(d[53]), "+f"(d[54]), "+f"(d[55]),
      "+f"(d[56]), "+f"(d[57]), "+f"(d[58]), "+f"(d[59]), "+f"(d[60]), "+f"(d[61]), "+f"(d[62]), "+f"(d[63]),
      "+f"(d[64]), "+f"(d[65]), "+f"(d[66]), "+f"(d[67]), "+f"(d[68]), "+f"(d[69]), "+f"(d[70]), "+f"(d[71]),
      "+f"(d[72]), "+f"(d[73]), "+f"(d[74]), "+f"(d[75]), "+f"(d[76]), "+f"(d[77]), "+f"(d[78]), "+f"(d[79]),
      "+f"(d[80]), "+f"(d[81]), "+f"(d[82]), "+f"(d[83]), "+f"(d[84]), "+f"(d[85]), "+f"(d[86]), "+f"(d[87]),
      "+f"(d[88]), "+f"(d[89]), "+f"(d[90]), "+f"(d[91]), "+f"(d[92]), "+f"(d[93]), "+f"(d[94]), "+f"(d[95]),
      "+f"(d[96]), "+f"(d[97]), "+f"(d[98]), "+f"(d[99]), "+f"(d[100]), "+f"(d[101]), "+f"(d[102]), "+f"(d[103]),
      "+f"(d[104]), "+f"(d[105]), "+f"(d[106]), "+f"(d[107]), "+f"(d[108]), "+f"(d[109]), "+f"(d[110]), "+f"(d[111]),
      "+f"(d[112]), "+f"(d[113]), "+f"(d[114]), "+f"(d[115]), "+f"(d[116]), "+f"(d[117]), "+f"(d[118]), "+f"(d[119]),
      "+f"(d[120]), "+f"(d[121]), "+f"(d[122]), "+f"(d[123]), "+f"(d[124]), "+f"(d[125]), "+f"(d[126]), "+f"(d[127])
    : "r"(da), "r"(db), "r"(sc), "n"(DESC_HI128));
}
template <uint32_t HI = DESC_HI128>
__device__ __forceinline__ void wgmma_rs_n64(float (&d)[32], const uint32_t (&a)[4], uint32_t db, int sc) {
  asm volatile("{\n.reg .pred p;\n.reg .b64 db;\nsetp.ne.b32 p, %37, 0;\nmov.b64 db, {%36, %38};\n"
    "wgmma.mma_async.sync.aligned.m64n64k16.f32.bf16.bf16 {%0, %1, %2, %3, %4, %5, %6, %7, %8, %9, %10, %11, %12, %13, %14, %15, %16, %17, %18, %19, %20, %21, %22, %23, %24, %25, %26, %27, %28, %29, %30, %31}, {%32, %33, %34, %35}, db, p, 1, 1, 1;\n}\n"
    : "+f"(d[0]), "+f"(d[1]), "+f"(d[2]), "+f"(d[3]), "+f"(d[4]), "+f"(d[5]), "+f"(d[6]), "+f"(d[7]),
      "+f"(d[8]), "+f"(d[9]), "+f"(d[10]), "+f"(d[11]), "+f"(d[12]), "+f"(d[13]), "+f"(d[14]), "+f"(d[15]),
      "+f"(d[16]), "+f"(d[17]), "+f"(d[18]), "+f"(d[19]), "+f"(d[20]), "+f"(d[21]), "+f"(d[22]), "+f"(d[23]),
      "+f"(d[24]), "+f"(d[25]), "+f"(d[26]), "+f"(d[27]), "+f"(d[28]), "+f"(d[29]), "+f"(d[30]), "+f"(d[31])
    : "r"(a[0]), "r"(a[1]), "r"(a[2]), "r"(a[3]), "r"(db), "r"(sc), "n"(HI));
}
template <uint32_t HI = DESC_HI128>
__device__ __forceinline__ void wgmma_rs_n128(float (&d)[64], const uint32_t (&a)[4], uint32_t db, int sc) {
  asm volatile("{\n.reg .pred p;\n.reg .b64 db;\nsetp.ne.b32 p, %69, 0;\nmov.b64 db, {%68, %70};\n"
    "wgmma.mma_async.sync.aligned.m64n128k16.f32.bf16.bf16 {%0, %1, %2, %3, %4, %5, %6, %7, %8, %9, %10, %11, %12, %13, %14, %15, %16, %17, %18, %19, %20, %21, %22, %23, %24, %25, %26, %27, %28, %29, %30, %31, %32, %33, %34, %35, %36, %37, %38, %39, %40, %41, %42, %43, %44, %45, %46, %47, %48, %49, %50, %51, %52, %53, %54, %55, %56, %57, %58, %59, %60, %61, %62, %63}, {%64, %65, %66, %67}, db, p, 1, 1, 1;\n}\n"
    : "+f"(d[0]), "+f"(d[1]), "+f"(d[2]), "+f"(d[3]), "+f"(d[4]), "+f"(d[5]), "+f"(d[6]), "+f"(d[7]),
      "+f"(d[8]), "+f"(d[9]), "+f"(d[10]), "+f"(d[11]), "+f"(d[12]), "+f"(d[13]), "+f"(d[14]), "+f"(d[15]),
      "+f"(d[16]), "+f"(d[17]), "+f"(d[18]), "+f"(d[19]), "+f"(d[20]), "+f"(d[21]), "+f"(d[22]), "+f"(d[23]),
      "+f"(d[24]), "+f"(d[25]), "+f"(d[26]), "+f"(d[27]), "+f"(d[28]), "+f"(d[29]), "+f"(d[30]), "+f"(d[31]),
      "+f"(d[32]), "+f"(d[33]), "+f"(d[34]), "+f"(d[35]), "+f"(d[36]), "+f"(d[37]), "+f"(d[38]), "+f"(d[39]),
      "+f"(d[40]), "+f"(d[41]), "+f"(d[42]), "+f"(d[43]), "+f"(d[44]), "+f"(d[45]), "+f"(d[46]), "+f"(d[47]),
      "+f"(d[48]), "+f"(d[49]), "+f"(d[50]), "+f"(d[51]), "+f"(d[52]), "+f"(d[53]), "+f"(d[54]), "+f"(d[55]),
      "+f"(d[56]), "+f"(d[57]), "+f"(d[58]), "+f"(d[59]), "+f"(d[60]), "+f"(d[61]), "+f"(d[62]), "+f"(d[63])
    : "r"(a[0]), "r"(a[1]), "r"(a[2]), "r"(a[3]), "r"(db), "r"(sc), "n"(HI));
}

template <int N> __device__ __forceinline__ void keep(float (&d)[N]) {
#pragma unroll
  for (int i = 0; i < N; i++) asm volatile("" : "+f"(d[i])::"memory");
}

__device__ __forceinline__ void keep(uint32_t (&d)[4]) { asm volatile("" : "+r"(d[0]), "+r"(d[1]), "+r"(d[2]), "+r"(d[3])::"memory"); }
template <int N> __device__ __forceinline__ void keep(uint32_t (&d)[N][4]) {
#pragma unroll
  for (int i = 0; i < N; i++) asm volatile("" : "+r"(d[i][0]), "+r"(d[i][1]), "+r"(d[i][2]), "+r"(d[i][3])::"memory");
}

__device__ __forceinline__ uint32_t pack2(float lo, float hi) {
  uint32_t r;
  asm("cvt.rn.bf16x2.f32 %0, %1, %2;" : "=r"(r) : "f"(hi), "f"(lo));
  return r;
}
__device__ __forceinline__ float bf_lo(uint32_t v) { return __uint_as_float(v << 16); }
__device__ __forceinline__ float bf_hi(uint32_t v) { return __uint_as_float(v & 0xffff0000u); }
__device__ __forceinline__ uint32_t hsub2(uint32_t a, uint32_t b) {
  uint32_t r;
  asm("sub.rn.bf16x2 %0, %1, %2;" : "=r"(r) : "r"(a), "r"(b));
  return r;
}
__device__ __forceinline__ uint32_t movm(uint32_t a) {
  uint32_t r;
  asm volatile("movmatrix.sync.aligned.m8n8.trans.b16 %0, %1;" : "=r"(r) : "r"(a));
  return r;
}
__device__ __forceinline__ void ldsm4(uint32_t (&v)[4], uint32_t a) {
  asm volatile("ldmatrix.sync.aligned.m8n8.x4.shared.b16 {%0,%1,%2,%3}, [%4];" : "=r"(v[0]), "=r"(v[1]), "=r"(v[2]), "=r"(v[3]) : "r"(a + own()) : "memory");
}
__device__ __forceinline__ void stsm4(uint32_t a, const uint32_t (&v)[4]) {
  asm volatile("stmatrix.sync.aligned.m8n8.x4.shared.b16 [%0], {%1,%2,%3,%4};" ::"r"(a + own()), "r"(v[0]), "r"(v[1]), "r"(v[2]), "r"(v[3]) : "memory");
}
__device__ __forceinline__ void mma16816(float (&d)[4], const uint32_t (&a)[4], uint32_t b0, uint32_t b1) {
  asm volatile("mma.sync.aligned.m16n8k16.row.col.f32.bf16.bf16.f32 {%0,%1,%2,%3}, {%4,%5,%6,%7}, {%8,%9}, {%10,%10,%10,%10};"
               : "=f"(d[0]), "=f"(d[1]), "=f"(d[2]), "=f"(d[3])
               : "r"(a[0]), "r"(a[1]), "r"(a[2]), "r"(a[3]), "r"(b0), "r"(b1), "f"(0.f));
}
__device__ __forceinline__ void mma1688_acc(float (&d)[4], uint32_t a0, uint32_t a1, uint32_t b0) {
  asm volatile("mma.sync.aligned.m16n8k8.row.col.f32.bf16.bf16.f32 {%0,%1,%2,%3}, {%4,%5}, {%6}, {%0,%1,%2,%3};"
               : "+f"(d[0]), "+f"(d[1]), "+f"(d[2]), "+f"(d[3]) : "r"(a0), "r"(a1), "r"(b0));
}
__device__ __forceinline__ float ex2(float x) { float y; asm("ex2.approx.ftz.f32 %0, %1;" : "=f"(y) : "f"(x)); return y; }
__device__ __forceinline__ float rcp(float x) { float y; asm("rcp.approx.ftz.f32 %0, %1;" : "=f"(y) : "f"(x)); return y; }
__device__ __forceinline__ float tanhf_hw(float x) { float y; asm("tanh.approx.f32 %0, %1;" : "=f"(y) : "f"(x)); return y; }
__device__ __forceinline__ uint32_t lds32(uint32_t a) { uint32_t v; asm volatile("ld.shared.u32 %0, [%1];" : "=r"(v) : "r"(a + own()) : "memory"); return v; }
__device__ __forceinline__ float2 lds64(uint32_t a) { float2 v; asm volatile("ld.shared.v2.f32 {%0,%1}, [%2];" : "=f"(v.x), "=f"(v.y) : "r"(a + own()) : "memory"); return v; }
__device__ __forceinline__ void lds128(uint32_t (&v)[4], uint32_t a) { asm volatile("ld.shared.v4.u32 {%0,%1,%2,%3}, [%4];" : "=r"(v[0]), "=r"(v[1]), "=r"(v[2]), "=r"(v[3]) : "r"(a + own()) : "memory"); }
__device__ __forceinline__ void sts128(uint32_t a, const uint32_t (&v)[4]) { asm volatile("st.shared.v4.u32 [%0], {%1,%2,%3,%4};" ::"r"(a + own()), "r"(v[0]), "r"(v[1]), "r"(v[2]), "r"(v[3]) : "memory"); }
__device__ __forceinline__ void ldg128_nc(uint32_t (&v)[4], const void* p) {
  asm volatile("ld.global.nc.L1::no_allocate.v4.u32 {%0,%1,%2,%3}, [%4];" : "=r"(v[0]), "=r"(v[1]), "=r"(v[2]), "=r"(v[3]) : "l"(p));
}
__device__ __forceinline__ uint32_t pin(uint32_t v, uint32_t zero) {
  asm volatile("{\n.reg .pred p;\n.reg .u32 c;\nmov.u32 c, %1;\nLP:\n.pragma \"nounroll\";\nsetp.eq.u32 p, c, 0;\n@p bra LD;\n"
               "nanosleep.u32 c;\nadd.u32 %0, %0, c;\nsub.u32 c, c, 1;\nbra LP;\nLD:\n}\n" : "+r"(v) : "r"(zero) : "memory");
  return v;
}
__device__ __forceinline__ void mbar_arrive_if(uint32_t b, bool cond) {
  asm volatile("{\n.reg .pred p;\nsetp.ne.u32 p, %1, 0;\n@p mbarrier.arrive.shared::cta.b64 _, [%0];\n}\n" ::"r"(b + own()), "r"((uint32_t)cond) : "memory");
}
__device__ __forceinline__ uint32_t ld_epoch(const unsigned* p) {
  uint32_t v;
  asm volatile("ld.relaxed.gpu.global.u32 %0, [%1];" : "=r"(v) : "l"(p) : "memory");
  return v;
}
__device__ __forceinline__ void ll_st(uint4* p, uint32_t a, uint32_t b, uint32_t c, uint32_t d, uint32_t tag) {
  asm volatile("st.relaxed.gpu.global.v4.b32 [%0], {%1, %2, %3, %4};" ::"l"(p), "r"((a & ~1u) | tag), "r"(b), "r"(c), "r"(d) : "memory");
}
__device__ __forceinline__ void ll_ld(uint32_t (&v)[4], const uint4* p) {
  asm volatile("{\n.reg .b128 t;\n.reg .b64 lo, hi;\nld.relaxed.gpu.global.b128 t, [%4];\nmov.b128 {lo, hi}, t;\n"
               "mov.b64 {%0, %1}, lo;\nmov.b64 {%2, %3}, hi;\n}\n"
               : "=r"(v[0]), "=r"(v[1]), "=r"(v[2]), "=r"(v[3]) : "l"(p) : "memory");
}
template <int N> __device__ __forceinline__ void ll_issue(uint32_t (&v)[N][4], const uint4* p, int stride) {
#pragma unroll
  for (int i = 0; i < N; i++) ll_ld(v[i], p + i * stride);
}
template <int N> __device__ __forceinline__ uint32_t ll_acc(const uint32_t (&v)[N][4], uint32_t tag, uint32_t acc = 0) {
#pragma unroll
  for (int i = 0; i < N; i++) asm("lop3.b32 %0, %1, %2, %0, 0xBE;" : "+r"(acc) : "r"(v[i][0]), "r"(tag));
  return acc;
}
__device__ __forceinline__ bool ll_any(uint32_t acc) { return __any_sync(0xffffffffu, acc & 1u); }
template <int N> __device__ __forceinline__ bool ll_bad(const uint32_t (&v)[N][4], uint32_t tag) { return ll_any(ll_acc<N>(v, tag)); }
template <int N> __device__ __forceinline__ void ll_clear(uint32_t (&v)[N][4]) {
#pragma unroll
  for (int i = 0; i < N; i++) v[i][0] &= ~1u;
}
template <int N> __device__ __forceinline__ void ll_spin(uint32_t (&v)[N][4], const uint4* p, int stride, uint32_t tag) {
  uint32_t it = 0;
#pragma unroll 1
  do { ll_issue<N>(v, p, stride); } while (ll_bad<N>(v, tag) && ++it < SPIN_LIMIT);
}
template <int N> __device__ __forceinline__ void ll_get(uint32_t (&v)[N][4], const uint4* p, int stride, uint32_t tag) {
  ll_spin<N>(v, p, stride, tag);
  ll_clear<N>(v);
}
template <int N> __device__ __forceinline__ void ll_wait(uint32_t (&v)[N][4], const uint4* p, int stride, uint32_t tag) {
  if (__builtin_expect(ll_bad<N>(v, tag), 0)) ll_spin<N>(v, p, stride, tag);
  ll_clear<N>(v);
}
__device__ __forceinline__ void unpack32(float (&d)[32], const uint32_t (&v)[4][4]) {
#pragma unroll
  for (int u = 0; u < 4; u++)
#pragma unroll
    for (int e = 0; e < 4; e++) { d[8 * u + 2 * e] = bf_lo(v[u][e]); d[8 * u + 2 * e + 1] = bf_hi(v[u][e]); }
}
__device__ __forceinline__ void pack32(uint32_t (&v)[4][4], const float (&d)[32]) {
#pragma unroll
  for (int u = 0; u < 4; u++)
#pragma unroll
    for (int e = 0; e < 4; e++) v[u][e] = pack2(d[8 * u + 2 * e], d[8 * u + 2 * e + 1]);
}
__device__ __forceinline__ uint32_t t_addr(int m) { return SB + ((0x01534620u >> (4 * m)) & 7u) * 32768u; }

__device__ __forceinline__ constexpr int w2_pass(int m) { return m < 4 ? m & 1 : m >> 1; }
__device__ __forceinline__ constexpr int w2_peer(int m) { return m < 4 ? m >> 1 : m & 1; }

__device__ __forceinline__ int kb_at(int i, int j) { return i == 0 ? j : (i - 1 + (i - 1 >= j ? 1 : 0)); }

__device__ __forceinline__ void init_bars(int set) {
  if (set >= 0 && elect_one()) {
    const uint32_t cnt = set < 5 ? 1 : 8;
#pragma unroll
    for (int i = 0; i < 8; i++) mbar_init(BAR + (24 + 8 * set + i) * 8, cnt);
    if (set == 9) {
#pragma unroll
      for (int i = 0; i < 9; i++) mbar_init(BAR + (B_EX + i) * 8, 4);
#pragma unroll
      for (int i = 0; i < 3; i++) mbar_init(BAR + (B_READY + i) * 8, i == 0 ? 2 : 3);
#pragma unroll
      for (int i = 0; i < 8; i++) mbar_init(BAR + (B_TAG + i) * 8, i < 1 ? 1 : i < 7 ? 4 : 3);
    }
    asm volatile("fence.mbarrier_init.release.cluster;" ::: "memory");
  }
  __syncwarp();
  asm volatile("barrier.cluster.arrive.relaxed.aligned;" ::: "memory");
  asm volatile("bar.arrive 4, 384;" ::: "memory");
  asm volatile("bar.sync 3, 384;" ::: "memory");
}

__global__ void __launch_bounds__(384, 1) fused_block_kernel(Scratch* __restrict__ X, const __nv_bfloat16* __restrict__ xp,
                                                             const __nv_bfloat16* __restrict__ wqkvp, const __nv_bfloat16* __restrict__ wop, const uint32_t zero,
                                                             const __grid_constant__ Params P) {
  extern __shared__ __align__(1024) uint8_t smem_raw[];
  if (smem_u32(smem_raw) != SB + own()) return;
  const int tid = threadIdx.x;
  const int warp = __shfl_sync(0xffffffffu, tid >> 5, 0);
  const int lane = tid & 31;
  const int cta = blockIdx.x;
  const int j = ((cta >> 1) & 1) * 4 + ((cta >> 4) & 1) * 2 + (cta & 1);
  const int g = ((cta >> 2) & 3) * 4 + (cta >> 5);

  if (warp >= 8) {
    asm volatile("setmaxnreg.dec.sync.aligned.u32 56;");
    if (warp == 8) {
      PSTAMPW(2, 0);
      const bool leader = elect_one();
      if (leader) {
        prefetch_map(&P.x); prefetch_map(&P.wqkv);
#pragma unroll
        for (int i = 0; i < 24; i++) mbar_init(BAR + i * 8, 1);
        asm volatile("fence.mbarrier_init.release.cluster;" ::: "memory");
      }
      __syncwarp();
      asm volatile("bar.arrive 3, 384;" ::: "memory");
      asm volatile("barrier.cluster.arrive.relaxed.aligned;" ::: "memory");
      auto ldx = [&](int p, int kb) {
        const uint32_t b = BAR + (B_FX + p * 8 + kb) * 8;
        mbar_expect_tx(b, 8192);
        tma3d(H0 + p * 65536 + kb * 8192, &P.x, kb * 64, p, g * 64, b);
      };
      auto ldkv = [&](int kb, int slot) {
        const uint32_t b = BAR + (B_FKV + kb) * 8, d = RING + slot * 16384;
        mbar_expect_tx(b, 16384);
        tma2d(d, &P.wqkv, 512 + 64 * j, kb * 64, b);
        tma2d(d + 8192, &P.wqkv, 1024 + 64 * j, kb * 64, b);
      };
      if (leader) {
#pragma unroll 1
        for (int i = 0; i < 8 + XO_DELAY; i++) {
          if (i < 8) ldx(0, i);
          if (i < 6) ldkv(i, i);
          if (i >= XO_DELAY) ldx(1, i - XO_DELAY);
        }
#pragma unroll
        for (int i = 0; i < 4; i++)
          asm volatile("cp.async.bulk.prefetch.tensor.2d.L2.global [%0, {%1, %2}];" ::"l"(&P.wqkv), "r"(512 + (i & 1) * 512 + 64 * j), "r"(384 + (i >> 1) * 64) : "memory");
        PSTAMPW(2, 2);
      }
      __syncwarp();
      asm volatile("bar.sync 4, 384;" ::: "memory");
      if (leader) {
        const int f0 = 224 * j + ((j & 1) ? 32 : 0);
        const int fh = 224 * j + ((j & 1) ? 0 : 192);
        prefetch_map(&P.wo); prefetch_map(&P.w1); prefetch_map(&P.w3); prefetch_map(&P.w1h);
        prefetch_map(&P.w3h); prefetch_map(&P.w2); prefetch_map(&P.out);
#pragma unroll 1
        for (int i = 0; i < 2; i++) { mbar_wait(BAR + (B_EKV + i) * 8); ldkv(6 + i, i); }
#pragma unroll 1
        for (int i = 0; i < 8; i++) {
          const uint32_t b = BAR + (B_FQ + i) * 8;
          mbar_wait(BAR + (B_EKV + 2 + (i >> 1)) * 8);
          mbar_expect_tx(b, 8192);
          tma2d(RING + (4 + i) * 8192, &P.wqkv, 64 * j, i * 64, b);
        }
        mbar_expect_tx(BAR + B_FWO * 8, 65536);
#pragma unroll 1
        for (int i = 0; i < 8; i++) {
          const int kb = (i + 1) & 7;
          mbar_wait(BAR + (B_EX + i) * 8);
          tma2d(H0 + kb * 8192, &P.wo, 64 * j, kb * 64, BAR + B_FWO * 8);
        }
#pragma unroll 1
        for (int i = 0; i < 8; i++) {
          const uint32_t b = BAR + (B_FA + i) * 8, d = RING + (i & 3) * 24576;
          const int k0 = kb_at(i, j) * 64;
          mbar_wait(BAR + (B_EKV + 7 + ((0xCBA98520u >> (4 * i)) & 15)) * 8);
          mbar_expect_tx(b, 24576);
          tma2d(d, &P.w1, f0, k0, b);
          tma2d(d + 8192, &P.w3, f0, k0, b);
          tma2d(d + 16384, &P.w1h, fh, k0, b);
          tma2d(d + 20480, &P.w3h, fh, k0, b);
        }
        uint32_t d = RING;
#pragma unroll 1
        for (int i = 0; i < 8; i++) {
          const uint32_t b = BAR + (B_FB + i) * 8;
          const int k0 = kb_at(i, j) * 64;
          mbar_wait(BAR + (B_EA + 5 + i) * 8);
          mbar_expect_tx(b, 32768);
          tma2d(d, &P.w1, f0 + 64, k0, b);
          tma2d(d + 8192, &P.w3, f0 + 64, k0, b);
          tma2d(d + 16384, &P.w1, f0 + 128, k0, b);
          tma2d(d + 24576, &P.w3, f0 + 128, k0, b);
          d = d == RING + 65536 ? RING : d + 32768;
        }
#pragma unroll 1
        for (int i = 0; i < 8; i++) {
          const int m = (0x76453210u >> (4 * i)) & 7;
          const uint32_t b = BAR + (B_FT + m) * 8;
          mbar_wait(BAR + (i < 5 ? B_EB + 3 + i : i < 7 ? B_HC - 5 + i : B_ET0) * 8);
          mbar_expect_tx(b, 28672);
          tma2d(t_addr(m), &P.w2, 64 * ((j + 2 + 2 * w2_pass(m)) & 7), 224 * (j ^ w2_peer(m)), b);
          PSTAMPW(2, 4 + i);
        }
#pragma unroll 1
        for (int q = 0; q < 2; q++) {
          mbar_expect_tx(BAR + (B_FIN + q) * 8, 16384);
          mbar_wait(BAR + (B_ET0 + 3 - q) * 8);
          PSTAMPW(2, 24 + q);
          asm volatile("cp.async.bulk.shared::cluster.global.mbarrier::complete_tx::bytes [%0], [%1], 16384, [%2];"
                       ::"r"(t_addr(q + 1) + own()), "l"(X->e4 + ((g * 8 + j) * 3 + q) * 1024), "r"(BAR + (B_FIN + q) * 8 + own()) : "memory");
        }
        X->epoch[cta] = X->epoch[cta] + 1;
      }
    } else {
      const int part = warp - 9;
      uint32_t tag;
      if (part == 2) {
        tag = ld_epoch(X->epoch + cta);
        init_bars(-1);
        tag = (tag + 1) & 1;
        if (lane == 0) {
          asm volatile("st.shared.u32 [%0], %1;" ::"r"(TAGS + own()), "r"(tag) : "memory");
          mbar_arrive(BAR + B_TAG * 8);
        }
      } else {
        init_bars(warp - 1);
        mbar_wait(BAR + B_TAG * 8);
        tag = lds32(TAGS);
      }
      PSTAMPW(3, 16 + part);
      auto clear8 = [&](uint4* p, int stride) {
#pragma unroll
        for (int i = 0; i < 8; i++) ll_st(p + i * stride + lane, 0, 0, 0, 0, tag ^ 1);
      };
      if (part == 0 && lane < 20)
        ll_st(lane < 16 ? X->e0s + g * 128 + 16 * j + lane : X->e0w + j * 64 + g * 4 + lane - 16, 0, 0, 0, 0, tag ^ 1);
      if (lane < 16) ll_st(X->e0c + ((j * 3 + part) * 16 + g) * 16 + lane, 0, 0, 0, 0, tag ^ 1);
      __syncwarp();
      if (lane == 0) mbar_arrive(BAR + B_CLR1 * 8);
      uint32_t v[8][4];
      {
        float s[4] = {0.f, 0.f, 0.f, 0.f}, q[4] = {0.f, 0.f, 0.f, 0.f};
        const uint32_t xa = H0 + ((lane >> 1) & 1) * 65536 + (8 * j + (lane >> 2)) * 128 + (lane & 1) * 64 + ((lane >> 1) & 3) * 16;
#pragma unroll 1
        for (int kb = part; kb < 8; kb += 3) {
          mbar_wait(BAR + (B_FX + kb) * 8);
          mbar_wait(BAR + (B_FX + 8 + kb) * 8);
          if (kb == 3 && lane == 0) l2_prefetch(wop + (size_t)(j * 64 + g * 4) * D_, 4096);
#pragma unroll
          for (int i = 0; i < 4; i++) lds128(v[i], (xa + kb * 8192) ^ (i * 16));
#pragma unroll
          for (int e = 0; e < 16; e++) {
            const float a = bf_lo(v[e >> 2][e & 3]), b = bf_hi(v[e >> 2][e & 3]);
            s[e & 3] += a + b; q[e & 3] = fmaf(a, a, q[e & 3]); q[e & 3] = fmaf(b, b, q[e & 3]);
          }
        }
        float ss = (s[0] + s[1]) + (s[2] + s[3]), qq = (q[0] + q[1]) + (q[2] + q[3]);
        ss += __shfl_xor_sync(0xffffffffu, ss, 1); qq += __shfl_xor_sync(0xffffffffu, qq, 1);
        if (part && !(lane & 1))
          asm volatile("st.shared.v2.f32 [%0], {%1,%2};" ::"r"(WB + own() + part * 128 - 128 + lane * 4), "f"(ss), "f"(qq) : "memory");
        if (part) asm volatile("bar.arrive 5, 96;" ::: "memory");
        else {
          asm volatile("bar.sync 5, 96;" ::: "memory");
          const float2 t1 = lds64(WB + (lane >> 1) * 8), t2 = lds64(WB + 128 + (lane >> 1) * 8);
          const float mean = (ss + t1.x + t2.x) * (1.f / D_);
          const float rs = rsqrtf(fmaxf(fmaf(-mean, mean, (qq + t1.y + t2.y) * (1.f / D_)), 0.f) + 1e-5f);
          if (!(lane & 1)) ll_st(X->e0s + g * 128 + 16 * j + (lane >> 1), __float_as_uint(mean), __float_as_uint(rs), 0, 0, tag);
        }
      }
      PSTAMPW(3, part * 4 + 2);
      if (lane == 0) l2_prefetch(part == 0 ? P.w2p + (size_t)cta * 14 * D_ : (part == 1 ? P.w1p : P.w3p) + (size_t)cta * 4 * F_, 14336);
      if (part == 0) {
        const __nv_bfloat16* wr = wop + (size_t)(j * 64 + g * 4 + (lane >> 3)) * D_ + (lane & 7) * 8;
#pragma unroll
        for (int i = 0; i < 8; i++) ldg128_nc(v[i], wr + i * 64);
        float s[4];
#pragma unroll
        for (int e = 0; e < 4; e++) {
          s[e] = 0.f;
#pragma unroll
          for (int i = 0; i < 8; i++) s[e] += bf_lo(v[i][e]) + bf_hi(v[i][e]);
        }
        float ss = (s[0] + s[1]) + (s[2] + s[3]);
#pragma unroll
        for (int o = 1; o <= 4; o <<= 1) ss += __shfl_xor_sync(0xffffffffu, ss, o);
        if ((lane & 7) == 0) ll_st(X->e0w + j * 64 + g * 4 + (lane >> 3), __float_as_uint(ss * (1.f / D_)), 0, 0, 0, tag);
      }
      PSTAMPW(3, part * 4 + 0);
      {
        uint32_t u[2][4];
        const uint4* us = (part == 0 ? X->e0w + j * 64 : X->e0s + g * 128 + (part - 1) * 64) + lane;
        const uint4* vs = X->e0c + ((j * 3 + part) * 16 + (lane >> 4) * 8) * 16 + (lane & 15);
        uint32_t it = 0;
#pragma unroll 1
        do { ll_issue<2>(u, us, 32); ll_issue<8>(v, vs, 16); } while (ll_any(ll_acc<8>(v, tag, ll_acc<2>(u, tag))) && ++it < SPIN_LIMIT);
        ll_clear<2>(u); ll_clear<8>(v);
#pragma unroll
        for (int i = 0; i < 2; i++) {
          if (part == 0) asm volatile("st.shared.u32 [%0], %1;" ::"r"(WB + own() + (i * 32 + lane) * 4), "r"(u[i][0]) : "memory");
          else asm volatile("st.shared.v2.u32 [%0], {%1,%2};" ::"r"(ST + own() + (part * 64 - 64 + i * 32 + lane) * 8), "r"(u[i][0]), "r"(u[i][1]) : "memory");
        }
        uint32_t o[4];
#pragma unroll
        for (int e = 0; e < 4; e++) {
          float s = 0.f;
#pragma unroll
          for (int i = 0; i < 8; i++) s += __uint_as_float(v[i][e]);
          o[e] = __float_as_uint(s + __shfl_xor_sync(0xffffffffu, s, 16));
        }
        if (lane < 16) sts128(CS + (part * 64 + lane * 4) * 4, o);
      }
      __syncwarp();
      if (lane == 0) mbar_arrive(BAR + (part == 0 ? B_WBAR : B_READY) * 8);
      PSTAMPW(3, part * 4 + 1);
      mbar_wait(BAR + (E4_WHEN) * 8);
#pragma unroll 1
      for (int u = 0; u < 4 * E4_ON; u++) {
        clear8(X->e4 + ((g * 8 + ((j + 2 + 2 * part) & 7)) * 3 + part) * 1024 + u * 32, 128);
        __nanosleep(CLR_SLEEP);
      }
      __syncwarp();
      if (lane == 0) mbar_arrive(BAR + B_CLR * 8);
      PSTAMPW(3, part * 4 + 3);
    }
  } else {
    const int p = warp >> 2, w = warp & 3;
    const int r = lane >> 2, c = lane & 3;
    init_bars(warp);
    asm volatile("setmaxnreg.inc.sync.aligned.u32 224;");
    PSTAMP(0);
    const uint32_t dAx = descA(H0) + p * 4096;
    const uint32_t Hn = H1 - p * 65536;
    const uint32_t moff = ((lane & 7) + ((lane >> 3) & 1) * 8) * 128 + (((lane >> 4) ^ (lane & 7)) << 4);
    const uint32_t Xw = H0 + p * 65536 + w * 2048;
    const int xw = (g * 2 + p) * 4 + w;
    uint32_t cv[8][4];
    if (p == 1) {
      mbar_wait(BAR + (B_FKV + SIDE_KB) * 8);
      const int wp = w < 3 ? w : 0;
      const __nv_bfloat16* wr = wqkvp + (size_t)(g * 32 + (lane >> 3) * 8) * (3 * D_) + wp * D_ + j * 64 + (lane & 7) * 8;
#pragma unroll
      for (int i = 0; i < 8; i++) ldg128_nc(cv[i], wr + (size_t)i * 3 * D_);
      mbar_wait(BAR + B_LAG * 8);
    }

    float akv[64];
    auto kvstep = [&](int kb) {
      mbar_wait(BAR + (B_FX + p * 8 + kb) * 8);
      mbar_wait(BAR + (B_FKV + kb) * 8);
      if (kb == 0) PSTAMP(2);
      const uint32_t da = dAx + kb * 512, db = descB(RING) + (kb < 6 ? kb : kb - 6) * 1024;
      wg_fence();
      wgmma_ss_n128(akv, da, db, kb);
#pragma unroll
      for (int k = 1; k < 4; k++) wgmma_ss_n128(akv, da + k * 2, db + k * 128, 1);
      wg_commit();
      mbar_arrive_if(BAR + B_LAG * 8, kb == LAG_KB - 1 && p == 0 && lane == 0);
      wg_wait<1>();
      mbar_arrive_if(BAR + (B_EKV + kb - 1) * 8, kb > 0 && lane == 0);
    };
#pragma unroll
    for (int kb = 0; kb < CS_KB; kb++) kvstep(kb);
    if (p == 1) {
      PSTAMP(29);
      mbar_wait(BAR + B_CLR1 * 8);
      const uint32_t tg = lds32(TAGS);
      const uint32_t hm = 0xffff0000u | (tg >> 1), sh = 16 + (tg >> 1);
      float cs[8];
#pragma unroll
      for (int e = 0; e < 4; e++) {
        float a = 0.f, b = 0.f;
#pragma unroll
        for (int i = 0; i < 8; i++) { a += __uint_as_float(cv[i][e] << sh); b += __uint_as_float(cv[i][e] & hm); }
        cs[2 * e] = a; cs[2 * e + 1] = b;
      }
      const bool up = lane & 8;
#pragma unroll
      for (int e = 0; e < 4; e++) {
        const float keepv = up ? cs[4 + e] : cs[e], give = up ? cs[e] : cs[4 + e];
        cs[e] = keepv + __shfl_xor_sync(0xffffffffu, give, 8);
        cs[e] += __shfl_xor_sync(0xffffffffu, cs[e], 16);
      }
      if (lane < 16 && w < 3)
        ll_st(X->e0c + ((j * 3 + w) * 16 + g) * 16 + (lane & 7) * 2 + (lane >> 3), __float_as_uint(cs[0]), __float_as_uint(cs[1]),
              __float_as_uint(cs[2]), __float_as_uint(cs[3]), tg);
      PSTAMP(1);
    }
#pragma unroll 1
    for (int kb = CS_KB; kb < 8; kb++) kvstep(kb);
    asm volatile("barrier.cluster.wait.aligned;" ::: "memory");
    uint32_t xres[4][4];
#pragma unroll
    for (int u = 0; u < 4; u++) ldsm4(xres[u], Xw + j * 8192 + (moff ^ (u << 5)));

    float aq[32];
    auto qstep = [&](int kb) {
      mbar_wait(BAR + (B_FQ + kb) * 8);
      const uint32_t da = dAx + kb * 512, db = descB(RING + 32768) + kb * 512;
      wg_fence();
      wgmma_ss_n64(aq, da, db, kb);
#pragma unroll
      for (int k = 1; k < 4; k++) wgmma_ss_n64(aq, da + k * 2, db + k * 128, 1);
      wg_commit();
      wg_wait<1>();
      mbar_arrive_if(BAR + (B_EQ + kb - 1) * 8, lane == 0);
      mbar_arrive_if(BAR + (B_EX + kb - 2) * 8, lane == 0 && p == 0 && kb >= 2);
    };
    qstep(0);
    keep(akv);
    PSTAMP(3);
    qstep(1);
    mbar_wait(BAR + B_READY * 8);
    PSTAMP(19);
    const uint32_t tag = lds32(TAGS);
    uint4* const xb = reinterpret_cast<uint4*>(X) + lane + (tag >> 1);
    constexpr int O_E4 = offsetof(Scratch, e4) / 16, O_E2 = offsetof(Scratch, e2) / 16, O_E3H = offsetof(Scratch, e3h) / 16;
    const float2 st0 = lds64(ST + (2 * (16 * w + r) + p) * 8);
    const float2 st1 = lds64(ST + (2 * (16 * w + r + 8) + p) * 8);
    uint32_t hi[4][4], lo[4][4];
    {
      float2 cs[16];
      auto cvt = [&](uint32_t (&d)[4][4], int b0, int ofs, const float2& st) {
#pragma unroll
        for (int b = b0; b < b0 + 8; b++) {
          if (ofs == 2) cs[b] = lds64(CS + (64 + b * 8 + 2 * c) * 4);
          const uint32_t v = pack2(fmaf(-st.x, cs[b].x, akv[4 * b + ofs]) * st.y, fmaf(-st.x, cs[b].y, akv[4 * b + ofs + 1]) * st.y);
          d[b >> 2][b & 3] = b < 8 ? v : movm(v);
        }
      };
      cvt(hi, 0, 2, st1);
      keep(hi[0]); keep(hi[1]);
      qstep(2);
      cvt(hi, 8, 2, st1);
      if (w == 3 && g < 15) {
        uint4* dst = X->e1 + ((g * 8 + j) * 2 + p) * 128 + lane;
#pragma unroll
        for (int i = 0; i < 4; i++) ll_st(dst + i * 32, hi[i][0], hi[i][1], hi[i][2], hi[i][3], tag);
      }
      PSTAMP(20);
      wg_bar(p);
#pragma unroll
      for (int i = 0; i < 4; i++) sts128(Xw + lane * 16 + i * 512, hi[i]);
      qstep(3);
      cvt(lo, 0, 0, st0);
      keep(lo[0]); keep(lo[1]);
      qstep(4);
      cvt(lo, 8, 0, st0);
    }
    PSTAMP(21);
    wg_bar(p);
    uint32_t prev[4][4];
    if (w > 0) {
#pragma unroll
      for (int i = 0; i < 4; i++) lds128(prev[i], Xw - 2048 + lane * 16 + i * 512);
    }
    if (p == 0) {
      asm volatile("fence.proxy.async.shared::cta;" ::: "memory");
      __syncwarp();
      if (lane == 0) mbar_arrive(BAR + (B_EX + 7) * 8);
    }
    PSTAMP(22);
    const uint4* halo = X->e1 + (((g - 1) * 8 + j) * 2 + p) * 128 + lane;
    const bool use_halo = w == 0 && g > 0;
    qstep(5);
    if (use_halo) ll_issue<4>(prev, halo, 32);
    qstep(6);
    qstep(7);
    PSTAMP(23);
    if (w == 0) {
      if (g > 0) {
        if (__builtin_expect(ll_bad<4>(prev, pin(tag, zero)), 0)) ll_spin<4>(prev, halo, 32, tag);
        ll_clear<4>(prev);
      } else {
#pragma unroll
        for (int i = 0; i < 4; i++)
#pragma unroll
          for (int e = 0; e < 4; e++) prev[i][e] = 0;
      }
    }
    wg_wait<0>();
    keep(aq);
    mbar_arrive_if(BAR + (B_EQ + 7) * 8, lane == 0);
    mbar_arrive_if(BAR + (B_EX + 6) * 8, lane == 0 && p == 0);
    PSTAMP(4);

    uint32_t of[4][4];
    mbar_wait(BAR + B_WBAR * 8);
    {
      const float sc = 0.25f * 1.4426950408889634f;
      const float nohalo = (g == 0 && w == 0) ? -INFINITY : 0.f;
      const bool up0 = 2 * c > r, up1 = 2 * c + 1 > r;
      const uint32_t mup = (up0 ? 0xffffu : 0u) | (up1 ? 0xffff0000u : 0u);
      uint4* dst = xb + O_E2 + (xw * 32 + 4 * j) * 32;
      float d0 = 0.f, d1 = 0.f;
#pragma unroll 1
      for (int hp = 0; hp < 2; hp++) {
#pragma unroll
        for (int e = 0; e < 4; e++) { of[0][e] = of[2][e]; of[1][e] = of[3][e]; }
#pragma unroll
        for (int h = 0; h < 2; h++) {
          uint32_t qf[4];
          const uint32_t co = (32 * hp + 16 * h + 2 * c) * 4;
          {
            const float2 ca = lds64(CS + co), cb = lds64(CS + co + 32);
            qf[0] = pack2(fmaf(-st0.x, ca.x, aq[8 * h + 0]) * st0.y, fmaf(-st0.x, ca.y, aq[8 * h + 1]) * st0.y);
            qf[1] = pack2(fmaf(-st1.x, ca.x, aq[8 * h + 2]) * st1.y, fmaf(-st1.x, ca.y, aq[8 * h + 3]) * st1.y);
            qf[2] = pack2(fmaf(-st0.x, cb.x, aq[8 * h + 4]) * st0.y, fmaf(-st0.x, cb.y, aq[8 * h + 5]) * st0.y);
            qf[3] = pack2(fmaf(-st1.x, cb.x, aq[8 * h + 6]) * st1.y, fmaf(-st1.x, cb.y, aq[8 * h + 7]) * st1.y);
          }
          const int e0 = 2 * h;
          float sp[4], sl[4], sh[4];
          mma16816(sp, qf, prev[0][e0], prev[0][e0 + 1]);
          mma16816(sl, qf, lo[0][e0], lo[0][e0 + 1]);
          mma16816(sh, qf, hi[0][e0], hi[0][e0 + 1]);
          float a0 = up0 ? sp[0] + nohalo : sl[0], a1 = up1 ? sp[1] + nohalo : sl[1];
          float b0 = up0 ? sl[2] : sh[2], b1 = up1 ? sl[3] : sh[3];
          float ma = fmaxf(a0, a1), mb = fmaxf(b0, b1);
          ma = fmaxf(ma, __shfl_xor_sync(0xffffffffu, ma, 1)); mb = fmaxf(mb, __shfl_xor_sync(0xffffffffu, mb, 1));
          ma = fmaxf(ma, __shfl_xor_sync(0xffffffffu, ma, 2)); mb = fmaxf(mb, __shfl_xor_sync(0xffffffffu, mb, 2));
          a0 = ex2((a0 - ma) * sc); a1 = ex2((a1 - ma) * sc); b0 = ex2((b0 - mb) * sc); b1 = ex2((b1 - mb) * sc);
          float sa = a0 + a1, sbb = b0 + b1;
          sa += __shfl_xor_sync(0xffffffffu, sa, 1); sbb += __shfl_xor_sync(0xffffffffu, sbb, 1);
          sa += __shfl_xor_sync(0xffffffffu, sa, 2); sbb += __shfl_xor_sync(0xffffffffu, sbb, 2);
          const float ia = rcp(sa), ib = rcp(sbb);
          const uint32_t pa = pack2(a0 * ia, a1 * ia), pb = pack2(b0 * ib, b1 * ib);
          const uint32_t pf[4] = {pa & mup, 0u, pa & ~mup, pb & mup};
          const uint32_t ph = pb & ~mup;
          float o0[4], o1[4];
          mma16816(o0, pf, prev[2][e0], lo[2][e0]);
          mma16816(o1, pf, prev[2][e0 + 1], lo[2][e0 + 1]);
          mma1688_acc(o0, 0u, ph, hi[2][e0]);
          mma1688_acc(o1, 0u, ph, hi[2][e0 + 1]);
          of[2 + h][0] = pack2(o0[0], o0[1]); of[2 + h][1] = pack2(o0[2], o0[3]);
          of[2 + h][2] = pack2(o1[0], o1[1]); of[2 + h][3] = pack2(o1[2], o1[3]);
          ll_st(dst + (2 * hp + h) * 32, of[2 + h][0], of[2 + h][1], of[2 + h][2], of[2 + h][3], tag);
          const float2 wa = lds64(WB + co), wb = lds64(WB + co + 32);
          d0 = fmaf(o0[0], wa.x, d0); d0 = fmaf(o0[1], wa.y, d0); d0 = fmaf(o1[0], wb.x, d0); d0 = fmaf(o1[1], wb.y, d0);
          d1 = fmaf(o0[2], wa.x, d1); d1 = fmaf(o0[3], wa.y, d1); d1 = fmaf(o1[2], wb.x, d1); d1 = fmaf(o1[3], wb.y, d1);
        }
#pragma unroll
        for (int e = 0; e < 16; e++) aq[e] = aq[16 + e];
#pragma unroll
        for (int e = 0; e < 4; e++) {
          prev[0][e] = prev[1][e]; prev[2][e] = prev[3][e];
          lo[0][e] = lo[1][e]; lo[2][e] = lo[3][e];
          hi[0][e] = hi[1][e]; hi[2][e] = hi[3][e];
        }
      }
#pragma unroll
      for (int o = 1; o <= 2; o <<= 1) { d0 += __shfl_xor_sync(0xffffffffu, d0, o); d1 += __shfl_xor_sync(0xffffffffu, d1, o); }
      if (c == 0) ll_st(X->e2s + (xw * 8 + j) * 8 + r, __float_as_uint(d0), __float_as_uint(d1), 0, 0, tag);
    }
    PSTAMP(5);

    float ah[32];
    uint32_t sv[2][4];
    unpack32(ah, xres);
    {
      uint32_t og[2][14][4];
      const uint4* osrc[7];
#pragma unroll
      for (int i = 0; i < 7; i++) osrc[i] = xb + O_E2 + (xw * 32 + 4 * kb_at(i + 1, j)) * 32;
      const uint4* ssrc = X->e2s + (xw * 8 + 2 * c) * 8 + r;
      auto oissue = [&](int hp) {
#pragma unroll
        for (int i = 0; i < 14; i++) ll_ld(og[hp][i], osrc[i >> 1] + (2 * hp + (i & 1)) * 32);
        if (hp == 1) ll_issue<2>(sv, ssrc, 8);
      };
      auto omma = [&](int hp) {
        ll_clear<14>(og[hp]);
        keep(og[hp]);
        wg_fence();
#pragma unroll
        for (int i = 0; i < 14; i++) wgmma_rs_n64(ah, og[hp][i], descB(H0) + kb_at((i >> 1) + 1, j) * 512 + (2 * hp + (i & 1)) * 128, 1);
        wg_commit();
      };
      mbar_wait(BAR + B_FWO * 8);
      keep(ah); keep(of);
      wg_fence();
#pragma unroll
      for (int k = 0; k < 4; k++) wgmma_rs_n64(ah, of[k], descB(H0) + j * 512 + k * 128, 1);
      wg_commit();
      uint32_t it = 0;
#pragma unroll 1
      do { oissue(0); } while (ll_bad<14>(og[0], tag) && ++it < SPIN_LIMIT);
      PSTAMP(6);
      oissue(1);
      omma(0);
      const uint32_t tg = pin(tag, zero);
      if (__builtin_expect(ll_any(ll_acc<14>(og[1], tg, ll_acc<2>(sv, tg))), 0)) {
#pragma unroll 1
        do { oissue(1); } while (ll_any(ll_acc<14>(og[1], tag, ll_acc<2>(sv, tag))) && ++it < SPIN_LIMIT);
      }
      PSTAMP(16);
      omma(1);
      ll_clear<2>(sv);
    }
    float m0 = __uint_as_float(sv[0][0]) + __uint_as_float(sv[1][0]), m1 = __uint_as_float(sv[0][1]) + __uint_as_float(sv[1][1]);
#pragma unroll
    for (int o = 1; o <= 2; o <<= 1) { m0 += __shfl_xor_sync(0xffffffffu, m0, o); m1 += __shfl_xor_sync(0xffffffffu, m1, o); }
    const uint32_t mu0 = pack2(m0 + st0.x, m0 + st0.x), mu1 = pack2(m1 + st1.x, m1 + st1.x);
    wg_wait<0>();
    keep(ah);
    if (lane == 0) mbar_arrive(BAR + B_WODONE * 8);
    PSTAMP(7);

    uint32_t hf[4][4], ra[4][4];
    pack32(hf, ah);
    {
      uint4* dst = xb + O_E3H + (xw * 32 + 4 * j) * 32;
#pragma unroll
      for (int u = 0; u < 4; u++) {
        ra[u][0] = hsub2(hf[u][0], mu0); ra[u][1] = hsub2(hf[u][1], mu1);
        ra[u][2] = hsub2(hf[u][2], mu0); ra[u][3] = hsub2(hf[u][3], mu1);
        ll_st(dst + u * 32, ra[u][0], ra[u][1], ra[u][2], ra[u][3], tag);
      }
      float s0 = 0.f, q0 = 0.f, s1 = 0.f, q1 = 0.f;
#pragma unroll
      for (int b = 0; b < 8; b++) {
        s0 += ah[4 * b] + ah[4 * b + 1]; s1 += ah[4 * b + 2] + ah[4 * b + 3];
        q0 = fmaf(ah[4 * b], ah[4 * b], q0); q0 = fmaf(ah[4 * b + 1], ah[4 * b + 1], q0);
        q1 = fmaf(ah[4 * b + 2], ah[4 * b + 2], q1); q1 = fmaf(ah[4 * b + 3], ah[4 * b + 3], q1);
      }
#pragma unroll
      for (int o = 1; o <= 2; o <<= 1) {
        s0 += __shfl_xor_sync(0xffffffffu, s0, o); q0 += __shfl_xor_sync(0xffffffffu, q0, o);
        s1 += __shfl_xor_sync(0xffffffffu, s1, o); q1 += __shfl_xor_sync(0xffffffffu, q1, o);
      }
      if (c == 0) ll_st(X->e3s + (xw * 8 + j) * 8 + r, __float_as_uint(s0), __float_as_uint(q0), __float_as_uint(s1), __float_as_uint(q1), tag);
      mbar_wait(BAR + (p == 0 ? B_EQ + 7 : B_WODONE) * 8);
    }
    PSTAMP(8);

    float rs0, rs1;
    auto swiglu = [&](float g0, float g1, float u0, float u1, float rs) -> uint32_t {
      const float hr = 0.5f * rs;
      const float x0 = g0 * hr, x1 = g1 * hr;
      const float t0 = tanhf_hw(x0), t1 = tanhf_hw(x1);
      return pack2(fmaf(x0, t0, x0) * (u0 * rs), fmaf(x1, t1, x1) * (u1 * rs));
    };
    uint32_t hA[6][4];
    {
      float a1[64], a2[32];
      const uint4* src = xb + O_E3H + xw * 32 * 32;
      uint32_t rb[4][4], rc[4][4], rd[4][4];
      auto fetch = [&](uint32_t (&a)[4][4], int i) { ll_issue<4>(a, src + kb_at(i, j) * 128, 32); };
      auto check = [&](uint32_t (&a)[4][4], uint32_t (&b)[4][4], int i) {
        const uint32_t tg = pin(tag, zero);
        if (__builtin_expect(ll_any(ll_acc<4>(a, tg, ll_acc<4>(b, tg))), 0)) {
          uint32_t it = 0;
#pragma unroll 1
          do { fetch(a, i); fetch(b, i + 1); } while (ll_any(ll_acc<4>(a, tag, ll_acc<4>(b, tag))) && ++it < SPIN_LIMIT);
        }
        ll_clear<4>(a); ll_clear<4>(b);
        keep(a); keep(b);
      };
      auto head = [&](uint32_t (&a)[4][4], int i) {
        mbar_wait(BAR + (B_FA + i) * 8);
        wg_fence();
        wgmma_rs_n64<DESC_HI64>(a2, a[0], descBh(RING + 16384) + (i & 3) * 1536, i);
        wgmma_rs_n128(a1, a[0], descB(RING) + (i & 3) * 1536, i);
        wg_commit();
#pragma unroll
        for (int u = 0; u < 4; u++) stsm4(Hn + w * 2048 + i * 8192 + (moff ^ (u << 5)), a[u]);
        wg_wait<1>();
        if (i > 0) mbar_arrive_if(BAR + (B_EA + i - 1) * 8, lane == 0);
      };
      auto rest = [&](uint32_t (&a)[4][4], int i) {
        wg_fence();
#pragma unroll
        for (int k = 1; k < 4; k++) {
          wgmma_rs_n64<DESC_HI64>(a2, a[k], descBh(RING + 16384) + (i & 3) * 1536 + k * 64, 1);
          wgmma_rs_n128(a1, a[k], descB(RING) + (i & 3) * 1536 + k * 128, 1);
        }
        wg_commit();
      };
      ll_clear<4>(ra);
      keep(ra);
      head(ra, 0); rest(ra, 0);
      ll_get<4>(rb, src + kb_at(1, j) * 128, 32, tag);
      keep(rb);
      PSTAMP(17);
      fetch(rc, 2); fetch(rd, 3);
      head(rb, 1); rest(rb, 1);
      check(rc, rd, 2);
      head(rc, 2); fetch(ra, 4); fetch(rb, 5); rest(rc, 2);
      head(rd, 3); rest(rd, 3);
      check(ra, rb, 4);
      head(ra, 4); fetch(rc, 6); fetch(rd, 7); ll_issue<2>(sv, X->e3s + (xw * 8 + 2 * c) * 8 + r, 8); rest(ra, 4);
      head(rb, 5); rest(rb, 5);
      check(rc, rd, 6);
      head(rc, 6); rest(rc, 6);
      head(rd, 7); rest(rd, 7);
      fence_async_smem();
      ll_wait<2>(sv, X->e3s + (xw * 8 + 2 * c) * 8 + r, 8, tag);
      float s0 = __uint_as_float(sv[0][0]) + __uint_as_float(sv[1][0]), q0 = __uint_as_float(sv[0][1]) + __uint_as_float(sv[1][1]);
      float s1 = __uint_as_float(sv[0][2]) + __uint_as_float(sv[1][2]), q1 = __uint_as_float(sv[0][3]) + __uint_as_float(sv[1][3]);
#pragma unroll
      for (int o = 1; o <= 2; o <<= 1) {
        s0 += __shfl_xor_sync(0xffffffffu, s0, o); q0 += __shfl_xor_sync(0xffffffffu, q0, o);
        s1 += __shfl_xor_sync(0xffffffffu, s1, o); q1 += __shfl_xor_sync(0xffffffffu, q1, o);
      }
      s0 *= 1.f / D_; s1 *= 1.f / D_;
      rs0 = rsqrtf(fmaxf(fmaf(-s0, s0, q0 * (1.f / D_)), 0.f) + 1e-5f);
      rs1 = rsqrtf(fmaxf(fmaf(-s1, s1, q1 * (1.f / D_)), 0.f) + 1e-5f);
      wg_wait<0>();
      keep(a1); keep(a2);
      if (lane == 0) mbar_arrive(BAR + (B_EA + 7) * 8);
      PSTAMP(9);
#pragma unroll
      for (int u = 0; u < 4; u++)
#pragma unroll
        for (int e = 0; e < 4; e++)
          hA[u][e] = swiglu(a1[8 * u + 2 * e], a1[8 * u + 2 * e + 1], a1[32 + 8 * u + 2 * e], a1[33 + 8 * u + 2 * e], (e & 1) ? rs1 : rs0);
#pragma unroll
      for (int u = 0; u < 2; u++)
#pragma unroll
        for (int e = 0; e < 4; e++)
          hA[4 + u][e] = swiglu(a2[8 * u + 2 * e], a2[8 * u + 2 * e + 1], a2[16 + 8 * u + 2 * e], a2[17 + 8 * u + 2 * e], (e & 1) ? rs1 : rs0);
      keep(hA);
      wg_bar(p);
    }
    PSTAMP(10);

    const uint32_t mbx = Hn + 32768 + w * 512 + lane * 16;
    auto send = [&](const uint32_t (&v)[4], uint32_t a, int part) {
      asm volatile("st.async.weak.shared::cluster.mbarrier::complete_tx::bytes.v4.b32 [%0], {%1,%2,%3,%4}, [%5];"
                   ::"r"(a + peer()), "r"(v[0]), "r"(v[1]), "r"(v[2]), "r"(v[3]), "r"(BAR + (B_HX + 2 * part + p) * 8 + peer()) : "memory");
    };
    uint32_t hB[8][4];
    {
      float ab[128];
      uint32_t db = descB(RING);
      const uint32_t dAn = descA(H1) - p * 4096;
      if (lane == 0 && w == 0) { mbar_expect_tx(BAR + (B_HX + p) * 8, 12288); mbar_expect_tx(BAR + (B_HX + 2 + p) * 8, 16384); }
#pragma unroll 1
      for (int i = 0; i < 8; i++) {
        mbar_wait(BAR + (B_FB + i) * 8);
        const uint32_t da = dAn + i * 512;
        wg_fence();
        wgmma_ss_n256(ab, da, db, i);
#pragma unroll
        for (int k = 1; k < 4; k++) wgmma_ss_n256(ab, da + k * 2, db + k * 128, 1);
        wg_commit();
        if (i == 7) {
          mbar_wait_cluster(BAR + (B_PF + p) * 8);
#pragma unroll
          for (int k = 0; k < 6; k++) send(hA[k], mbx + k * 2048, 0);
        }
        wg_wait<1>();
        mbar_arrive_if(BAR + (B_EB + i - 1) * 8, i > 0 && lane == 0);
        if (i == 6 && lane == 0) mbar_arrive_peer(BAR + (B_PF + p) * 8);
        db = db == descB(RING + 65536) ? descB(RING) : db + 2048;
      }
      wg_wait<0>();
      keep(ab);
      mbar_arrive_if(BAR + (B_EB + 7) * 8, lane == 0);
      if (lane == 0) mbar_arrive_peer(BAR + (B_PF + 2 + p) * 8);
      PSTAMP(11);
#pragma unroll
      for (int u = 0; u < 8; u++) {
        const int o = (u >> 2) * 64 + (u & 3) * 8;
#pragma unroll
        for (int e = 0; e < 4; e++)
          hB[u][e] = swiglu(ab[o + 2 * e], ab[o + 2 * e + 1], ab[o + 32 + 2 * e], ab[o + 33 + 2 * e], (e & 1) ? rs1 : rs0);
        if (u == 3) mbar_wait_cluster(BAR + (B_PF + 2 + p) * 8);
        if (u >= 4 && u < 4 + SEND_EARLY) send(hB[u - 4], mbx + (2 + u) * 2048, 1);
      }
      keep(hB);
    }
    PSTAMP(12);

    {
      float ya[32], y[32];
      uint32_t hP[14][4];
      const uint32_t offA = (j & 1) ? 256 : 0, offH = (j & 1) ? 0 : 1536;
      uint4* e4 = xb + O_E4 + g * 24576 + warp * 128;
      const uint32_t stg = H0 + p * 65536 + 28672 + (w >> 1) * 32768 + (w & 1) * 2048;
      auto mm = [&](float (&d)[32], int m, int k0, int k1) {
        if (k0 == 0) mbar_wait(BAR + (B_FT + m) * 8);
        const uint32_t T = descB(0) + (t_addr(m) >> 4);
        const uint32_t oA = w2_peer(m) ? 256 - offA : offA, oH = w2_peer(m) ? 1536 - offH : offH;
        wg_fence();
#pragma unroll
        for (int k = k0; k < k1; k++) {
          const uint32_t db = T + (k < 4 ? oA + k * 128 : k < 6 ? oH + (k - 4) * 128 : oA + 512 + (k - 6) * 128);
          if (w2_peer(m)) wgmma_rs_n64(d, hP[k], db, 1);
          else if (k < 6) wgmma_rs_n64(d, hA[k], db, k);
          else wgmma_rs_n64(d, hB[k - 6], db, 1);
        }
        wg_commit();
      };
      auto next = [&](float (&d)[32], int m, float (&dp)[32], int q) {
        mm(d, m, 0, 3);
        wg_wait<1>();
        keep(dp);
        mbar_arrive_if(BAR + (B_ET0 + q) * 8, lane == 0);
        uint4* dst = e4 + (((j + 2 + 2 * q) & 7) * 3 + q) * 1024;
#pragma unroll
        for (int u = 0; u < 4; u++)
          ll_st(dst + u * 32, pack2(dp[8 * u], dp[8 * u + 1]), pack2(dp[8 * u + 2], dp[8 * u + 3]),
                pack2(dp[8 * u + 4], dp[8 * u + 5]), pack2(dp[8 * u + 6], dp[8 * u + 7]), tag);
        if (q == 2) mbar_wait(BAR + (B_ET0 + 2) * 8);
        mm(d, m, 3, 14);
      };
#pragma unroll
      for (int i = 0; i < 4; i++) {
        const uint32_t a = i ? pin(mbx, zero) : mbx;
#pragma unroll
        for (int k = SEND_EARLY + (8 - SEND_EARLY) * i / 4; k < SEND_EARLY + (8 - SEND_EARLY) * (i + 1) / 4; k++) send(hB[k], a + (6 + k) * 2048, 1);
        if (i < 3) mm(ya, 0, 5 * i, i < 2 ? 5 * i + 5 : 14);
        else mm(y, 1, 0, 6);
      }
      mbar_wait_cluster(BAR + (B_HX + p) * 8);
#pragma unroll
      for (int k = 0; k < 6; k++) lds128(hP[k], mbx + k * 2048);
      mm(y, 1, 6, 14);
      keep(hP[0]); keep(hP[1]); keep(hP[2]); keep(hP[3]); keep(hP[4]); keep(hP[5]);
      mm(ya, 2, 0, 3);
      PSTAMP(18);
      mbar_wait_cluster(BAR + (B_HX + 2 + p) * 8);
      PSTAMP(24);
#pragma unroll
      for (int k = 6; k < 14; k++) lds128(hP[k], mbx + k * 2048);
      mm(ya, 2, 3, 6);
      keep(hP);
      mbar_arrive_if(BAR + (B_HC + p) * 8, lane == 0);
      mm(ya, 2, 6, 14);
      mbar_wait(BAR + B_CLR * 8);
      next(y, 3, ya, 0);
      PSTAMP(27);
      next(ya, 4, y, 1);
      mbar_arrive_if(BAR + (B_ET0 + 3) * 8, lane == 0);
      mm(ya, 5, 0, 14);
      PSTAMP(26);
      next(y, 6, ya, 2);
      PSTAMP(28);
      uint32_t in[4][4], lt[4][4];
      const uint4* insrc = e4 + j * 3 * 1024;
      mm(y, 7, 0, 7);
      ll_issue<4>(lt, insrc + 2048, 32);
      mm(y, 7, 7, 14);
      mbar_wait(BAR + B_FIN * 8);
      mbar_wait(BAR + (B_FIN + 1) * 8);
      wg_wait<0>();
      keep(y);
      PSTAMP(13);
      const uint32_t ident = (2 * c == r ? 0x3f80u : 0u) | (2 * c + 1 == r ? 0x3f800000u : 0u);
      auto acc = [&](const uint32_t (&v)[4][4]) {
#pragma unroll
        for (int u = 0; u < 4; u++) {
          mma1688_acc(*reinterpret_cast<float (*)[4]>(&y[8 * u]), v[u][0], v[u][1], ident);
          mma1688_acc(*reinterpret_cast<float (*)[4]>(&y[8 * u + 4]), v[u][2], v[u][3], ident);
        }
      };
      acc(hf);
#pragma unroll
      for (int q = 0; q < 2; q++) {
#pragma unroll
        for (int u = 0; u < 4; u++) lds128(in[u], t_addr(q + 1) + warp * 2048 + lane * 16 + u * 512);
        ll_wait<4>(in, insrc + q * 1024, 32, tag);
        acc(in);
      }
      PSTAMP(25);
      if (ll_bad<4>(lt, pin(tag, zero))) {
        ll_spin<4>(lt, insrc + 2048, 32, tag);
      }
      ll_clear<4>(lt);
      acc(lt);
      PSTAMP(14);
#pragma unroll
      for (int u = 0; u < 4; u++) {
        uint32_t o[4];
#pragma unroll
        for (int e = 0; e < 4; e++) o[e] = pack2(y[8 * u + 2 * e], y[8 * u + 2 * e + 1]);
        stsm4(stg + (moff ^ (u << 5)), o);
      }
      fence_async_smem();
      __syncwarp();
      if (elect_one()) {
        tma3d_store(&P.out, stg, 64 * j, p, g * 64 + 16 * w);
        asm volatile("cp.async.bulk.commit_group;" ::: "memory");
        asm volatile("cp.async.bulk.wait_group.read 0;" ::: "memory");
      }
      PSTAMP(15);
    }
  }
}

typedef CUresult (*EncodeFn)(CUtensorMap*, CUtensorMapDataType, cuuint32_t, void*, const cuuint64_t*, const cuuint64_t*,
                             const cuuint32_t*, const cuuint32_t*, CUtensorMapInterleave, CUtensorMapSwizzle,
                             CUtensorMapL2promotion, CUtensorMapFloatOOBfill);

void enc2d(EncodeFn f, CUtensorMap* m, const void* base, uint64_t cols, uint64_t rows, uint32_t bc, uint32_t br, CUtensorMapSwizzle sw) {
  cuuint64_t gd[2] = {cols, rows}, gs[1] = {cols * 2};
  cuuint32_t bd[2] = {bc, br}, es[2] = {1, 1};
  f(m, CU_TENSOR_MAP_DATA_TYPE_BFLOAT16, 2, const_cast<void*>(base), gd, gs, bd, es, CU_TENSOR_MAP_INTERLEAVE_NONE, sw,
    CU_TENSOR_MAP_L2_PROMOTION_L2_128B, CU_TENSOR_MAP_FLOAT_OOB_FILL_NONE);
}
void enc_par(EncodeFn f, CUtensorMap* m, const void* base, uint32_t pairs) {
  cuuint64_t gd[3] = {(cuuint64_t)D_, 2, (cuuint64_t)S_ / 2}, gs[2] = {D_ * 2, D_ * 4};
  cuuint32_t bd[3] = {64, 1, pairs}, es[3] = {1, 1, 1};
  f(m, CU_TENSOR_MAP_DATA_TYPE_BFLOAT16, 3, const_cast<void*>(base), gd, gs, bd, es, CU_TENSOR_MAP_INTERLEAVE_NONE,
    CU_TENSOR_MAP_SWIZZLE_128B, CU_TENSOR_MAP_L2_PROMOTION_L2_128B, CU_TENSOR_MAP_FLOAT_OOB_FILL_NONE);
}

}

extern "C" void kernel_launch(void* const* d_in, const int* in_sizes, int n_in, void* d_out, int out_size) {
  (void)in_sizes; (void)n_in; (void)out_size;
  static EncodeFn enc = nullptr;
  static Scratch* scratch = nullptr;
  if (!enc) {
    void* fn = nullptr;
    cudaDriverEntryPointQueryResult q;
    cudaGetDriverEntryPoint("cuTensorMapEncodeTiled", &fn, cudaEnableDefault, &q);
    enc = (EncodeFn)fn;
    cudaGetSymbolAddress((void**)&scratch, g_scratch);
    cudaFuncSetAttribute(fused_block_kernel, cudaFuncAttributeMaxDynamicSharedMemorySize, SMEM_BYTES);
  }
  Params P;
  const __nv_bfloat16* xp = (const __nv_bfloat16*)d_in[0];
  const __nv_bfloat16* wqkvp = (const __nv_bfloat16*)d_in[1];
  const __nv_bfloat16* wop = (const __nv_bfloat16*)d_in[2];
  P.w1p = (const __nv_bfloat16*)d_in[4];
  P.w3p = (const __nv_bfloat16*)d_in[5];
  P.w2p = (const __nv_bfloat16*)d_in[6];
  enc_par(enc, &P.x, xp, 64);
  enc_par(enc, &P.out, d_out, 16);
  enc2d(enc, &P.wqkv, wqkvp, 3 * D_, D_, 64, 64, CU_TENSOR_MAP_SWIZZLE_128B);
  enc2d(enc, &P.wo, wop, D_, D_, 64, 64, CU_TENSOR_MAP_SWIZZLE_128B);
  enc2d(enc, &P.w1, P.w1p, F_, D_, 64, 64, CU_TENSOR_MAP_SWIZZLE_128B);
  enc2d(enc, &P.w3, P.w3p, F_, D_, 64, 64, CU_TENSOR_MAP_SWIZZLE_128B);
  enc2d(enc, &P.w1h, P.w1p, F_, D_, 32, 64, CU_TENSOR_MAP_SWIZZLE_64B);
  enc2d(enc, &P.w3h, P.w3p, F_, D_, 32, 64, CU_TENSOR_MAP_SWIZZLE_64B);
  enc2d(enc, &P.w2, P.w2p, D_, F_, 64, 224, CU_TENSOR_MAP_SWIZZLE_128B);

  cudaLaunchConfig_t cfg = {};
  cfg.gridDim = dim3(128);
  cfg.blockDim = dim3(384);
  cfg.dynamicSmemBytes = SMEM_BYTES;
  cfg.stream = cudaStreamPerThread;
  cudaLaunchAttribute at[2];
  at[0].id = cudaLaunchAttributeCooperative;
  at[0].val.cooperative = 1;
  cfg.attrs = at;
  cfg.numAttrs = 1;
  at[1].id = cudaLaunchAttributeClusterDimension;
  at[1].val.clusterDim.x = 2; at[1].val.clusterDim.y = 1; at[1].val.clusterDim.z = 1;
  cfg.numAttrs = 2;
  cudaLaunchKernelEx(&cfg, fused_block_kernel, scratch, xp, wqkvp, wop, 0u, P);
}
```

```cpp
#include <cuda_runtime.h>
#include <cuda.h>
#include <cuda_bf16.h>
#include <stdint.h>
#include <stddef.h>

namespace {

constexpr int S_ = 2048, D_ = 512, F_ = 1792;
#define LAG_KB 3
#define E4_FIRST 7
#define PP_AHEAD 1
#define SIDE_KB 0
#define CLR_MODE 1
#define W2_HEAD 3
#define CLR_SLEEP 400
#define CMAP 2
#define E4_ON 1
#define E4_WHEN (B_EA + 7)
#define SEND_EARLY 2
#define CS_KB 3
#define WO_KB 3
#define GATHER_SLEEP 200
#define PF_MODE 1
#define CLR_SLEEP2 100
#define CLR_WHEN (B_EQ + 5)
#define XO_DELAY 2

constexpr uint32_t SPIN_LIMIT = 1u << 18;

struct Scratch {
  uint4 e4[16 * 8 * 3 * 8 * 4 * 32];
  uint4 e2[16 * 2 * 4 * 32 * 32];
  uint4 e3h[16 * 2 * 4 * 32 * 32];
  uint4 e1[16 * 8 * 2 * 4 * 32];
  uint4 e2s[16 * 2 * 4 * 8 * 8];
  uint4 e3s[16 * 2 * 4 * 8 * 8];
  uint4 e0c[8 * 3 * 16 * 16];
  uint4 e0s[2048];
  uint4 e0w[8 * 64];
  unsigned epoch[128];
};
__device__ Scratch g_scratch;
#define PSTAMP(i)
#define PSTAMPW(slot, i)
#define W2STAMP(i)

struct alignas(64) Params {
  CUtensorMap x, out, wqkv, wo, w1, w3, w1h, w3h, w2;
  const __nv_bfloat16 *w1p, *w3p, *w2p;
};

constexpr uint32_t SB = 1024;
constexpr uint32_t H0 = SB;
constexpr uint32_t H1 = SB + 65536;
constexpr uint32_t RING = SB + 131072;
constexpr uint32_t BAR = SB + 229376;
constexpr uint32_t TAGS = BAR + 1016;
constexpr uint32_t CS = BAR + 1024;
constexpr uint32_t ST = CS + 768;
constexpr uint32_t WB = ST + 1024;
constexpr uint32_t SMEM_BYTES = 232448;
static_assert(WB + 256 <= SB + SMEM_BYTES, "smem");

enum : int {
  B_FX = 0,
  B_FKV = 16, B_FQ = 24, B_FWO = 32, B_FA = 40, B_FB = 48, B_FT = 56,
  B_EKV = 64, B_EQ = 72, B_EA = 80, B_EB = 88, B_ET0 = 96,
  B_WODONE = 103,
  B_WBAR = 39,
  B_FIN = 33,
  B_EX = 104,
  B_LAG = 112, B_READY = 113, B_X114 = 114, B_CLR = 115, B_OG = 116, B_TAG = 117,
  B_HX = 35,
  B_PF = 118,
  B_HC = 122,
  B_CLR1 = 124, B_CLR2 = 125
};

__device__ __forceinline__ uint32_t smem_u32(const void* p) { return (uint32_t)__cvta_generic_to_shared(p); }
__device__ __forceinline__ uint32_t own() { return (blockIdx.x & 1) << 24; }
__device__ __forceinline__ uint32_t peer() { return (~blockIdx.x & 1) << 24; }
__device__ __forceinline__ void mbar_init(uint32_t b, uint32_t c) { asm volatile("mbarrier.init.shared::cta.b64 [%0], %1;" ::"r"(b + own()), "r"(c) : "memory"); }
__device__ __forceinline__ void mbar_expect_tx(uint32_t b, uint32_t bytes) { asm volatile("mbarrier.arrive.expect_tx.shared::cta.b64 _, [%0], %1;" ::"r"(b + own()), "r"(bytes) : "memory"); }
__device__ __forceinline__ void mbar_arrive(uint32_t b) { asm volatile("mbarrier.arrive.shared::cta.b64 _, [%0];" ::"r"(b + own()) : "memory"); }
__device__ __forceinline__ void mbar_wait(uint32_t b) {
  asm volatile("{\n.reg .pred p;\n.reg .u32 c;\nmov.u32 c, 0;\nLW:\n.pragma \"nounroll\";\n"
               "mbarrier.try_wait.parity.shared::cta.b64 p, [%0], 0;\nadd.u32 c, c, 1;\nsetp.gt.or.u32 p, c, %1, p;\n@!p bra LW;\n}\n"
               ::"r"(b + own()), "n"(SPIN_LIMIT) : "memory");
}
__device__ __forceinline__ void mbar_arrive_peer(uint32_t b) {
  asm volatile("mbarrier.arrive.relaxed.cluster.shared::cluster.b64 _, [%0];" ::"r"(b + peer()) : "memory");
}
__device__ __forceinline__ void mbar_wait_cluster(uint32_t b) {
  asm volatile("{\n.reg .pred p;\n.reg .u32 c;\nmov.u32 c, 0;\nLW:\n.pragma \"nounroll\";\n"
               "mbarrier.try_wait.parity.acquire.cluster.shared::cta.b64 p, [%0], 0;\nadd.u32 c, c, 1;\nsetp.gt.or.u32 p, c, %1, p;\n@!p bra LW;\n}\n"
               ::"r"(b + own()), "n"(SPIN_LIMIT) : "memory");
}
__device__ __forceinline__ bool elect_one() {
  uint32_t p;
  asm volatile("{\n.reg .pred P;\nelect.sync _|P, 0xffffffff;\nselp.u32 %0, 1, 0, P;\n}\n" : "=r"(p));
  return p;
}
__device__ __forceinline__ void tma2d(uint32_t dst, const CUtensorMap* m, int c0, int c1, uint32_t bar) {
  dst += own(); bar += own();
  asm volatile("cp.async.bulk.tensor.2d.shared::cluster.global.mbarrier::complete_tx::bytes [%0], [%1, {%3, %4}], [%2];"
               ::"r"(dst), "l"(m), "r"(bar), "r"(c0), "r"(c1) : "memory");
}
__device__ __forceinline__ void tma3d(uint32_t dst, const CUtensorMap* m, int c0, int c1, int c2, uint32_t bar) {
  dst += own(); bar += own();
  asm volatile("cp.async.bulk.tensor.3d.shared::cluster.global.mbarrier::complete_tx::bytes [%0], [%1, {%3, %4, %5}], [%2];"
               ::"r"(dst), "l"(m), "r"(bar), "r"(c0), "r"(c1), "r"(c2) : "memory");
}
__device__ __forceinline__ void tma3d_store(const CUtensorMap* m, uint32_t src, int c0, int c1, int c2) {
  asm volatile("cp.async.bulk.tensor.3d.global.shared::cta.bulk_group [%0, {%2, %3, %4}], [%1];"
               ::"l"(m), "r"(src + own()), "r"(c0), "r"(c1), "r"(c2) : "memory");
}
__device__ __forceinline__ void l2_prefetch(const void* p, uint32_t bytes) {
  asm volatile("cp.async.bulk.prefetch.L2.global [%0], %1;" ::"l"(p), "r"(bytes) : "memory");
}
__device__ __forceinline__ void prefetch_map(const CUtensorMap* m) { asm volatile("prefetch.tensormap [%0];" ::"l"(m) : "memory"); }
__device__ __forceinline__ void fence_async_smem() { asm volatile("fence.proxy.async.shared::cta;" ::: "memory"); }
__device__ __forceinline__ void wg_fence() { asm volatile("wgmma.fence.sync.aligned;" ::: "memory"); }
__device__ __forceinline__ void wg_commit() { asm volatile("wgmma.commit_group.sync.aligned;" ::: "memory"); }
template <int N> __device__ __forceinline__ void wg_wait() { asm volatile("wgmma.wait_group.sync.aligned %0;" ::"n"(N) : "memory"); }
__device__ __forceinline__ void wg_bar(int p) {
  if (p == 0) asm volatile("bar.sync 1, 128;" ::: "memory"); else asm volatile("bar.sync 2, 128;" ::: "memory");
}
constexpr uint32_t DESC_HI128 = (1024 >> 4) | (1u << 30);
constexpr uint32_t DESC_HI64 = (512 >> 4) | (2u << 30);
__device__ __forceinline__ constexpr uint32_t descA(uint32_t addr) { return (addr >> 4) | (1u << 16); }
__device__ __forceinline__ constexpr uint32_t descB(uint32_t addr) { return (addr >> 4) | ((8192u >> 4) << 16); }
__device__ __forceinline__ constexpr uint32_t descBh(uint32_t addr) { return (addr >> 4) | ((4096u >> 4) << 16); }

__device__ __forceinline__ void wgmma_ss_n64(float (&d)[32], uint32_t da, uint32_t db, int sc) {
  asm volatile("{\n.reg .pred p;\n.reg .b64 da, db;\nsetp.ne.b32 p, %34, 0;\nmov.b64 da, {%32, %35};\nmov.b64 db, {%33, %35};\n"
    "wgmma.mma_async.sync.aligned.m64n64k16.f32.bf16.bf16 {%0, %1, %2, %3, %4, %5, %6, %7, %8, %9, %10, %11, %12, %13, %14, %15, %16, %17, %18, %19, %20, %21, %22, %23, %24, %25, %26, %27, %28, %29, %30, %31}, da, db, p, 1, 1, 0, 1;\n}\n"
    : "+f"(d[0]), "+f"(d[1]), "+f"(d[2]), "+f"(d[3]), "+f"(d[4]), "+f"(d[5]), "+f"(d[6]), "+f"(d[7]),
      "+f"(d[8]), "+f"(d[9]), "+f"(d[10]), "+f"(d[11]), "+f"(d[12]), "+f"(d[13]), "+f"(d[14]), "+f"(d[15]),
      "+f"(d[16]), "+f"(d[17]), "+f"(d[18]), "+f"(d[19]), "+f"(d[20]), "+f"(d[21]), "+f"(d[22]), "+f"(d[23]),
      "+f"(d[24]), "+f"(d[25]), "+f"(d[26]), "+f"(d[27]), "+f"(d[28]), "+f"(d[29]), "+f"(d[30]), "+f"(d[31])
    : "r"(da), "r"(db), "r"(sc), "n"(DESC_HI128));
}
__device__ __forceinline__ void wgmma_ss_n128(float (&d)[64], uint32_t da, uint32_t db, int sc) {
  asm volatile("{\n.reg .pred p;\n.reg .b64 da, db;\nsetp.ne.b32 p, %66, 0;\nmov.b64 da, {%64, %67};\nmov.b64 db, {%65, %67};\n"
    "wgmma.mma_async.sync.aligned.m64n128k16.f32.bf16.bf16 {%0, %1, %2, %3, %4, %5, %6, %7, %8, %9, %10, %11, %12, %13, %14, %15, %16, %17, %18, %19, %20, %21, %22, %23, %24, %25, %26, %27, %28, %29, %30, %31, %32, %33, %34, %35, %36, %37, %38, %39, %40, %41, %42, %43, %44, %45, %46, %47, %48, %49, %50, %51, %52, %53, %54, %55, %56, %57, %58, %59, %60, %61, %62, %63}, da, db, p, 1, 1, 0, 1;\n}\n"
    : "+f"(d[0]), "+f"(d[1]), "+f"(d[2]), "+f"(d[3]), "+f"(d[4]), "+f"(d[5]), "+f"(d[6]), "+f"(d[7]),
      "+f"(d[8]), "+f"(d[9]), "+f"(d[10]), "+f"(d[11]), "+f"(d[12]), "+f"(d[13]), "+f"(d[14]), "+f"(d[15]),
      "+f"(d[16]), "+f"(d[17]), "+f"(d[18]), "+f"(d[19]), "+f"(d[20]), "+f"(d[21]), "+f"(d[22]), "+f"(d[23]),
      "+f"(d[24]), "+f"(d[25]), "+f"(d[26]), "+f"(d[27]), "+f"(d[28]), "+f"(d[29]), "+f"(d[30]), "+f"(d[31]),
      "+f"(d[32]), "+f"(d[33]), "+f"(d[34]), "+f"(d[35]), "+f"(d[36]), "+f"(d[37]), "+f"(d[38]), "+f"(d[39]),
      "+f"(d[40]), "+f"(d[41]), "+f"(d[42]), "+f"(d[43]), "+f"(d[44]), "+f"(d[45]), "+f"(d[46]), "+f"(d[47]),
      "+f"(d[48]), "+f"(d[49]), "+f"(d[50]), "+f"(d[51]), "+f"(d[52]), "+f"(d[53]), "+f"(d[54]), "+f"(d[55]),
      "+f"(d[56]), "+f"(d[57]), "+f"(d[58]), "+f"(d[59]), "+f"(d[60]), "+f"(d[61]), "+f"(d[62]), "+f"(d[63])
    : "r"(da), "r"(db), "r"(sc), "n"(DESC_HI128));
}
__device__ __forceinline__ void wgmma_ss_n256(float (&d)[128], uint32_t da, uint32_t db, int sc) {
  asm volatile("{\n.reg .pred p;\n.reg .b64 da, db;\nsetp.ne.b32 p, %130, 0;\nmov.b64 da, {%128, %131};\nmov.b64 db, {%129, %131};\n"
    "wgmma.mma_async.sync.aligned.m64n256k16.f32.bf16.bf16 {%0, %1, %2, %3, %4, %5, %6, %7, %8, %9, %10, %11, %12, %13, %14, %15, %16, %17, %18, %19, %20, %21, %22, %23, %24, %25, %26, %27, %28, %29, %30, %31, %32, %33, %34, %35, %36, %37, %38, %39, %40, %41, %42, %43, %44, %45, %46, %47, %48, %49, %50, %51, %52, %53, %54, %55, %56, %57, %58, %59, %60, %61, %62, %63, %64, %65, %66, %67, %68, %69, %70, %71, %72, %73, %74, %75, %76, %77, %78, %79, %80, %81, %82, %83, %84, %85, %86, %87, %88, %89, %90, %91, %92, %93, %94, %95, %96, %97, %98, %99, %100, %101, %102, %103, %104, %105, %106, %107, %108, %109, %110, %111, %112, %113, %114, %115, %116, %117, %118, %119, %120, %121, %122, %123, %124, %125, %126, %127}, da, db, p, 1, 1, 0, 1;\n}\n"
    : "+f"(d[0]), "+f"(d[1]), "+f"(d[2]), "+f"(d[3]), "+f"(d[4]), "+f"(d[5]), "+f"(d[6]), "+f"(d[7]),
      "+f"(d[8]), "+f"(d[9]), "+f"(d[10]), "+f"(d[11]), "+f"(d[12]), "+f"(d[13]), "+f"(d[14]), "+f"(d[15]),
      "+f"(d[16]), "+f"(d[17]), "+f"(d[18]), "+f"(d[19]), "+f"(d[20]), "+f"(d[21]), "+f"(d[22]), "+f"(d[23]),
      "+f"(d[24]), "+f"(d[25]), "+f"(d[26]), "+f"(d[27]), "+f"(d[28]), "+f"(d[29]), "+f"(d[30]), "+f"(d[31]),
      "+f"(d[32]), "+f"(d[33]), "+f"(d[34]), "+f"(d[35]), "+f"(d[36]), "+f"(d[37]), "+f"(d[38]), "+f"(d[39]),
      "+f"(d[40]), "+f"(d[41]), "+f"(d[42]), "+f"(d[43]), "+f"(d[44]), "+f"(d[45]), "+f"(d[46]), "+f"(d[47]),
      "+f"(d[48]), "+f"(d[49]), "+f"(d[50]), "+f"(d[51]), "+f"(d[52]), "+f"(d[53]), "+f"(d[54]), "+f"(d[55]),
      "+f"(d[56]), "+f"(d[57]), "+f"(d[58]), "+f"(d[59]), "+f"(d[60]), "+f"(d[61]), "+f"(d[62]), "+f"(d[63]),
      "+f"(d[64]), "+f"(d[65]), "+f"(d[66]), "+f"(d[67]), "+f"(d[68]), "+f"(d[69]), "+f"(d[70]), "+f"(d[71]),
      "+f"(d[72]), "+f"(d[73]), "+f"(d[74]), "+f"(d[75]), "+f"(d[76]), "+f"(d[77]), "+f"(d[78]), "+f"(d[79]),
      "+f"(d[80]), "+f"(d[81]), "+f"(d[82]), "+f"(d[83]), "+f"(d[84]), "+f"(d[85]), "+f"(d[86]), "+f"(d[87]),
      "+f"(d[88]), "+f"(d[89]), "+f"(d[90]), "+f"(d[91]), "+f"(d[92]), "+f"(d[93]), "+f"(d[94]), "+f"(d[95]),
      "+f"(d[96]), "+f"(d[97]), "+f"(d[98]), "+f"(d[99]), "+f"(d[100]), "+f"(d[101]), "+f"(d[102]), "+f"(d[103]),
      "+f"(d[104]), "+f"(d[105]), "+f"(d[106]), "+f"(d[107]), "+f"(d[108]), "+f"(d[109]), "+f"(d[110]), "+f"(d[111]),
      "+f"(d[112]), "+f"(d[113]), "+f"(d[114]), "+f"(d[115]), "+f"(d[116]), "+f"(d[117]), "+f"(d[118]), "+f"(d[119]),
      "+f"(d[120]), "+f"(d[121]), "+f"(d[122]), "+f"(d[123]), "+f"(d[124]), "+f"(d[125]), "+f"(d[126]), "+f"(d[127])
    : "r"(da), "r"(db), "r"(sc), "n"(DESC_HI128));
}
template <uint32_t HI = DESC_HI128>
__device__ __forceinline__ void wgmma_rs_n64(float (&d)[32], const uint32_t (&a)[4], uint32_t db, int sc) {
  asm volatile("{\n.reg .pred p;\n.reg .b64 db;\nsetp.ne.b32 p, %37, 0;\nmov.b64 db, {%36, %38};\n"
    "wgmma.mma_async.sync.aligned.m64n64k16.f32.bf16.bf16 {%0, %1, %2, %3, %4, %5, %6, %7, %8, %9, %10, %11, %12, %13, %14, %15, %16, %17, %18, %19, %20, %21, %22, %23, %24, %25, %26, %27, %28, %29, %30, %31}, {%32, %33, %34, %35}, db, p, 1, 1, 1;\n}\n"
    : "+f"(d[0]), "+f"(d[1]), "+f"(d[2]), "+f"(d[3]), "+f"(d[4]), "+f"(d[5]), "+f"(d[6]), "+f"(d[7]),
      "+f"(d[8]), "+f"(d[9]), "+f"(d[10]), "+f"(d[11]), "+f"(d[12]), "+f"(d[13]), "+f"(d[14]), "+f"(d[15]),
      "+f"(d[16]), "+f"(d[17]), "+f"(d[18]), "+f"(d[19]), "+f"(d[20]), "+f"(d[21]), "+f"(d[22]), "+f"(d[23]),
      "+f"(d[24]), "+f"(d[25]), "+f"(d[26]), "+f"(d[27]), "+f"(d[28]), "+f"(d[29]), "+f"(d[30]), "+f"(d[31])
    : "r"(a[0]), "r"(a[1]), "r"(a[2]), "r"(a[3]), "r"(db), "r"(sc), "n"(HI));
}
template <uint32_t HI = DESC_HI128>
__device__ __forceinline__ void wgmma_rs_n128(float (&d)[64], const uint32_t (&a)[4], uint32_t db, int sc) {
  asm volatile("{\n.reg .pred p;\n.reg .b64 db;\nsetp.ne.b32 p, %69, 0;\nmov.b64 db, {%68, %70};\n"
    "wgmma.mma_async.sync.aligned.m64n128k16.f32.bf16.bf16 {%0, %1, %2, %3, %4, %5, %6, %7, %8, %9, %10, %11, %12, %13, %14, %15, %16, %17, %18, %19, %20, %21, %22, %23, %24, %25, %26, %27, %28, %29, %30, %31, %32, %33, %34, %35, %36, %37, %38, %39, %40, %41, %42, %43, %44, %45, %46, %47, %48, %49, %50, %51, %52, %53, %54, %55, %56, %57, %58, %59, %60, %61, %62, %63}, {%64, %65, %66, %67}, db, p, 1, 1, 1;\n}\n"
    : "+f"(d[0]), "+f"(d[1]), "+f"(d[2]), "+f"(d[3]), "+f"(d[4]), "+f"(d[5]), "+f"(d[6]), "+f"(d[7]),
      "+f"(d[8]), "+f"(d[9]), "+f"(d[10]), "+f"(d[11]), "+f"(d[12]), "+f"(d[13]), "+f"(d[14]), "+f"(d[15]),
      "+f"(d[16]), "+f"(d[17]), "+f"(d[18]), "+f"(d[19]), "+f"(d[20]), "+f"(d[21]), "+f"(d[22]), "+f"(d[23]),
      "+f"(d[24]), "+f"(d[25]), "+f"(d[26]), "+f"(d[27]), "+f"(d[28]), "+f"(d[29]), "+f"(d[30]), "+f"(d[31]),
      "+f"(d[32]), "+f"(d[33]), "+f"(d[34]), "+f"(d[35]), "+f"(d[36]), "+f"(d[37]), "+f"(d[38]), "+f"(d[39]),
      "+f"(d[40]), "+f"(d[41]), "+f"(d[42]), "+f"(d[43]), "+f"(d[44]), "+f"(d[45]), "+f"(d[46]), "+f"(d[47]),
      "+f"(d[48]), "+f"(d[49]), "+f"(d[50]), "+f"(d[51]), "+f"(d[52]), "+f"(d[53]), "+f"(d[54]), "+f"(d[55]),
      "+f"(d[56]), "+f"(d[57]), "+f"(d[58]), "+f"(d[59]), "+f"(d[60]), "+f"(d[61]), "+f"(d[62]), "+f"(d[63])
    : "r"(a[0]), "r"(a[1]), "r"(a[2]), "r"(a[3]), "r"(db), "r"(sc), "n"(HI));
}

template <int N> __device__ __forceinline__ void keep(float (&d)[N]) {
#pragma unroll
  for (int i = 0; i < N; i++) asm volatile("" : "+f"(d[i])::"memory");
}

__device__ __forceinline__ void keep(uint32_t (&d)[4]) { asm volatile("" : "+r"(d[0]), "+r"(d[1]), "+r"(d[2]), "+r"(d[3])::"memory"); }
template <int N> __device__ __forceinline__ void keep(uint32_t (&d)[N][4]) {
#pragma unroll
  for (int i = 0; i < N; i++) asm volatile("" : "+r"(d[i][0]), "+r"(d[i][1]), "+r"(d[i][2]), "+r"(d[i][3])::"memory");
}

__device__ __forceinline__ uint32_t pack2(float lo, float hi) {
  uint32_t r;
  asm("cvt.rn.bf16x2.f32 %0, %1, %2;" : "=r"(r) : "f"(hi), "f"(lo));
  return r;
}
__device__ __forceinline__ float bf_lo(uint32_t v) { return __uint_as_float(v << 16); }
__device__ __forceinline__ float bf_hi(uint32_t v) { return __uint_as_float(v & 0xffff0000u); }
__device__ __forceinline__ uint32_t hsub2(uint32_t a, uint32_t b) {
  uint32_t r;
  asm("sub.rn.bf16x2 %0, %1, %2;" : "=r"(r) : "r"(a), "r"(b));
  return r;
}
__device__ __forceinline__ uint32_t movm(uint32_t a) {
  uint32_t r;
  asm volatile("movmatrix.sync.aligned.m8n8.trans.b16 %0, %1;" : "=r"(r) : "r"(a));
  return r;
}
__device__ __forceinline__ void ldsm4(uint32_t (&v)[4], uint32_t a) {
  asm volatile("ldmatrix.sync.aligned.m8n8.x4.shared.b16 {%0,%1,%2,%3}, [%4];" : "=r"(v[0]), "=r"(v[1]), "=r"(v[2]), "=r"(v[3]) : "r"(a + own()) : "memory");
}
__device__ __forceinline__ void stsm4(uint32_t a, const uint32_t (&v)[4]) {
  asm volatile("stmatrix.sync.aligned.m8n8.x4.shared.b16 [%0], {%1,%2,%3,%4};" ::"r"(a + own()), "r"(v[0]), "r"(v[1]), "r"(v[2]), "r"(v[3]) : "memory");
}
__device__ __forceinline__ void mma16816(float (&d)[4], const uint32_t (&a)[4], uint32_t b0, uint32_t b1) {
  asm volatile("mma.sync.aligned.m16n8k16.row.col.f32.bf16.bf16.f32 {%0,%1,%2,%3}, {%4,%5,%6,%7}, {%8,%9}, {%10,%10,%10,%10};"
               : "=f"(d[0]), "=f"(d[1]), "=f"(d[2]), "=f"(d[3])
               : "r"(a[0]), "r"(a[1]), "r"(a[2]), "r"(a[3]), "r"(b0), "r"(b1), "f"(0.f));
}
__device__ __forceinline__ void mma1688_acc(float (&d)[4], uint32_t a0, uint32_t a1, uint32_t b0) {
  asm volatile("mma.sync.aligned.m16n8k8.row.col.f32.bf16.bf16.f32 {%0,%1,%2,%3}, {%4,%5}, {%6}, {%0,%1,%2,%3};"
               : "+f"(d[0]), "+f"(d[1]), "+f"(d[2]), "+f"(d[3]) : "r"(a0), "r"(a1), "r"(b0));
}
__device__ __forceinline__ float ex2(float x) { float y; asm("ex2.approx.ftz.f32 %0, %1;" : "=f"(y) : "f"(x)); return y; }
__device__ __forceinline__ float rcp(float x) { float y; asm("rcp.approx.ftz.f32 %0, %1;" : "=f"(y) : "f"(x)); return y; }
__device__ __forceinline__ float tanhf_hw(float x) { float y; asm("tanh.approx.f32 %0, %1;" : "=f"(y) : "f"(x)); return y; }
__device__ __forceinline__ uint32_t lds32(uint32_t a) { uint32_t v; asm volatile("ld.shared.u32 %0, [%1];" : "=r"(v) : "r"(a + own()) : "memory"); return v; }
__device__ __forceinline__ float2 lds64(uint32_t a) { float2 v; asm volatile("ld.shared.v2.f32 {%0,%1}, [%2];" : "=f"(v.x), "=f"(v.y) : "r"(a + own()) : "memory"); return v; }
__device__ __forceinline__ void lds128(uint32_t (&v)[4], uint32_t a) { asm volatile("ld.shared.v4.u32 {%0,%1,%2,%3}, [%4];" : "=r"(v[0]), "=r"(v[1]), "=r"(v[2]), "=r"(v[3]) : "r"(a + own()) : "memory"); }
__device__ __forceinline__ void sts128(uint32_t a, const uint32_t (&v)[4]) { asm volatile("st.shared.v4.u32 [%0], {%1,%2,%3,%4};" ::"r"(a + own()), "r"(v[0]), "r"(v[1]), "r"(v[2]), "r"(v[3]) : "memory"); }
__device__ __forceinline__ void ldg128_nc(uint32_t (&v)[4], const void* p) {
  asm volatile("ld.global.nc.L1::no_allocate.v4.u32 {%0,%1,%2,%3}, [%4];" : "=r"(v[0]), "=r"(v[1]), "=r"(v[2]), "=r"(v[3]) : "l"(p));
}
__device__ __forceinline__ uint32_t pin(uint32_t v, uint32_t zero) {
  asm volatile("{\n.reg .pred p;\n.reg .u32 c;\nmov.u32 c, %1;\nLP:\n.pragma \"nounroll\";\nsetp.eq.u32 p, c, 0;\n@p bra LD;\n"
               "nanosleep.u32 c;\nadd.u32 %0, %0, c;\nsub.u32 c, c, 1;\nbra LP;\nLD:\n}\n" : "+r"(v) : "r"(zero) : "memory");
  return v;
}
__device__ __forceinline__ void mbar_arrive_if(uint32_t b, bool cond) {
  asm volatile("{\n.reg .pred p;\nsetp.ne.u32 p, %1, 0;\n@p mbarrier.arrive.shared::cta.b64 _, [%0];\n}\n" ::"r"(b + own()), "r"((uint32_t)cond) : "memory");
}
__device__ __forceinline__ uint32_t ld_epoch(const unsigned* p) {
  uint32_t v;
  asm volatile("ld.relaxed.gpu.global.u32 %0, [%1];" : "=r"(v) : "l"(p) : "memory");
  return v;
}
__device__ __forceinline__ void ll_st(uint4* p, uint32_t a, uint32_t b, uint32_t c, uint32_t d, uint32_t tag) {
  asm volatile("st.relaxed.gpu.global.v4.b32 [%0], {%1, %2, %3, %4};" ::"l"(p), "r"((a & ~1u) | tag), "r"(b), "r"(c), "r"(d) : "memory");
}
__device__ __forceinline__ void ll_ld(uint32_t (&v)[4], const uint4* p) {
  asm volatile("{\n.reg .b128 t;\n.reg .b64 lo, hi;\nld.relaxed.gpu.global.b128 t, [%4];\nmov.b128 {lo, hi}, t;\n"
               "mov.b64 {%0, %1}, lo;\nmov.b64 {%2, %3}, hi;\n}\n"
               : "=r"(v[0]), "=r"(v[1]), "=r"(v[2]), "=r"(v[3]) : "l"(p) : "memory");
}
template <int N> __device__ __forceinline__ void ll_issue(uint32_t (&v)[N][4], const uint4* p, int stride) {
#pragma unroll
  for (int i = 0; i < N; i++) ll_ld(v[i], p + i * stride);
}
template <int N> __device__ __forceinline__ uint32_t ll_acc(const uint32_t (&v)[N][4], uint32_t tag, uint32_t acc = 0) {
#pragma unroll
  for (int i = 0; i < N; i++) asm("lop3.b32 %0, %1, %2, %0, 0xBE;" : "+r"(acc) : "r"(v[i][0]), "r"(tag));
  return acc;
}
__device__ __forceinline__ bool ll_any(uint32_t acc) { return __any_sync(0xffffffffu, acc & 1u); }
template <int N> __device__ __forceinline__ bool ll_bad(const uint32_t (&v)[N][4], uint32_t tag) { return ll_any(ll_acc<N>(v, tag)); }
template <int N> __device__ __forceinline__ void ll_clear(uint32_t (&v)[N][4]) {
#pragma unroll
  for (int i = 0; i < N; i++) v[i][0] &= ~1u;
}
template <int N> __device__ __forceinline__ void ll_spin(uint32_t (&v)[N][4], const uint4* p, int stride, uint32_t tag) {
  uint32_t it = 0;
#pragma unroll 1
  do { ll_issue<N>(v, p, stride); } while (ll_bad<N>(v, tag) && ++it < SPIN_LIMIT);
}
template <int N> __device__ __forceinline__ void ll_get(uint32_t (&v)[N][4], const uint4* p, int stride, uint32_t tag) {
  ll_spin<N>(v, p, stride, tag);
  ll_clear<N>(v);
}
template <int N> __device__ __forceinline__ void ll_wait(uint32_t (&v)[N][4], const uint4* p, int stride, uint32_t tag) {
  if (__builtin_expect(ll_bad<N>(v, tag), 0)) ll_spin<N>(v, p, stride, tag);
  ll_clear<N>(v);
}
__device__ __forceinline__ void unpack32(float (&d)[32], const uint32_t (&v)[4][4]) {
#pragma unroll
  for (int u = 0; u < 4; u++)
#pragma unroll
    for (int e = 0; e < 4; e++) { d[8 * u + 2 * e] = bf_lo(v[u][e]); d[8 * u + 2 * e + 1] = bf_hi(v[u][e]); }
}
__device__ __forceinline__ void pack32(uint32_t (&v)[4][4], const float (&d)[32]) {
#pragma unroll
  for (int u = 0; u < 4; u++)
#pragma unroll
    for (int e = 0; e < 4; e++) v[u][e] = pack2(d[8 * u + 2 * e], d[8 * u + 2 * e + 1]);
}
__device__ __forceinline__ uint32_t t_addr(int m) { return SB + ((0x01534620u >> (4 * m)) & 7u) * 32768u; }

__device__ __forceinline__ constexpr int w2_pass(int m) { return m < 4 ? m & 1 : m >> 1; }
__device__ __forceinline__ constexpr int w2_peer(int m) { return m < 4 ? m >> 1 : m & 1; }

__device__ __forceinline__ int kb_at(int i, int j) { return i == 0 ? j : (i - 1 + (i - 1 >= j ? 1 : 0)); }

__device__ __forceinline__ void init_bars(int set) {
  if (set >= 0 && elect_one()) {
    const uint32_t cnt = set < 5 ? 1 : 8;
#pragma unroll
    for (int i = 0; i < 8; i++) mbar_init(BAR + (24 + 8 * set + i) * 8, cnt);
    if (set == 9) {
#pragma unroll
      for (int i = 0; i < 9; i++) mbar_init(BAR + (B_EX + i) * 8, 4);
#pragma unroll
      for (int i = 0; i < 4; i++) mbar_init(BAR + (B_READY + i) * 8, i == 0 ? 2 : i == 3 ? 4 : 3);
#pragma unroll
      for (int i = 0; i < 9; i++) mbar_init(BAR + (B_TAG + i) * 8, i < 1 || i == 8 ? 1 : i < 7 ? 4 : 3);
    }
    asm volatile("fence.mbarrier_init.release.cluster;" ::: "memory");
  }
  __syncwarp();
  asm volatile("barrier.cluster.arrive.relaxed.aligned;" ::: "memory");
  asm volatile("bar.arrive 4, 384;" ::: "memory");
  asm volatile("bar.sync 3, 384;" ::: "memory");
}

__device__ __forceinline__ void load_a(const Params& P, int i, int j) {
  const int f0 = 224 * j + ((j & 1) ? 32 : 0);
  const int fh = 224 * j + ((j & 1) ? 0 : 192);
  const uint32_t b = BAR + (B_FA + i) * 8, d = RING + (i & 3) * 24576;
  const int k0 = kb_at(i, j) * 64;
  mbar_expect_tx(b, 24576);
  tma2d(d, &P.w1, f0, k0, b);
  tma2d(d + 8192, &P.w3, f0, k0, b);
  tma2d(d + 16384, &P.w1h, fh, k0, b);
  tma2d(d + 20480, &P.w3h, fh, k0, b);
}

__global__ void __launch_bounds__(384, 1) fused_block_kernel(Scratch* __restrict__ X, const __nv_bfloat16* __restrict__ xp,
                                                             const __nv_bfloat16* __restrict__ wqkvp, const __nv_bfloat16* __restrict__ wop, const uint32_t zero,
                                                             const __grid_constant__ Params P) {
  extern __shared__ __align__(1024) uint8_t smem_raw[];
  if (smem_u32(smem_raw) != SB + own()) return;
  const int tid = threadIdx.x;
  const int warp = __shfl_sync(0xffffffffu, tid >> 5, 0);
  const int lane = tid & 31;
  const int cta = blockIdx.x;
  const int j = ((cta >> 1) & 1) * 4 + ((cta >> 4) & 1) * 2 + (cta & 1);
  const int g = ((cta >> 2) & 3) * 4 + (cta >> 5);

  if (warp >= 8) {
    asm volatile("setmaxnreg.dec.sync.aligned.u32 56;");
    if (warp == 8) {
      PSTAMPW(2, 0);
      const bool leader = elect_one();
      if (leader) {
        prefetch_map(&P.x); prefetch_map(&P.wqkv);
#pragma unroll
        for (int i = 0; i < 24; i++) mbar_init(BAR + i * 8, 1);
        asm volatile("fence.mbarrier_init.release.cluster;" ::: "memory");
      }
      __syncwarp();
      asm volatile("bar.arrive 3, 384;" ::: "memory");
      asm volatile("barrier.cluster.arrive.relaxed.aligned;" ::: "memory");
      auto ldx = [&](int p, int kb) {
        const uint32_t b = BAR + (B_FX + p * 8 + kb) * 8;
        mbar_expect_tx(b, 8192);
        tma3d(H0 + p * 65536 + kb * 8192, &P.x, kb * 64, p, g * 64, b);
      };
      auto ldkv = [&](int kb, int slot) {
        const uint32_t b = BAR + (B_FKV + kb) * 8, d = RING + slot * 16384;
        mbar_expect_tx(b, 16384);
        tma2d(d, &P.wqkv, 512 + 64 * j, kb * 64, b);
        tma2d(d + 8192, &P.wqkv, 1024 + 64 * j, kb * 64, b);
      };
      if (leader) {
#pragma unroll 1
        for (int i = 0; i < 8 + XO_DELAY; i++) {
          if (i < 8) ldx(0, i);
          if (i < 6) ldkv(i, i);
          if (i >= XO_DELAY) ldx(1, i - XO_DELAY);
        }
#pragma unroll
        for (int i = 0; i < 4; i++)
          asm volatile("cp.async.bulk.prefetch.tensor.2d.L2.global [%0, {%1, %2}];" ::"l"(&P.wqkv), "r"(512 + (i & 1) * 512 + 64 * j), "r"(384 + (i >> 1) * 64) : "memory");
        PSTAMPW(2, 2);
      }
      __syncwarp();
      asm volatile("bar.sync 4, 384;" ::: "memory");
      if (leader) {
        const int f0 = 224 * j + ((j & 1) ? 32 : 0);
        prefetch_map(&P.wo); prefetch_map(&P.w1); prefetch_map(&P.w3); prefetch_map(&P.w1h);
        prefetch_map(&P.w3h); prefetch_map(&P.w2); prefetch_map(&P.out);
#pragma unroll 1
        for (int i = 0; i < 2; i++) { mbar_wait(BAR + (B_EKV + i) * 8); ldkv(6 + i, i); }
#pragma unroll 1
        for (int i = 0; i < 8; i++) {
          const uint32_t b = BAR + (B_FQ + i) * 8;
          mbar_wait(BAR + (B_EKV + 2 + (i >> 1)) * 8);
          mbar_expect_tx(b, 8192);
          tma2d(RING + (4 + i) * 8192, &P.wqkv, 64 * j, i * 64, b);
        }
        mbar_expect_tx(BAR + B_FWO * 8, 65536);
#pragma unroll 1
        for (int i = 0; i < 8; i++) {
          const int kb = (i + 1) & 7;
          mbar_wait(BAR + (B_EX + i) * 8);
          tma2d(H0 + kb * 8192, &P.wo, 64 * j, kb * 64, BAR + B_FWO * 8);
        }
        mbar_wait(BAR + B_OG * 8);
#pragma unroll 1
        for (int i = 2; i < 8; i++) {
          mbar_wait(BAR + (B_EQ + (i == 2 ? 4 : 4 + i)) * 8);
          load_a(P, i, j);
        }
        uint32_t d = RING;
#pragma unroll 1
        for (int i = 0; i < 8; i++) {
          const uint32_t b = BAR + (B_FB + i) * 8;
          const int k0 = kb_at(i, j) * 64;
          mbar_wait(BAR + (B_EA + 5 + i) * 8);
          mbar_expect_tx(b, 32768);
          tma2d(d, &P.w1, f0 + 64, k0, b);
          tma2d(d + 8192, &P.w3, f0 + 64, k0, b);
          tma2d(d + 16384, &P.w1, f0 + 128, k0, b);
          tma2d(d + 24576, &P.w3, f0 + 128, k0, b);
          d = d == RING + 65536 ? RING : d + 32768;
        }
#pragma unroll 1
        for (int i = 0; i < 8; i++) {
          const int m = (0x76453210u >> (4 * i)) & 7;
          const uint32_t b = BAR + (B_FT + m) * 8;
          mbar_wait(BAR + (i < 5 ? B_EB + 3 + i : i < 7 ? B_HC - 5 + i : B_ET0) * 8);
          mbar_expect_tx(b, 28672);
          tma2d(t_addr(m), &P.w2, 64 * ((j + 2 + 2 * w2_pass(m)) & 7), 224 * (j ^ w2_peer(m)), b);
          PSTAMPW(2, 4 + i);
        }
#pragma unroll 1
        for (int q = 0; q < 2; q++) {
          mbar_expect_tx(BAR + (B_FIN + q) * 8, 16384);
          mbar_wait(BAR + (B_ET0 + 3 - q) * 8);
          PSTAMPW(2, 24 + q);
          asm volatile("cp.async.bulk.shared::cluster.global.mbarrier::complete_tx::bytes [%0], [%1], 16384, [%2];"
                       ::"r"(t_addr(q + 1) + own()), "l"(X->e4 + ((g * 8 + j) * 3 + q) * 1024), "r"(BAR + (B_FIN + q) * 8 + own()) : "memory");
        }
        X->epoch[cta] = X->epoch[cta] + 1;
      }
    } else {
      const int part = warp - 9;
      uint32_t tag;
      if (part == 2) {
        tag = ld_epoch(X->epoch + cta);
        init_bars(-1);
        tag = (tag + 1) & 1;
        if (lane == 0) {
          asm volatile("st.shared.u32 [%0], %1;" ::"r"(TAGS + own()), "r"(tag) : "memory");
          mbar_arrive(BAR + B_TAG * 8);
        }
      } else {
        init_bars(warp - 1);
        mbar_wait(BAR + B_TAG * 8);
        tag = lds32(TAGS);
      }
      PSTAMPW(3, 16 + part);
      auto clear8 = [&](uint4* p, int stride) {
#pragma unroll
        for (int i = 0; i < 8; i++) ll_st(p + i * stride + lane, 0, 0, 0, 0, tag ^ 1);
      };
      if (part == 0 && lane < 20)
        ll_st(lane < 16 ? X->e0s + g * 128 + 16 * j + lane : X->e0w + j * 64 + g * 4 + lane - 16, 0, 0, 0, 0, tag ^ 1);
      if (lane < 16) ll_st(X->e0c + ((j * 3 + part) * 16 + g) * 16 + lane, 0, 0, 0, 0, tag ^ 1);
      if (CLR_MODE && part == 1) clear8(X->e1 + (g * 8 + j) * 256, 32);
      __syncwarp();
      if (lane == 0) mbar_arrive(BAR + B_CLR1 * 8);
      uint32_t v[8][4];
      {
        float s[4] = {0.f, 0.f, 0.f, 0.f}, q[4] = {0.f, 0.f, 0.f, 0.f};
        const uint32_t xa = H0 + ((lane >> 1) & 1) * 65536 + (8 * j + (lane >> 2)) * 128 + (lane & 1) * 64 + ((lane >> 1) & 3) * 16;
#pragma unroll 1
        for (int kb = part; kb < 8; kb += 3) {
          mbar_wait(BAR + (B_FX + kb) * 8);
          mbar_wait(BAR + (B_FX + 8 + kb) * 8);
          if (kb == 3 && lane == 0) l2_prefetch(wop + (size_t)(j * 64 + g * 4) * D_, 4096);
#pragma unroll
          for (int i = 0; i < 4; i++) lds128(v[i], (xa + kb * 8192) ^ (i * 16));
#pragma unroll
          for (int e = 0; e < 16; e++) {
            const float a = bf_lo(v[e >> 2][e & 3]), b = bf_hi(v[e >> 2][e & 3]);
            s[e & 3] += a + b; q[e & 3] = fmaf(a, a, q[e & 3]); q[e & 3] = fmaf(b, b, q[e & 3]);
          }
        }
        float ss = (s[0] + s[1]) + (s[2] + s[3]), qq = (q[0] + q[1]) + (q[2] + q[3]);
        ss += __shfl_xor_sync(0xffffffffu, ss, 1); qq += __shfl_xor_sync(0xffffffffu, qq, 1);
        if (part && !(lane & 1))
          asm volatile("st.shared.v2.f32 [%0], {%1,%2};" ::"r"(WB + own() + part * 128 - 128 + lane * 4), "f"(ss), "f"(qq) : "memory");
        if (part) asm volatile("bar.arrive 5, 96;" ::: "memory");
        else {
          asm volatile("bar.sync 5, 96;" ::: "memory");
          const float2 t1 = lds64(WB + (lane >> 1) * 8), t2 = lds64(WB + 128 + (lane >> 1) * 8);
          const float mean = (ss + t1.x + t2.x) * (1.f / D_);
          const float rs = rsqrtf(fmaxf(fmaf(-mean, mean, (qq + t1.y + t2.y) * (1.f / D_)), 0.f) + 1e-5f);
          if (!(lane & 1)) ll_st(X->e0s + g * 128 + 16 * j + (lane >> 1), __float_as_uint(mean), __float_as_uint(rs), 0, 0, tag);
        }
      }
      PSTAMPW(3, part * 4 + 2);
      if (PF_MODE == 0 && lane == 0) l2_prefetch(part == 0 ? P.w2p + (size_t)cta * 14 * D_ : (part == 1 ? P.w1p : P.w3p) + (size_t)cta * 4 * F_, 14336);
      if (part == 0) {
        const __nv_bfloat16* wr = wop + (size_t)(j * 64 + g * 4 + (lane >> 3)) * D_ + (lane & 7) * 8;
#pragma unroll
        for (int i = 0; i < 8; i++) ldg128_nc(v[i], wr + i * 64);
        float s[4];
#pragma unroll
        for (int e = 0; e < 4; e++) {
          s[e] = 0.f;
#pragma unroll
          for (int i = 0; i < 8; i++) s[e] += bf_lo(v[i][e]) + bf_hi(v[i][e]);
        }
        float ss = (s[0] + s[1]) + (s[2] + s[3]);
#pragma unroll
        for (int o = 1; o <= 4; o <<= 1) ss += __shfl_xor_sync(0xffffffffu, ss, o);
        if ((lane & 7) == 0) ll_st(X->e0w + j * 64 + g * 4 + (lane >> 3), __float_as_uint(ss * (1.f / D_)), 0, 0, 0, tag);
      }
      PSTAMPW(3, part * 4 + 0);
      {
        uint32_t u[2][4];
        const uint4* us = (part == 0 ? X->e0w + j * 64 : X->e0s + g * 128 + (part - 1) * 64) + lane;
        const uint4* vs = X->e0c + ((j * 3 + part) * 16 + (lane >> 4) * 8) * 16 + (lane & 15);
        uint32_t it = 0;
#pragma unroll 1
        do { ll_issue<2>(u, us, 32); ll_issue<8>(v, vs, 16); } while (ll_any(ll_acc<8>(v, tag, ll_acc<2>(u, tag))) && ++it < SPIN_LIMIT);
        ll_clear<2>(u); ll_clear<8>(v);
#pragma unroll
        for (int i = 0; i < 2; i++) {
          if (part == 0) asm volatile("st.shared.u32 [%0], %1;" ::"r"(WB + own() + (i * 32 + lane) * 4), "r"(u[i][0]) : "memory");
          else asm volatile("st.shared.v2.u32 [%0], {%1,%2};" ::"r"(ST + own() + (part * 64 - 64 + i * 32 + lane) * 8), "r"(u[i][0]), "r"(u[i][1]) : "memory");
        }
        uint32_t o[4];
#pragma unroll
        for (int e = 0; e < 4; e++) {
          float s = 0.f;
#pragma unroll
          for (int i = 0; i < 8; i++) s += __uint_as_float(v[i][e]);
          o[e] = __float_as_uint(s + __shfl_xor_sync(0xffffffffu, s, 16));
        }
        if (lane < 16) sts128(CS + (part * 64 + lane * 4) * 4, o);
      }
      __syncwarp();
      if (lane == 0) mbar_arrive(BAR + (part == 0 ? B_WBAR : B_READY) * 8);
      PSTAMPW(3, part * 4 + 1);
      if (part == 1 && elect_one()) {
#pragma unroll 1
        for (int i = 0; i < 2; i++) { mbar_wait(BAR + (B_EKV + 7 + 2 * i) * 8); load_a(P, i, j); }
      }
      if (CLR_MODE && part == 2) {
        mbar_wait(BAR + (CLR_WHEN) * 8);
#pragma unroll
        for (int i = 0; i < 2; i++) ll_st(X->e3s + ((g * 8 + i * 4 + (lane >> 3)) * 8 + j) * 8 + (lane & 7), 0, 0, 0, 0, tag ^ 1);
#pragma unroll 1
        for (int u = 0; u < 4; u++) {
          clear8(X->e3h + (g * 256 + 4 * j + u) * 32, 1024);
          __nanosleep(CLR_SLEEP2);
        }
      }
      __syncwarp();
      if (part == 2 && lane == 0) mbar_arrive(BAR + B_CLR2 * 8);
      PSTAMPW(3, 20 + part);
      if (PF_MODE == 2) mbar_wait(BAR + (B_FQ + 7) * 8);
      if (PF_MODE >= 1 && lane == 0) l2_prefetch(part == 0 ? P.w2p + (size_t)cta * 14 * D_ : (part == 1 ? P.w1p : P.w3p) + (size_t)cta * 4 * F_, 14336);
      mbar_wait(BAR + (E4_WHEN) * 8);
#pragma unroll 1
      for (int u = 0; u < 4 * E4_ON; u++) {
        clear8(X->e4 + ((g * 8 + ((j + 2 + 2 * part) & 7)) * 3 + part) * 1024 + u * 32, 128);
        __nanosleep(CLR_SLEEP);
      }
      __syncwarp();
      if (lane == 0) mbar_arrive(BAR + B_CLR * 8);
      PSTAMPW(3, part * 4 + 3);
    }
  } else {
    const int p = warp >> 2, w = warp & 3;
    const int r = lane >> 2, c = lane & 3;
    init_bars(warp);
    asm volatile("setmaxnreg.inc.sync.aligned.u32 224;");
    PSTAMP(0);
    const uint32_t dAx = descA(H0) + p * 4096;
    const uint32_t Hn = H1 - p * 65536;
    const uint32_t moff = ((lane & 7) + ((lane >> 3) & 1) * 8) * 128 + (((lane >> 4) ^ (lane & 7)) << 4);
    const uint32_t Xw = H0 + p * 65536 + w * 2048;
    const int xw = (g * 2 + p) * 4 + w;
    uint32_t cv[8][4];
    if (p == 1) {
      mbar_wait(BAR + (B_FKV + SIDE_KB) * 8);
      const int wp = w < 3 ? w : 0;
      const __nv_bfloat16* wr = wqkvp + (size_t)(g * 32 + (lane >> 3) * 8) * (3 * D_) + wp * D_ + j * 64 + (lane & 7) * 8;
#pragma unroll
      for (int i = 0; i < 8; i++) ldg128_nc(cv[i], wr + (size_t)i * 3 * D_);
      mbar_wait(BAR + B_LAG * 8);
    }

    float akv[64];
    auto kvstep = [&](int kb) {
      mbar_wait(BAR + (B_FX + p * 8 + kb) * 8);
      mbar_wait(BAR + (B_FKV + kb) * 8);
      if (kb == 0) PSTAMP(2);
      const uint32_t da = dAx + kb * 512, db = descB(RING) + (kb < 6 ? kb : kb - 6) * 1024;
      wg_fence();
      wgmma_ss_n128(akv, da, db, kb);
#pragma unroll
      for (int k = 1; k < 4; k++) wgmma_ss_n128(akv, da + k * 2, db + k * 128, 1);
      wg_commit();
      mbar_arrive_if(BAR + B_LAG * 8, kb == LAG_KB - 1 && p == 0 && lane == 0);
      wg_wait<1>();
      mbar_arrive_if(BAR + (B_EKV + kb - 1) * 8, kb > 0 && lane == 0);
    };
#pragma unroll
    for (int kb = 0; kb < CS_KB; kb++) kvstep(kb);
    if (p == 1) {
      PSTAMP(29);
      mbar_wait(BAR + B_CLR1 * 8);
      const uint32_t tg = lds32(TAGS);
      const uint32_t hm = 0xffff0000u | (tg >> 1), sh = 16 + (tg >> 1);
      float cs[8];
#pragma unroll
      for (int e = 0; e < 4; e++) {
        float a = 0.f, b = 0.f;
#pragma unroll
        for (int i = 0; i < 8; i++) { a += __uint_as_float(cv[i][e] << sh); b += __uint_as_float(cv[i][e] & hm); }
        cs[2 * e] = a; cs[2 * e + 1] = b;
      }
      const bool up = lane & 8;
#pragma unroll
      for (int e = 0; e < 4; e++) {
        const float keepv = up ? cs[4 + e] : cs[e], give = up ? cs[e] : cs[4 + e];
        cs[e] = keepv + __shfl_xor_sync(0xffffffffu, give, 8);
        cs[e] += __shfl_xor_sync(0xffffffffu, cs[e], 16);
      }
      if (lane < 16 && w < 3)
        ll_st(X->e0c + ((j * 3 + w) * 16 + g) * 16 + (lane & 7) * 2 + (lane >> 3), __float_as_uint(cs[0]), __float_as_uint(cs[1]),
              __float_as_uint(cs[2]), __float_as_uint(cs[3]), tg);
      PSTAMP(1);
    }
#pragma unroll 1
    for (int kb = CS_KB; kb < 8; kb++) kvstep(kb);
    asm volatile("barrier.cluster.wait.aligned;" ::: "memory");
    uint32_t xres[4][4];
#pragma unroll
    for (int u = 0; u < 4; u++) ldsm4(xres[u], Xw + j * 8192 + (moff ^ (u << 5)));

    float aq[32];
    auto qstep = [&](int kb) {
      mbar_wait(BAR + (B_FQ + kb) * 8);
      const uint32_t da = dAx + kb * 512, db = descB(RING + 32768) + kb * 512;
      wg_fence();
      wgmma_ss_n64(aq, da, db, kb);
#pragma unroll
      for (int k = 1; k < 4; k++) wgmma_ss_n64(aq, da + k * 2, db + k * 128, 1);
      wg_commit();
      wg_wait<1>();
      mbar_arrive_if(BAR + (B_EQ + kb - 1) * 8, lane == 0);
      mbar_arrive_if(BAR + (B_EX + kb - 2) * 8, lane == 0 && p == 0 && kb >= 2);
    };
    qstep(0);
    keep(akv);
    PSTAMP(3);
    qstep(1);
    mbar_wait(BAR + B_READY * 8);
    PSTAMP(19);
    const uint32_t tag = lds32(TAGS);
    uint4* const xb = reinterpret_cast<uint4*>(X) + lane + (tag >> 1);
    constexpr int O_E4 = offsetof(Scratch, e4) / 16, O_E2 = offsetof(Scratch, e2) / 16, O_E3H = offsetof(Scratch, e3h) / 16;
    const float2 st0 = lds64(ST + (2 * (16 * w + r) + p) * 8);
    const float2 st1 = lds64(ST + (2 * (16 * w + r + 8) + p) * 8);
    uint32_t hi[4][4], lo[4][4];
    {
      float2 cs[16];
      auto cvt = [&](uint32_t (&d)[4][4], int b0, int ofs, const float2& st) {
#pragma unroll
        for (int b = b0; b < b0 + 8; b++) {
          if (ofs == 2) cs[b] = lds64(CS + (64 + b * 8 + 2 * c) * 4);
          const uint32_t v = pack2(fmaf(-st.x, cs[b].x, akv[4 * b + ofs]) * st.y, fmaf(-st.x, cs[b].y, akv[4 * b + ofs + 1]) * st.y);
          d[b >> 2][b & 3] = b < 8 ? v : movm(v);
        }
      };
      cvt(hi, 0, 2, st1);
      keep(hi[0]); keep(hi[1]);
      qstep(2);
      cvt(hi, 8, 2, st1);
      if (w == 3 && g < 15) {
        uint4* dst = X->e1 + ((g * 8 + j) * 2 + p) * 128 + lane;
#pragma unroll
        for (int i = 0; i < 4; i++) ll_st(dst + i * 32, hi[i][0], hi[i][1], hi[i][2], hi[i][3], tag);
      }
      PSTAMP(20);
      wg_bar(p);
#pragma unroll
      for (int i = 0; i < 4; i++) sts128(Xw + lane * 16 + i * 512, hi[i]);
      qstep(3);
      cvt(lo, 0, 0, st0);
      keep(lo[0]); keep(lo[1]);
      qstep(4);
      cvt(lo, 8, 0, st0);
    }
    PSTAMP(21);
    wg_bar(p);
    uint32_t prev[4][4];
    if (w > 0) {
#pragma unroll
      for (int i = 0; i < 4; i++) lds128(prev[i], Xw - 2048 + lane * 16 + i * 512);
    }
    if (p == 0) {
      asm volatile("fence.proxy.async.shared::cta;" ::: "memory");
      __syncwarp();
      if (lane == 0) mbar_arrive(BAR + (B_EX + 7) * 8);
    }
    PSTAMP(22);
    const uint4* halo = X->e1 + (((g - 1) * 8 + j) * 2 + p) * 128 + lane;
    const bool use_halo = w == 0 && g > 0;
    qstep(5);
    if (use_halo) ll_issue<4>(prev, halo, 32);
    qstep(6);
    qstep(7);
    PSTAMP(23);
    if (w == 0) {
      if (g > 0) {
        if (__builtin_expect(ll_bad<4>(prev, pin(tag, zero)), 0)) ll_spin<4>(prev, halo, 32, tag);
        ll_clear<4>(prev);
      } else {
#pragma unroll
        for (int i = 0; i < 4; i++)
#pragma unroll
          for (int e = 0; e < 4; e++) prev[i][e] = 0;
      }
    }
    wg_wait<0>();
    keep(aq);
    mbar_arrive_if(BAR + (B_EQ + 7) * 8, lane == 0);
    mbar_arrive_if(BAR + (B_EX + 6) * 8, lane == 0 && p == 0);
    PSTAMP(4);

    uint32_t of[4][4];
    mbar_wait(BAR + B_WBAR * 8);
    {
      const float sc = 0.25f * 1.4426950408889634f;
      const float nohalo = (g == 0 && w == 0) ? -INFINITY : 0.f;
      const bool up0 = 2 * c > r, up1 = 2 * c + 1 > r;
      const uint32_t mup = (up0 ? 0xffffu : 0u) | (up1 ? 0xffff0000u : 0u);
      uint4* dst = xb + O_E2 + (xw * 32 + 4 * j) * 32;
      float d0 = 0.f, d1 = 0.f;
#pragma unroll 1
      for (int hp = 0; hp < 2; hp++) {
#pragma unroll
        for (int e = 0; e < 4; e++) { of[0][e] = of[2][e]; of[1][e] = of[3][e]; }
#pragma unroll
        for (int h = 0; h < 2; h++) {
          uint32_t qf[4];
          const uint32_t co = (32 * hp + 16 * h + 2 * c) * 4;
          {
            const float2 ca = lds64(CS + co), cb = lds64(CS + co + 32);
            qf[0] = pack2(fmaf(-st0.x, ca.x, aq[8 * h + 0]) * st0.y, fmaf(-st0.x, ca.y, aq[8 * h + 1]) * st0.y);
            qf[1] = pack2(fmaf(-st1.x, ca.x, aq[8 * h + 2]) * st1.y, fmaf(-st1.x, ca.y, aq[8 * h + 3]) * st1.y);
            qf[2] = pack2(fmaf(-st0.x, cb.x, aq[8 * h + 4]) * st0.y, fmaf(-st0.x, cb.y, aq[8 * h + 5]) * st0.y);
            qf[3] = pack2(fmaf(-st1.x, cb.x, aq[8 * h + 6]) * st1.y, fmaf(-st1.x, cb.y, aq[8 * h + 7]) * st1.y);
          }
          const int e0 = 2 * h;
          float sp[4], sl[4], sh[4];
          mma16816(sp, qf, prev[0][e0], prev[0][e0 + 1]);
          mma16816(sl, qf, lo[0][e0], lo[0][e0 + 1]);
          mma16816(sh, qf, hi[0][e0], hi[0][e0 + 1]);
          float a0 = up0 ? sp[0] + nohalo : sl[0], a1 = up1 ? sp[1] + nohalo : sl[1];
          float b0 = up0 ? sl[2] : sh[2], b1 = up1 ? sl[3] : sh[3];
          float ma = fmaxf(a0, a1), mb = fmaxf(b0, b1);
          ma = fmaxf(ma, __shfl_xor_sync(0xffffffffu, ma, 1)); mb = fmaxf(mb, __shfl_xor_sync(0xffffffffu, mb, 1));
          ma = fmaxf(ma, __shfl_xor_sync(0xffffffffu, ma, 2)); mb = fmaxf(mb, __shfl_xor_sync(0xffffffffu, mb, 2));
          a0 = ex2((a0 - ma) * sc); a1 = ex2((a1 - ma) * sc); b0 = ex2((b0 - mb) * sc); b1 = ex2((b1 - mb) * sc);
          float sa = a0 + a1, sbb = b0 + b1;
          sa += __shfl_xor_sync(0xffffffffu, sa, 1); sbb += __shfl_xor_sync(0xffffffffu, sbb, 1);
          sa += __shfl_xor_sync(0xffffffffu, sa, 2); sbb += __shfl_xor_sync(0xffffffffu, sbb, 2);
          const float ia = rcp(sa), ib = rcp(sbb);
          const uint32_t pa = pack2(a0 * ia, a1 * ia), pb = pack2(b0 * ib, b1 * ib);
          const uint32_t pf[4] = {pa & mup, 0u, pa & ~mup, pb & mup};
          const uint32_t ph = pb & ~mup;
          float o0[4], o1[4];
          mma16816(o0, pf, prev[2][e0], lo[2][e0]);
          mma16816(o1, pf, prev[2][e0 + 1], lo[2][e0 + 1]);
          mma1688_acc(o0, 0u, ph, hi[2][e0]);
          mma1688_acc(o1, 0u, ph, hi[2][e0 + 1]);
          of[2 + h][0] = pack2(o0[0], o0[1]); of[2 + h][1] = pack2(o0[2], o0[3]);
          of[2 + h][2] = pack2(o1[0], o1[1]); of[2 + h][3] = pack2(o1[2], o1[3]);
          ll_st(dst + (2 * hp + h) * 32, of[2 + h][0], of[2 + h][1], of[2 + h][2], of[2 + h][3], tag);
          const float2 wa = lds64(WB + co), wb = lds64(WB + co + 32);
          d0 = fmaf(o0[0], wa.x, d0); d0 = fmaf(o0[1], wa.y, d0); d0 = fmaf(o1[0], wb.x, d0); d0 = fmaf(o1[1], wb.y, d0);
          d1 = fmaf(o0[2], wa.x, d1); d1 = fmaf(o0[3], wa.y, d1); d1 = fmaf(o1[2], wb.x, d1); d1 = fmaf(o1[3], wb.y, d1);
        }
#pragma unroll
        for (int e = 0; e < 16; e++) aq[e] = aq[16 + e];
#pragma unroll
        for (int e = 0; e < 4; e++) {
          prev[0][e] = prev[1][e]; prev[2][e] = prev[3][e];
          lo[0][e] = lo[1][e]; lo[2][e] = lo[3][e];
          hi[0][e] = hi[1][e]; hi[2][e] = hi[3][e];
        }
      }
#pragma unroll
      for (int o = 1; o <= 2; o <<= 1) { d0 += __shfl_xor_sync(0xffffffffu, d0, o); d1 += __shfl_xor_sync(0xffffffffu, d1, o); }
      if (c == 0) ll_st(X->e2s + (xw * 8 + j) * 8 + r, __float_as_uint(d0), __float_as_uint(d1), 0, 0, tag);
    }
    PSTAMP(5);

    float ah[32];
    uint32_t sv[2][4];
    unpack32(ah, xres);
    {
      uint32_t og[2][14][4];
      const uint4* osrc[7];
#pragma unroll
      for (int i = 0; i < 7; i++) osrc[i] = xb + O_E2 + (xw * 32 + 4 * kb_at(i + 1, j)) * 32;
      const uint4* ssrc = X->e2s + (xw * 8 + 2 * c) * 8 + r;
      auto oissue = [&](int hp) {
#pragma unroll
        for (int i = 0; i < 14; i++) ll_ld(og[hp][i], osrc[i >> 1] + (2 * hp + (i & 1)) * 32);
        if (hp == 1) ll_issue<2>(sv, ssrc, 8);
      };
      auto omma = [&](int hp) {
        ll_clear<14>(og[hp]);
        keep(og[hp]);
        wg_fence();
#pragma unroll
        for (int i = 0; i < 14; i++) wgmma_rs_n64(ah, og[hp][i], descB(H0) + kb_at((i >> 1) + 1, j) * 512 + (2 * hp + (i & 1)) * 128, 1);
        wg_commit();
      };
      mbar_wait(BAR + B_FWO * 8);
      keep(ah); keep(of);
      wg_fence();
#pragma unroll
      for (int k = 0; k < 4; k++) wgmma_rs_n64(ah, of[k], descB(H0) + j * 512 + k * 128, 1);
      wg_commit();
      uint32_t it = 0;
#pragma unroll 1
      do { oissue(0); } while (ll_bad<14>(og[0], tag) && ++it < SPIN_LIMIT);
      PSTAMP(6);
      oissue(1);
      omma(0);
      const uint32_t tg = pin(tag, zero);
      if (__builtin_expect(ll_any(ll_acc<14>(og[1], tg, ll_acc<2>(sv, tg))), 0)) {
#pragma unroll 1
        do { oissue(1); } while (ll_any(ll_acc<14>(og[1], tag, ll_acc<2>(sv, tag))) && ++it < SPIN_LIMIT);
      }
      PSTAMP(16);
      mbar_arrive_if(BAR + B_OG * 8, lane == 0 && p == 0);
      omma(1);
      ll_clear<2>(sv);
    }
    float m0 = __uint_as_float(sv[0][0]) + __uint_as_float(sv[1][0]), m1 = __uint_as_float(sv[0][1]) + __uint_as_float(sv[1][1]);
#pragma unroll
    for (int o = 1; o <= 2; o <<= 1) { m0 += __shfl_xor_sync(0xffffffffu, m0, o); m1 += __shfl_xor_sync(0xffffffffu, m1, o); }
    const uint32_t mu0 = pack2(m0 + st0.x, m0 + st0.x), mu1 = pack2(m1 + st1.x, m1 + st1.x);
    wg_wait<0>();
    keep(ah);
    if (lane == 0) mbar_arrive(BAR + B_WODONE * 8);
    PSTAMP(7);

    uint32_t hf[4][4], ra[4][4];
    pack32(hf, ah);
    mbar_wait(BAR + B_CLR2 * 8);
    {
      uint4* dst = xb + O_E3H + (xw * 32 + 4 * j) * 32;
#pragma unroll
      for (int u = 0; u < 4; u++) {
        ra[u][0] = hsub2(hf[u][0], mu0); ra[u][1] = hsub2(hf[u][1], mu1);
        ra[u][2] = hsub2(hf[u][2], mu0); ra[u][3] = hsub2(hf[u][3], mu1);
        ll_st(dst + u * 32, ra[u][0], ra[u][1], ra[u][2], ra[u][3], tag);
      }
      float s0 = 0.f, q0 = 0.f, s1 = 0.f, q1 = 0.f;
#pragma unroll
      for (int b = 0; b < 8; b++) {
        s0 += ah[4 * b] + ah[4 * b + 1]; s1 += ah[4 * b + 2] + ah[4 * b + 3];
        q0 = fmaf(ah[4 * b], ah[4 * b], q0); q0 = fmaf(ah[4 * b + 1], ah[4 * b + 1], q0);
        q1 = fmaf(ah[4 * b + 2], ah[4 * b + 2], q1); q1 = fmaf(ah[4 * b + 3], ah[4 * b + 3], q1);
      }
#pragma unroll
      for (int o = 1; o <= 2; o <<= 1) {
        s0 += __shfl_xor_sync(0xffffffffu, s0, o); q0 += __shfl_xor_sync(0xffffffffu, q0, o);
        s1 += __shfl_xor_sync(0xffffffffu, s1, o); q1 += __shfl_xor_sync(0xffffffffu, q1, o);
      }
      if (c == 0) ll_st(X->e3s + (xw * 8 + j) * 8 + r, __float_as_uint(s0), __float_as_uint(q0), __float_as_uint(s1), __float_as_uint(q1), tag);
      mbar_wait(BAR + (p == 0 ? B_EQ + 7 : B_WODONE) * 8);
    }
    PSTAMP(8);

    float rs0, rs1;
    auto swiglu = [&](float g0, float g1, float u0, float u1, float rs) -> uint32_t {
      const float hr = 0.5f * rs;
      const float x0 = g0 * hr, x1 = g1 * hr;
      const float t0 = tanhf_hw(x0), t1 = tanhf_hw(x1);
      return pack2(fmaf(x0, t0, x0) * (u0 * rs), fmaf(x1, t1, x1) * (u1 * rs));
    };
    uint32_t hA[6][4];
    {
      float a1[64], a2[32];
      const uint4* src = xb + O_E3H + xw * 32 * 32;
      uint32_t rb[4][4], rc[4][4], rd[4][4];
      auto fetch = [&](uint32_t (&a)[4][4], int i) { ll_issue<4>(a, src + kb_at(i, j) * 128, 32); };
      auto check = [&](uint32_t (&a)[4][4], uint32_t (&b)[4][4], int i) {
        const uint32_t tg = pin(tag, zero);
        if (__builtin_expect(ll_any(ll_acc<4>(a, tg, ll_acc<4>(b, tg))), 0)) {
          uint32_t it = 0;
#pragma unroll 1
          do { fetch(a, i); fetch(b, i + 1); } while (ll_any(ll_acc<4>(a, tag, ll_acc<4>(b, tag))) && ++it < SPIN_LIMIT);
        }
        ll_clear<4>(a); ll_clear<4>(b);
        keep(a); keep(b);
      };
      auto head = [&](uint32_t (&a)[4][4], int i) {
        mbar_wait(BAR + (B_FA + i) * 8);
        wg_fence();
        wgmma_rs_n64<DESC_HI64>(a2, a[0], descBh(RING + 16384) + (i & 3) * 1536, i);
        wgmma_rs_n128(a1, a[0], descB(RING) + (i & 3) * 1536, i);
        wg_commit();
#pragma unroll
        for (int u = 0; u < 4; u++) stsm4(Hn + w * 2048 + i * 8192 + (moff ^ (u << 5)), a[u]);
        wg_wait<1>();
        if (i > 0) mbar_arrive_if(BAR + (B_EA + i - 1) * 8, lane == 0);
      };
      auto rest = [&](uint32_t (&a)[4][4], int i) {
        wg_fence();
#pragma unroll
        for (int k = 1; k < 4; k++) {
          wgmma_rs_n64<DESC_HI64>(a2, a[k], descBh(RING + 16384) + (i & 3) * 1536 + k * 64, 1);
          wgmma_rs_n128(a1, a[k], descB(RING) + (i & 3) * 1536 + k * 128, 1);
        }
        wg_commit();
      };
      ll_clear<4>(ra);
      keep(ra);
      head(ra, 0); rest(ra, 0);
      ll_get<4>(rb, src + kb_at(1, j) * 128, 32, tag);
      keep(rb);
      PSTAMP(17);
      fetch(rc, 2); fetch(rd, 3);
      head(rb, 1); rest(rb, 1);
      check(rc, rd, 2);
      head(rc, 2); fetch(ra, 4); fetch(rb, 5); rest(rc, 2);
      head(rd, 3); rest(rd, 3);
      check(ra, rb, 4);
      head(ra, 4); fetch(rc, 6); fetch(rd, 7); ll_issue<2>(sv, X->e3s + (xw * 8 + 2 * c) * 8 + r, 8); rest(ra, 4);
      head(rb, 5); rest(rb, 5);
      check(rc, rd, 6);
      head(rc, 6); rest(rc, 6);
      head(rd, 7); rest(rd, 7);
      fence_async_smem();
      ll_wait<2>(sv, X->e3s + (xw * 8 + 2 * c) * 8 + r, 8, tag);
      float s0 = __uint_as_float(sv[0][0]) + __uint_as_float(sv[1][0]), q0 = __uint_as_float(sv[0][1]) + __uint_as_float(sv[1][1]);
      float s1 = __uint_as_float(sv[0][2]) + __uint_as_float(sv[1][2]), q1 = __uint_as_float(sv[0][3]) + __uint_as_float(sv[1][3]);
#pragma unroll
      for (int o = 1; o <= 2; o <<= 1) {
        s0 += __shfl_xor_sync(0xffffffffu, s0, o); q0 += __shfl_xor_sync(0xffffffffu, q0, o);
        s1 += __shfl_xor_sync(0xffffffffu, s1, o); q1 += __shfl_xor_sync(0xffffffffu, q1, o);
      }
      s0 *= 1.f / D_; s1 *= 1.f / D_;
      rs0 = rsqrtf(fmaxf(fmaf(-s0, s0, q0 * (1.f / D_)), 0.f) + 1e-5f);
      rs1 = rsqrtf(fmaxf(fmaf(-s1, s1, q1 * (1.f / D_)), 0.f) + 1e-5f);
      wg_wait<0>();
      keep(a1); keep(a2);
      if (lane == 0) mbar_arrive(BAR + (B_EA + 7) * 8);
      PSTAMP(9);
#pragma unroll
      for (int u = 0; u < 4; u++)
#pragma unroll
        for (int e = 0; e < 4; e++)
          hA[u][e] = swiglu(a1[8 * u + 2 * e], a1[8 * u + 2 * e + 1], a1[32 + 8 * u + 2 * e], a1[33 + 8 * u + 2 * e], (e & 1) ? rs1 : rs0);
#pragma unroll
      for (int u = 0; u < 2; u++)
#pragma unroll
        for (int e = 0; e < 4; e++)
          hA[4 + u][e] = swiglu(a2[8 * u + 2 * e], a2[8 * u + 2 * e + 1], a2[16 + 8 * u + 2 * e], a2[17 + 8 * u + 2 * e], (e & 1) ? rs1 : rs0);
      keep(hA);
      wg_bar(p);
    }
    PSTAMP(10);

    const uint32_t mbx = Hn + 32768 + w * 512 + lane * 16;
    auto send = [&](const uint32_t (&v)[4], uint32_t a, int part) {
      asm volatile("st.async.weak.shared::cluster.mbarrier::complete_tx::bytes.v4.b32 [%0], {%1,%2,%3,%4}, [%5];"
                   ::"r"(a + peer()), "r"(v[0]), "r"(v[1]), "r"(v[2]), "r"(v[3]), "r"(BAR + (B_HX + 2 * part + p) * 8 + peer()) : "memory");
    };
    uint32_t hB[8][4];
    {
      float ab[128];
      uint32_t db = descB(RING);
      const uint32_t dAn = descA(H1) - p * 4096;
      if (lane == 0 && w == 0) { mbar_expect_tx(BAR + (B_HX + p) * 8, 12288); mbar_expect_tx(BAR + (B_HX + 2 + p) * 8, 16384); }
#pragma unroll 1
      for (int i = 0; i < 8; i++) {
        mbar_wait(BAR + (B_FB + i) * 8);
        const uint32_t da = dAn + i * 512;
        wg_fence();
        wgmma_ss_n256(ab, da, db, i);
#pragma unroll
        for (int k = 1; k < 4; k++) wgmma_ss_n256(ab, da + k * 2, db + k * 128, 1);
        wg_commit();
        if (i == 7) {
          mbar_wait_cluster(BAR + (B_PF + p) * 8);
#pragma unroll
          for (int k = 0; k < 6; k++) send(hA[k], mbx + k * 2048, 0);
        }
        wg_wait<1>();
        mbar_arrive_if(BAR + (B_EB + i - 1) * 8, i > 0 && lane == 0);
        if (i == 6 && lane == 0) mbar_arrive_peer(BAR + (B_PF + p) * 8);
        db = db == descB(RING + 65536) ? descB(RING) : db + 2048;
      }
      wg_wait<0>();
      keep(ab);
      mbar_arrive_if(BAR + (B_EB + 7) * 8, lane == 0);
      if (lane == 0) mbar_arrive_peer(BAR + (B_PF + 2 + p) * 8);
      PSTAMP(11);
#pragma unroll
      for (int u = 0; u < 8; u++) {
        const int o = (u >> 2) * 64 + (u & 3) * 8;
#pragma unroll
        for (int e = 0; e < 4; e++)
          hB[u][e] = swiglu(ab[o + 2 * e], ab[o + 2 * e + 1], ab[o + 32 + 2 * e], ab[o + 33 + 2 * e], (e & 1) ? rs1 : rs0);
        if (u == 3) mbar_wait_cluster(BAR + (B_PF + 2 + p) * 8);
        if (u >= 4 && u < 4 + SEND_EARLY) send(hB[u - 4], mbx + (2 + u) * 2048, 1);
      }
      keep(hB);
    }
    PSTAMP(12);

    {
      float ya[32], y[32];
      uint32_t hP[14][4];
      const uint32_t offA = (j & 1) ? 256 : 0, offH = (j & 1) ? 0 : 1536;
      uint4* e4 = xb + O_E4 + g * 24576 + warp * 128;
      const uint32_t stg = H0 + p * 65536 + 28672 + (w >> 1) * 32768 + (w & 1) * 2048;
      auto mm = [&](float (&d)[32], int m, int k0, int k1) {
        if (k0 == 0) mbar_wait(BAR + (B_FT + m) * 8);
        const uint32_t T = descB(0) + (t_addr(m) >> 4);
        const uint32_t oA = w2_peer(m) ? 256 - offA : offA, oH = w2_peer(m) ? 1536 - offH : offH;
        wg_fence();
#pragma unroll
        for (int k = k0; k < k1; k++) {
          const uint32_t db = T + (k < 4 ? oA + k * 128 : k < 6 ? oH + (k - 4) * 128 : oA + 512 + (k - 6) * 128);
          if (w2_peer(m)) wgmma_rs_n64(d, hP[k], db, 1);
          else if (k < 6) wgmma_rs_n64(d, hA[k], db, k);
          else wgmma_rs_n64(d, hB[k - 6], db, 1);
        }
        wg_commit();
      };
      auto next = [&](float (&d)[32], int m, float (&dp)[32], int q) {
        mm(d, m, 0, 3);
        wg_wait<1>();
        keep(dp);
        mbar_arrive_if(BAR + (B_ET0 + q) * 8, lane == 0);
        uint4* dst = e4 + (((j + 2 + 2 * q) & 7) * 3 + q) * 1024;
#pragma unroll
        for (int u = 0; u < 4; u++)
          ll_st(dst + u * 32, pack2(dp[8 * u], dp[8 * u + 1]), pack2(dp[8 * u + 2], dp[8 * u + 3]),
                pack2(dp[8 * u + 4], dp[8 * u + 5]), pack2(dp[8 * u + 6], dp[8 * u + 7]), tag);
        if (q == 2) mbar_wait(BAR + (B_ET0 + 2) * 8);
        mm(d, m, 3, 14);
      };
#pragma unroll
      for (int i = 0; i < 4; i++) {
        const uint32_t a = i ? pin(mbx, zero) : mbx;
#pragma unroll
        for (int k = SEND_EARLY + (8 - SEND_EARLY) * i / 4; k < SEND_EARLY + (8 - SEND_EARLY) * (i + 1) / 4; k++) send(hB[k], a + (6 + k) * 2048, 1);
        if (i < 3) mm(ya, 0, 5 * i, i < 2 ? 5 * i + 5 : 14);
        else mm(y, 1, 0, 6);
      }
      mbar_wait_cluster(BAR + (B_HX + p) * 8);
#pragma unroll
      for (int k = 0; k < 6; k++) lds128(hP[k], mbx + k * 2048);
      mm(y, 1, 6, 14);
      keep(hP[0]); keep(hP[1]); keep(hP[2]); keep(hP[3]); keep(hP[4]); keep(hP[5]);
      mm(ya, 2, 0, 3);
      PSTAMP(18);
      mbar_wait_cluster(BAR + (B_HX + 2 + p) * 8);
      PSTAMP(24);
#pragma unroll
      for (int k = 6; k < 14; k++) lds128(hP[k], mbx + k * 2048);
      mm(ya, 2, 3, 6);
      keep(hP);
      mbar_arrive_if(BAR + (B_HC + p) * 8, lane == 0);
      mm(ya, 2, 6, 14);
      mbar_wait(BAR + B_CLR * 8);
      next(y, 3, ya, 0);
      PSTAMP(27);
      next(ya, 4, y, 1);
      mbar_arrive_if(BAR + (B_ET0 + 3) * 8, lane == 0);
      mm(ya, 5, 0, 14);
      PSTAMP(26);
      next(y, 6, ya, 2);
      PSTAMP(28);
      uint32_t in[4][4], lt[4][4];
      const uint4* insrc = e4 + j * 3 * 1024;
      mm(y, 7, 0, 7);
      ll_issue<4>(lt, insrc + 2048, 32);
      mm(y, 7, 7, 14);
      mbar_wait(BAR + B_FIN * 8);
      mbar_wait(BAR + (B_FIN + 1) * 8);
      wg_wait<0>();
      keep(y);
      PSTAMP(13);
      const uint32_t ident = (2 * c == r ? 0x3f80u : 0u) | (2 * c + 1 == r ? 0x3f800000u : 0u);
      auto acc = [&](const uint32_t (&v)[4][4]) {
#pragma unroll
        for (int u = 0; u < 4; u++) {
          mma1688_acc(*reinterpret_cast<float (*)[4]>(&y[8 * u]), v[u][0], v[u][1], ident);
          mma1688_acc(*reinterpret_cast<float (*)[4]>(&y[8 * u + 4]), v[u][2], v[u][3], ident);
        }
      };
      acc(hf);
#pragma unroll
      for (int q = 0; q < 2; q++) {
#pragma unroll
        for (int u = 0; u < 4; u++) lds128(in[u], t_addr(q + 1) + warp * 2048 + lane * 16 + u * 512);
        ll_wait<4>(in, insrc + q * 1024, 32, tag);
        acc(in);
      }
      PSTAMP(25);
      if (ll_bad<4>(lt, pin(tag, zero))) {
        ll_spin<4>(lt, insrc + 2048, 32, tag);
      }
      ll_clear<4>(lt);
      acc(lt);
      PSTAMP(14);
#pragma unroll
      for (int u = 0; u < 4; u++) {
        uint32_t o[4];
#pragma unroll
        for (int e = 0; e < 4; e++) o[e] = pack2(y[8 * u + 2 * e], y[8 * u + 2 * e + 1]);
        stsm4(stg + (moff ^ (u << 5)), o);
      }
      fence_async_smem();
      __syncwarp();
      if (elect_one()) {
        tma3d_store(&P.out, stg, 64 * j, p, g * 64 + 16 * w);
        asm volatile("cp.async.bulk.commit_group;" ::: "memory");
        asm volatile("cp.async.bulk.wait_group.read 0;" ::: "memory");
      }
      PSTAMP(15);
    }
  }
}

typedef CUresult (*EncodeFn)(CUtensorMap*, CUtensorMapDataType, cuuint32_t, void*, const cuuint64_t*, const cuuint64_t*,
                             const cuuint32_t*, const cuuint32_t*, CUtensorMapInterleave, CUtensorMapSwizzle,
                             CUtensorMapL2promotion, CUtensorMapFloatOOBfill);

void enc2d(EncodeFn f, CUtensorMap* m, const void* base, uint64_t cols, uint64_t rows, uint32_t bc, uint32_t br, CUtensorMapSwizzle sw) {
  cuuint64_t gd[2] = {cols, rows}, gs[1] = {cols * 2};
  cuuint32_t bd[2] = {bc, br}, es[2] = {1, 1};
  f(m, CU_TENSOR_MAP_DATA_TYPE_BFLOAT16, 2, const_cast<void*>(base), gd, gs, bd, es, CU_TENSOR_MAP_INTERLEAVE_NONE, sw,
    CU_TENSOR_MAP_L2_PROMOTION_L2_128B, CU_TENSOR_MAP_FLOAT_OOB_FILL_NONE);
}
void enc_par(EncodeFn f, CUtensorMap* m, const void* base, uint32_t pairs) {
  cuuint64_t gd[3] = {(cuuint64_t)D_, 2, (cuuint64_t)S_ / 2}, gs[2] = {D_ * 2, D_ * 4};
  cuuint32_t bd[3] = {64, 1, pairs}, es[3] = {1, 1, 1};
  f(m, CU_TENSOR_MAP_DATA_TYPE_BFLOAT16, 3, const_cast<void*>(base), gd, gs, bd, es, CU_TENSOR_MAP_INTERLEAVE_NONE,
    CU_TENSOR_MAP_SWIZZLE_128B, CU_TENSOR_MAP_L2_PROMOTION_L2_128B, CU_TENSOR_MAP_FLOAT_OOB_FILL_NONE);
}

}

extern "C" void kernel_launch(void* const* d_in, const int* in_sizes, int n_in, void* d_out, int out_size) {
  (void)in_sizes; (void)n_in; (void)out_size;
  static EncodeFn enc = nullptr;
  static Scratch* scratch = nullptr;
  if (!enc) {
    void* fn = nullptr;
    cudaDriverEntryPointQueryResult q;
    cudaGetDriverEntryPoint("cuTensorMapEncodeTiled", &fn, cudaEnableDefault, &q);
    enc = (EncodeFn)fn;
    cudaGetSymbolAddress((void**)&scratch, g_scratch);
    cudaFuncSetAttribute(fused_block_kernel, cudaFuncAttributeMaxDynamicSharedMemorySize, SMEM_BYTES);
  }
  Params P;
  const __nv_bfloat16* xp = (const __nv_bfloat16*)d_in[0];
  const __nv_bfloat16* wqkvp = (const __nv_bfloat16*)d_in[1];
  const __nv_bfloat16* wop = (const __nv_bfloat16*)d_in[2];
  P.w1p = (const __nv_bfloat16*)d_in[4];
  P.w3p = (const __nv_bfloat16*)d_in[5];
  P.w2p = (const __nv_bfloat16*)d_in[6];
  enc_par(enc, &P.x, xp, 64);
  enc_par(enc, &P.out, d_out, 16);
  enc2d(enc, &P.wqkv, wqkvp, 3 * D_, D_, 64, 64, CU_TENSOR_MAP_SWIZZLE_128B);
  enc2d(enc, &P.wo, wop, D_, D_, 64, 64, CU_TENSOR_MAP_SWIZZLE_128B);
  enc2d(enc, &P.w1, P.w1p, F_, D_, 64, 64, CU_TENSOR_MAP_SWIZZLE_128B);
  enc2d(enc, &P.w3, P.w3p, F_, D_, 64, 64, CU_TENSOR_MAP_SWIZZLE_128B);
  enc2d(enc, &P.w1h, P.w1p, F_, D_, 32, 64, CU_TENSOR_MAP_SWIZZLE_64B);
  enc2d(enc, &P.w3h, P.w3p, F_, D_, 32, 64, CU_TENSOR_MAP_SWIZZLE_64B);
  enc2d(enc, &P.w2, P.w2p, D_, F_, 64, 224, CU_TENSOR_MAP_SWIZZLE_128B);

  cudaLaunchConfig_t cfg = {};
  cfg.gridDim = dim3(128);
  cfg.blockDim = dim3(384);
  cfg.dynamicSmemBytes = SMEM_BYTES;
  cfg.stream = cudaStreamPerThread;
  cudaLaunchAttribute at[2];
  at[0].id = cudaLaunchAttributeCooperative;
  at[0].val.cooperative = 1;
  cfg.attrs = at;
  cfg.numAttrs = 1;
  at[1].id = cudaLaunchAttributeClusterDimension;
  at[1].val.clusterDim.x = 2; at[1].val.clusterDim.y = 1; at[1].val.clusterDim.z = 1;
  cfg.numAttrs = 2;
  cudaLaunchKernelEx(&cfg, fused_block_kernel, scratch, xp, wqkvp, wop, 0u, P);
}
```

```cpp
#include <cuda_runtime.h>
#include <cuda.h>
#include <cuda_bf16.h>
#include <stdint.h>
#include <stddef.h>

namespace {

constexpr int S_ = 2048, D_ = 512, F_ = 1792;
#define LAG_KB 3
#define E4_FIRST 7
#define PP_AHEAD 1
#define SIDE_KB 0
#define CLR_MODE 1
#define W2_HEAD 3
#define CLR_SLEEP 400
#define CMAP 2
#define E4_ON 1
#define E4_WHEN (B_EA + 7)
#define SEND_EARLY 2
#define CS_KB 3
#define WO_KB 3
#define GATHER_SLEEP 200
#define PF_MODE 1
#define CLR_SLEEP2 100
#define CLR_WHEN (B_EQ + 5)
#define XO_DELAY 2

constexpr uint32_t SPIN_LIMIT = 1u << 18;

struct Scratch {
  uint4 e4[16 * 8 * 3 * 8 * 4 * 32];
  uint4 e2[16 * 2 * 4 * 32 * 32];
  uint4 e3h[16 * 2 * 4 * 32 * 32];
  uint4 e1[16 * 8 * 2 * 4 * 32];
  uint4 e2s[16 * 2 * 4 * 8 * 8];
  uint4 e3s[16 * 2 * 4 * 8 * 8];
  uint4 e0c[8 * 3 * 16 * 16];
  uint4 e0s[2048];
  uint4 e0w[8 * 64];
  unsigned epoch[128];
};
__device__ Scratch g_scratch;
#define PSTAMP(i)
#define PSTAMPW(slot, i)
#define W2STAMP(i)

struct alignas(64) Params {
  CUtensorMap x, out, wqkv, wo, w1, w3, w1h, w3h, w2;
  const __nv_bfloat16 *w1p, *w3p, *w2p;
};

constexpr uint32_t SB = 1024;
constexpr uint32_t H0 = SB;
constexpr uint32_t H1 = SB + 65536;
constexpr uint32_t RING = SB + 131072;
constexpr uint32_t BAR = SB + 229376;
constexpr uint32_t TAGS = BAR + 1016;
constexpr uint32_t CS = BAR + 1024;
constexpr uint32_t ST = CS + 768;
constexpr uint32_t WB = ST + 1024;
constexpr uint32_t SMEM_BYTES = 232448;
static_assert(WB + 256 <= SB + SMEM_BYTES, "smem");

enum : int {
  B_FX = 0,
  B_FKV = 16, B_FQ = 24, B_FWO = 32, B_FA = 40, B_FB = 48, B_FT = 56,
  B_EKV = 64, B_EQ = 72, B_EA = 80, B_EB = 88, B_ET0 = 96,
  B_WODONE = 103,
  B_WBAR = 39,
  B_FIN = 33,
  B_EX = 104,
  B_LAG = 112, B_READY = 113, B_X114 = 114, B_CLR = 115, B_OG = 116, B_TAG = 117,
  B_HX = 35,
  B_PF = 118,
  B_HC = 122,
  B_CLR1 = 124, B_CLR2 = 125
};

__device__ __forceinline__ uint32_t smem_u32(const void* p) { return (uint32_t)__cvta_generic_to_shared(p); }
__device__ __forceinline__ uint32_t own() { return (blockIdx.x & 1) << 24; }
__device__ __forceinline__ uint32_t peer() { return (~blockIdx.x & 1) << 24; }
__device__ __forceinline__ void mbar_init(uint32_t b, uint32_t c) { asm volatile("mbarrier.init.shared::cta.b64 [%0], %1;" ::"r"(b + own()), "r"(c) : "memory"); }
__device__ __forceinline__ void mbar_expect_tx(uint32_t b, uint32_t bytes) { asm volatile("mbarrier.arrive.expect_tx.shared::cta.b64 _, [%0], %1;" ::"r"(b + own()), "r"(bytes) : "memory"); }
__device__ __forceinline__ void mbar_arrive(uint32_t b) { asm volatile("mbarrier.arrive.shared::cta.b64 _, [%0];" ::"r"(b + own()) : "memory"); }
__device__ __forceinline__ void mbar_wait(uint32_t b) {
  asm volatile("{\n.reg .pred p;\n.reg .u32 c;\nmov.u32 c, 0;\nLW:\n.pragma \"nounroll\";\n"
               "mbarrier.try_wait.parity.shared::cta.b64 p, [%0], 0;\nadd.u32 c, c, 1;\nsetp.gt.or.u32 p, c, %1, p;\n@!p bra LW;\n}\n"
               ::"r"(b + own()), "n"(SPIN_LIMIT) : "memory");
}
__device__ __forceinline__ void mbar_arrive_peer(uint32_t b) {
  asm volatile("mbarrier.arrive.relaxed.cluster.shared::cluster.b64 _, [%0];" ::"r"(b + peer()) : "memory");
}
__device__ __forceinline__ void mbar_wait_cluster(uint32_t b) {
  asm volatile("{\n.reg .pred p;\n.reg .u32 c;\nmov.u32 c, 0;\nLW:\n.pragma \"nounroll\";\n"
               "mbarrier.try_wait.parity.acquire.cluster.shared::cta.b64 p, [%0], 0;\nadd.u32 c, c, 1;\nsetp.gt.or.u32 p, c, %1, p;\n@!p bra LW;\n}\n"
               ::"r"(b + own()), "n"(SPIN_LIMIT) : "memory");
}
__device__ __forceinline__ bool elect_one() {
  uint32_t p;
  asm volatile("{\n.reg .pred P;\nelect.sync _|P, 0xffffffff;\nselp.u32 %0, 1, 0, P;\n}\n" : "=r"(p));
  return p;
}
__device__ __forceinline__ void tma2d(uint32_t dst, const CUtensorMap* m, int c0, int c1, uint32_t bar) {
  dst += own(); bar += own();
  asm volatile("cp.async.bulk.tensor.2d.shared::cluster.global.mbarrier::complete_tx::bytes [%0], [%1, {%3, %4}], [%2];"
               ::"r"(dst), "l"(m), "r"(bar), "r"(c0), "r"(c1) : "memory");
}
__device__ __forceinline__ void tma3d(uint32_t dst, const CUtensorMap* m, int c0, int c1, int c2, uint32_t bar) {
  dst += own(); bar += own();
  asm volatile("cp.async.bulk.tensor.3d.shared::cluster.global.mbarrier::complete_tx::bytes [%0], [%1, {%3, %4, %5}], [%2];"
               ::"r"(dst), "l"(m), "r"(bar), "r"(c0), "r"(c1), "r"(c2) : "memory");
}
__device__ __forceinline__ void tma3d_store(const CUtensorMap* m, uint32_t src, int c0, int c1, int c2) {
  asm volatile("cp.async.bulk.tensor.3d.global.shared::cta.bulk_group [%0, {%2, %3, %4}], [%1];"
               ::"l"(m), "r"(src + own()), "r"(c0), "r"(c1), "r"(c2) : "memory");
}
__device__ __forceinline__ void l2_prefetch(const void* p, uint32_t bytes) {
  asm volatile("cp.async.bulk.prefetch.L2.global [%0], %1;" ::"l"(p), "r"(bytes) : "memory");
}
__device__ __forceinline__ void prefetch_map(const CUtensorMap* m) { asm volatile("prefetch.tensormap [%0];" ::"l"(m) : "memory"); }
__device__ __forceinline__ void fence_async_smem() { asm volatile("fence.proxy.async.shared::cta;" ::: "memory"); }
__device__ __forceinline__ void wg_fence() { asm volatile("wgmma.fence.sync.aligned;" ::: "memory"); }
__device__ __forceinline__ void wg_commit() { asm volatile("wgmma.commit_group.sync.aligned;" ::: "memory"); }
template <int N> __device__ __forceinline__ void wg_wait() { asm volatile("wgmma.wait_group.sync.aligned %0;" ::"n"(N) : "memory"); }
__device__ __forceinline__ void wg_bar(int p) {
  if (p == 0) asm volatile("bar.sync 1, 128;" ::: "memory"); else asm volatile("bar.sync 2, 128;" ::: "memory");
}
constexpr uint32_t DESC_HI128 = (1024 >> 4) | (1u << 30);
constexpr uint32_t DESC_HI64 = (512 >> 4) | (2u << 30);
__device__ __forceinline__ constexpr uint32_t descA(uint32_t addr) { return (addr >> 4) | (1u << 16); }
__device__ __forceinline__ constexpr uint32_t descB(uint32_t addr) { return (addr >> 4) | ((8192u >> 4) << 16); }
__device__ __forceinline__ constexpr uint32_t descBh(uint32_t addr) { return (addr >> 4) | ((4096u >> 4) << 16); }

__device__ __forceinline__ void wgmma_ss_n64(float (&d)[32], uint32_t da, uint32_t db, int sc) {
  asm volatile("{\n.reg .pred p;\n.reg .b64 da, db;\nsetp.ne.b32 p, %34, 0;\nmov.b64 da, {%32, %35};\nmov.b64 db, {%33, %35};\n"
    "wgmma.mma_async.sync.aligned.m64n64k16.f32.bf16.bf16 {%0, %1, %2, %3, %4, %5, %6, %7, %8, %9, %10, %11, %12, %13, %14, %15, %16, %17, %18, %19, %20, %21, %22, %23, %24, %25, %26, %27, %28, %29, %30, %31}, da, db, p, 1, 1, 0, 1;\n}\n"
    : "+f"(d[0]), "+f"(d[1]), "+f"(d[2]), "+f"(d[3]), "+f"(d[4]), "+f"(d[5]), "+f"(d[6]), "+f"(d[7]),
      "+f"(d[8]), "+f"(d[9]), "+f"(d[10]), "+f"(d[11]), "+f"(d[12]), "+f"(d[13]), "+f"(d[14]), "+f"(d[15]),
      "+f"(d[16]), "+f"(d[17]), "+f"(d[18]), "+f"(d[19]), "+f"(d[20]), "+f"(d[21]), "+f"(d[22]), "+f"(d[23]),
      "+f"(d[24]), "+f"(d[25]), "+f"(d[26]), "+f"(d[27]), "+f"(d[28]), "+f"(d[29]), "+f"(d[30]), "+f"(d[31])
    : "r"(da), "r"(db), "r"(sc), "n"(DESC_HI128));
}
__device__ __forceinline__ void wgmma_ss_n128(float (&d)[64], uint32_t da, uint32_t db, int sc) {
  asm volatile("{\n.reg .pred p;\n.reg .b64 da, db;\nsetp.ne.b32 p, %66, 0;\nmov.b64 da, {%64, %67};\nmov.b64 db, {%65, %67};\n"
    "wgmma.mma_async.sync.aligned.m64n128k16.f32.bf16.bf16 {%0, %1, %2, %3, %4, %5, %6, %7, %8, %9, %10, %11, %12, %13, %14, %15, %16, %17, %18, %19, %20, %21, %22, %23, %24, %25, %26, %27, %28, %29, %30, %31, %32, %33, %34, %35, %36, %37, %38, %39, %40, %41, %42, %43, %44, %45, %46, %47, %48, %49, %50, %51, %52, %53, %54, %55, %56, %57, %58, %59, %60, %61, %62, %63}, da, db, p, 1, 1, 0, 1;\n}\n"
    : "+f"(d[0]), "+f"(d[1]), "+f"(d[2]), "+f"(d[3]), "+f"(d[4]), "+f"(d[5]), "+f"(d[6]), "+f"(d[7]),
      "+f"(d[8]), "+f"(d[9]), "+f"(d[10]), "+f"(d[11]), "+f"(d[12]), "+f"(d[13]), "+f"(d[14]), "+f"(d[15]),
      "+f"(d[16]), "+f"(d[17]), "+f"(d[18]), "+f"(d[19]), "+f"(d[20]), "+f"(d[21]), "+f"(d[22]), "+f"(d[23]),
      "+f"(d[24]), "+f"(d[25]), "+f"(d[26]), "+f"(d[27]), "+f"(d[28]), "+f"(d[29]), "+f"(d[30]), "+f"(d[31]),
      "+f"(d[32]), "+f"(d[33]), "+f"(d[34]), "+f"(d[35]), "+f"(d[36]), "+f"(d[37]), "+f"(d[38]), "+f"(d[39]),
      "+f"(d[40]), "+f"(d[41]), "+f"(d[42]), "+f"(d[43]), "+f"(d[44]), "+f"(d[45]), "+f"(d[46]), "+f"(d[47]),
      "+f"(d[48]), "+f"(d[49]), "+f"(d[50]), "+f"(d[51]), "+f"(d[52]), "+f"(d[53]), "+f"(d[54]), "+f"(d[55]),
      "+f"(d[56]), "+f"(d[57]), "+f"(d[58]), "+f"(d[59]), "+f"(d[60]), "+f"(d[61]), "+f"(d[62]), "+f"(d[63])
    : "r"(da), "r"(db), "r"(sc), "n"(DESC_HI128));
}
__device__ __forceinline__ void wgmma_ss_n256(float (&d)[128], uint32_t da, uint32_t db, int sc) {
  asm volatile("{\n.reg .pred p;\n.reg .b64 da, db;\nsetp.ne.b32 p, %130, 0;\nmov.b64 da, {%128, %131};\nmov.b64 db, {%129, %131};\n"
    "wgmma.mma_async.sync.aligned.m64n256k16.f32.bf16.bf16 {%0, %1, %2, %3, %4, %5, %6, %7, %8, %9, %10, %11, %12, %13, %14, %15, %16, %17, %18, %19, %20, %21, %22, %23, %24, %25, %26, %27, %28, %29, %30, %31, %32, %33, %34, %35, %36, %37, %38, %39, %40, %41, %42, %43, %44, %45, %46, %47, %48, %49, %50, %51, %52, %53, %54, %55, %56, %57, %58, %59, %60, %61, %62, %63, %64, %65, %66, %67, %68, %69, %70, %71, %72, %73, %74, %75, %76, %77, %78, %79, %80, %81, %82, %83, %84, %85, %86, %87, %88, %89, %90, %91, %92, %93, %94, %95, %96, %97, %98, %99, %100, %101, %102, %103, %104, %105, %106, %107, %108, %109, %110, %111, %112, %113, %114, %115, %116, %117, %118, %119, %120, %121, %122, %123, %124, %125, %126, %127}, da, db, p, 1, 1, 0, 1;\n}\n"
    : "+f"(d[0]), "+f"(d[1]), "+f"(d[2]), "+f"(d[3]), "+f"(d[4]), "+f"(d[5]), "+f"(d[6]), "+f"(d[7]),
      "+f"(d[8]), "+f"(d[9]), "+f"(d[10]), "+f"(d[11]), "+f"(d[12]), "+f"(d[13]), "+f"(d[14]), "+f"(d[15]),
      "+f"(d[16]), "+f"(d[17]), "+f"(d[18]), "+f"(d[19]), "+f"(d[20]), "+f"(d[21]), "+f"(d[22]), "+f"(d[23]),
      "+f"(d[24]), "+f"(d[25]), "+f"(d[26]), "+f"(d[27]), "+f"(d[28]), "+f"(d[29]), "+f"(d[30]), "+f"(d[31]),
      "+f"(d[32]), "+f"(d[33]), "+f"(d[34]), "+f"(d[35]), "+f"(d[36]), "+f"(d[37]), "+f"(d[38]), "+f"(d[39]),
      "+f"(d[40]), "+f"(d[41]), "+f"(d[42]), "+f"(d[43]), "+f"(d[44]), "+f"(d[45]), "+f"(d[46]), "+f"(d[47]),
      "+f"(d[48]), "+f"(d[49]), "+f"(d[50]), "+f"(d[51]), "+f"(d[52]), "+f"(d[53]), "+f"(d[54]), "+f"(d[55]),
      "+f"(d[56]), "+f"(d[57]), "+f"(d[58]), "+f"(d[59]), "+f"(d[60]), "+f"(d[61]), "+f"(d[62]), "+f"(d[63]),
      "+f"(d[64]), "+f"(d[65]), "+f"(d[66]), "+f"(d[67]), "+f"(d[68]), "+f"(d[69]), "+f"(d[70]), "+f"(d[71]),
      "+f"(d[72]), "+f"(d[73]), "+f"(d[74]), "+f"(d[75]), "+f"(d[76]), "+f"(d[77]), "+f"(d[78]), "+f"(d[79]),
      "+f"(d[80]), "+f"(d[81]), "+f"(d[82]), "+f"(d[83]), "+f"(d[84]), "+f"(d[85]), "+f"(d[86]), "+f"(d[87]),
      "+f"(d[88]), "+f"(d[89]), "+f"(d[90]), "+f"(d[91]), "+f"(d[92]), "+f"(d[93]), "+f"(d[94]), "+f"(d[95]),
      "+f"(d[96]), "+f"(d[97]), "+f"(d[98]), "+f"(d[99]), "+f"(d[100]), "+f"(d[101]), "+f"(d[102]), "+f"(d[103]),
      "+f"(d[104]), "+f"(d[105]), "+f"(d[106]), "+f"(d[107]), "+f"(d[108]), "+f"(d[109]), "+f"(d[110]), "+f"(d[111]),
      "+f"(d[112]), "+f"(d[113]), "+f"(d[114]), "+f"(d[115]), "+f"(d[116]), "+f"(d[117]), "+f"(d[118]), "+f"(d[119]),
      "+f"(d[120]), "+f"(d[121]), "+f"(d[122]), "+f"(d[123]), "+f"(d[124]), "+f"(d[125]), "+f"(d[126]), "+f"(d[127])
    : "r"(da), "r"(db), "r"(sc), "n"(DESC_HI128));
}
template <uint32_t HI = DESC_HI128>
__device__ __forceinline__ void wgmma_rs_n64(float (&d)[32], const uint32_t (&a)[4], uint32_t db, int sc) {
  asm volatile("{\n.reg .pred p;\n.reg .b64 db;\nsetp.ne.b32 p, %37, 0;\nmov.b64 db, {%36, %38};\n"
    "wgmma.mma_async.sync.aligned.m64n64k16.f32.bf16.bf16 {%0, %1, %2, %3, %4, %5, %6, %7, %8, %9, %10, %11, %12, %13, %14, %15, %16, %17, %18, %19, %20, %21, %22, %23, %24, %25, %26, %27, %28, %29, %30, %31}, {%32, %33, %34, %35}, db, p, 1, 1, 1;\n}\n"
    : "+f"(d[0]), "+f"(d[1]), "+f"(d[2]), "+f"(d[3]), "+f"(d[4]), "+f"(d[5]), "+f"(d[6]), "+f"(d[7]),
      "+f"(d[8]), "+f"(d[9]), "+f"(d[10]), "+f"(d[11]), "+f"(d[12]), "+f"(d[13]), "+f"(d[14]), "+f"(d[15]),
      "+f"(d[16]), "+f"(d[17]), "+f"(d[18]), "+f"(d[19]), "+f"(d[20]), "+f"(d[21]), "+f"(d[22]), "+f"(d[23]),
      "+f"(d[24]), "+f"(d[25]), "+f"(d[26]), "+f"(d[27]), "+f"(d[28]), "+f"(d[29]), "+f"(d[30]), "+f"(d[31])
    : "r"(a[0]), "r"(a[1]), "r"(a[2]), "r"(a[3]), "r"(db), "r"(sc), "n"(HI));
}
template <uint32_t HI = DESC_HI128>
__device__ __forceinline__ void wgmma_rs_n128(float (&d)[64], const uint32_t (&a)[4], uint32_t db, int sc) {
  asm volatile("{\n.reg .pred p;\n.reg .b64 db;\nsetp.ne.b32 p, %69, 0;\nmov.b64 db, {%68, %70};\n"
    "wgmma.mma_async.sync.aligned.m64n128k16.f32.bf16.bf16 {%0, %1, %2, %3, %4, %5, %6, %7, %8, %9, %10, %11, %12, %13, %14, %15, %16, %17, %18, %19, %20, %21, %22, %23, %24, %25, %26, %27, %28, %29, %30, %31, %32, %33, %34, %35, %36, %37, %38, %39, %40, %41, %42, %43, %44, %45, %46, %47, %48, %49, %50, %51, %52, %53, %54, %55, %56, %57, %58, %59, %60, %61, %62, %63}, {%64, %65, %66, %67}, db, p, 1, 1, 1;\n}\n"
    : "+f"(d[0]), "+f"(d[1]), "+f"(d[2]), "+f"(d[3]), "+f"(d[4]), "+f"(d[5]), "+f"(d[6]), "+f"(d[7]),
      "+f"(d[8]), "+f"(d[9]), "+f"(d[10]), "+f"(d[11]), "+f"(d[12]), "+f"(d[13]), "+f"(d[14]), "+f"(d[15]),
      "+f"(d[16]), "+f"(d[17]), "+f"(d[18]), "+f"(d[19]), "+f"(d[20]), "+f"(d[21]), "+f"(d[22]), "+f"(d[23]),
      "+f"(d[24]), "+f"(d[25]), "+f"(d[26]), "+f"(d[27]), "+f"(d[28]), "+f"(d[29]), "+f"(d[30]), "+f"(d[31]),
      "+f"(d[32]), "+f"(d[33]), "+f"(d[34]), "+f"(d[35]), "+f"(d[36]), "+f"(d[37]), "+f"(d[38]), "+f"(d[39]),
      "+f"(d[40]), "+f"(d[41]), "+f"(d[42]), "+f"(d[43]), "+f"(d[44]), "+f"(d[45]), "+f"(d[46]), "+f"(d[47]),
      "+f"(d[48]), "+f"(d[49]), "+f"(d[50]), "+f"(d[51]), "+f"(d[52]), "+f"(d[53]), "+f"(d[54]), "+f"(d[55]),
      "+f"(d[56]), "+f"(d[57]), "+f"(d[58]), "+f"(d[59]), "+f"(d[60]), "+f"(d[61]), "+f"(d[62]), "+f"(d[63])
    : "r"(a[0]), "r"(a[1]), "r"(a[2]), "r"(a[3]), "r"(db), "r"(sc), "n"(HI));
}

template <int N> __device__ __forceinline__ void keep(float (&d)[N]) {
#pragma unroll
  for (int i = 0; i < N; i++) asm volatile("" : "+f"(d[i])::"memory");
}

__device__ __forceinline__ void keep(uint32_t (&d)[4]) { asm volatile("" : "+r"(d[0]), "+r"(d[1]), "+r"(d[2]), "+r"(d[3])::"memory"); }
template <int N> __device__ __forceinline__ void keep(uint32_t (&d)[N][4]) {
#pragma unroll
  for (int i = 0; i < N; i++) asm volatile("" : "+r"(d[i][0]), "+r"(d[i][1]), "+r"(d[i][2]), "+r"(d[i][3])::"memory");
}

__device__ __forceinline__ uint32_t pack2(float lo, float hi) {
  uint32_t r;
  asm("cvt.rn.bf16x2.f32 %0, %1, %2;" : "=r"(r) : "f"(hi), "f"(lo));
  return r;
}
__device__ __forceinline__ float bf_lo(uint32_t v) { return __uint_as_float(v << 16); }
__device__ __forceinline__ float bf_hi(uint32_t v) { return __uint_as_float(v & 0xffff0000u); }
__device__ __forceinline__ uint32_t hsub2(uint32_t a, uint32_t b) {
  uint32_t r;
  asm("sub.rn.bf16x2 %0, %1, %2;" : "=r"(r) : "r"(a), "r"(b));
  return r;
}
__device__ __forceinline__ uint32_t movm(uint32_t a) {
  uint32_t r;
  asm volatile("movmatrix.sync.aligned.m8n8.trans.b16 %0, %1;" : "=r"(r) : "r"(a));
  return r;
}
__device__ __forceinline__ void ldsm4(uint32_t (&v)[4], uint32_t a) {
  asm volatile("ldmatrix.sync.aligned.m8n8.x4.shared.b16 {%0,%1,%2,%3}, [%4];" : "=r"(v[0]), "=r"(v[1]), "=r"(v[2]), "=r"(v[3]) : "r"(a + own()) : "memory");
}
__device__ __forceinline__ void stsm4(uint32_t a, const uint32_t (&v)[4]) {
  asm volatile("stmatrix.sync.aligned.m8n8.x4.shared.b16 [%0], {%1,%2,%3,%4};" ::"r"(a + own()), "r"(v[0]), "r"(v[1]), "r"(v[2]), "r"(v[3]) : "memory");
}
__device__ __forceinline__ void mma16816(float (&d)[4], const uint32_t (&a)[4], uint32_t b0, uint32_t b1) {
  asm volatile("mma.sync.aligned.m16n8k16.row.col.f32.bf16.bf16.f32 {%0,%1,%2,%3}, {%4,%5,%6,%7}, {%8,%9}, {%10,%10,%10,%10};"
               : "=f"(d[0]), "=f"(d[1]), "=f"(d[2]), "=f"(d[3])
               : "r"(a[0]), "r"(a[1]), "r"(a[2]), "r"(a[3]), "r"(b0), "r"(b1), "f"(0.f));
}
__device__ __forceinline__ void mma16816_acc(float (&d)[4], const uint32_t (&a)[4], uint32_t b0, uint32_t b1) {
  asm volatile("mma.sync.aligned.m16n8k16.row.col.f32.bf16.bf16.f32 {%0,%1,%2,%3}, {%4,%5,%6,%7}, {%8,%9}, {%0,%1,%2,%3};"
               : "+f"(d[0]), "+f"(d[1]), "+f"(d[2]), "+f"(d[3])
               : "r"(a[0]), "r"(a[1]), "r"(a[2]), "r"(a[3]), "r"(b0), "r"(b1));
}
__device__ __forceinline__ void mma1688_acc(float (&d)[4], uint32_t a0, uint32_t a1, uint32_t b0) {
  asm volatile("mma.sync.aligned.m16n8k8.row.col.f32.bf16.bf16.f32 {%0,%1,%2,%3}, {%4,%5}, {%6}, {%0,%1,%2,%3};"
               : "+f"(d[0]), "+f"(d[1]), "+f"(d[2]), "+f"(d[3]) : "r"(a0), "r"(a1), "r"(b0));
}
__device__ __forceinline__ float ex2(float x) { float y; asm("ex2.approx.ftz.f32 %0, %1;" : "=f"(y) : "f"(x)); return y; }
__device__ __forceinline__ float rcp(float x) { float y; asm("rcp.approx.ftz.f32 %0, %1;" : "=f"(y) : "f"(x)); return y; }
__device__ __forceinline__ float tanhf_hw(float x) { float y; asm("tanh.approx.f32 %0, %1;" : "=f"(y) : "f"(x)); return y; }
__device__ __forceinline__ uint32_t lds32(uint32_t a) { uint32_t v; asm volatile("ld.shared.u32 %0, [%1];" : "=r"(v) : "r"(a + own()) : "memory"); return v; }
__device__ __forceinline__ float2 lds64(uint32_t a) { float2 v; asm volatile("ld.shared.v2.f32 {%0,%1}, [%2];" : "=f"(v.x), "=f"(v.y) : "r"(a + own()) : "memory"); return v; }
__device__ __forceinline__ void lds128(uint32_t (&v)[4], uint32_t a) { asm volatile("ld.shared.v4.u32 {%0,%1,%2,%3}, [%4];" : "=r"(v[0]), "=r"(v[1]), "=r"(v[2]), "=r"(v[3]) : "r"(a + own()) : "memory"); }
__device__ __forceinline__ void sts128(uint32_t a, const uint32_t (&v)[4]) { asm volatile("st.shared.v4.u32 [%0], {%1,%2,%3,%4};" ::"r"(a + own()), "r"(v[0]), "r"(v[1]), "r"(v[2]), "r"(v[3]) : "memory"); }
__device__ __forceinline__ void ldg128_nc(uint32_t (&v)[4], const void* p) {
  asm volatile("ld.global.nc.L1::no_allocate.v4.u32 {%0,%1,%2,%3}, [%4];" : "=r"(v[0]), "=r"(v[1]), "=r"(v[2]), "=r"(v[3]) : "l"(p));
}
__device__ __forceinline__ uint32_t pin(uint32_t v, uint32_t zero) {
  asm volatile("{\n.reg .pred p;\n.reg .u32 c;\nmov.u32 c, %1;\nLP:\n.pragma \"nounroll\";\nsetp.eq.u32 p, c, 0;\n@p bra LD;\n"
               "nanosleep.u32 c;\nadd.u32 %0, %0, c;\nsub.u32 c, c, 1;\nbra LP;\nLD:\n}\n" : "+r"(v) : "r"(zero) : "memory");
  return v;
}
__device__ __forceinline__ void mbar_arrive_if(uint32_t b, bool cond) {
  asm volatile("{\n.reg .pred p;\nsetp.ne.u32 p, %1, 0;\n@p mbarrier.arrive.shared::cta.b64 _, [%0];\n}\n" ::"r"(b + own()), "r"((uint32_t)cond) : "memory");
}
__device__ __forceinline__ uint32_t ld_epoch(const unsigned* p) {
  uint32_t v;
  asm volatile("ld.relaxed.gpu.global.u32 %0, [%1];" : "=r"(v) : "l"(p) : "memory");
  return v;
}
__device__ __forceinline__ void ll_st(uint4* p, uint32_t a, uint32_t b, uint32_t c, uint32_t d, uint32_t tag) {
  asm volatile("st.relaxed.gpu.global.v4.b32 [%0], {%1, %2, %3, %4};" ::"l"(p), "r"((a & ~1u) | tag), "r"(b), "r"(c), "r"(d) : "memory");
}
__device__ __forceinline__ void ll_ld(uint32_t (&v)[4], const uint4* p) {
  asm volatile("{\n.reg .b128 t;\n.reg .b64 lo, hi;\nld.relaxed.gpu.global.b128 t, [%4];\nmov.b128 {lo, hi}, t;\n"
               "mov.b64 {%0, %1}, lo;\nmov.b64 {%2, %3}, hi;\n}\n"
               : "=r"(v[0]), "=r"(v[1]), "=r"(v[2]), "=r"(v[3]) : "l"(p) : "memory");
}
template <int N> __device__ __forceinline__ void ll_issue(uint32_t (&v)[N][4], const uint4* p, int stride) {
#pragma unroll
  for (int i = 0; i < N; i++) ll_ld(v[i], p + i * stride);
}
__device__ __forceinline__ uint32_t ll_mix(uint32_t a, uint32_t b, uint32_t tag) {
  uint32_t r;
  asm("lop3.b32 %0, %1, %2, %3, 0xD4;" : "=r"(r) : "r"(a), "r"(b), "r"(tag));
  return r;
}
template <int LO, int HI, int N> __device__ __forceinline__ uint32_t ll_tree(const uint32_t (&v)[N][4], uint32_t tag) {
  if constexpr (HI - LO == 1) return v[LO][0];
  else return ll_mix(ll_tree<LO, (LO + HI) / 2>(v, tag), ll_tree<(LO + HI) / 2, HI>(v, tag), tag);
}
template <int N> __device__ __forceinline__ uint32_t ll_red(const uint32_t (&v)[N][4], uint32_t tag) { return ll_tree<0, N>(v, tag); }
__device__ __forceinline__ bool ll_any(uint32_t red, uint32_t tag) { return __any_sync(0xffffffffu, (red ^ tag) & 1u); }
template <int N> __device__ __forceinline__ bool ll_bad(const uint32_t (&v)[N][4], uint32_t tag) { return ll_any(ll_red<N>(v, tag), tag); }
template <int N, int M> __device__ __forceinline__ bool ll_bad2(const uint32_t (&v)[N][4], const uint32_t (&u)[M][4], uint32_t tag) {
  return ll_any(ll_mix(ll_red<N>(v, tag), ll_red<M>(u, tag), tag), tag);
}
template <int N> __device__ __forceinline__ void ll_clear(uint32_t (&v)[N][4]) {
#pragma unroll
  for (int i = 0; i < N; i++) v[i][0] &= ~1u;
}
template <int N> __device__ __forceinline__ void ll_spin(uint32_t (&v)[N][4], const uint4* p, int stride, uint32_t tag) {
  uint32_t it = 0;
#pragma unroll 1
  do { ll_issue<N>(v, p, stride); } while (ll_bad<N>(v, tag) && ++it < SPIN_LIMIT);
}
template <int N> __device__ __forceinline__ void ll_get(uint32_t (&v)[N][4], const uint4* p, int stride, uint32_t tag) {
  ll_spin<N>(v, p, stride, tag);
  ll_clear<N>(v);
}
template <int N> __device__ __forceinline__ void ll_wait(uint32_t (&v)[N][4], const uint4* p, int stride, uint32_t tag) {
  if (__builtin_expect(ll_bad<N>(v, tag), 0)) ll_spin<N>(v, p, stride, tag);
  ll_clear<N>(v);
}
__device__ __forceinline__ void unpack32(float (&d)[32], const uint32_t (&v)[4][4]) {
#pragma unroll
  for (int u = 0; u < 4; u++)
#pragma unroll
    for (int e = 0; e < 4; e++) { d[8 * u + 2 * e] = bf_lo(v[u][e]); d[8 * u + 2 * e + 1] = bf_hi(v[u][e]); }
}
__device__ __forceinline__ void pack32(uint32_t (&v)[4][4], const float (&d)[32]) {
#pragma unroll
  for (int u = 0; u < 4; u++)
#pragma unroll
    for (int e = 0; e < 4; e++) v[u][e] = pack2(d[8 * u + 2 * e], d[8 * u + 2 * e + 1]);
}
__device__ __forceinline__ uint32_t t_addr(int m) { return SB + ((0x01534620u >> (4 * m)) & 7u) * 32768u; }

__device__ __forceinline__ constexpr int w2_pass(int m) { return m < 4 ? m & 1 : m >> 1; }
__device__ __forceinline__ constexpr int w2_peer(int m) { return m < 4 ? m >> 1 : m & 1; }

__device__ __forceinline__ int kb_at(int i, int j) { return i == 0 ? j : (i - 1 + (i - 1 >= j ? 1 : 0)); }

__device__ __forceinline__ void init_bars(int set) {
  if (set >= 0 && elect_one()) {
    const uint32_t cnt = set < 5 ? 1 : 8;
#pragma unroll
    for (int i = 0; i < 8; i++) mbar_init(BAR + (24 + 8 * set + i) * 8, cnt);
    if (set == 9) {
#pragma unroll
      for (int i = 0; i < 9; i++) mbar_init(BAR + (B_EX + i) * 8, 4);
#pragma unroll
      for (int i = 0; i < 4; i++) mbar_init(BAR + (B_READY + i) * 8, i == 0 ? 2 : i == 3 ? 4 : 3);
#pragma unroll
      for (int i = 0; i < 9; i++) mbar_init(BAR + (B_TAG + i) * 8, i < 1 || i == 8 ? 1 : i < 7 ? 4 : 3);
    }
    asm volatile("fence.mbarrier_init.release.cluster;" ::: "memory");
  }
  __syncwarp();
  asm volatile("barrier.cluster.arrive.relaxed.aligned;" ::: "memory");
  asm volatile("bar.arrive 4, 384;" ::: "memory");
  asm volatile("bar.sync 3, 384;" ::: "memory");
}

__device__ __forceinline__ void load_a(const Params& P, int i, int j) {
  const int f0 = 224 * j + ((j & 1) ? 32 : 0);
  const int fh = 224 * j + ((j & 1) ? 0 : 192);
  const uint32_t b = BAR + (B_FA + i) * 8, d = RING + (i & 3) * 24576;
  const int k0 = kb_at(i, j) * 64;
  mbar_expect_tx(b, 24576);
  tma2d(d, &P.w1, f0, k0, b);
  tma2d(d + 8192, &P.w3, f0, k0, b);
  tma2d(d + 16384, &P.w1h, fh, k0, b);
  tma2d(d + 20480, &P.w3h, fh, k0, b);
}

__global__ void __launch_bounds__(384, 1) fused_block_kernel(Scratch* __restrict__ X, const __nv_bfloat16* __restrict__ xp,
                                                             const __nv_bfloat16* __restrict__ wqkvp, const __nv_bfloat16* __restrict__ wop, const uint32_t zero,
                                                             const __grid_constant__ Params P) {
  extern __shared__ __align__(1024) uint8_t smem_raw[];
  if (smem_u32(smem_raw) != SB + own()) return;
  const int tid = threadIdx.x;
  const int warp = __shfl_sync(0xffffffffu, tid >> 5, 0);
  const int lane = tid & 31;
  const int cta = blockIdx.x;
  const int j = ((cta >> 1) & 1) * 4 + ((cta >> 4) & 1) * 2 + (cta & 1);
  const int g = ((cta >> 2) & 3) * 4 + (cta >> 5);

  if (warp >= 8) {
    asm volatile("setmaxnreg.dec.sync.aligned.u32 56;");
    if (warp == 8) {
      PSTAMPW(2, 0);
      const bool leader = elect_one();
      if (leader) {
        prefetch_map(&P.x); prefetch_map(&P.wqkv);
#pragma unroll
        for (int i = 0; i < 24; i++) mbar_init(BAR + i * 8, 1);
        asm volatile("fence.mbarrier_init.release.cluster;" ::: "memory");
      }
      __syncwarp();
      asm volatile("bar.arrive 3, 384;" ::: "memory");
      asm volatile("barrier.cluster.arrive.relaxed.aligned;" ::: "memory");
      auto ldx = [&](int p, int kb) {
        const uint32_t b = BAR + (B_FX + p * 8 + kb) * 8;
        mbar_expect_tx(b, 8192);
        tma3d(H0 + p * 65536 + kb * 8192, &P.x, kb * 64, p, g * 64, b);
      };
      auto ldkv = [&](int kb, int slot) {
        const uint32_t b = BAR + (B_FKV + kb) * 8, d = RING + slot * 16384;
        mbar_expect_tx(b, 16384);
        tma2d(d, &P.wqkv, 512 + 64 * j, kb * 64, b);
        tma2d(d + 8192, &P.wqkv, 1024 + 64 * j, kb * 64, b);
      };
      if (leader) {
#pragma unroll 1
        for (int i = 0; i < 8 + XO_DELAY; i++) {
          if (i < 8) ldx(0, i);
          if (i < 6) ldkv(i, i);
          if (i >= XO_DELAY) ldx(1, i - XO_DELAY);
        }
#pragma unroll
        for (int i = 0; i < 4; i++)
          asm volatile("cp.async.bulk.prefetch.tensor.2d.L2.global [%0, {%1, %2}];" ::"l"(&P.wqkv), "r"(512 + (i & 1) * 512 + 64 * j), "r"(384 + (i >> 1) * 64) : "memory");
        PSTAMPW(2, 2);
      }
      __syncwarp();
      asm volatile("bar.sync 4, 384;" ::: "memory");
      if (leader) {
        const int f0 = 224 * j + ((j & 1) ? 32 : 0);
        prefetch_map(&P.wo); prefetch_map(&P.w1); prefetch_map(&P.w3); prefetch_map(&P.w1h);
        prefetch_map(&P.w3h); prefetch_map(&P.w2); prefetch_map(&P.out);
#pragma unroll 1
        for (int i = 0; i < 2; i++) { mbar_wait(BAR + (B_EKV + i) * 8); ldkv(6 + i, i); }
#pragma unroll 1
        for (int i = 0; i < 8; i++) {
          const uint32_t b = BAR + (B_FQ + i) * 8;
          mbar_wait(BAR + (B_EKV + 2 + (i >> 1)) * 8);
          mbar_expect_tx(b, 8192);
          tma2d(RING + (4 + i) * 8192, &P.wqkv, 64 * j, i * 64, b);
        }
        mbar_expect_tx(BAR + B_FWO * 8, 65536);
#pragma unroll 1
        for (int i = 0; i < 8; i++) {
          const int kb = (i + 1) & 7;
          mbar_wait(BAR + (B_EX + i) * 8);
          tma2d(H0 + kb * 8192, &P.wo, 64 * j, kb * 64, BAR + B_FWO * 8);
        }
        mbar_wait(BAR + B_OG * 8);
#pragma unroll 1
        for (int i = 2; i < 8; i++) {
          mbar_wait(BAR + (B_EQ + (i == 2 ? 4 : 4 + i)) * 8);
          load_a(P, i, j);
        }
        uint32_t d = RING;
#pragma unroll 1
        for (int i = 0; i < 8; i++) {
          const uint32_t b = BAR + (B_FB + i) * 8;
          const int k0 = kb_at(i, j) * 64;
          mbar_wait(BAR + (B_EA + 5 + i) * 8);
          mbar_expect_tx(b, 32768);
          tma2d(d, &P.w1, f0 + 64, k0, b);
          tma2d(d + 8192, &P.w3, f0 + 64, k0, b);
          tma2d(d + 16384, &P.w1, f0 + 128, k0, b);
          tma2d(d + 24576, &P.w3, f0 + 128, k0, b);
          d = d == RING + 65536 ? RING : d + 32768;
        }
#pragma unroll 1
        for (int i = 0; i < 8; i++) {
          const int m = (0x76453210u >> (4 * i)) & 7;
          const uint32_t b = BAR + (B_FT + m) * 8;
          mbar_wait(BAR + (i < 5 ? B_EB + 3 + i : i < 7 ? B_HC - 5 + i : B_ET0) * 8);
          mbar_expect_tx(b, 28672);
          tma2d(t_addr(m), &P.w2, 64 * ((j + 2 + 2 * w2_pass(m)) & 7), 224 * (j ^ w2_peer(m)), b);
          PSTAMPW(2, 4 + i);
        }
#pragma unroll 1
        for (int q = 0; q < 2; q++) {
          mbar_expect_tx(BAR + (B_FIN + q) * 8, 16384);
          mbar_wait(BAR + (B_ET0 + 3 - q) * 8);
          PSTAMPW(2, 24 + q);
          asm volatile("cp.async.bulk.shared::cluster.global.mbarrier::complete_tx::bytes [%0], [%1], 16384, [%2];"
                       ::"r"(t_addr(q + 1) + own()), "l"(X->e4 + ((g * 8 + j) * 3 + q) * 1024), "r"(BAR + (B_FIN + q) * 8 + own()) : "memory");
        }
        X->epoch[cta] = X->epoch[cta] + 1;
      }
    } else {
      const int part = warp - 9;
      uint32_t tag;
      if (part == 2) {
        tag = ld_epoch(X->epoch + cta);
        init_bars(-1);
        tag = (tag + 1) & 1;
        if (lane == 0) {
          asm volatile("st.shared.u32 [%0], %1;" ::"r"(TAGS + own()), "r"(tag) : "memory");
          mbar_arrive(BAR + B_TAG * 8);
        }
      } else {
        init_bars(warp - 1);
        mbar_wait(BAR + B_TAG * 8);
        tag = lds32(TAGS);
      }
      PSTAMPW(3, 16 + part);
      auto clear8 = [&](uint4* p, int stride) {
#pragma unroll
        for (int i = 0; i < 8; i++) ll_st(p + i * stride + lane, 0, 0, 0, 0, tag ^ 1);
      };
      if (part == 0 && lane < 20)
        ll_st(lane < 16 ? X->e0s + g * 128 + 16 * j + lane : X->e0w + j * 64 + g * 4 + lane - 16, 0, 0, 0, 0, tag ^ 1);
      if (lane < 16) ll_st(X->e0c + ((j * 3 + part) * 16 + g) * 16 + lane, 0, 0, 0, 0, tag ^ 1);
      if (CLR_MODE && part == 1) clear8(X->e1 + (g * 8 + j) * 256, 32);
      __syncwarp();
      if (lane == 0) mbar_arrive(BAR + B_CLR1 * 8);
      uint32_t v[8][4];
      {
        float sm[4] = {0.f, 0.f, 0.f, 0.f}, qe[4] = {0.f, 0.f, 0.f, 0.f}, qo[4] = {0.f, 0.f, 0.f, 0.f};
        const uint32_t xa = H0 + ((lane >> 3) & 1) * 65536 + (8 * j + (lane & 7)) * 128 + (((lane >> 4) ^ (lane & 7)) << 4);
#pragma unroll 1
        for (int kb = part; kb < 8; kb += 3) {
          mbar_wait(BAR + (B_FX + kb) * 8);
          mbar_wait(BAR + (B_FX + 8 + kb) * 8);
          if (kb == 3 && lane == 0) l2_prefetch(wop + (size_t)(j * 64 + g * 4) * D_, 4096);
#pragma unroll
          for (int i = 0; i < 4; i++) ldsm4(v[i], (xa + kb * 8192) ^ (i << 5));
#pragma unroll
          for (int i = 0; i < 4; i++) {
            mma16816_acc(sm, v[i], 0x3f803f80u, 0x3f803f80u);
            mma16816_acc(qe, v[i], v[i][0], v[i][2]);
            mma16816_acc(qo, v[i], v[i][1], v[i][3]);
          }
        }
        const int r = lane >> 2;
        const bool diag = (lane & 3) == (r >> 1);
        uint32_t t[4] = {__float_as_uint(sm[0]), __float_as_uint(r & 1 ? qe[1] : qe[0]), __float_as_uint(sm[2]), __float_as_uint(r & 1 ? qo[3] : qo[2])};
        if (part && diag) sts128(WB + part * 128 - 128 + r * 16, t);
        if (part) asm volatile("bar.arrive 5, 96;" ::: "memory");
        else {
          asm volatile("bar.sync 5, 96;" ::: "memory");
          uint32_t t1[4], t2[4];
          lds128(t1, WB + r * 16); lds128(t2, WB + 128 + r * 16);
#pragma unroll
          for (int e = 0; e < 2; e++) {
            const float mean = (__uint_as_float(t[2 * e]) + __uint_as_float(t1[2 * e]) + __uint_as_float(t2[2 * e])) * (1.f / D_);
            const float ex2 = (__uint_as_float(t[2 * e + 1]) + __uint_as_float(t1[2 * e + 1]) + __uint_as_float(t2[2 * e + 1])) * (1.f / D_);
            const float rs = rsqrtf(fmaxf(fmaf(-mean, mean, ex2), 0.f) + 1e-5f);
            if (diag) ll_st(X->e0s + g * 128 + 16 * j + 2 * r + e, __float_as_uint(mean), __float_as_uint(rs), 0, 0, tag);
          }
        }
      }
      PSTAMPW(3, part * 4 + 2);
      if (PF_MODE == 0 && lane == 0) l2_prefetch(part == 0 ? P.w2p + (size_t)cta * 14 * D_ : (part == 1 ? P.w1p : P.w3p) + (size_t)cta * 4 * F_, 14336);
      if (part == 0) {
        const __nv_bfloat16* wr = wop + (size_t)(j * 64 + g * 4 + (lane >> 3)) * D_ + (lane & 7) * 8;
#pragma unroll
        for (int i = 0; i < 8; i++) ldg128_nc(v[i], wr + i * 64);
        float s[4];
#pragma unroll
        for (int e = 0; e < 4; e++) {
          s[e] = 0.f;
#pragma unroll
          for (int i = 0; i < 8; i++) s[e] += bf_lo(v[i][e]) + bf_hi(v[i][e]);
        }
        float ss = (s[0] + s[1]) + (s[2] + s[3]);
#pragma unroll
        for (int o = 1; o <= 4; o <<= 1) ss += __shfl_xor_sync(0xffffffffu, ss, o);
        if ((lane & 7) == 0) ll_st(X->e0w + j * 64 + g * 4 + (lane >> 3), __float_as_uint(ss * (1.f / D_)), 0, 0, 0, tag);
      }
      PSTAMPW(3, part * 4 + 0);
      {
        ll_get<8>(v, X->e0c + ((j * 3 + part) * 16 + (lane >> 4) * 8) * 16 + (lane & 15), 16, tag);
        if (part == 0) {
          uint32_t u[2][4];
          ll_get<2>(u, X->e0w + j * 64 + lane, 32, tag);
#pragma unroll
          for (int i = 0; i < 2; i++) asm volatile("st.shared.u32 [%0], %1;" ::"r"(WB + own() + (i * 32 + lane) * 4), "r"(u[i][0]) : "memory");
        }
        uint32_t o[4];
#pragma unroll
        for (int e = 0; e < 4; e++) {
          float s = 0.f;
#pragma unroll
          for (int i = 0; i < 8; i++) s += __uint_as_float(v[i][e]);
          o[e] = __float_as_uint(s + __shfl_xor_sync(0xffffffffu, s, 16));
        }
        if (lane < 16) sts128(CS + (part * 64 + lane * 4) * 4, o);
      }
      __syncwarp();
      if (lane == 0) mbar_arrive(BAR + (part == 0 ? B_WBAR : B_READY) * 8);
      PSTAMPW(3, part * 4 + 1);
      if (part == 1 && elect_one()) {
#pragma unroll 1
        for (int i = 0; i < 2; i++) { mbar_wait(BAR + (B_EKV + 7 + 2 * i) * 8); load_a(P, i, j); }
      }
      if (CLR_MODE && part == 2) {
        mbar_wait(BAR + (CLR_WHEN) * 8);
#pragma unroll
        for (int i = 0; i < 2; i++) ll_st(X->e3s + ((g * 8 + i * 4 + (lane >> 3)) * 8 + j) * 8 + (lane & 7), 0, 0, 0, 0, tag ^ 1);
#pragma unroll 1
        for (int u = 0; u < 4; u++) {
          clear8(X->e3h + (g * 256 + 4 * j + u) * 32, 1024);
          __nanosleep(CLR_SLEEP2);
        }
      }
      __syncwarp();
      if (part == 2 && lane == 0) mbar_arrive(BAR + B_CLR2 * 8);
      PSTAMPW(3, 20 + part);
      if (PF_MODE == 2) mbar_wait(BAR + (B_FQ + 7) * 8);
      if (PF_MODE >= 1 && lane == 0) l2_prefetch(part == 0 ? P.w2p + (size_t)cta * 14 * D_ : (part == 1 ? P.w1p : P.w3p) + (size_t)cta * 4 * F_, 14336);
      mbar_wait(BAR + (E4_WHEN) * 8);
#pragma unroll 1
      for (int u = 0; u < 4 * E4_ON; u++) {
        clear8(X->e4 + ((g * 8 + ((j + 2 + 2 * part) & 7)) * 3 + part) * 1024 + u * 32, 128);
        __nanosleep(CLR_SLEEP);
      }
      __syncwarp();
      if (lane == 0) mbar_arrive(BAR + B_CLR * 8);
      PSTAMPW(3, part * 4 + 3);
    }
  } else {
    const int p = warp >> 2, w = warp & 3;
    const int r = lane >> 2, c = lane & 3;
    init_bars(warp);
    asm volatile("setmaxnreg.inc.sync.aligned.u32 224;");
    PSTAMP(0);
    const uint32_t dAx = descA(H0) + p * 4096;
    const uint32_t Hn = H1 - p * 65536;
    const uint32_t moff = ((lane & 7) + ((lane >> 3) & 1) * 8) * 128 + (((lane >> 4) ^ (lane & 7)) << 4);
    const uint32_t Xw = H0 + p * 65536 + w * 2048;
    const int xw = (g * 2 + p) * 4 + w;
    uint32_t cv[8][4];
    if (p == 1) {
      mbar_wait(BAR + (B_FKV + SIDE_KB) * 8);
      const int wp = w < 3 ? w : 0;
      const __nv_bfloat16* wr = wqkvp + (size_t)(g * 32 + (lane >> 3) * 8) * (3 * D_) + wp * D_ + j * 64 + (lane & 7) * 8;
#pragma unroll
      for (int i = 0; i < 8; i++) ldg128_nc(cv[i], wr + (size_t)i * 3 * D_);
      mbar_wait(BAR + B_LAG * 8);
    }

    float akv[64];
    auto kvstep = [&](int kb) {
      mbar_wait(BAR + (B_FX + p * 8 + kb) * 8);
      mbar_wait(BAR + (B_FKV + kb) * 8);
      if (kb == 0) PSTAMP(2);
      const uint32_t da = dAx + kb * 512, db = descB(RING) + (kb < 6 ? kb : kb - 6) * 1024;
      wg_fence();
      wgmma_ss_n128(akv, da, db, kb);
#pragma unroll
      for (int k = 1; k < 4; k++) wgmma_ss_n128(akv, da + k * 2, db + k * 128, 1);
      wg_commit();
      mbar_arrive_if(BAR + B_LAG * 8, kb == LAG_KB - 1 && p == 0 && lane == 0);
      wg_wait<1>();
      mbar_arrive_if(BAR + (B_EKV + kb - 1) * 8, kb > 0 && lane == 0);
    };
#pragma unroll
    for (int kb = 0; kb < CS_KB; kb++) kvstep(kb);
    if (p == 1) {
      PSTAMP(29);
      mbar_wait(BAR + B_CLR1 * 8);
      const uint32_t tg = lds32(TAGS);
      const uint32_t hm = 0xffff0000u | (tg >> 1), sh = 16 + (tg >> 1);
      float cs[8];
#pragma unroll
      for (int e = 0; e < 4; e++) {
        float a = 0.f, b = 0.f;
#pragma unroll
        for (int i = 0; i < 8; i++) { a += __uint_as_float(cv[i][e] << sh); b += __uint_as_float(cv[i][e] & hm); }
        cs[2 * e] = a; cs[2 * e + 1] = b;
      }
      const bool up = lane & 8;
#pragma unroll
      for (int e = 0; e < 4; e++) {
        const float keepv = up ? cs[4 + e] : cs[e], give = up ? cs[e] : cs[4 + e];
        cs[e] = keepv + __shfl_xor_sync(0xffffffffu, give, 8);
        cs[e] += __shfl_xor_sync(0xffffffffu, cs[e], 16);
      }
      if (lane < 16 && w < 3)
        ll_st(X->e0c + ((j * 3 + w) * 16 + g) * 16 + (lane & 7) * 2 + (lane >> 3), __float_as_uint(cs[0]), __float_as_uint(cs[1]),
              __float_as_uint(cs[2]), __float_as_uint(cs[3]), tg);
      PSTAMP(1);
    }
#pragma unroll 1
    for (int kb = CS_KB; kb < 8; kb++) kvstep(kb);
    asm volatile("barrier.cluster.wait.aligned;" ::: "memory");
    uint32_t xres[4][4];
#pragma unroll
    for (int u = 0; u < 4; u++) ldsm4(xres[u], Xw + j * 8192 + (moff ^ (u << 5)));

    float aq[32];
    auto qstep = [&](int kb) {
      mbar_wait(BAR + (B_FQ + kb) * 8);
      const uint32_t da = dAx + kb * 512, db = descB(RING + 32768) + kb * 512;
      wg_fence();
      wgmma_ss_n64(aq, da, db, kb);
#pragma unroll
      for (int k = 1; k < 4; k++) wgmma_ss_n64(aq, da + k * 2, db + k * 128, 1);
      wg_commit();
      wg_wait<1>();
      mbar_arrive_if(BAR + (B_EQ + kb - 1) * 8, lane == 0);
      mbar_arrive_if(BAR + (B_EX + kb - 2) * 8, lane == 0 && p == 0 && kb >= 2);
    };
    mbar_wait(BAR + B_CLR1 * 8);
    const uint32_t tag = lds32(TAGS);
    uint32_t sv[2][4];
    const uint4* stsrc = X->e0s + g * 128 + 2 * (16 * w + r) + p;
    qstep(0);
    ll_issue<2>(sv, stsrc, 16);
    keep(akv);
    PSTAMP(3);
    qstep(1);
    mbar_wait(BAR + B_READY * 8);
    if (__builtin_expect(ll_bad<2>(sv, pin(tag, zero)), 0)) ll_spin<2>(sv, stsrc, 16, tag);
    PSTAMP(19);
    uint4* const xb = reinterpret_cast<uint4*>(X) + lane + (tag >> 1);
    constexpr int O_E4 = offsetof(Scratch, e4) / 16, O_E2 = offsetof(Scratch, e2) / 16, O_E3H = offsetof(Scratch, e3h) / 16;
    const float2 st0 = make_float2(__uint_as_float(sv[0][0] & ~1u), __uint_as_float(sv[0][1]));
    const float2 st1 = make_float2(__uint_as_float(sv[1][0] & ~1u), __uint_as_float(sv[1][1]));
    uint32_t hi[4][4], lo[4][4];
    {
      float2 cs[16];
      auto cvt = [&](uint32_t (&d)[4][4], int b0, int ofs, const float2& st) {
#pragma unroll
        for (int b = b0; b < b0 + 8; b++) {
          if (ofs == 2) cs[b] = lds64(CS + (64 + b * 8 + 2 * c) * 4);
          const uint32_t v = pack2(fmaf(-st.x, cs[b].x, akv[4 * b + ofs]) * st.y, fmaf(-st.x, cs[b].y, akv[4 * b + ofs + 1]) * st.y);
          d[b >> 2][b & 3] = b < 8 ? v : movm(v);
        }
      };
      cvt(hi, 0, 2, st1);
      keep(hi[0]); keep(hi[1]);
      qstep(2);
      cvt(hi, 8, 2, st1);
      if (w == 3 && g < 15) {
        uint4* dst = X->e1 + ((g * 8 + j) * 2 + p) * 128 + lane;
#pragma unroll
        for (int i = 0; i < 4; i++) ll_st(dst + i * 32, hi[i][0], hi[i][1], hi[i][2], hi[i][3], tag);
      }
      PSTAMP(20);
      wg_bar(p);
#pragma unroll
      for (int i = 0; i < 4; i++) sts128(Xw + lane * 16 + i * 512, hi[i]);
      qstep(3);
      cvt(lo, 0, 0, st0);
      keep(lo[0]); keep(lo[1]);
      qstep(4);
      cvt(lo, 8, 0, st0);
    }
    PSTAMP(21);
    wg_bar(p);
    uint32_t prev[4][4];
    if (w > 0) {
#pragma unroll
      for (int i = 0; i < 4; i++) lds128(prev[i], Xw - 2048 + lane * 16 + i * 512);
    }
    if (p == 0) {
      asm volatile("fence.proxy.async.shared::cta;" ::: "memory");
      __syncwarp();
      if (lane == 0) mbar_arrive(BAR + (B_EX + 7) * 8);
    }
    PSTAMP(22);
    const uint4* halo = X->e1 + (((g - 1) * 8 + j) * 2 + p) * 128 + lane;
    const bool use_halo = w == 0 && g > 0;
    qstep(5);
    if (use_halo) ll_issue<4>(prev, halo, 32);
    qstep(6);
    qstep(7);
    PSTAMP(23);
    if (w == 0) {
      if (g > 0) {
        if (__builtin_expect(ll_bad<4>(prev, pin(tag, zero)), 0)) ll_spin<4>(prev, halo, 32, tag);
        ll_clear<4>(prev);
      } else {
#pragma unroll
        for (int i = 0; i < 4; i++)
#pragma unroll
          for (int e = 0; e < 4; e++) prev[i][e] = 0;
      }
    }
    wg_wait<0>();
    keep(aq);
    mbar_arrive_if(BAR + (B_EQ + 7) * 8, lane == 0);
    mbar_arrive_if(BAR + (B_EX + 6) * 8, lane == 0 && p == 0);
    PSTAMP(4);

    uint32_t of[4][4];
    mbar_wait(BAR + B_WBAR * 8);
    {
      const float sc = 0.25f * 1.4426950408889634f;
      const float nohalo = (g == 0 && w == 0) ? -INFINITY : 0.f;
      const bool up0 = 2 * c > r, up1 = 2 * c + 1 > r;
      const uint32_t mup = (up0 ? 0xffffu : 0u) | (up1 ? 0xffff0000u : 0u);
      uint4* dst = xb + O_E2 + (xw * 32 + 4 * j) * 32;
      float d0 = 0.f, d1 = 0.f;
#pragma unroll 1
      for (int hp = 0; hp < 2; hp++) {
#pragma unroll
        for (int e = 0; e < 4; e++) { of[0][e] = of[2][e]; of[1][e] = of[3][e]; }
#pragma unroll
        for (int h = 0; h < 2; h++) {
          uint32_t qf[4];
          const uint32_t co = (32 * hp + 16 * h + 2 * c) * 4;
          {
            const float2 ca = lds64(CS + co), cb = lds64(CS + co + 32);
            qf[0] = pack2(fmaf(-st0.x, ca.x, aq[8 * h + 0]) * st0.y, fmaf(-st0.x, ca.y, aq[8 * h + 1]) * st0.y);
            qf[1] = pack2(fmaf(-st1.x, ca.x, aq[8 * h + 2]) * st1.y, fmaf(-st1.x, ca.y, aq[8 * h + 3]) * st1.y);
            qf[2] = pack2(fmaf(-st0.x, cb.x, aq[8 * h + 4]) * st0.y, fmaf(-st0.x, cb.y, aq[8 * h + 5]) * st0.y);
            qf[3] = pack2(fmaf(-st1.x, cb.x, aq[8 * h + 6]) * st1.y, fmaf(-st1.x, cb.y, aq[8 * h + 7]) * st1.y);
          }
          const int e0 = 2 * h;
          float sp[4], sl[4], sh[4];
          mma16816(sp, qf, prev[0][e0], prev[0][e0 + 1]);
          mma16816(sl, qf, lo[0][e0], lo[0][e0 + 1]);
          mma16816(sh, qf, hi[0][e0], hi[0][e0 + 1]);
          float a0 = up0 ? sp[0] + nohalo : sl[0], a1 = up1 ? sp[1] + nohalo : sl[1];
          float b0 = up0 ? sl[2] : sh[2], b1 = up1 ? sl[3] : sh[3];
          float ma = fmaxf(a0, a1), mb = fmaxf(b0, b1);
          ma = fmaxf(ma, __shfl_xor_sync(0xffffffffu, ma, 1)); mb = fmaxf(mb, __shfl_xor_sync(0xffffffffu, mb, 1));
          ma = fmaxf(ma, __shfl_xor_sync(0xffffffffu, ma, 2)); mb = fmaxf(mb, __shfl_xor_sync(0xffffffffu, mb, 2));
          a0 = ex2((a0 - ma) * sc); a1 = ex2((a1 - ma) * sc); b0 = ex2((b0 - mb) * sc); b1 = ex2((b1 - mb) * sc);
          float sa = a0 + a1, sbb = b0 + b1;
          sa += __shfl_xor_sync(0xffffffffu, sa, 1); sbb += __shfl_xor_sync(0xffffffffu, sbb, 1);
          sa += __shfl_xor_sync(0xffffffffu, sa, 2); sbb += __shfl_xor_sync(0xffffffffu, sbb, 2);
          const float ia = rcp(sa), ib = rcp(sbb);
          const uint32_t pa = pack2(a0 * ia, a1 * ia), pb = pack2(b0 * ib, b1 * ib);
          const uint32_t pf[4] = {pa & mup, 0u, pa & ~mup, pb & mup};
          const uint32_t ph = pb & ~mup;
          float o0[4], o1[4];
          mma16816(o0, pf, prev[2][e0], lo[2][e0]);
          mma16816(o1, pf, prev[2][e0 + 1], lo[2][e0 + 1]);
          mma1688_acc(o0, 0u, ph, hi[2][e0]);
          mma1688_acc(o1, 0u, ph, hi[2][e0 + 1]);
          of[2 + h][0] = pack2(o0[0], o0[1]); of[2 + h][1] = pack2(o0[2], o0[3]);
          of[2 + h][2] = pack2(o1[0], o1[1]); of[2 + h][3] = pack2(o1[2], o1[3]);
          ll_st(dst + (2 * hp + h) * 32, of[2 + h][0], of[2 + h][1], of[2 + h][2], of[2 + h][3], tag);
          const float2 wa = lds64(WB + co), wb = lds64(WB + co + 32);
          d0 = fmaf(o0[0], wa.x, d0); d0 = fmaf(o0[1], wa.y, d0); d0 = fmaf(o1[0], wb.x, d0); d0 = fmaf(o1[1], wb.y, d0);
          d1 = fmaf(o0[2], wa.x, d1); d1 = fmaf(o0[3], wa.y, d1); d1 = fmaf(o1[2], wb.x, d1); d1 = fmaf(o1[3], wb.y, d1);
        }
#pragma unroll
        for (int e = 0; e < 16; e++) aq[e] = aq[16 + e];
#pragma unroll
        for (int e = 0; e < 4; e++) {
          prev[0][e] = prev[1][e]; prev[2][e] = prev[3][e];
          lo[0][e] = lo[1][e]; lo[2][e] = lo[3][e];
          hi[0][e] = hi[1][e]; hi[2][e] = hi[3][e];
        }
      }
#pragma unroll
      for (int o = 1; o <= 2; o <<= 1) { d0 += __shfl_xor_sync(0xffffffffu, d0, o); d1 += __shfl_xor_sync(0xffffffffu, d1, o); }
      if (c == 0) ll_st(X->e2s + (xw * 8 + j) * 8 + r, __float_as_uint(d0), __float_as_uint(d1), 0, 0, tag);
    }
    PSTAMP(5);

    float ah[32];
    unpack32(ah, xres);
    {
      uint32_t og[2][14][4];
      const uint4* osrc[7];
#pragma unroll
      for (int i = 0; i < 7; i++) osrc[i] = xb + O_E2 + (xw * 32 + 4 * kb_at(i + 1, j)) * 32;
      const uint4* ssrc = X->e2s + (xw * 8 + 2 * c) * 8 + r;
      auto oissue = [&](int hp) {
#pragma unroll
        for (int i = 0; i < 14; i++) ll_ld(og[hp][i], osrc[i >> 1] + (2 * hp + (i & 1)) * 32);
        if (hp == 1) ll_issue<2>(sv, ssrc, 8);
      };
      auto omma = [&](int hp) {
        ll_clear<14>(og[hp]);
        keep(og[hp]);
        wg_fence();
#pragma unroll
        for (int i = 0; i < 14; i++) wgmma_rs_n64(ah, og[hp][i], descB(H0) + kb_at((i >> 1) + 1, j) * 512 + (2 * hp + (i & 1)) * 128, 1);
        wg_commit();
      };
      mbar_wait(BAR + B_FWO * 8);
      keep(ah); keep(of);
      wg_fence();
#pragma unroll
      for (int k = 0; k < 4; k++) wgmma_rs_n64(ah, of[k], descB(H0) + j * 512 + k * 128, 1);
      wg_commit();
      uint32_t it = 0;
#pragma unroll 1
      do { oissue(0); } while (ll_bad<14>(og[0], tag) && ++it < SPIN_LIMIT);
      PSTAMP(6);
      oissue(1);
      omma(0);
      const uint32_t tg = pin(tag, zero);
      if (__builtin_expect(ll_bad2<14, 2>(og[1], sv, tg), 0)) {
#pragma unroll 1
        do { oissue(1); } while (ll_bad2<14, 2>(og[1], sv, tag) && ++it < SPIN_LIMIT);
      }
      PSTAMP(16);
      mbar_arrive_if(BAR + B_OG * 8, lane == 0 && p == 0);
      omma(1);
      ll_clear<2>(sv);
    }
    float m0 = __uint_as_float(sv[0][0]) + __uint_as_float(sv[1][0]), m1 = __uint_as_float(sv[0][1]) + __uint_as_float(sv[1][1]);
#pragma unroll
    for (int o = 1; o <= 2; o <<= 1) { m0 += __shfl_xor_sync(0xffffffffu, m0, o); m1 += __shfl_xor_sync(0xffffffffu, m1, o); }
    const uint32_t mu0 = pack2(m0 + st0.x, m0 + st0.x), mu1 = pack2(m1 + st1.x, m1 + st1.x);
    wg_wait<0>();
    keep(ah);
    if (lane == 0) mbar_arrive(BAR + B_WODONE * 8);
    PSTAMP(7);

    uint32_t hf[4][4], ra[4][4];
    pack32(hf, ah);
    mbar_wait(BAR + B_CLR2 * 8);
    {
      uint4* dst = xb + O_E3H + (xw * 32 + 4 * j) * 32;
#pragma unroll
      for (int u = 0; u < 4; u++) {
        ra[u][0] = hsub2(hf[u][0], mu0); ra[u][1] = hsub2(hf[u][1], mu1);
        ra[u][2] = hsub2(hf[u][2], mu0); ra[u][3] = hsub2(hf[u][3], mu1);
        ll_st(dst + u * 32, ra[u][0], ra[u][1], ra[u][2], ra[u][3], tag);
      }
      float s0 = 0.f, q0 = 0.f, s1 = 0.f, q1 = 0.f;
#pragma unroll
      for (int b = 0; b < 8; b++) {
        s0 += ah[4 * b] + ah[4 * b + 1]; s1 += ah[4 * b + 2] + ah[4 * b + 3];
        q0 = fmaf(ah[4 * b], ah[4 * b], q0); q0 = fmaf(ah[4 * b + 1], ah[4 * b + 1], q0);
        q1 = fmaf(ah[4 * b + 2], ah[4 * b + 2], q1); q1 = fmaf(ah[4 * b + 3], ah[4 * b + 3], q1);
      }
#pragma unroll
      for (int o = 1; o <= 2; o <<= 1) {
        s0 += __shfl_xor_sync(0xffffffffu, s0, o); q0 += __shfl_xor_sync(0xffffffffu, q0, o);
        s1 += __shfl_xor_sync(0xffffffffu, s1, o); q1 += __shfl_xor_sync(0xffffffffu, q1, o);
      }
      if (c == 0) ll_st(X->e3s + (xw * 8 + j) * 8 + r, __float_as_uint(s0), __float_as_uint(q0), __float_as_uint(s1), __float_as_uint(q1), tag);
      mbar_wait(BAR + (p == 0 ? B_EQ + 7 : B_WODONE) * 8);
    }
    PSTAMP(8);

    float rs0, rs1;
    auto swiglu = [&](float g0, float g1, float u0, float u1, float rs) -> uint32_t {
      const float hr = 0.5f * rs;
      const float x0 = g0 * hr, x1 = g1 * hr;
      const float t0 = tanhf_hw(x0), t1 = tanhf_hw(x1);
      return pack2(fmaf(x0, t0, x0) * (u0 * rs), fmaf(x1, t1, x1) * (u1 * rs));
    };
    uint32_t hA[6][4];
    {
      float a1[64], a2[32];
      const uint4* src = xb + O_E3H + xw * 32 * 32;
      uint32_t rb[4][4], rc[4][4], rd[4][4];
      auto fetch = [&](uint32_t (&a)[4][4], int i) { ll_issue<4>(a, src + kb_at(i, j) * 128, 32); };
      auto check = [&](uint32_t (&a)[4][4], uint32_t (&b)[4][4], int i) {
        const uint32_t tg = pin(tag, zero);
        if (__builtin_expect(ll_bad2<4, 4>(a, b, tg), 0)) {
          uint32_t it = 0;
#pragma unroll 1
          do { fetch(a, i); fetch(b, i + 1); } while (ll_bad2<4, 4>(a, b, tag) && ++it < SPIN_LIMIT);
        }
        ll_clear<4>(a); ll_clear<4>(b);
        keep(a); keep(b);
      };
      auto head = [&](uint32_t (&a)[4][4], int i) {
        mbar_wait(BAR + (B_FA + i) * 8);
        wg_fence();
        wgmma_rs_n64<DESC_HI64>(a2, a[0], descBh(RING + 16384) + (i & 3) * 1536, i);
        wgmma_rs_n128(a1, a[0], descB(RING) + (i & 3) * 1536, i);
        wg_commit();
#pragma unroll
        for (int u = 0; u < 4; u++) stsm4(Hn + w * 2048 + i * 8192 + (moff ^ (u << 5)), a[u]);
        wg_wait<1>();
        if (i > 0) mbar_arrive_if(BAR + (B_EA + i - 1) * 8, lane == 0);
      };
      auto rest = [&](uint32_t (&a)[4][4], int i) {
        wg_fence();
#pragma unroll
        for (int k = 1; k < 4; k++) {
          wgmma_rs_n64<DESC_HI64>(a2, a[k], descBh(RING + 16384) + (i & 3) * 1536 + k * 64, 1);
          wgmma_rs_n128(a1, a[k], descB(RING) + (i & 3) * 1536 + k * 128, 1);
        }
        wg_commit();
      };
      ll_clear<4>(ra);
      keep(ra);
      head(ra, 0); rest(ra, 0);
      ll_get<4>(rb, src + kb_at(1, j) * 128, 32, tag);
      keep(rb);
      PSTAMP(17);
      fetch(rc, 2); fetch(rd, 3);
      head(rb, 1); rest(rb, 1);
      check(rc, rd, 2);
      head(rc, 2); fetch(ra, 4); fetch(rb, 5); rest(rc, 2);
      head(rd, 3); rest(rd, 3);
      check(ra, rb, 4);
      head(ra, 4); fetch(rc, 6); fetch(rd, 7); ll_issue<2>(sv, X->e3s + (xw * 8 + 2 * c) * 8 + r, 8); rest(ra, 4);
      head(rb, 5); rest(rb, 5);
      check(rc, rd, 6);
      head(rc, 6); rest(rc, 6);
      head(rd, 7); rest(rd, 7);
      fence_async_smem();
      ll_wait<2>(sv, X->e3s + (xw * 8 + 2 * c) * 8 + r, 8, tag);
      float s0 = __uint_as_float(sv[0][0]) + __uint_as_float(sv[1][0]), q0 = __uint_as_float(sv[0][1]) + __uint_as_float(sv[1][1]);
      float s1 = __uint_as_float(sv[0][2]) + __uint_as_float(sv[1][2]), q1 = __uint_as_float(sv[0][3]) + __uint_as_float(sv[1][3]);
#pragma unroll
      for (int o = 1; o <= 2; o <<= 1) {
        s0 += __shfl_xor_sync(0xffffffffu, s0, o); q0 += __shfl_xor_sync(0xffffffffu, q0, o);
        s1 += __shfl_xor_sync(0xffffffffu, s1, o); q1 += __shfl_xor_sync(0xffffffffu, q1, o);
      }
      s0 *= 1.f / D_; s1 *= 1.f / D_;
      rs0 = rsqrtf(fmaxf(fmaf(-s0, s0, q0 * (1.f / D_)), 0.f) + 1e-5f);
      rs1 = rsqrtf(fmaxf(fmaf(-s1, s1, q1 * (1.f / D_)), 0.f) + 1e-5f);
      wg_wait<0>();
      keep(a1); keep(a2);
      if (lane == 0) mbar_arrive(BAR + (B_EA + 7) * 8);
      PSTAMP(9);
#pragma unroll
      for (int u = 0; u < 4; u++)
#pragma unroll
        for (int e = 0; e < 4; e++)
          hA[u][e] = swiglu(a1[8 * u + 2 * e], a1[8 * u + 2 * e + 1], a1[32 + 8 * u + 2 * e], a1[33 + 8 * u + 2 * e], (e & 1) ? rs1 : rs0);
#pragma unroll
      for (int u = 0; u < 2; u++)
#pragma unroll
        for (int e = 0; e < 4; e++)
          hA[4 + u][e] = swiglu(a2[8 * u + 2 * e], a2[8 * u + 2 * e + 1], a2[16 + 8 * u + 2 * e], a2[17 + 8 * u + 2 * e], (e & 1) ? rs1 : rs0);
      keep(hA);
      wg_bar(p);
    }
    PSTAMP(10);

    const uint32_t mbx = Hn + 32768 + w * 512 + lane * 16;
    auto send = [&](const uint32_t (&v)[4], uint32_t a, int part) {
      asm volatile("st.async.weak.shared::cluster.mbarrier::complete_tx::bytes.v4.b32 [%0], {%1,%2,%3,%4}, [%5];"
                   ::"r"(a + peer()), "r"(v[0]), "r"(v[1]), "r"(v[2]), "r"(v[3]), "r"(BAR + (B_HX + 2 * part + p) * 8 + peer()) : "memory");
    };
    uint32_t hB[8][4];
    {
      float ab[128];
      uint32_t db = descB(RING);
      const uint32_t dAn = descA(H1) - p * 4096;
      if (lane == 0 && w == 0) { mbar_expect_tx(BAR + (B_HX + p) * 8, 12288); mbar_expect_tx(BAR + (B_HX + 2 + p) * 8, 16384); }
#pragma unroll 1
      for (int i = 0; i < 8; i++) {
        mbar_wait(BAR + (B_FB + i) * 8);
        const uint32_t da = dAn + i * 512;
        wg_fence();
        wgmma_ss_n256(ab, da, db, i);
#pragma unroll
        for (int k = 1; k < 4; k++) wgmma_ss_n256(ab, da + k * 2, db + k * 128, 1);
        wg_commit();
        if (i == 7) {
          mbar_wait_cluster(BAR + (B_PF + p) * 8);
#pragma unroll
          for (int k = 0; k < 6; k++) send(hA[k], mbx + k * 2048, 0);
        }
        wg_wait<1>();
        mbar_arrive_if(BAR + (B_EB + i - 1) * 8, i > 0 && lane == 0);
        if (i == 6 && lane == 0) mbar_arrive_peer(BAR + (B_PF + p) * 8);
        db = db == descB(RING + 65536) ? descB(RING) : db + 2048;
      }
      wg_wait<0>();
      keep(ab);
      mbar_arrive_if(BAR + (B_EB + 7) * 8, lane == 0);
      if (lane == 0) mbar_arrive_peer(BAR + (B_PF + 2 + p) * 8);
      PSTAMP(11);
#pragma unroll
      for (int u = 0; u < 8; u++) {
        const int o = (u >> 2) * 64 + (u & 3) * 8;
#pragma unroll
        for (int e = 0; e < 4; e++)
          hB[u][e] = swiglu(ab[o + 2 * e], ab[o + 2 * e + 1], ab[o + 32 + 2 * e], ab[o + 33 + 2 * e], (e & 1) ? rs1 : rs0);
        if (u == 3) mbar_wait_cluster(BAR + (B_PF + 2 + p) * 8);
        if (u >= 4 && u < 4 + SEND_EARLY) send(hB[u - 4], mbx + (2 + u) * 2048, 1);
      }
      keep(hB);
    }
    PSTAMP(12);

    {
      float ya[32], y[32];
      uint32_t hP[14][4];
      const uint32_t offA = (j & 1) ? 256 : 0, offH = (j & 1) ? 0 : 1536;
      uint4* e4 = xb + O_E4 + g * 24576 + warp * 128;
      const uint32_t stg = H0 + p * 65536 + 28672 + (w >> 1) * 32768 + (w & 1) * 2048;
      auto mm = [&](float (&d)[32], int m, int k0, int k1) {
        if (k0 == 0) mbar_wait(BAR + (B_FT + m) * 8);
        const uint32_t T = descB(0) + (t_addr(m) >> 4);
        const uint32_t oA = w2_peer(m) ? 256 - offA : offA, oH = w2_peer(m) ? 1536 - offH : offH;
        wg_fence();
#pragma unroll
        for (int k = k0; k < k1; k++) {
          const uint32_t db = T + (k < 4 ? oA + k * 128 : k < 6 ? oH + (k - 4) * 128 : oA + 512 + (k - 6) * 128);
          if (w2_peer(m)) wgmma_rs_n64(d, hP[k], db, 1);
          else if (k < 6) wgmma_rs_n64(d, hA[k], db, k);
          else wgmma_rs_n64(d, hB[k - 6], db, 1);
        }
        wg_commit();
      };
      auto next = [&](float (&d)[32], int m, float (&dp)[32], int q) {
        mm(d, m, 0, 3);
        wg_wait<1>();
        keep(dp);
        mbar_arrive_if(BAR + (B_ET0 + q) * 8, lane == 0);
        uint4* dst = e4 + (((j + 2 + 2 * q) & 7) * 3 + q) * 1024;
#pragma unroll
        for (int u = 0; u < 4; u++)
          ll_st(dst + u * 32, pack2(dp[8 * u], dp[8 * u + 1]), pack2(dp[8 * u + 2], dp[8 * u + 3]),
                pack2(dp[8 * u + 4], dp[8 * u + 5]), pack2(dp[8 * u + 6], dp[8 * u + 7]), tag);
        if (q == 2) mbar_wait(BAR + (B_ET0 + 2) * 8);
        mm(d, m, 3, 14);
      };
#pragma unroll
      for (int i = 0; i < 4; i++) {
        const uint32_t a = i ? pin(mbx, zero) : mbx;
#pragma unroll
        for (int k = SEND_EARLY + (8 - SEND_EARLY) * i / 4; k < SEND_EARLY + (8 - SEND_EARLY) * (i + 1) / 4; k++) send(hB[k], a + (6 + k) * 2048, 1);
        if (i < 3) mm(ya, 0, 5 * i, i < 2 ? 5 * i + 5 : 14);
        else mm(y, 1, 0, 6);
      }
      mbar_wait_cluster(BAR + (B_HX + p) * 8);
#pragma unroll
      for (int k = 0; k < 6; k++) lds128(hP[k], mbx + k * 2048);
      mm(y, 1, 6, 14);
      keep(hP[0]); keep(hP[1]); keep(hP[2]); keep(hP[3]); keep(hP[4]); keep(hP[5]);
      mm(ya, 2, 0, 3);
      PSTAMP(18);
      mbar_wait_cluster(BAR + (B_HX + 2 + p) * 8);
      PSTAMP(24);
#pragma unroll
      for (int k = 6; k < 14; k++) lds128(hP[k], mbx + k * 2048);
      mm(ya, 2, 3, 6);
      keep(hP);
      mbar_arrive_if(BAR + (B_HC + p) * 8, lane == 0);
      mm(ya, 2, 6, 14);
      mbar_wait(BAR + B_CLR * 8);
      next(y, 3, ya, 0);
      PSTAMP(27);
      next(ya, 4, y, 1);
      mbar_arrive_if(BAR + (B_ET0 + 3) * 8, lane == 0);
      mm(ya, 5, 0, 14);
      PSTAMP(26);
      next(y, 6, ya, 2);
      PSTAMP(28);
      uint32_t in[4][4], lt[4][4];
      const uint4* insrc = e4 + j * 3 * 1024;
      mm(y, 7, 0, 7);
      ll_issue<4>(lt, insrc + 2048, 32);
      mm(y, 7, 7, 14);
      mbar_wait(BAR + B_FIN * 8);
      mbar_wait(BAR + (B_FIN + 1) * 8);
      wg_wait<0>();
      keep(y);
      PSTAMP(13);
      const uint32_t ident = (2 * c == r ? 0x3f80u : 0u) | (2 * c + 1 == r ? 0x3f800000u : 0u);
      auto acc = [&](const uint32_t (&v)[4][4]) {
#pragma unroll
        for (int u = 0; u < 4; u++) {
          mma1688_acc(*reinterpret_cast<float (*)[4]>(&y[8 * u]), v[u][0], v[u][1], ident);
          mma1688_acc(*reinterpret_cast<float (*)[4]>(&y[8 * u + 4]), v[u][2], v[u][3], ident);
        }
      };
      acc(hf);
#pragma unroll
      for (int q = 0; q < 2; q++) {
#pragma unroll
        for (int u = 0; u < 4; u++) lds128(in[u], t_addr(q + 1) + warp * 2048 + lane * 16 + u * 512);
        ll_wait<4>(in, insrc + q * 1024, 32, tag);
        acc(in);
      }
      PSTAMP(25);
      if (ll_bad<4>(lt, pin(tag, zero))) {
        ll_spin<4>(lt, insrc + 2048, 32, tag);
      }
      ll_clear<4>(lt);
      acc(lt);
      PSTAMP(14);
#pragma unroll
      for (int u = 0; u < 4; u++) {
        uint32_t o[4];
#pragma unroll
        for (int e = 0; e < 4; e++) o[e] = pack2(y[8 * u + 2 * e], y[8 * u + 2 * e + 1]);
        stsm4(stg + (moff ^ (u << 5)), o);
      }
      fence_async_smem();
      __syncwarp();
      if (elect_one()) {
        tma3d_store(&P.out, stg, 64 * j, p, g * 64 + 16 * w);
        asm volatile("cp.async.bulk.commit_group;" ::: "memory");
        asm volatile("cp.async.bulk.wait_group.read 0;" ::: "memory");
      }
      PSTAMP(15);
    }
  }
}

typedef CUresult (*EncodeFn)(CUtensorMap*, CUtensorMapDataType, cuuint32_t, void*, const cuuint64_t*, const cuuint64_t*,
                             const cuuint32_t*, const cuuint32_t*, CUtensorMapInterleave, CUtensorMapSwizzle,
                             CUtensorMapL2promotion, CUtensorMapFloatOOBfill);

void enc2d(EncodeFn f, CUtensorMap* m, const void* base, uint64_t cols, uint64_t rows, uint32_t bc, uint32_t br, CUtensorMapSwizzle sw) {
  cuuint64_t gd[2] = {cols, rows}, gs[1] = {cols * 2};
  cuuint32_t bd[2] = {bc, br}, es[2] = {1, 1};
  f(m, CU_TENSOR_MAP_DATA_TYPE_BFLOAT16, 2, const_cast<void*>(base), gd, gs, bd, es, CU_TENSOR_MAP_INTERLEAVE_NONE, sw,
    CU_TENSOR_MAP_L2_PROMOTION_L2_128B, CU_TENSOR_MAP_FLOAT_OOB_FILL_NONE);
}
void enc_par(EncodeFn f, CUtensorMap* m, const void* base, uint32_t pairs) {
  cuuint64_t gd[3] = {(cuuint64_t)D_, 2, (cuuint64_t)S_ / 2}, gs[2] = {D_ * 2, D_ * 4};
  cuuint32_t bd[3] = {64, 1, pairs}, es[3] = {1, 1, 1};
  f(m, CU_TENSOR_MAP_DATA_TYPE_BFLOAT16, 3, const_cast<void*>(base), gd, gs, bd, es, CU_TENSOR_MAP_INTERLEAVE_NONE,
    CU_TENSOR_MAP_SWIZZLE_128B, CU_TENSOR_MAP_L2_PROMOTION_L2_128B, CU_TENSOR_MAP_FLOAT_OOB_FILL_NONE);
}

}

extern "C" void kernel_launch(void* const* d_in, const int* in_sizes, int n_in, void* d_out, int out_size) {
  (void)in_sizes; (void)n_in; (void)out_size;
  static EncodeFn enc = nullptr;
  static Scratch* scratch = nullptr;
  if (!enc) {
    void* fn = nullptr;
    cudaDriverEntryPointQueryResult q;
    cudaGetDriverEntryPoint("cuTensorMapEncodeTiled", &fn, cudaEnableDefault, &q);
    enc = (EncodeFn)fn;
    cudaGetSymbolAddress((void**)&scratch, g_scratch);
    cudaFuncSetAttribute(fused_block_kernel, cudaFuncAttributeMaxDynamicSharedMemorySize, SMEM_BYTES);
  }
  Params P;
  const __nv_bfloat16* xp = (const __nv_bfloat16*)d_in[0];
  const __nv_bfloat16* wqkvp = (const __nv_bfloat16*)d_in[1];
  const __nv_bfloat16* wop = (const __nv_bfloat16*)d_in[2];
  P.w1p = (const __nv_bfloat16*)d_in[4];
  P.w3p = (const __nv_bfloat16*)d_in[5];
  P.w2p = (const __nv_bfloat16*)d_in[6];
  enc_par(enc, &P.x, xp, 64);
  enc_par(enc, &P.out, d_out, 16);
  enc2d(enc, &P.wqkv, wqkvp, 3 * D_, D_, 64, 64, CU_TENSOR_MAP_SWIZZLE_128B);
  enc2d(enc, &P.wo, wop, D_, D_, 64, 64, CU_TENSOR_MAP_SWIZZLE_128B);
  enc2d(enc, &P.w1, P.w1p, F_, D_, 64, 64, CU_TENSOR_MAP_SWIZZLE_128B);
  enc2d(enc, &P.w3, P.w3p, F_, D_, 64, 64, CU_TENSOR_MAP_SWIZZLE_128B);
  enc2d(enc, &P.w1h, P.w1p, F_, D_, 32, 64, CU_TENSOR_MAP_SWIZZLE_64B);
  enc2d(enc, &P.w3h, P.w3p, F_, D_, 32, 64, CU_TENSOR_MAP_SWIZZLE_64B);
  enc2d(enc, &P.w2, P.w2p, D_, F_, 64, 224, CU_TENSOR_MAP_SWIZZLE_128B);

  cudaLaunchConfig_t cfg = {};
  cfg.gridDim = dim3(128);
  cfg.blockDim = dim3(384);
  cfg.dynamicSmemBytes = SMEM_BYTES;
  cfg.stream = cudaStreamPerThread;
  cudaLaunchAttribute at[2];
  at[0].id = cudaLaunchAttributeCooperative;
  at[0].val.cooperative = 1;
  cfg.attrs = at;
  cfg.numAttrs = 1;
  at[1].id = cudaLaunchAttributeClusterDimension;
  at[1].val.clusterDim.x = 2; at[1].val.clusterDim.y = 1; at[1].val.clusterDim.z = 1;
  cfg.numAttrs = 2;
  cudaLaunchKernelEx(&cfg, fused_block_kernel, scratch, xp, wqkvp, wop, 0u, P);
}
```

```cpp
#include <cuda_runtime.h>
#include <cuda.h>
#include <cuda_bf16.h>
#include <stdint.h>
#include <stddef.h>

namespace {

constexpr int S_ = 2048, D_ = 512, F_ = 1792;
#define LAG_KB 3
#define E4_FIRST 7
#define PP_AHEAD 1
#define SIDE_KB 0
#define CLR_MODE 2
#define W2_HEAD 3
#define CLR_SLEEP 400
#define CMAP 4
#define E4_ON 1
#define E4_WHEN (B_EA + 7)
#define SEND_EARLY 2
#define CS_KB 3
#define WO_KB 3
#define GATHER_SLEEP 200
#define PF_MODE 1
#define CLR_SLEEP2 100
#define CLR_WHEN (B_EQ + 2)
#define QLATE 0
#define SIDE_SLEEP 0
#define XO_DELAY 2

constexpr uint32_t SPIN_LIMIT = 1u << 18;

struct Scratch {
  uint4 e4[16 * 8 * 3 * 8 * 4 * 32];
  uint4 e2[16 * 2 * 4 * 32 * 32];
  uint4 e3h[16 * 2 * 4 * 32 * 32];
  uint4 e1[16 * 8 * 2 * 4 * 32];
  uint4 e2s[16 * 2 * 4 * 8 * 8];
  uint4 e3s[16 * 2 * 4 * 8 * 8];
  uint4 e0c[8 * 3 * 16 * 16];
  uint4 e0s[2048];
  uint4 e0w[8 * 64];
  unsigned epoch[128];
};
__device__ Scratch g_scratch;
#define PSTAMP(i)
#define PSTAMPW(slot, i)
#define W2STAMP(i)

struct alignas(64) Params {
  CUtensorMap x, out, wqkv, wo, w1, w3, w1h, w3h, w2;
  const __nv_bfloat16 *w1p, *w3p, *w2p;
};

constexpr uint32_t SB = 1024;
constexpr uint32_t H0 = SB;
constexpr uint32_t H1 = SB + 65536;
constexpr uint32_t RING = SB + 131072;
constexpr uint32_t BAR = SB + 229376;
constexpr uint32_t TAGS = BAR + 1016;
constexpr uint32_t CS = BAR + 1024;
constexpr uint32_t ST = CS + 768;
constexpr uint32_t WB = ST + 1024;
constexpr uint32_t SMEM_BYTES = 232448;
static_assert(WB + 256 <= SB + SMEM_BYTES, "smem");

enum : int {
  B_FX = 0,
  B_FKV = 16, B_FQ = 24, B_FWO = 32, B_FA = 40, B_FB = 48, B_FT = 56,
  B_EKV = 64, B_EQ = 72, B_EA = 80, B_EB = 88, B_ET0 = 96,
  B_WODONE = 103,
  B_FIN = 33,
  B_EX = 104,
  B_LAG = 112, B_READY = 113, B_WBAR = 114, B_CLR = 115, B_OG = 116, B_TAG = 117,
  B_HX = 35,
  B_PF = 118,
  B_HC = 122,
  B_CLR1 = 124, B_CLR2 = 125
};

__device__ __forceinline__ uint32_t smem_u32(const void* p) { return (uint32_t)__cvta_generic_to_shared(p); }
__device__ __forceinline__ uint32_t own() { return (blockIdx.x & 1) << 24; }
__device__ __forceinline__ uint32_t peer() { return (~blockIdx.x & 1) << 24; }
__device__ __forceinline__ void mbar_init(uint32_t b, uint32_t c) { asm volatile("mbarrier.init.shared::cta.b64 [%0], %1;" ::"r"(b + own()), "r"(c) : "memory"); }
__device__ __forceinline__ void mbar_expect_tx(uint32_t b, uint32_t bytes) { asm volatile("mbarrier.arrive.expect_tx.shared::cta.b64 _, [%0], %1;" ::"r"(b + own()), "r"(bytes) : "memory"); }
__device__ __forceinline__ void mbar_arrive(uint32_t b) { asm volatile("mbarrier.arrive.shared::cta.b64 _, [%0];" ::"r"(b + own()) : "memory"); }
__device__ __forceinline__ void mbar_wait(uint32_t b) {
  asm volatile("{\n.reg .pred p;\n.reg .u32 c;\nmov.u32 c, 0;\nLW:\n.pragma \"nounroll\";\n"
               "mbarrier.try_wait.parity.shared::cta.b64 p, [%0], 0;\nadd.u32 c, c, 1;\nsetp.gt.or.u32 p, c, %1, p;\n@!p bra LW;\n}\n"
               ::"r"(b + own()), "n"(SPIN_LIMIT) : "memory");
}
__device__ __forceinline__ void mbar_arrive_peer(uint32_t b) {
  asm volatile("mbarrier.arrive.relaxed.cluster.shared::cluster.b64 _, [%0];" ::"r"(b + peer()) : "memory");
}
__device__ __forceinline__ void mbar_wait_cluster(uint32_t b) {
  asm volatile("{\n.reg .pred p;\n.reg .u32 c;\nmov.u32 c, 0;\nLW:\n.pragma \"nounroll\";\n"
               "mbarrier.try_wait.parity.acquire.cluster.shared::cta.b64 p, [%0], 0;\nadd.u32 c, c, 1;\nsetp.gt.or.u32 p, c, %1, p;\n@!p bra LW;\n}\n"
               ::"r"(b + own()), "n"(SPIN_LIMIT) : "memory");
}
__device__ __forceinline__ bool elect_one() {
  uint32_t p;
  asm volatile("{\n.reg .pred P;\nelect.sync _|P, 0xffffffff;\nselp.u32 %0, 1, 0, P;\n}\n" : "=r"(p));
  return p;
}
__device__ __forceinline__ void tma2d(uint32_t dst, const CUtensorMap* m, int c0, int c1, uint32_t bar) {
  dst += own(); bar += own();
  asm volatile("cp.async.bulk.tensor.2d.shared::cluster.global.mbarrier::complete_tx::bytes [%0], [%1, {%3, %4}], [%2];"
               ::"r"(dst), "l"(m), "r"(bar), "r"(c0), "r"(c1) : "memory");
}
__device__ __forceinline__ void tma3d(uint32_t dst, const CUtensorMap* m, int c0, int c1, int c2, uint32_t bar) {
  dst += own(); bar += own();
  asm volatile("cp.async.bulk.tensor.3d.shared::cluster.global.mbarrier::complete_tx::bytes [%0], [%1, {%3, %4, %5}], [%2];"
               ::"r"(dst), "l"(m), "r"(bar), "r"(c0), "r"(c1), "r"(c2) : "memory");
}
__device__ __forceinline__ void tma3d_store(const CUtensorMap* m, uint32_t src, int c0, int c1, int c2) {
  asm volatile("cp.async.bulk.tensor.3d.global.shared::cta.bulk_group [%0, {%2, %3, %4}], [%1];"
               ::"l"(m), "r"(src + own()), "r"(c0), "r"(c1), "r"(c2) : "memory");
}
__device__ __forceinline__ void l2_prefetch(const void* p, uint32_t bytes) {
  asm volatile("cp.async.bulk.prefetch.L2.global [%0], %1;" ::"l"(p), "r"(bytes) : "memory");
}
__device__ __forceinline__ void prefetch_map(const CUtensorMap* m) { asm volatile("prefetch.tensormap [%0];" ::"l"(m) : "memory"); }
__device__ __forceinline__ void fence_async_smem() { asm volatile("fence.proxy.async.shared::cta;" ::: "memory"); }
__device__ __forceinline__ void wg_fence() { asm volatile("wgmma.fence.sync.aligned;" ::: "memory"); }
__device__ __forceinline__ void wg_commit() { asm volatile("wgmma.commit_group.sync.aligned;" ::: "memory"); }
template <int N> __device__ __forceinline__ void wg_wait() { asm volatile("wgmma.wait_group.sync.aligned %0;" ::"n"(N) : "memory"); }
__device__ __forceinline__ void wg_bar(int p) {
  if (p == 0) asm volatile("bar.sync 1, 128;" ::: "memory"); else asm volatile("bar.sync 2, 128;" ::: "memory");
}
constexpr uint32_t DESC_HI128 = (1024 >> 4) | (1u << 30);
constexpr uint32_t DESC_HI64 = (512 >> 4) | (2u << 30);
__device__ __forceinline__ constexpr uint32_t descA(uint32_t addr) { return (addr >> 4) | (1u << 16); }
__device__ __forceinline__ constexpr uint32_t descB(uint32_t addr) { return (addr >> 4) | ((8192u >> 4) << 16); }
__device__ __forceinline__ constexpr uint32_t descBh(uint32_t addr) { return (addr >> 4) | ((4096u >> 4) << 16); }

__device__ __forceinline__ void wgmma_ss_n64(float (&d)[32], uint32_t da, uint32_t db, int sc) {
  asm volatile("{\n.reg .pred p;\n.reg .b64 da, db;\nsetp.ne.b32 p, %34, 0;\nmov.b64 da, {%32, %35};\nmov.b64 db, {%33, %35};\n"
    "wgmma.mma_async.sync.aligned.m64n64k16.f32.bf16.bf16 {%0, %1, %2, %3, %4, %5, %6, %7, %8, %9, %10, %11, %12, %13, %14, %15, %16, %17, %18, %19, %20, %21, %22, %23, %24, %25, %26, %27, %28, %29, %30, %31}, da, db, p, 1, 1, 0, 1;\n}\n"
    : "+f"(d[0]), "+f"(d[1]), "+f"(d[2]), "+f"(d[3]), "+f"(d[4]), "+f"(d[5]), "+f"(d[6]), "+f"(d[7]),
      "+f"(d[8]), "+f"(d[9]), "+f"(d[10]), "+f"(d[11]), "+f"(d[12]), "+f"(d[13]), "+f"(d[14]), "+f"(d[15]),
      "+f"(d[16]), "+f"(d[17]), "+f"(d[18]), "+f"(d[19]), "+f"(d[20]), "+f"(d[21]), "+f"(d[22]), "+f"(d[23]),
      "+f"(d[24]), "+f"(d[25]), "+f"(d[26]), "+f"(d[27]), "+f"(d[28]), "+f"(d[29]), "+f"(d[30]), "+f"(d[31])
    : "r"(da), "r"(db), "r"(sc), "n"(DESC_HI128));
}
__device__ __forceinline__ void wgmma_ss_n128(float (&d)[64], uint32_t da, uint32_t db, int sc) {
  asm volatile("{\n.reg .pred p;\n.reg .b64 da, db;\nsetp.ne.b32 p, %66, 0;\nmov.b64 da, {%64, %67};\nmov.b64 db, {%65, %67};\n"
    "wgmma.mma_async.sync.aligned.m64n128k16.f32.bf16.bf16 {%0, %1, %2, %3, %4, %5, %6, %7, %8, %9, %10, %11, %12, %13, %14, %15, %16, %17, %18, %19, %20, %21, %22, %23, %24, %25, %26, %27, %28, %29, %30, %31, %32, %33, %34, %35, %36, %37, %38, %39, %40, %41, %42, %43, %44, %45, %46, %47, %48, %49, %50, %51, %52, %53, %54, %55, %56, %57, %58, %59, %60, %61, %62, %63}, da, db, p, 1, 1, 0, 1;\n}\n"
    : "+f"(d[0]), "+f"(d[1]), "+f"(d[2]), "+f"(d[3]), "+f"(d[4]), "+f"(d[5]), "+f"(d[6]), "+f"(d[7]),
      "+f"(d[8]), "+f"(d[9]), "+f"(d[10]), "+f"(d[11]), "+f"(d[12]), "+f"(d[13]), "+f"(d[14]), "+f"(d[15]),
      "+f"(d[16]), "+f"(d[17]), "+f"(d[18]), "+f"(d[19]), "+f"(d[20]), "+f"(d[21]), "+f"(d[22]), "+f"(d[23]),
      "+f"(d[24]), "+f"(d[25]), "+f"(d[26]), "+f"(d[27]), "+f"(d[28]), "+f"(d[29]), "+f"(d[30]), "+f"(d[31]),
      "+f"(d[32]), "+f"(d[33]), "+f"(d[34]), "+f"(d[35]), "+f"(d[36]), "+f"(d[37]), "+f"(d[38]), "+f"(d[39]),
      "+f"(d[40]), "+f"(d[41]), "+f"(d[42]), "+f"(d[43]), "+f"(d[44]), "+f"(d[45]), "+f"(d[46]), "+f"(d[47]),
      "+f"(d[48]), "+f"(d[49]), "+f"(d[50]), "+f"(d[51]), "+f"(d[52]), "+f"(d[53]), "+f"(d[54]), "+f"(d[55]),
      "+f"(d[56]), "+f"(d[57]), "+f"(d[58]), "+f"(d[59]), "+f"(d[60]), "+f"(d[61]), "+f"(d[62]), "+f"(d[63])
    : "r"(da), "r"(db), "r"(sc), "n"(DESC_HI128));
}
__device__ __forceinline__ void wgmma_ss_n256(float (&d)[128], uint32_t da, uint32_t db, int sc) {
  asm volatile("{\n.reg .pred p;\n.reg .b64 da, db;\nsetp.ne.b32 p, %130, 0;\nmov.b64 da, {%128, %131};\nmov.b64 db, {%129, %131};\n"
    "wgmma.mma_async.sync.aligned.m64n256k16.f32.bf16.bf16 {%0, %1, %2, %3, %4, %5, %6, %7, %8, %9, %10, %11, %12, %13, %14, %15, %16, %17, %18, %19, %20, %21, %22, %23, %24, %25, %26, %27, %28, %29, %30, %31, %32, %33, %34, %35, %36, %37, %38, %39, %40, %41, %42, %43, %44, %45, %46, %47, %48, %49, %50, %51, %52, %53, %54, %55, %56, %57, %58, %59, %60, %61, %62, %63, %64, %65, %66, %67, %68, %69, %70, %71, %72, %73, %74, %75, %76, %77, %78, %79, %80, %81, %82, %83, %84, %85, %86, %87, %88, %89, %90, %91, %92, %93, %94, %95, %96, %97, %98, %99, %100, %101, %102, %103, %104, %105, %106, %107, %108, %109, %110, %111, %112, %113, %114, %115, %116, %117, %118, %119, %120, %121, %122, %123, %124, %125, %126, %127}, da, db, p, 1, 1, 0, 1;\n}\n"
    : "+f"(d[0]), "+f"(d[1]), "+f"(d[2]), "+f"(d[3]), "+f"(d[4]), "+f"(d[5]), "+f"(d[6]), "+f"(d[7]),
      "+f"(d[8]), "+f"(d[9]), "+f"(d[10]), "+f"(d[11]), "+f"(d[12]), "+f"(d[13]), "+f"(d[14]), "+f"(d[15]),
      "+f"(d[16]), "+f"(d[17]), "+f"(d[18]), "+f"(d[19]), "+f"(d[20]), "+f"(d[21]), "+f"(d[22]), "+f"(d[23]),
      "+f"(d[24]), "+f"(d[25]), "+f"(d[26]), "+f"(d[27]), "+f"(d[28]), "+f"(d[29]), "+f"(d[30]), "+f"(d[31]),
      "+f"(d[32]), "+f"(d[33]), "+f"(d[34]), "+f"(d[35]), "+f"(d[36]), "+f"(d[37]), "+f"(d[38]), "+f"(d[39]),
      "+f"(d[40]), "+f"(d[41]), "+f"(d[42]), "+f"(d[43]), "+f"(d[44]), "+f"(d[45]), "+f"(d[46]), "+f"(d[47]),
      "+f"(d[48]), "+f"(d[49]), "+f"(d[50]), "+f"(d[51]), "+f"(d[52]), "+f"(d[53]), "+f"(d[54]), "+f"(d[55]),
      "+f"(d[56]), "+f"(d[57]), "+f"(d[58]), "+f"(d[59]), "+f"(d[60]), "+f"(d[61]), "+f"(d[62]), "+f"(d[63]),
      "+f"(d[64]), "+f"(d[65]), "+f"(d[66]), "+f"(d[67]), "+f"(d[68]), "+f"(d[69]), "+f"(d[70]), "+f"(d[71]),
      "+f"(d[72]), "+f"(d[73]), "+f"(d[74]), "+f"(d[75]), "+f"(d[76]), "+f"(d[77]), "+f"(d[78]), "+f"(d[79]),
      "+f"(d[80]), "+f"(d[81]), "+f"(d[82]), "+f"(d[83]), "+f"(d[84]), "+f"(d[85]), "+f"(d[86]), "+f"(d[87]),
      "+f"(d[88]), "+f"(d[89]), "+f"(d[90]), "+f"(d[91]), "+f"(d[92]), "+f"(d[93]), "+f"(d[94]), "+f"(d[95]),
      "+f"(d[96]), "+f"(d[97]), "+f"(d[98]), "+f"(d[99]), "+f"(d[100]), "+f"(d[101]), "+f"(d[102]), "+f"(d[103]),
      "+f"(d[104]), "+f"(d[105]), "+f"(d[106]), "+f"(d[107]), "+f"(d[108]), "+f"(d[109]), "+f"(d[110]), "+f"(d[111]),
      "+f"(d[112]), "+f"(d[113]), "+f"(d[114]), "+f"(d[115]), "+f"(d[116]), "+f"(d[117]), "+f"(d[118]), "+f"(d[119]),
      "+f"(d[120]), "+f"(d[121]), "+f"(d[122]), "+f"(d[123]), "+f"(d[124]), "+f"(d[125]), "+f"(d[126]), "+f"(d[127])
    : "r"(da), "r"(db), "r"(sc), "n"(DESC_HI128));
}
template <uint32_t HI = DESC_HI128>
__device__ __forceinline__ void wgmma_rs_n64(float (&d)[32], const uint32_t (&a)[4], uint32_t db, int sc) {
  asm volatile("{\n.reg .pred p;\n.reg .b64 db;\nsetp.ne.b32 p, %37, 0;\nmov.b64 db, {%36, %38};\n"
    "wgmma.mma_async.sync.aligned.m64n64k16.f32.bf16.bf16 {%0, %1, %2, %3, %4, %5, %6, %7, %8, %9, %10, %11, %12, %13, %14, %15, %16, %17, %18, %19, %20, %21, %22, %23, %24, %25, %26, %27, %28, %29, %30, %31}, {%32, %33, %34, %35}, db, p, 1, 1, 1;\n}\n"
    : "+f"(d[0]), "+f"(d[1]), "+f"(d[2]), "+f"(d[3]), "+f"(d[4]), "+f"(d[5]), "+f"(d[6]), "+f"(d[7]),
      "+f"(d[8]), "+f"(d[9]), "+f"(d[10]), "+f"(d[11]), "+f"(d[12]), "+f"(d[13]), "+f"(d[14]), "+f"(d[15]),
      "+f"(d[16]), "+f"(d[17]), "+f"(d[18]), "+f"(d[19]), "+f"(d[20]), "+f"(d[21]), "+f"(d[22]), "+f"(d[23]),
      "+f"(d[24]), "+f"(d[25]), "+f"(d[26]), "+f"(d[27]), "+f"(d[28]), "+f"(d[29]), "+f"(d[30]), "+f"(d[31])
    : "r"(a[0]), "r"(a[1]), "r"(a[2]), "r"(a[3]), "r"(db), "r"(sc), "n"(HI));
}
template <uint32_t HI = DESC_HI128>
__device__ __forceinline__ void wgmma_rs_n128(float (&d)[64], const uint32_t (&a)[4], uint32_t db, int sc) {
  asm volatile("{\n.reg .pred p;\n.reg .b64 db;\nsetp.ne.b32 p, %69, 0;\nmov.b64 db, {%68, %70};\n"
    "wgmma.mma_async.sync.aligned.m64n128k16.f32.bf16.bf16 {%0, %1, %2, %3, %4, %5, %6, %7, %8, %9, %10, %11, %12, %13, %14, %15, %16, %17, %18, %19, %20, %21, %22, %23, %24, %25, %26, %27, %28, %29, %30, %31, %32, %33, %34, %35, %36, %37, %38, %39, %40, %41, %42, %43, %44, %45, %46, %47, %48, %49, %50, %51, %52, %53, %54, %55, %56, %57, %58, %59, %60, %61, %62, %63}, {%64, %65, %66, %67}, db, p, 1, 1, 1;\n}\n"
    : "+f"(d[0]), "+f"(d[1]), "+f"(d[2]), "+f"(d[3]), "+f"(d[4]), "+f"(d[5]), "+f"(d[6]), "+f"(d[7]),
      "+f"(d[8]), "+f"(d[9]), "+f"(d[10]), "+f"(d[11]), "+f"(d[12]), "+f"(d[13]), "+f"(d[14]), "+f"(d[15]),
      "+f"(d[16]), "+f"(d[17]), "+f"(d[18]), "+f"(d[19]), "+f"(d[20]), "+f"(d[21]), "+f"(d[22]), "+f"(d[23]),
      "+f"(d[24]), "+f"(d[25]), "+f"(d[26]), "+f"(d[27]), "+f"(d[28]), "+f"(d[29]), "+f"(d[30]), "+f"(d[31]),
      "+f"(d[32]), "+f"(d[33]), "+f"(d[34]), "+f"(d[35]), "+f"(d[36]), "+f"(d[37]), "+f"(d[38]), "+f"(d[39]),
      "+f"(d[40]), "+f"(d[41]), "+f"(d[42]), "+f"(d[43]), "+f"(d[44]), "+f"(d[45]), "+f"(d[46]), "+f"(d[47]),
      "+f"(d[48]), "+f"(d[49]), "+f"(d[50]), "+f"(d[51]), "+f"(d[52]), "+f"(d[53]), "+f"(d[54]), "+f"(d[55]),
      "+f"(d[56]), "+f"(d[57]), "+f"(d[58]), "+f"(d[59]), "+f"(d[60]), "+f"(d[61]), "+f"(d[62]), "+f"(d[63])
    : "r"(a[0]), "r"(a[1]), "r"(a[2]), "r"(a[3]), "r"(db), "r"(sc), "n"(HI));
}

template <int N> __device__ __forceinline__ void keep(float (&d)[N]) {
#pragma unroll
  for (int i = 0; i < N; i++) asm volatile("" : "+f"(d[i])::"memory");
}

__device__ __forceinline__ void keep(uint32_t (&d)[4]) { asm volatile("" : "+r"(d[0]), "+r"(d[1]), "+r"(d[2]), "+r"(d[3])::"memory"); }
template <int N> __device__ __forceinline__ void keep(uint32_t (&d)[N][4]) {
#pragma unroll
  for (int i = 0; i < N; i++) asm volatile("" : "+r"(d[i][0]), "+r"(d[i][1]), "+r"(d[i][2]), "+r"(d[i][3])::"memory");
}

__device__ __forceinline__ uint32_t pack2(float lo, float hi) {
  uint32_t r;
  asm("cvt.rn.bf16x2.f32 %0, %1, %2;" : "=r"(r) : "f"(hi), "f"(lo));
  return r;
}
__device__ __forceinline__ float bf_lo(uint32_t v) { return __uint_as_float(v << 16); }
__device__ __forceinline__ float bf_hi(uint32_t v) { return __uint_as_float(v & 0xffff0000u); }
__device__ __forceinline__ uint32_t hsub2(uint32_t a, uint32_t b) {
  uint32_t r;
  asm("sub.rn.bf16x2 %0, %1, %2;" : "=r"(r) : "r"(a), "r"(b));
  return r;
}
__device__ __forceinline__ uint32_t movm(uint32_t a) {
  uint32_t r;
  asm volatile("movmatrix.sync.aligned.m8n8.trans.b16 %0, %1;" : "=r"(r) : "r"(a));
  return r;
}
__device__ __forceinline__ void ldsm4(uint32_t (&v)[4], uint32_t a) {
  asm volatile("ldmatrix.sync.aligned.m8n8.x4.shared.b16 {%0,%1,%2,%3}, [%4];" : "=r"(v[0]), "=r"(v[1]), "=r"(v[2]), "=r"(v[3]) : "r"(a + own()) : "memory");
}
__device__ __forceinline__ void stsm4(uint32_t a, const uint32_t (&v)[4]) {
  asm volatile("stmatrix.sync.aligned.m8n8.x4.shared.b16 [%0], {%1,%2,%3,%4};" ::"r"(a + own()), "r"(v[0]), "r"(v[1]), "r"(v[2]), "r"(v[3]) : "memory");
}
__device__ __forceinline__ void mma16816(float (&d)[4], const uint32_t (&a)[4], uint32_t b0, uint32_t b1) {
  asm volatile("mma.sync.aligned.m16n8k16.row.col.f32.bf16.bf16.f32 {%0,%1,%2,%3}, {%4,%5,%6,%7}, {%8,%9}, {%10,%10,%10,%10};"
               : "=f"(d[0]), "=f"(d[1]), "=f"(d[2]), "=f"(d[3])
               : "r"(a[0]), "r"(a[1]), "r"(a[2]), "r"(a[3]), "r"(b0), "r"(b1), "f"(0.f));
}
__device__ __forceinline__ void mma1688_acc(float (&d)[4], uint32_t a0, uint32_t a1, uint32_t b0) {
  asm volatile("mma.sync.aligned.m16n8k8.row.col.f32.bf16.bf16.f32 {%0,%1,%2,%3}, {%4,%5}, {%6}, {%0,%1,%2,%3};"
               : "+f"(d[0]), "+f"(d[1]), "+f"(d[2]), "+f"(d[3]) : "r"(a0), "r"(a1), "r"(b0));
}
__device__ __forceinline__ float ex2(float x) { float y; asm("ex2.approx.ftz.f32 %0, %1;" : "=f"(y) : "f"(x)); return y; }
__device__ __forceinline__ float rcp(float x) { float y; asm("rcp.approx.ftz.f32 %0, %1;" : "=f"(y) : "f"(x)); return y; }
__device__ __forceinline__ float tanhf_hw(float x) { float y; asm("tanh.approx.f32 %0, %1;" : "=f"(y) : "f"(x)); return y; }
__device__ __forceinline__ uint32_t lds32(uint32_t a) { uint32_t v; asm volatile("ld.shared.u32 %0, [%1];" : "=r"(v) : "r"(a + own()) : "memory"); return v; }
__device__ __forceinline__ float2 lds64(uint32_t a) { float2 v; asm volatile("ld.shared.v2.f32 {%0,%1}, [%2];" : "=f"(v.x), "=f"(v.y) : "r"(a + own()) : "memory"); return v; }
__device__ __forceinline__ void lds128(uint32_t (&v)[4], uint32_t a) { asm volatile("ld.shared.v4.u32 {%0,%1,%2,%3}, [%4];" : "=r"(v[0]), "=r"(v[1]), "=r"(v[2]), "=r"(v[3]) : "r"(a + own()) : "memory"); }
__device__ __forceinline__ void sts128(uint32_t a, const uint32_t (&v)[4]) { asm volatile("st.shared.v4.u32 [%0], {%1,%2,%3,%4};" ::"r"(a + own()), "r"(v[0]), "r"(v[1]), "r"(v[2]), "r"(v[3]) : "memory"); }
__device__ __forceinline__ void ldg128_nc(uint32_t (&v)[4], const void* p) {
  asm volatile("ld.global.nc.L1::no_allocate.v4.u32 {%0,%1,%2,%3}, [%4];" : "=r"(v[0]), "=r"(v[1]), "=r"(v[2]), "=r"(v[3]) : "l"(p));
}
__device__ __forceinline__ uint32_t pin(uint32_t v, uint32_t zero) {
  asm volatile("{\n.reg .pred p;\n.reg .u32 c;\nmov.u32 c, %1;\nLP:\n.pragma \"nounroll\";\nsetp.eq.u32 p, c, 0;\n@p bra LD;\n"
               "nanosleep.u32 c;\nadd.u32 %0, %0, c;\nsub.u32 c, c, 1;\nbra LP;\nLD:\n}\n" : "+r"(v) : "r"(zero) : "memory");
  return v;
}
__device__ __forceinline__ void pin7(const uint4* (&p)[7], uint32_t zero) {
  asm volatile("{\n.reg .pred p;\n.reg .u64 c;\ncvt.u64.u32 c, %7;\nLP:\n.pragma \"nounroll\";\nsetp.eq.u64 p, c, 0;\n@p bra LD;\n"
               "add.u64 %0, %0, c;\nadd.u64 %1, %1, c;\nadd.u64 %2, %2, c;\nadd.u64 %3, %3, c;\nadd.u64 %4, %4, c;\n"
               "add.u64 %5, %5, c;\nadd.u64 %6, %6, c;\nsub.u64 c, c, 1;\nbra LP;\nLD:\n}\n"
               : "+l"(p[0]), "+l"(p[1]), "+l"(p[2]), "+l"(p[3]), "+l"(p[4]), "+l"(p[5]), "+l"(p[6]) : "r"(zero) : "memory");
}
__device__ __forceinline__ void pin32(float (&d)[32], uint32_t zero) {
  if (__builtin_expect(zero != 0, 0)) {
#pragma unroll 1
    for (uint32_t c = zero; c; c--) {
      const float t = d[0];
#pragma unroll
      for (int i = 0; i < 31; i++) d[i] = d[i + 1];
      d[31] = t;
    }
  }
}
__device__ __forceinline__ void mbar_arrive_if(uint32_t b, bool cond) {
  asm volatile("{\n.reg .pred p;\nsetp.ne.u32 p, %1, 0;\n@p mbarrier.arrive.shared::cta.b64 _, [%0];\n}\n" ::"r"(b + own()), "r"((uint32_t)cond) : "memory");
}
__device__ __forceinline__ uint32_t ld_epoch(const unsigned* p) {
  uint32_t v;
  asm volatile("ld.relaxed.gpu.global.u32 %0, [%1];" : "=r"(v) : "l"(p) : "memory");
  return v;
}
__device__ __forceinline__ void ll_st(uint4* p, uint32_t a, uint32_t b, uint32_t c, uint32_t d, uint32_t tag) {
  asm volatile("st.relaxed.gpu.global.v4.b32 [%0], {%1, %2, %3, %4};" ::"l"(p), "r"((a & ~1u) | tag), "r"(b), "r"(c), "r"(d) : "memory");
}
__device__ __forceinline__ void ll_ld(uint32_t (&v)[4], const uint4* p) {
  asm volatile("{\n.reg .b128 t;\n.reg .b64 lo, hi;\nld.relaxed.gpu.global.b128 t, [%4];\nmov.b128 {lo, hi}, t;\n"
               "mov.b64 {%0, %1}, lo;\nmov.b64 {%2, %3}, hi;\n}\n"
               : "=r"(v[0]), "=r"(v[1]), "=r"(v[2]), "=r"(v[3]) : "l"(p) : "memory");
}
template <int N> __device__ __forceinline__ void ll_issue(uint32_t (&v)[N][4], const uint4* p, int stride) {
#pragma unroll
  for (int i = 0; i < N; i++) ll_ld(v[i], p + i * stride);
}
__device__ __forceinline__ uint32_t ll_mix(uint32_t a, uint32_t b, uint32_t tag) {
  uint32_t r;
  asm("lop3.b32 %0, %1, %2, %3, 0xD4;" : "=r"(r) : "r"(a), "r"(b), "r"(tag));
  return r;
}
template <int LO, int HI, int N> __device__ __forceinline__ uint32_t ll_tree(const uint32_t (&v)[N][4], uint32_t tag) {
  if constexpr (HI - LO == 1) return v[LO][0];
  else return ll_mix(ll_tree<LO, (LO + HI) / 2>(v, tag), ll_tree<(LO + HI) / 2, HI>(v, tag), tag);
}
template <int N> __device__ __forceinline__ uint32_t ll_red(const uint32_t (&v)[N][4], uint32_t tag) { return ll_tree<0, N>(v, tag); }
__device__ __forceinline__ bool ll_any(uint32_t red, uint32_t tag) { return __any_sync(0xffffffffu, (red ^ tag) & 1u); }
template <int N> __device__ __forceinline__ bool ll_bad(const uint32_t (&v)[N][4], uint32_t tag) { return ll_any(ll_red<N>(v, tag), tag); }
template <int N, int M> __device__ __forceinline__ bool ll_bad2(const uint32_t (&v)[N][4], const uint32_t (&u)[M][4], uint32_t tag) {
  return ll_any(ll_mix(ll_red<N>(v, tag), ll_red<M>(u, tag), tag), tag);
}
template <int N> __device__ __forceinline__ void ll_clear(uint32_t (&v)[N][4]) {
#pragma unroll
  for (int i = 0; i < N; i++) v[i][0] &= ~1u;
}
template <int N> __device__ __forceinline__ void ll_spin(uint32_t (&v)[N][4], const uint4* p, int stride, uint32_t tag) {
  uint32_t it = 0;
#pragma unroll 1
  do { ll_issue<N>(v, p, stride); } while (ll_bad<N>(v, tag) && ++it < SPIN_LIMIT);
}
template <int N> __device__ __forceinline__ void ll_get(uint32_t (&v)[N][4], const uint4* p, int stride, uint32_t tag) {
  ll_spin<N>(v, p, stride, tag);
  ll_clear<N>(v);
}
template <int N> __device__ __forceinline__ void ll_wait(uint32_t (&v)[N][4], const uint4* p, int stride, uint32_t tag) {
  if (__builtin_expect(ll_bad<N>(v, tag), 0)) ll_spin<N>(v, p, stride, tag);
  ll_clear<N>(v);
}
__device__ __forceinline__ void unpack32(float (&d)[32], const uint32_t (&v)[4][4]) {
#pragma unroll
  for (int u = 0; u < 4; u++)
#pragma unroll
    for (int e = 0; e < 4; e++) { d[8 * u + 2 * e] = bf_lo(v[u][e]); d[8 * u + 2 * e + 1] = bf_hi(v[u][e]); }
}
__device__ __forceinline__ void pack32(uint32_t (&v)[4][4], const float (&d)[32]) {
#pragma unroll
  for (int u = 0; u < 4; u++)
#pragma unroll
    for (int e = 0; e < 4; e++) v[u][e] = pack2(d[8 * u + 2 * e], d[8 * u + 2 * e + 1]);
}
__device__ __forceinline__ uint32_t t_addr(int m) { return SB + ((0x01534620u >> (4 * m)) & 7u) * 32768u; }

__device__ __forceinline__ constexpr int w2_pass(int m) { return m < 4 ? m & 1 : m >> 1; }
__device__ __forceinline__ constexpr int w2_peer(int m) { return m < 4 ? m >> 1 : m & 1; }

__device__ __forceinline__ int kb_at(int i, int j) { return i == 0 ? j : (i - 1 + (i - 1 >= j ? 1 : 0)); }

__device__ __forceinline__ void init_bars(int set) {
  if (set >= 0 && elect_one()) {
    const uint32_t cnt = set < 5 ? 1 : 8;
#pragma unroll
    for (int i = 0; i < 8; i++) mbar_init(BAR + (24 + 8 * set + i) * 8, cnt);
    if (set == 9) {
#pragma unroll
      for (int i = 0; i < 9; i++) mbar_init(BAR + (B_EX + i) * 8, 4);
#pragma unroll
      for (int i = 0; i < 4; i++) mbar_init(BAR + (B_READY + i) * 8, i < 2 ? 2 : i == 3 ? 4 : 3);
#pragma unroll
      for (int i = 0; i < 9; i++) mbar_init(BAR + (B_TAG + i) * 8, i < 1 || i == 8 ? 1 : i < 7 ? 4 : 3);
    }
    asm volatile("fence.mbarrier_init.release.cluster;" ::: "memory");
  }
  __syncwarp();
  asm volatile("barrier.cluster.arrive.relaxed.aligned;" ::: "memory");
  asm volatile("bar.arrive 4, 384;" ::: "memory");
  asm volatile("bar.sync 3, 384;" ::: "memory");
}

__device__ __forceinline__ void load_a(const Params& P, int i, int j) {
  const int f0 = 224 * j + ((j & 1) ? 32 : 0);
  const int fh = 224 * j + ((j & 1) ? 0 : 192);
  const uint32_t b = BAR + (B_FA + i) * 8, d = RING + (i & 3) * 24576;
  const int k0 = kb_at(i, j) * 64;
  mbar_expect_tx(b, 24576);
  tma2d(d, &P.w1, f0, k0, b);
  tma2d(d + 8192, &P.w3, f0, k0, b);
  tma2d(d + 16384, &P.w1h, fh, k0, b);
  tma2d(d + 20480, &P.w3h, fh, k0, b);
}

__global__ void __launch_bounds__(384, 1) fused_block_kernel(Scratch* __restrict__ X, const __nv_bfloat16* __restrict__ xp,
                                                             const __nv_bfloat16* __restrict__ wqkvp, const __nv_bfloat16* __restrict__ wop, const uint32_t zero,
                                                             const __grid_constant__ Params P) {
  extern __shared__ __align__(1024) uint8_t smem_raw[];
  if (smem_u32(smem_raw) != SB + own()) return;
  const int tid = threadIdx.x;
  const int warp = __shfl_sync(0xffffffffu, tid >> 5, 0);
  const int lane = tid & 31;
  const int cta = blockIdx.x;
  const int cl = cta >> 1;
  const int c7 = cl - 36, i7 = (c7 * 37) >> 8;
  const int set = cl < 4 ? 15 : cl < 36 ? (cl - 4) & 7 : 8 + c7 - 7 * i7;
  const int idx = cl < 4 ? cl : cl < 36 ? (cl - 4) >> 3 : i7;
  const int g = (set & 14) + (idx >> 1), j = (set & 1) * 4 + (idx & 1) * 2 + (cta & 1);

  if (warp >= 8) {
    asm volatile("setmaxnreg.dec.sync.aligned.u32 56;");
    if (warp == 8) {
      PSTAMPW(2, 0);
      const bool leader = elect_one();
      if (leader) {
        prefetch_map(&P.x); prefetch_map(&P.wqkv);
#pragma unroll
        for (int i = 0; i < 24; i++) mbar_init(BAR + i * 8, 1);
        asm volatile("fence.mbarrier_init.release.cluster;" ::: "memory");
      }
      __syncwarp();
      asm volatile("bar.arrive 3, 384;" ::: "memory");
      asm volatile("barrier.cluster.arrive.relaxed.aligned;" ::: "memory");
      auto ldx = [&](int p, int kb) {
        const uint32_t b = BAR + (B_FX + p * 8 + kb) * 8;
        mbar_expect_tx(b, 8192);
        tma3d(H0 + p * 65536 + kb * 8192, &P.x, kb * 64, p, g * 64, b);
      };
      auto ldkv = [&](int kb, int slot) {
        const uint32_t b = BAR + (B_FKV + kb) * 8, d = RING + slot * 16384;
        mbar_expect_tx(b, 16384);
        tma2d(d, &P.wqkv, 512 + 64 * j, kb * 64, b);
        tma2d(d + 8192, &P.wqkv, 1024 + 64 * j, kb * 64, b);
      };
      if (leader) {
#pragma unroll 1
        for (int i = 0; i < 8 + XO_DELAY; i++) {
          if (i < 8) ldx(0, i);
          if (i < 6) ldkv(i, i);
          if (i >= XO_DELAY) ldx(1, i - XO_DELAY);
        }
#pragma unroll
        for (int i = 0; i < 4; i++)
          asm volatile("cp.async.bulk.prefetch.tensor.2d.L2.global [%0, {%1, %2}];" ::"l"(&P.wqkv), "r"(512 + (i & 1) * 512 + 64 * j), "r"(384 + (i >> 1) * 64) : "memory");
        PSTAMPW(2, 2);
      }
      __syncwarp();
      asm volatile("bar.sync 4, 384;" ::: "memory");
      if (leader) {
        const int f0 = 224 * j + ((j & 1) ? 32 : 0);
        prefetch_map(&P.wo); prefetch_map(&P.w1); prefetch_map(&P.w3); prefetch_map(&P.w1h);
        prefetch_map(&P.w3h); prefetch_map(&P.w2); prefetch_map(&P.out);
#pragma unroll 1
        for (int i = 0; i < 2; i++) { mbar_wait(BAR + (B_EKV + i) * 8); ldkv(6 + i, i); }
#pragma unroll 1
        for (int i = 0; i < 4; i++) {
          const uint32_t b = BAR + (B_FQ + i) * 8;
          mbar_wait(BAR + (B_EKV + 2 + i) * 8);
          mbar_expect_tx(b, 16384);
          tma2d(RING + 32768 + i * 16384, &P.wqkv, 64 * j, i * 128, b);
          tma2d(RING + 40960 + i * 16384, &P.wqkv, 64 * j, i * 128 + 64, b);
        }
        mbar_expect_tx(BAR + B_FWO * 8, 65536);
#pragma unroll 1
        for (int i = 1; i < 9; i++) {
          mbar_wait(BAR + (B_EX + (i >> 1)) * 8);
          tma2d(H0 + (i & 7) * 8192, &P.wo, 64 * j, (i & 7) * 64, BAR + B_FWO * 8);
        }
        mbar_wait(BAR + B_OG * 8);
#pragma unroll 1
        for (int i = 2; i < 8; i++) {
          mbar_wait(BAR + (i < 4 ? B_EQ + i : B_EA + i - 4) * 8);
          load_a(P, i, j);
        }
        uint32_t d = RING;
#pragma unroll 1
        for (int i = 0; i < 8; i++) {
          const uint32_t b = BAR + (B_FB + i) * 8;
          const int k0 = kb_at(i, j) * 64;
          mbar_wait(BAR + (B_EA + 5 + i) * 8);
          mbar_expect_tx(b, 32768);
          tma2d(d, &P.w1, f0 + 64, k0, b);
          tma2d(d + 8192, &P.w3, f0 + 64, k0, b);
          tma2d(d + 16384, &P.w1, f0 + 128, k0, b);
          tma2d(d + 24576, &P.w3, f0 + 128, k0, b);
          d = d == RING + 65536 ? RING : d + 32768;
        }
#pragma unroll 1
        for (int i = 0; i < 8; i++) {
          const int m = (0x76453210u >> (4 * i)) & 7;
          const uint32_t b = BAR + (B_FT + m) * 8;
          mbar_wait(BAR + (i < 5 ? B_EB + 3 + i : i < 7 ? B_HC - 5 + i : B_ET0) * 8);
          mbar_expect_tx(b, 28672);
          tma2d(t_addr(m), &P.w2, 64 * ((j + 2 + 2 * w2_pass(m)) & 7), 224 * (j ^ w2_peer(m)), b);
          PSTAMPW(2, 4 + i);
        }
#pragma unroll 1
        for (int q = 0; q < 2; q++) {
          mbar_expect_tx(BAR + (B_FIN + q) * 8, 16384);
          mbar_wait(BAR + (B_ET0 + 3 - q) * 8);
          PSTAMPW(2, 24 + q);
          asm volatile("cp.async.bulk.shared::cluster.global.mbarrier::complete_tx::bytes [%0], [%1], 16384, [%2];"
                       ::"r"(t_addr(q + 1) + own()), "l"(X->e4 + ((g * 8 + j) * 3 + q) * 1024), "r"(BAR + (B_FIN + q) * 8 + own()) : "memory");
        }
        X->epoch[cta] = X->epoch[cta] + 1;
      }
    } else {
      const int part = warp - 9;
      uint32_t tag;
      if (part == 2) {
        tag = ld_epoch(X->epoch + cta);
        init_bars(-1);
        tag = (tag + 1) & 1;
        if (lane == 0) {
          asm volatile("st.shared.u32 [%0], %1;" ::"r"(TAGS + own()), "r"(tag) : "memory");
          mbar_arrive(BAR + B_TAG * 8);
        }
      } else {
        init_bars(warp - 1);
        mbar_wait(BAR + B_TAG * 8);
        tag = lds32(TAGS);
      }
      PSTAMPW(3, 16 + part);
      auto clear8 = [&](uint4* p, int stride) {
#pragma unroll
        for (int i = 0; i < 8; i++) ll_st(p + i * stride + lane, 0, 0, 0, 0, tag ^ 1);
      };
      if (part == 0 && lane < 20)
        ll_st(lane < 16 ? X->e0s + g * 128 + 16 * j + lane : X->e0w + j * 64 + g * 4 + lane - 16, 0, 0, 0, 0, tag ^ 1);
      if (lane < 16) ll_st(X->e0c + ((j * 3 + part) * 16 + g) * 16 + lane, 0, 0, 0, 0, tag ^ 1);
      if (CLR_MODE && part == 1) clear8(X->e1 + (g * 8 + j) * 256, 32);
      __syncwarp();
      if (lane == 0) mbar_arrive(BAR + B_CLR1 * 8);
      uint32_t v[8][4];
      {
        float s[4] = {0.f, 0.f, 0.f, 0.f}, q[4] = {0.f, 0.f, 0.f, 0.f};
        const uint32_t xa = H0 + ((lane >> 1) & 1) * 65536 + (8 * j + (lane >> 2)) * 128 + (lane & 1) * 64 + ((lane >> 1) & 3) * 16;
#pragma unroll 1
        for (int kb = (part + 2) % 3; kb < 8; kb += 3) {
          mbar_wait(BAR + (B_FX + kb) * 8);
          mbar_wait(BAR + (B_FX + 8 + kb) * 8);
          if (kb == 3 && lane == 0) l2_prefetch(wop + (size_t)(j * 64 + g * 4) * D_, 4096);
#pragma unroll
          for (int i = 0; i < 4; i++) lds128(v[i], (xa + kb * 8192) ^ (i * 16));
#pragma unroll
          for (int e = 0; e < 16; e++) {
            const float a = bf_lo(v[e >> 2][e & 3]), b = bf_hi(v[e >> 2][e & 3]);
            s[e & 3] += a + b; q[e & 3] = fmaf(a, a, q[e & 3]); q[e & 3] = fmaf(b, b, q[e & 3]);
          }
        }
        float ss = (s[0] + s[1]) + (s[2] + s[3]), qq = (q[0] + q[1]) + (q[2] + q[3]);
        ss += __shfl_xor_sync(0xffffffffu, ss, 1); qq += __shfl_xor_sync(0xffffffffu, qq, 1);
        if (part && !(lane & 1))
          asm volatile("st.shared.v2.f32 [%0], {%1,%2};" ::"r"(WB + own() + part * 128 - 128 + lane * 4), "f"(ss), "f"(qq) : "memory");
        if (part) asm volatile("bar.arrive 5, 96;" ::: "memory");
        else {
          asm volatile("bar.sync 5, 96;" ::: "memory");
          const float2 t1 = lds64(WB + (lane >> 1) * 8), t2 = lds64(WB + 128 + (lane >> 1) * 8);
          const float mean = (ss + t1.x + t2.x) * (1.f / D_);
          const float rs = rsqrtf(fmaxf(fmaf(-mean, mean, (qq + t1.y + t2.y) * (1.f / D_)), 0.f) + 1e-5f);
          if (!(lane & 1)) ll_st(X->e0s + g * 128 + 16 * j + (lane >> 1), __float_as_uint(mean), __float_as_uint(rs), 0, 0, tag);
        }
      }
      PSTAMPW(3, part * 4 + 2);
      if (PF_MODE == 0 && lane == 0) l2_prefetch(part == 0 ? P.w2p + (size_t)cta * 14 * D_ : (part == 1 ? P.w1p : P.w3p) + (size_t)cta * 4 * F_, 14336);
      if (part == 0) {
        const __nv_bfloat16* wr = wop + (size_t)(j * 64 + g * 4 + (lane >> 3)) * D_ + (lane & 7) * 8;
#pragma unroll
        for (int i = 0; i < 8; i++) ldg128_nc(v[i], wr + i * 64);
        float s[4];
#pragma unroll
        for (int e = 0; e < 4; e++) {
          s[e] = 0.f;
#pragma unroll
          for (int i = 0; i < 8; i++) s[e] += bf_lo(v[i][e]) + bf_hi(v[i][e]);
        }
        float ss = (s[0] + s[1]) + (s[2] + s[3]);
#pragma unroll
        for (int o = 1; o <= 4; o <<= 1) ss += __shfl_xor_sync(0xffffffffu, ss, o);
        if ((lane & 7) == 0) ll_st(X->e0w + j * 64 + g * 4 + (lane >> 3), __float_as_uint(ss * (1.f / D_)), 0, 0, 0, tag);
      }
      PSTAMPW(3, part * 4 + 0);
      {
        ll_get<8>(v, X->e0c + ((j * 3 + part) * 16 + (lane >> 4) * 8) * 16 + (lane & 15), 16, tag);
        if (part == 0) {
          uint32_t u[2][4];
          ll_get<2>(u, X->e0w + j * 64 + lane, 32, tag);
#pragma unroll
          for (int i = 0; i < 2; i++) asm volatile("st.shared.u32 [%0], %1;" ::"r"(WB + own() + (i * 32 + lane) * 4), "r"(u[i][0]) : "memory");
        }
        uint32_t o[4];
#pragma unroll
        for (int e = 0; e < 4; e++) {
          float s = 0.f;
#pragma unroll
          for (int i = 0; i < 8; i++) s += __uint_as_float(v[i][e]);
          o[e] = __float_as_uint(s + __shfl_xor_sync(0xffffffffu, s, 16));
        }
        if (lane < 16) sts128(CS + (part * 64 + lane * 4) * 4, o);
      }
      __syncwarp();
      if (lane == 0) mbar_arrive(BAR + (part == 0 ? B_WBAR : B_READY) * 8);
      PSTAMPW(3, part * 4 + 1);
      if (part == 1 && elect_one()) {
#pragma unroll 1
        for (int i = 0; i < 2; i++) { mbar_wait(BAR + (B_EKV + 7 + i) * 8); load_a(P, i, j); }
      }
      if (CLR_MODE > 1 && part == 2) {
#pragma unroll
        for (int i = 0; i < 2; i++) ll_st(X->e2s + ((g * 8 + i * 4 + (lane >> 3)) * 8 + j) * 8 + (lane & 7), 0, 0, 0, 0, tag ^ 1);
#pragma unroll 1
        for (int u = 0; u < 4; u++) {
          clear8(X->e2 + (g * 256 + 4 * j + u) * 32, 1024);
          __nanosleep(CLR_SLEEP2);
        }
        __syncwarp();
      }
      if (part == 2 && lane == 0) mbar_arrive(BAR + B_WBAR * 8);
      if (CLR_MODE && part == 2) {
        mbar_wait(BAR + (CLR_WHEN) * 8);
#pragma unroll
        for (int i = 0; i < 2; i++) ll_st(X->e3s + ((g * 8 + i * 4 + (lane >> 3)) * 8 + j) * 8 + (lane & 7), 0, 0, 0, 0, tag ^ 1);
#pragma unroll 1
        for (int u = 0; u < 4; u++) {
          clear8(X->e3h + (g * 256 + 4 * j + u) * 32, 1024);
          __nanosleep(CLR_SLEEP2);
        }
      }
      __syncwarp();
      if (part == 2 && lane == 0) mbar_arrive(BAR + B_CLR2 * 8);
      PSTAMPW(3, 20 + part);
      if (PF_MODE == 2) mbar_wait(BAR + (B_FQ + 7) * 8);
      if (PF_MODE >= 1 && lane == 0) l2_prefetch(part == 0 ? P.w2p + (size_t)cta * 14 * D_ : (part == 1 ? P.w1p : P.w3p) + (size_t)cta * 4 * F_, 14336);
      mbar_wait(BAR + (E4_WHEN) * 8);
#pragma unroll 1
      for (int u = 0; u < 4 * E4_ON; u++) {
        clear8(X->e4 + ((g * 8 + ((j + 2 + 2 * part) & 7)) * 3 + part) * 1024 + u * 32, 128);
        __nanosleep(CLR_SLEEP);
      }
      __syncwarp();
      if (lane == 0) mbar_arrive(BAR + B_CLR * 8);
      PSTAMPW(3, part * 4 + 3);
    }
  } else {
    const int p = warp >> 2, w = warp & 3;
    const int r = lane >> 2, c = lane & 3;
    init_bars(warp);
    asm volatile("setmaxnreg.inc.sync.aligned.u32 224;");
    PSTAMP(0);
    const uint32_t dAx = descA(H0) + p * 4096;
    const uint32_t Hn = H1 - p * 65536;
    const uint32_t moff = ((lane & 7) + ((lane >> 3) & 1) * 8) * 128 + (((lane >> 4) ^ (lane & 7)) << 4);
    const uint32_t Xw = H0 + p * 65536 + w * 2048;
    const int xw = (g * 2 + p) * 4 + w;
    uint32_t cv[8][4];
    if (p == 1) {
      if (SIDE_KB >= 0 || (QLATE && w == 0)) mbar_wait(BAR + (B_FKV + (SIDE_KB >= 0 ? SIDE_KB : 0)) * 8);
      else __nanosleep(SIDE_SLEEP);
      const int wp = w < 3 ? w : 1;
      const __nv_bfloat16* wr = wqkvp + (size_t)(g * 32 + (lane >> 3) * 8) * (3 * D_) + wp * D_ + j * 64 + (lane & 7) * 8;
#pragma unroll
      for (int i = 0; i < 8; i++) ldg128_nc(cv[i], wr + (size_t)i * 3 * D_);
      mbar_wait(BAR + B_LAG * 8);
    }

    float akv[64];
    auto kvstep = [&](int kb) {
      mbar_wait(BAR + (B_FX + p * 8 + kb) * 8);
      mbar_wait(BAR + (B_FKV + kb) * 8);
      if (kb == 0) PSTAMP(2);
      const uint32_t da = dAx + kb * 512, db = descB(RING) + (kb < 6 ? kb : kb - 6) * 1024;
      wg_fence();
      wgmma_ss_n128(akv, da, db, kb);
#pragma unroll
      for (int k = 1; k < 4; k++) wgmma_ss_n128(akv, da + k * 2, db + k * 128, 1);
      wg_commit();
      mbar_arrive_if(BAR + B_LAG * 8, kb == LAG_KB - 1 && p == 0 && lane == 0);
      wg_wait<1>();
      mbar_arrive_if(BAR + (B_EKV + kb - 1) * 8, kb > 0 && lane == 0);
    };
#pragma unroll
    for (int kb = 0; kb < CS_KB; kb++) kvstep(kb);
    if (p == 1) {
      PSTAMP(29);
      mbar_wait(BAR + B_CLR1 * 8);
      const uint32_t tg = lds32(TAGS);
      const uint32_t hm = 0xffff0000u | (tg >> 1), sh = 16 + (tg >> 1);
      float cs[8];
#pragma unroll
      for (int e = 0; e < 4; e++) {
        float a = 0.f, b = 0.f;
#pragma unroll
        for (int i = 0; i < 8; i++) { a += __uint_as_float(cv[i][e] << sh); b += __uint_as_float(cv[i][e] & hm); }
        cs[2 * e] = a; cs[2 * e + 1] = b;
      }
      const bool up = lane & 8;
#pragma unroll
      for (int e = 0; e < 4; e++) {
        const float keepv = up ? cs[4 + e] : cs[e], give = up ? cs[e] : cs[4 + e];
        cs[e] = keepv + __shfl_xor_sync(0xffffffffu, give, 8);
        cs[e] += __shfl_xor_sync(0xffffffffu, cs[e], 16);
      }
      if (lane < 16 && w < 3)
        ll_st(X->e0c + ((j * 3 + w) * 16 + g) * 16 + (lane & 7) * 2 + (lane >> 3), __float_as_uint(cs[0]), __float_as_uint(cs[1]),
              __float_as_uint(cs[2]), __float_as_uint(cs[3]), tg);
      PSTAMP(1);
    }
#pragma unroll 1
    for (int kb = CS_KB; kb < 8; kb++) kvstep(kb);
    asm volatile("barrier.cluster.wait.aligned;" ::: "memory");
    uint32_t xres[4][4];
#pragma unroll
    for (int u = 0; u < 4; u++) ldsm4(xres[u], Xw + j * 8192 + (moff ^ (u << 5)));

    float aq[32];
    auto qstep = [&](int i) {
      mbar_wait(BAR + (B_FQ + i) * 8);
      wg_fence();
#pragma unroll
      for (int k = 0; k < 8; k++)
        wgmma_ss_n64(aq, dAx + i * 1024 + (k >> 2) * 512 + (k & 3) * 2, descB(RING + 32768) + i * 1024 + k * 128, i | k);
      wg_commit();
      wg_wait<1>();
      mbar_arrive_if(BAR + (B_EQ + i - 1) * 8, lane == 0);
      if (i) mbar_arrive_if(BAR + (B_EX + i - 1) * 8, lane == 0 && p == 0);
    };
    mbar_wait(BAR + B_CLR1 * 8);
    const uint32_t tag = lds32(TAGS);
    uint32_t sv[2][4];
    const uint4* stsrc = X->e0s + g * 128 + 2 * (16 * w + r) + p;
    qstep(0);
    ll_issue<2>(sv, stsrc, 16);
    keep(akv);
    PSTAMP(3);
    qstep(1);
    mbar_wait(BAR + B_READY * 8);
    if (__builtin_expect(ll_bad<2>(sv, pin(tag, zero)), 0)) ll_spin<2>(sv, stsrc, 16, tag);
    PSTAMP(19);
    uint4* const xb = reinterpret_cast<uint4*>(X) + lane + (tag >> 1);
    constexpr int O_E4 = offsetof(Scratch, e4) / 16, O_E2 = offsetof(Scratch, e2) / 16, O_E3H = offsetof(Scratch, e3h) / 16;
    const float2 st0 = make_float2(__uint_as_float(sv[0][0] & ~1u), __uint_as_float(sv[0][1]));
    const float2 st1 = make_float2(__uint_as_float(sv[1][0] & ~1u), __uint_as_float(sv[1][1]));
    uint32_t hi[4][4], lo[4][4];
    {
      float2 cs[16];
      auto cvt = [&](uint32_t (&d)[4][4], int b0, int ofs, const float2& st) {
#pragma unroll
        for (int b = b0; b < b0 + 8; b++) {
          if (ofs == 2) cs[b] = lds64(CS + (64 + b * 8 + 2 * c) * 4);
          const uint32_t v = pack2(fmaf(-st.x, cs[b].x, akv[4 * b + ofs]) * st.y, fmaf(-st.x, cs[b].y, akv[4 * b + ofs + 1]) * st.y);
          d[b >> 2][b & 3] = b < 8 ? v : movm(v);
        }
      };
      cvt(hi, 0, 2, st1);
      cvt(hi, 8, 2, st1);
      if (w == 3 && g < 15) {
        uint4* dst = X->e1 + ((g * 8 + j) * 2 + p) * 128 + lane;
#pragma unroll
        for (int i = 0; i < 4; i++) ll_st(dst + i * 32, hi[i][0], hi[i][1], hi[i][2], hi[i][3], tag);
      }
      PSTAMP(20);
      wg_bar(p);
#pragma unroll
      for (int i = 0; i < 4; i++) sts128(Xw + lane * 16 + i * 512, hi[i]);
      qstep(2);
      cvt(lo, 0, 0, st0);
      cvt(lo, 8, 0, st0);
      keep(lo);
    }
    PSTAMP(21);
    wg_bar(p);
    uint32_t prev[4][4];
    if (w > 0) {
#pragma unroll
      for (int i = 0; i < 4; i++) lds128(prev[i], Xw - 2048 + lane * 16 + i * 512);
    }
    if (p == 0) {
      asm volatile("fence.proxy.async.shared::cta;" ::: "memory");
      __syncwarp();
      if (lane == 0) mbar_arrive(BAR + (B_EX + 4) * 8);
    }
    PSTAMP(22);
    const uint4* halo = X->e1 + (((g - 1) * 8 + j) * 2 + p) * 128 + lane;
    const bool use_halo = w == 0 && g > 0;
    if (use_halo) ll_issue<4>(prev, halo, 32);
    qstep(3);
    float ah[32];
    unpack32(ah, xres);
    const uint4* osrc[7];
#pragma unroll
    for (int i = 0; i < 7; i++) osrc[i] = xb + O_E2 + (xw * 32 + 4 * kb_at(i + 1, j)) * 32;
    pin7(osrc, zero);
    pin32(ah, zero);
    PSTAMP(23);
    if (w == 0) {
      if (g > 0) {
        if (__builtin_expect(ll_bad<4>(prev, pin(tag, zero)), 0)) ll_spin<4>(prev, halo, 32, tag);
        ll_clear<4>(prev);
      } else {
#pragma unroll
        for (int i = 0; i < 4; i++)
#pragma unroll
          for (int e = 0; e < 4; e++) prev[i][e] = 0;
      }
    }
    wg_wait<0>();
    keep(aq);
    mbar_arrive_if(BAR + (B_EQ + 3) * 8, lane == 0);
    mbar_arrive_if(BAR + (B_EX + 3) * 8, lane == 0 && p == 0);
    PSTAMP(4);

    uint32_t of[4][4];
    mbar_wait(BAR + B_WBAR * 8);
    {
      const float sc = 0.25f * 1.4426950408889634f;
      const float nohalo = (g == 0 && w == 0) ? -INFINITY : 0.f;
      const bool up0 = 2 * c > r, up1 = 2 * c + 1 > r;
      const uint32_t mup = (up0 ? 0xffffu : 0u) | (up1 ? 0xffff0000u : 0u);
      uint4* dst = xb + O_E2 + (xw * 32 + 4 * j) * 32;
      float d0 = 0.f, d1 = 0.f;
      const float sca = sc * st0.y, scb = sc * st1.y;
#pragma unroll
      for (int h = 0; h < 4; h++) {
        uint32_t qf[4];
        const uint32_t co = (16 * h + 2 * c) * 4;
        {
          const float2 ca = lds64(CS + co), cb = lds64(CS + co + 32);
          qf[0] = pack2(fmaf(-st0.x, ca.x, aq[8 * h + 0]), fmaf(-st0.x, ca.y, aq[8 * h + 1]));
          qf[1] = pack2(fmaf(-st1.x, ca.x, aq[8 * h + 2]), fmaf(-st1.x, ca.y, aq[8 * h + 3]));
          qf[2] = pack2(fmaf(-st0.x, cb.x, aq[8 * h + 4]), fmaf(-st0.x, cb.y, aq[8 * h + 5]));
          qf[3] = pack2(fmaf(-st1.x, cb.x, aq[8 * h + 6]), fmaf(-st1.x, cb.y, aq[8 * h + 7]));
        }
        const int i0 = h >> 1, e0 = (2 * h) & 3;
        float sp[4], sl[4], sh[4];
        mma16816(sp, qf, prev[i0][e0], prev[i0][e0 + 1]);
        mma16816(sl, qf, lo[i0][e0], lo[i0][e0 + 1]);
        mma16816(sh, qf, hi[i0][e0], hi[i0][e0 + 1]);
        float a0 = up0 ? sp[0] + nohalo : sl[0], a1 = up1 ? sp[1] + nohalo : sl[1];
        float b0 = up0 ? sl[2] : sh[2], b1 = up1 ? sl[3] : sh[3];
        float ma = fmaxf(a0, a1), mb = fmaxf(b0, b1);
        ma = fmaxf(ma, __shfl_xor_sync(0xffffffffu, ma, 1)); mb = fmaxf(mb, __shfl_xor_sync(0xffffffffu, mb, 1));
        ma = fmaxf(ma, __shfl_xor_sync(0xffffffffu, ma, 2)); mb = fmaxf(mb, __shfl_xor_sync(0xffffffffu, mb, 2));
        a0 = ex2((a0 - ma) * sca); a1 = ex2((a1 - ma) * sca); b0 = ex2((b0 - mb) * scb); b1 = ex2((b1 - mb) * scb);
        float sa = a0 + a1, sbb = b0 + b1;
        sa += __shfl_xor_sync(0xffffffffu, sa, 1); sbb += __shfl_xor_sync(0xffffffffu, sbb, 1);
        sa += __shfl_xor_sync(0xffffffffu, sa, 2); sbb += __shfl_xor_sync(0xffffffffu, sbb, 2);
        const float ia = rcp(sa), ib = rcp(sbb);
        const uint32_t pa = pack2(a0 * ia, a1 * ia), pb = pack2(b0 * ib, b1 * ib);
        const uint32_t pf[4] = {pa & mup, 0u, pa & ~mup, pb & mup};
        const uint32_t ph = pb & ~mup;
        float o0[4], o1[4];
        mma16816(o0, pf, prev[2 + i0][e0], lo[2 + i0][e0]);
        mma16816(o1, pf, prev[2 + i0][e0 + 1], lo[2 + i0][e0 + 1]);
        mma1688_acc(o0, 0u, ph, hi[2 + i0][e0]);
        mma1688_acc(o1, 0u, ph, hi[2 + i0][e0 + 1]);
        of[h][0] = pack2(o0[0], o0[1]); of[h][1] = pack2(o0[2], o0[3]);
        of[h][2] = pack2(o1[0], o1[1]); of[h][3] = pack2(o1[2], o1[3]);
        ll_st(dst + h * 32, of[h][0], of[h][1], of[h][2], of[h][3], tag);
        const float2 wa = lds64(WB + co), wb = lds64(WB + co + 32);
        d0 = fmaf(o0[0], wa.x, d0); d0 = fmaf(o0[1], wa.y, d0); d0 = fmaf(o1[0], wb.x, d0); d0 = fmaf(o1[1], wb.y, d0);
        d1 = fmaf(o0[2], wa.x, d1); d1 = fmaf(o0[3], wa.y, d1); d1 = fmaf(o1[2], wb.x, d1); d1 = fmaf(o1[3], wb.y, d1);
      }
#pragma unroll
      for (int o = 1; o <= 2; o <<= 1) { d0 += __shfl_xor_sync(0xffffffffu, d0, o); d1 += __shfl_xor_sync(0xffffffffu, d1, o); }
      if (c == 0) ll_st(X->e2s + (xw * 8 + j) * 8 + r, __float_as_uint(d0), __float_as_uint(d1), 0, 0, tag);
    }
    PSTAMP(5);

    {
      uint32_t og[2][14][4];
      const uint4* ssrc = X->e2s + (xw * 8 + 2 * c) * 8 + r;
      auto oissue = [&](int hp) {
#pragma unroll
        for (int i = 0; i < 14; i++) ll_ld(og[hp][i], osrc[i >> 1] + (2 * hp + (i & 1)) * 32);
        if (hp == 1) ll_issue<2>(sv, ssrc, 8);
      };
      auto omma = [&](int hp) {
        ll_clear<14>(og[hp]);
        keep(og[hp]);
        wg_fence();
#pragma unroll
        for (int i = 0; i < 14; i++) wgmma_rs_n64(ah, og[hp][i], descB(H0) + kb_at((i >> 1) + 1, j) * 512 + (2 * hp + (i & 1)) * 128, 1);
        wg_commit();
      };
      mbar_wait(BAR + B_FWO * 8);
      keep(ah); keep(of);
      wg_fence();
#pragma unroll
      for (int k = 0; k < 4; k++) wgmma_rs_n64(ah, of[k], descB(H0) + j * 512 + k * 128, 1);
      wg_commit();
      uint32_t it = 0;
#pragma unroll 1
      do { oissue(0); } while (ll_bad<14>(og[0], tag) && ++it < SPIN_LIMIT);
      PSTAMP(6);
      oissue(1);
      omma(0);
      const uint32_t tg = pin(tag, zero);
      if (__builtin_expect(ll_bad2<14, 2>(og[1], sv, tg), 0)) {
#pragma unroll 1
        do { oissue(1); } while (ll_bad2<14, 2>(og[1], sv, tag) && ++it < SPIN_LIMIT);
      }
      PSTAMP(16);
      mbar_arrive_if(BAR + B_OG * 8, lane == 0 && p == 0);
      omma(1);
      ll_clear<2>(sv);
    }
    float m0 = __uint_as_float(sv[0][0]) + __uint_as_float(sv[1][0]), m1 = __uint_as_float(sv[0][1]) + __uint_as_float(sv[1][1]);
#pragma unroll
    for (int o = 1; o <= 2; o <<= 1) { m0 += __shfl_xor_sync(0xffffffffu, m0, o); m1 += __shfl_xor_sync(0xffffffffu, m1, o); }
    const uint32_t mu0 = pack2(m0 + st0.x, m0 + st0.x), mu1 = pack2(m1 + st1.x, m1 + st1.x);
    wg_wait<0>();
    keep(ah);
    if (lane == 0) mbar_arrive(BAR + B_WODONE * 8);
    PSTAMP(7);

    uint32_t hf[4][4], ra[4][4];
    pack32(hf, ah);
    mbar_wait(BAR + B_CLR2 * 8);
    {
      uint4* dst = xb + O_E3H + (xw * 32 + 4 * j) * 32;
#pragma unroll
      for (int u = 0; u < 4; u++) {
        ra[u][0] = hsub2(hf[u][0], mu0); ra[u][1] = hsub2(hf[u][1], mu1);
        ra[u][2] = hsub2(hf[u][2], mu0); ra[u][3] = hsub2(hf[u][3], mu1);
        ll_st(dst + u * 32, ra[u][0], ra[u][1], ra[u][2], ra[u][3], tag);
      }
      mbar_wait(BAR + (p == 0 ? B_EQ + 3 : B_WODONE) * 8);
    }
    PSTAMP(8);

    float rs0, rs1;
    auto swiglu = [&](float g0, float g1, float u0, float u1, float rs) -> uint32_t {
      const float hr = 0.5f * rs;
      const float x0 = g0 * hr, x1 = g1 * hr;
      const float t0 = tanhf_hw(x0), t1 = tanhf_hw(x1);
      return pack2(fmaf(x0, t0, x0) * (u0 * rs), fmaf(x1, t1, x1) * (u1 * rs));
    };
    uint32_t hA[6][4];
    {
      float a1[64], a2[32];
      const uint4* src = xb + O_E3H + xw * 32 * 32;
      uint32_t rb[4][4], rc[4][4], rd[4][4];
      auto fetch = [&](uint32_t (&a)[4][4], int i) { ll_issue<4>(a, src + kb_at(i, j) * 128, 32); };
      auto check = [&](uint32_t (&a)[4][4], uint32_t (&b)[4][4], int i) {
        const uint32_t tg = pin(tag, zero);
        if (__builtin_expect(ll_bad2<4, 4>(a, b, tg), 0)) {
          uint32_t it = 0;
#pragma unroll 1
          do { fetch(a, i); fetch(b, i + 1); } while (ll_bad2<4, 4>(a, b, tag) && ++it < SPIN_LIMIT);
        }
        ll_clear<4>(a); ll_clear<4>(b);
        keep(a); keep(b);
      };
      auto head = [&](uint32_t (&a)[4][4], int i) {
        mbar_wait(BAR + (B_FA + i) * 8);
        wg_fence();
        wgmma_rs_n64<DESC_HI64>(a2, a[0], descBh(RING + 16384) + (i & 3) * 1536, i);
        wgmma_rs_n128(a1, a[0], descB(RING) + (i & 3) * 1536, i);
        wg_commit();
#pragma unroll
        for (int u = 0; u < 4; u++) stsm4(Hn + w * 2048 + i * 8192 + (moff ^ (u << 5)), a[u]);
        wg_wait<1>();
        if (i > 0) mbar_arrive_if(BAR + (B_EA + i - 1) * 8, lane == 0);
      };
      auto rest = [&](uint32_t (&a)[4][4], int i) {
        wg_fence();
#pragma unroll
        for (int k = 1; k < 4; k++) {
          wgmma_rs_n64<DESC_HI64>(a2, a[k], descBh(RING + 16384) + (i & 3) * 1536 + k * 64, 1);
          wgmma_rs_n128(a1, a[k], descB(RING) + (i & 3) * 1536 + k * 128, 1);
        }
        wg_commit();
      };
      ll_clear<4>(ra);
      keep(ra);
      head(ra, 0); rest(ra, 0);
      {
      float s0 = 0.f, q0 = 0.f, s1 = 0.f, q1 = 0.f;
#pragma unroll
      for (int b = 0; b < 8; b++) {
        s0 += ah[4 * b] + ah[4 * b + 1]; s1 += ah[4 * b + 2] + ah[4 * b + 3];
        q0 = fmaf(ah[4 * b], ah[4 * b], q0); q0 = fmaf(ah[4 * b + 1], ah[4 * b + 1], q0);
        q1 = fmaf(ah[4 * b + 2], ah[4 * b + 2], q1); q1 = fmaf(ah[4 * b + 3], ah[4 * b + 3], q1);
      }
#pragma unroll
      for (int o = 1; o <= 2; o <<= 1) {
        s0 += __shfl_xor_sync(0xffffffffu, s0, o); q0 += __shfl_xor_sync(0xffffffffu, q0, o);
        s1 += __shfl_xor_sync(0xffffffffu, s1, o); q1 += __shfl_xor_sync(0xffffffffu, q1, o);
      }
      if (c == 0) ll_st(X->e3s + (xw * 8 + j) * 8 + r, __float_as_uint(s0), __float_as_uint(q0), __float_as_uint(s1), __float_as_uint(q1), tag);
      }
      ll_get<4>(rb, src + kb_at(1, j) * 128, 32, tag);
      keep(rb);
      PSTAMP(17);
      fetch(rc, 2); fetch(rd, 3);
      head(rb, 1); rest(rb, 1);
      check(rc, rd, 2);
      head(rc, 2); fetch(ra, 4); fetch(rb, 5); rest(rc, 2);
      head(rd, 3); rest(rd, 3);
      check(ra, rb, 4);
      head(ra, 4); fetch(rc, 6); fetch(rd, 7); ll_issue<2>(sv, X->e3s + (xw * 8 + 2 * c) * 8 + r, 8); rest(ra, 4);
      head(rb, 5); rest(rb, 5);
      check(rc, rd, 6);
      head(rc, 6); rest(rc, 6);
      head(rd, 7); rest(rd, 7);
      fence_async_smem();
      ll_wait<2>(sv, X->e3s + (xw * 8 + 2 * c) * 8 + r, 8, tag);
      float s0 = __uint_as_float(sv[0][0]) + __uint_as_float(sv[1][0]), q0 = __uint_as_float(sv[0][1]) + __uint_as_float(sv[1][1]);
      float s1 = __uint_as_float(sv[0][2]) + __uint_as_float(sv[1][2]), q1 = __uint_as_float(sv[0][3]) + __uint_as_float(sv[1][3]);
#pragma unroll
      for (int o = 1; o <= 2; o <<= 1) {
        s0 += __shfl_xor_sync(0xffffffffu, s0, o); q0 += __shfl_xor_sync(0xffffffffu, q0, o);
        s1 += __shfl_xor_sync(0xffffffffu, s1, o); q1 += __shfl_xor_sync(0xffffffffu, q1, o);
      }
      s0 *= 1.f / D_; s1 *= 1.f / D_;
      rs0 = rsqrtf(fmaxf(fmaf(-s0, s0, q0 * (1.f / D_)), 0.f) + 1e-5f);
      rs1 = rsqrtf(fmaxf(fmaf(-s1, s1, q1 * (1.f / D_)), 0.f) + 1e-5f);
      wg_wait<0>();
      keep(a1); keep(a2);
      if (lane == 0) mbar_arrive(BAR + (B_EA + 7) * 8);
      PSTAMP(9);
#pragma unroll
      for (int u = 0; u < 4; u++)
#pragma unroll
        for (int e = 0; e < 4; e++)
          hA[u][e] = swiglu(a1[8 * u + 2 * e], a1[8 * u + 2 * e + 1], a1[32 + 8 * u + 2 * e], a1[33 + 8 * u + 2 * e], (e & 1) ? rs1 : rs0);
#pragma unroll
      for (int u = 0; u < 2; u++)
#pragma unroll
        for (int e = 0; e < 4; e++)
          hA[4 + u][e] = swiglu(a2[8 * u + 2 * e], a2[8 * u + 2 * e + 1], a2[16 + 8 * u + 2 * e], a2[17 + 8 * u + 2 * e], (e & 1) ? rs1 : rs0);
      keep(hA);
      wg_bar(p);
    }
    PSTAMP(10);

    const uint32_t mbx = Hn + 32768 + w * 512 + lane * 16;
    auto send = [&](const uint32_t (&v)[4], uint32_t a, int part) {
      asm volatile("st.async.weak.shared::cluster.mbarrier::complete_tx::bytes.v4.b32 [%0], {%1,%2,%3,%4}, [%5];"
                   ::"r"(a + peer()), "r"(v[0]), "r"(v[1]), "r"(v[2]), "r"(v[3]), "r"(BAR + (B_HX + 2 * part + p) * 8 + peer()) : "memory");
    };
    uint32_t hB[8][4];
    {
      float ab[128];
      uint32_t db = descB(RING);
      const uint32_t dAn = descA(H1) - p * 4096;
      if (lane == 0 && w == 0) { mbar_expect_tx(BAR + (B_HX + p) * 8, 12288); mbar_expect_tx(BAR + (B_HX + 2 + p) * 8, 16384); }
#pragma unroll 1
      for (int i = 0; i < 8; i++) {
        mbar_wait(BAR + (B_FB + i) * 8);
        const uint32_t da = dAn + i * 512;
        wg_fence();
        wgmma_ss_n256(ab, da, db, i);
#pragma unroll
        for (int k = 1; k < 4; k++) wgmma_ss_n256(ab, da + k * 2, db + k * 128, 1);
        wg_commit();
        if (i == 7) {
          mbar_wait_cluster(BAR + (B_PF + p) * 8);
#pragma unroll
          for (int k = 0; k < 6; k++) send(hA[k], mbx + k * 2048, 0);
        }
        wg_wait<1>();
        mbar_arrive_if(BAR + (B_EB + i - 1) * 8, i > 0 && lane == 0);
        if (i == 6 && lane == 0) mbar_arrive_peer(BAR + (B_PF + p) * 8);
        db = db == descB(RING + 65536) ? descB(RING) : db + 2048;
      }
      wg_wait<0>();
      keep(ab);
      mbar_arrive_if(BAR + (B_EB + 7) * 8, lane == 0);
      if (lane == 0) mbar_arrive_peer(BAR + (B_PF + 2 + p) * 8);
      PSTAMP(11);
#pragma unroll
      for (int u = 0; u < 8; u++) {
        const int o = (u >> 2) * 64 + (u & 3) * 8;
#pragma unroll
        for (int e = 0; e < 4; e++)
          hB[u][e] = swiglu(ab[o + 2 * e], ab[o + 2 * e + 1], ab[o + 32 + 2 * e], ab[o + 33 + 2 * e], (e & 1) ? rs1 : rs0);
        if (u == 3) mbar_wait_cluster(BAR + (B_PF + 2 + p) * 8);
        if (u >= 4 && u < 4 + SEND_EARLY) send(hB[u - 4], mbx + (2 + u) * 2048, 1);
      }
      keep(hB);
    }
    PSTAMP(12);

    {
      float ya[32], y[32];
      uint32_t hP[14][4];
      const uint32_t offA = (j & 1) ? 256 : 0, offH = (j & 1) ? 0 : 1536;
      uint4* e4 = xb + O_E4 + g * 24576 + warp * 128;
      const uint32_t stg = H0 + p * 65536 + 28672 + (w >> 1) * 32768 + (w & 1) * 2048;
      auto mm = [&](float (&d)[32], int m, int k0, int k1) {
        if (k0 == 0) mbar_wait(BAR + (B_FT + m) * 8);
        const uint32_t T = descB(0) + (t_addr(m) >> 4);
        const uint32_t oA = w2_peer(m) ? 256 - offA : offA, oH = w2_peer(m) ? 1536 - offH : offH;
        wg_fence();
#pragma unroll
        for (int k = k0; k < k1; k++) {
          const uint32_t db = T + (k < 4 ? oA + k * 128 : k < 6 ? oH + (k - 4) * 128 : oA + 512 + (k - 6) * 128);
          if (w2_peer(m)) wgmma_rs_n64(d, hP[k], db, 1);
          else if (k < 6) wgmma_rs_n64(d, hA[k], db, k);
          else wgmma_rs_n64(d, hB[k - 6], db, 1);
        }
        wg_commit();
      };
      auto next = [&](float (&d)[32], int m, float (&dp)[32], int q) {
        mm(d, m, 0, 3);
        wg_wait<1>();
        keep(dp);
        mbar_arrive_if(BAR + (B_ET0 + q) * 8, lane == 0);
        uint4* dst = e4 + (((j + 2 + 2 * q) & 7) * 3 + q) * 1024;
#pragma unroll
        for (int u = 0; u < 4; u++)
          ll_st(dst + u * 32, pack2(dp[8 * u], dp[8 * u + 1]), pack2(dp[8 * u + 2], dp[8 * u + 3]),
                pack2(dp[8 * u + 4], dp[8 * u + 5]), pack2(dp[8 * u + 6], dp[8 * u + 7]), tag);
        if (q == 2) mbar_wait(BAR + (B_ET0 + 2) * 8);
        mm(d, m, 3, 14);
      };
#pragma unroll
      for (int i = 0; i < 4; i++) {
        const uint32_t a = i ? pin(mbx, zero) : mbx;
#pragma unroll
        for (int k = SEND_EARLY + (8 - SEND_EARLY) * i / 4; k < SEND_EARLY + (8 - SEND_EARLY) * (i + 1) / 4; k++) send(hB[k], a + (6 + k) * 2048, 1);
        if (i < 3) mm(ya, 0, 5 * i, i < 2 ? 5 * i + 5 : 14);
        else mm(y, 1, 0, 6);
      }
      mbar_wait_cluster(BAR + (B_HX + p) * 8);
#pragma unroll
      for (int k = 0; k < 6; k++) lds128(hP[k], mbx + k * 2048);
      mm(y, 1, 6, 14);
      keep(hP[0]); keep(hP[1]); keep(hP[2]); keep(hP[3]); keep(hP[4]); keep(hP[5]);
      mm(ya, 2, 0, 3);
      PSTAMP(18);
      mbar_wait_cluster(BAR + (B_HX + 2 + p) * 8);
      PSTAMP(24);
#pragma unroll
      for (int k = 6; k < 14; k++) lds128(hP[k], mbx + k * 2048);
      mm(ya, 2, 3, 6);
      keep(hP);
      mbar_arrive_if(BAR + (B_HC + p) * 8, lane == 0);
      mm(ya, 2, 6, 14);
      mbar_wait(BAR + B_CLR * 8);
      next(y, 3, ya, 0);
      PSTAMP(27);
      next(ya, 4, y, 1);
      mbar_arrive_if(BAR + (B_ET0 + 3) * 8, lane == 0);
      mm(ya, 5, 0, 14);
      PSTAMP(26);
      next(y, 6, ya, 2);
      PSTAMP(28);
      uint32_t in[4][4], lt[4][4];
      const uint4* insrc = e4 + j * 3 * 1024;
      mm(y, 7, 0, 7);
      ll_issue<4>(lt, insrc + 2048, 32);
      mm(y, 7, 7, 14);
      mbar_wait(BAR + B_FIN * 8);
      mbar_wait(BAR + (B_FIN + 1) * 8);
      wg_wait<0>();
      keep(y);
      PSTAMP(13);
      const uint32_t ident = (2 * c == r ? 0x3f80u : 0u) | (2 * c + 1 == r ? 0x3f800000u : 0u);
      auto acc = [&](const uint32_t (&v)[4][4]) {
#pragma unroll
        for (int u = 0; u < 4; u++) {
          mma1688_acc(*reinterpret_cast<float (*)[4]>(&y[8 * u]), v[u][0], v[u][1], ident);
          mma1688_acc(*reinterpret_cast<float (*)[4]>(&y[8 * u + 4]), v[u][2], v[u][3], ident);
        }
      };
      acc(hf);
#pragma unroll
      for (int q = 0; q < 2; q++) {
#pragma unroll
        for (int u = 0; u < 4; u++) lds128(in[u], t_addr(q + 1) + warp * 2048 + lane * 16 + u * 512);
        ll_wait<4>(in, insrc + q * 1024, 32, tag);
        acc(in);
      }
      PSTAMP(25);
      if (ll_bad<4>(lt, pin(tag, zero))) {
        ll_spin<4>(lt, insrc + 2048, 32, tag);
      }
      ll_clear<4>(lt);
      acc(lt);
      PSTAMP(14);
#pragma unroll
      for (int u = 0; u < 4; u++) {
        uint32_t o[4];
#pragma unroll
        for (int e = 0; e < 4; e++) o[e] = pack2(y[8 * u + 2 * e], y[8 * u + 2 * e + 1]);
        stsm4(stg + (moff ^ (u << 5)), o);
      }
      fence_async_smem();
      __syncwarp();
      if (elect_one()) {
        tma3d_store(&P.out, stg, 64 * j, p, g * 64 + 16 * w);
        asm volatile("cp.async.bulk.commit_group;" ::: "memory");
        asm volatile("cp.async.bulk.wait_group.read 0;" ::: "memory");
      }
      PSTAMP(15);
    }
  }
}

typedef CUresult (*EncodeFn)(CUtensorMap*, CUtensorMapDataType, cuuint32_t, void*, const cuuint64_t*, const cuuint64_t*,
                             const cuuint32_t*, const cuuint32_t*, CUtensorMapInterleave, CUtensorMapSwizzle,
                             CUtensorMapL2promotion, CUtensorMapFloatOOBfill);

void enc2d(EncodeFn f, CUtensorMap* m, const void* base, uint64_t cols, uint64_t rows, uint32_t bc, uint32_t br, CUtensorMapSwizzle sw) {
  cuuint64_t gd[2] = {cols, rows}, gs[1] = {cols * 2};
  cuuint32_t bd[2] = {bc, br}, es[2] = {1, 1};
  f(m, CU_TENSOR_MAP_DATA_TYPE_BFLOAT16, 2, const_cast<void*>(base), gd, gs, bd, es, CU_TENSOR_MAP_INTERLEAVE_NONE, sw,
    CU_TENSOR_MAP_L2_PROMOTION_L2_128B, CU_TENSOR_MAP_FLOAT_OOB_FILL_NONE);
}
void enc_par(EncodeFn f, CUtensorMap* m, const void* base, uint32_t pairs) {
  cuuint64_t gd[3] = {(cuuint64_t)D_, 2, (cuuint64_t)S_ / 2}, gs[2] = {D_ * 2, D_ * 4};
  cuuint32_t bd[3] = {64, 1, pairs}, es[3] = {1, 1, 1};
  f(m, CU_TENSOR_MAP_DATA_TYPE_BFLOAT16, 3, const_cast<void*>(base), gd, gs, bd, es, CU_TENSOR_MAP_INTERLEAVE_NONE,
    CU_TENSOR_MAP_SWIZZLE_128B, CU_TENSOR_MAP_L2_PROMOTION_L2_128B, CU_TENSOR_MAP_FLOAT_OOB_FILL_NONE);
}

}

extern "C" void kernel_launch(void* const* d_in, const int* in_sizes, int n_in, void* d_out, int out_size) {
  (void)in_sizes; (void)n_in; (void)out_size;
  static EncodeFn enc = nullptr;
  static Scratch* scratch = nullptr;
  if (!enc) {
    void* fn = nullptr;
    cudaDriverEntryPointQueryResult q;
    cudaGetDriverEntryPoint("cuTensorMapEncodeTiled", &fn, cudaEnableDefault, &q);
    enc = (EncodeFn)fn;
    cudaGetSymbolAddress((void**)&scratch, g_scratch);
    cudaFuncSetAttribute(fused_block_kernel, cudaFuncAttributeMaxDynamicSharedMemorySize, SMEM_BYTES);
  }
  Params P;
  const __nv_bfloat16* xp = (const __nv_bfloat16*)d_in[0];
  const __nv_bfloat16* wqkvp = (const __nv_bfloat16*)d_in[1];
  const __nv_bfloat16* wop = (const __nv_bfloat16*)d_in[2];
  P.w1p = (const __nv_bfloat16*)d_in[4];
  P.w3p = (const __nv_bfloat16*)d_in[5];
  P.w2p = (const __nv_bfloat16*)d_in[6];
  enc_par(enc, &P.x, xp, 64);
  enc_par(enc, &P.out, d_out, 16);
  enc2d(enc, &P.wqkv, wqkvp, 3 * D_, D_, 64, 64, CU_TENSOR_MAP_SWIZZLE_128B);
  enc2d(enc, &P.wo, wop, D_, D_, 64, 64, CU_TENSOR_MAP_SWIZZLE_128B);
  enc2d(enc, &P.w1, P.w1p, F_, D_, 64, 64, CU_TENSOR_MAP_SWIZZLE_128B);
  enc2d(enc, &P.w3, P.w3p, F_, D_, 64, 64, CU_TENSOR_MAP_SWIZZLE_128B);
  enc2d(enc, &P.w1h, P.w1p, F_, D_, 32, 64, CU_TENSOR_MAP_SWIZZLE_64B);
  enc2d(enc, &P.w3h, P.w3p, F_, D_, 32, 64, CU_TENSOR_MAP_SWIZZLE_64B);
  enc2d(enc, &P.w2, P.w2p, D_, F_, 64, 224, CU_TENSOR_MAP_SWIZZLE_128B);

  cudaLaunchConfig_t cfg = {};
  cfg.gridDim = dim3(128);
  cfg.blockDim = dim3(384);
  cfg.dynamicSmemBytes = SMEM_BYTES;
  cfg.stream = cudaStreamPerThread;
  cudaLaunchAttribute at[2];
  at[0].id = cudaLaunchAttributeCooperative;
  at[0].val.cooperative = 1;
  cfg.attrs = at;
  cfg.numAttrs = 1;
  at[1].id = cudaLaunchAttributeClusterDimension;
  at[1].val.clusterDim.x = 2; at[1].val.clusterDim.y = 1; at[1].val.clusterDim.z = 1;
  cfg.numAttrs = 2;
  cudaLaunchKernelEx(&cfg, fused_block_kernel, scratch, xp, wqkvp, wop, 0u, P);
}
```

```cpp
#include <cuda_runtime.h>
#include <cuda.h>
#include <cuda_bf16.h>
#include <stdint.h>
#include <stddef.h>

namespace {

constexpr int S_ = 2048, D_ = 512, F_ = 1792;
#define LAG_KB 3
#define XO_DELAY 2
#define CS_KB 3
#define CMAP 4
#define O_SLEEP 0
#define H_SLEEP 0

constexpr uint32_t SPIN_LIMIT = 1u << 18;

constexpr uint32_t R_O = 0;
constexpr uint32_t R_H = 16384;
constexpr uint32_t R_OS = 32768;
constexpr uint32_t R_HS = 33792;
constexpr uint32_t REC = 34816;
constexpr uint32_t X_E4 = 128 * REC;
constexpr uint32_t X_E1 = X_E4 + 16 * 24 * 16384;
constexpr uint32_t X_CS = X_E1 + 256 * 2048;
constexpr uint32_t X_ST = X_CS + 384 * 256;
constexpr uint32_t X_WB = X_ST + 2048 * 16;
constexpr uint32_t X_EP = X_WB + 512 * 16;
__device__ __align__(1024) char g_scratch[X_EP + 512];
#define PSTAMP(i)
#define PSTAMPW(slot, i)

struct alignas(64) Params {
  CUtensorMap x, out, wqkv, wo, w1, w3, w1h, w3h, w2;
  const __nv_bfloat16 *w1p, *w3p, *w2p;
};

constexpr uint32_t SB = 1024;
constexpr uint32_t H0 = SB;
constexpr uint32_t H1 = SB + 65536;
constexpr uint32_t RING = SB + 131072;
constexpr uint32_t BAR = SB + 229376;
constexpr uint32_t TAGS = BAR + 1016;
constexpr uint32_t CS = BAR + 1024;
constexpr uint32_t WB = CS + 768;
constexpr uint32_t SMEM_BYTES = 232448;
static_assert(WB + 256 <= SB + SMEM_BYTES, "smem");

enum : int {
  B_FX = 0,
  B_FKV = 16, B_FQ = 24, B_TAG = 28, B_CLRH = 29, B_FWO = 32,
  B_FIN = 33,
  B_HX = 35,
  B_FA = 40, B_FB = 48, B_FT = 56,
  B_EKV = 64, B_EQ = 72, B_EA = 80, B_EB = 88,
  B_ET0 = 96,
  B_WODONE = 103,
  B_EX = 104,
  B_LAG = 109, B_OG = 110,
  B_PF = 112,
  B_HC = 116,
  B_READY = 120,
  B_WBAR = 121,
  B_CLR1 = 122,
  B_CLR4 = 123
};

__device__ __forceinline__ uint32_t smem_u32(const void* p) { return (uint32_t)__cvta_generic_to_shared(p); }
__device__ __forceinline__ uint32_t own() { return (blockIdx.x & 1) << 24; }
__device__ __forceinline__ uint32_t peer() { return (~blockIdx.x & 1) << 24; }
__device__ __forceinline__ void mbar_init(uint32_t b, uint32_t c) { asm volatile("mbarrier.init.shared::cta.b64 [%0], %1;" ::"r"(b + own()), "r"(c) : "memory"); }
__device__ __forceinline__ void mbar_expect_tx(uint32_t b, uint32_t bytes) { asm volatile("mbarrier.arrive.expect_tx.shared::cta.b64 _, [%0], %1;" ::"r"(b + own()), "r"(bytes) : "memory"); }
__device__ __forceinline__ void mbar_arrive(uint32_t b) { asm volatile("mbarrier.arrive.shared::cta.b64 _, [%0];" ::"r"(b + own()) : "memory"); }
__device__ __forceinline__ void mbar_wait(uint32_t b) {
  asm volatile("{\n.reg .pred p;\n.reg .u32 c;\nmov.u32 c, 0;\nLW:\n.pragma \"nounroll\";\n"
               "mbarrier.try_wait.parity.shared::cta.b64 p, [%0], 0;\nadd.u32 c, c, 1;\nsetp.gt.or.u32 p, c, %1, p;\n@!p bra LW;\n}\n"
               ::"r"(b + own()), "n"(SPIN_LIMIT) : "memory");
}
__device__ __forceinline__ void mbar_arrive_peer(uint32_t b) {
  asm volatile("mbarrier.arrive.relaxed.cluster.shared::cluster.b64 _, [%0];" ::"r"(b + peer()) : "memory");
}
__device__ __forceinline__ void mbar_wait_cluster(uint32_t b) {
  asm volatile("{\n.reg .pred p;\n.reg .u32 c;\nmov.u32 c, 0;\nLW:\n.pragma \"nounroll\";\n"
               "mbarrier.try_wait.parity.acquire.cluster.shared::cta.b64 p, [%0], 0;\nadd.u32 c, c, 1;\nsetp.gt.or.u32 p, c, %1, p;\n@!p bra LW;\n}\n"
               ::"r"(b + own()), "n"(SPIN_LIMIT) : "memory");
}
__device__ __forceinline__ bool elect_one() {
  uint32_t p;
  asm volatile("{\n.reg .pred P;\nelect.sync _|P, 0xffffffff;\nselp.u32 %0, 1, 0, P;\n}\n" : "=r"(p));
  return p;
}
__device__ __forceinline__ void tma2d(uint32_t dst, const CUtensorMap* m, int c0, int c1, uint32_t bar) {
  dst += own(); bar += own();
  asm volatile("cp.async.bulk.tensor.2d.shared::cluster.global.mbarrier::complete_tx::bytes [%0], [%1, {%3, %4}], [%2];"
               ::"r"(dst), "l"(m), "r"(bar), "r"(c0), "r"(c1) : "memory");
}
__device__ __forceinline__ void tma3d(uint32_t dst, const CUtensorMap* m, int c0, int c1, int c2, uint32_t bar) {
  dst += own(); bar += own();
  asm volatile("cp.async.bulk.tensor.3d.shared::cluster.global.mbarrier::complete_tx::bytes [%0], [%1, {%3, %4, %5}], [%2];"
               ::"r"(dst), "l"(m), "r"(bar), "r"(c0), "r"(c1), "r"(c2) : "memory");
}
__device__ __forceinline__ void tma3d_store(const CUtensorMap* m, uint32_t src, int c0, int c1, int c2) {
  asm volatile("cp.async.bulk.tensor.3d.global.shared::cta.bulk_group [%0, {%2, %3, %4}], [%1];"
               ::"l"(m), "r"(src + own()), "r"(c0), "r"(c1), "r"(c2) : "memory");
}
__device__ __forceinline__ void l2_prefetch(const void* p, uint32_t bytes) {
  asm volatile("cp.async.bulk.prefetch.L2.global [%0], %1;" ::"l"(p), "r"(bytes) : "memory");
}
__device__ __forceinline__ void prefetch_map(const CUtensorMap* m) { asm volatile("prefetch.tensormap [%0];" ::"l"(m) : "memory"); }
__device__ __forceinline__ void fence_async_smem() { asm volatile("fence.proxy.async.shared::cta;" ::: "memory"); }
__device__ __forceinline__ void wg_fence() { asm volatile("wgmma.fence.sync.aligned;" ::: "memory"); }
__device__ __forceinline__ void wg_commit() { asm volatile("wgmma.commit_group.sync.aligned;" ::: "memory"); }
template <int N> __device__ __forceinline__ void wg_wait() { asm volatile("wgmma.wait_group.sync.aligned %0;" ::"n"(N) : "memory"); }
__device__ __forceinline__ void wg_bar(int p) {
  if (p == 0) asm volatile("bar.sync 1, 128;" ::: "memory"); else asm volatile("bar.sync 2, 128;" ::: "memory");
}
constexpr uint32_t DESC_HI128 = (1024 >> 4) | (1u << 30);
constexpr uint32_t DESC_HI64 = (512 >> 4) | (2u << 30);
__device__ __forceinline__ constexpr uint32_t descA(uint32_t addr) { return (addr >> 4) | (1u << 16); }
__device__ __forceinline__ constexpr uint32_t descB(uint32_t addr) { return (addr >> 4) | ((8192u >> 4) << 16); }
__device__ __forceinline__ constexpr uint32_t descBh(uint32_t addr) { return (addr >> 4) | ((4096u >> 4) << 16); }

__device__ __forceinline__ void wgmma_ss_n64(float (&d)[32], uint32_t da, uint32_t db, int sc) {
  asm volatile("{\n.reg .pred p;\n.reg .b64 da, db;\nsetp.ne.b32 p, %34, 0;\nmov.b64 da, {%32, %35};\nmov.b64 db, {%33, %35};\n"
    "wgmma.mma_async.sync.aligned.m64n64k16.f32.bf16.bf16 {%0, %1, %2, %3, %4, %5, %6, %7, %8, %9, %10, %11, %12, %13, %14, %15, %16, %17, %18, %19, %20, %21, %22, %23, %24, %25, %26, %27, %28, %29, %30, %31}, da, db, p, 1, 1, 0, 1;\n}\n"
    : "+f"(d[0]), "+f"(d[1]), "+f"(d[2]), "+f"(d[3]), "+f"(d[4]), "+f"(d[5]), "+f"(d[6]), "+f"(d[7]),
      "+f"(d[8]), "+f"(d[9]), "+f"(d[10]), "+f"(d[11]), "+f"(d[12]), "+f"(d[13]), "+f"(d[14]), "+f"(d[15]),
      "+f"(d[16]), "+f"(d[17]), "+f"(d[18]), "+f"(d[19]), "+f"(d[20]), "+f"(d[21]), "+f"(d[22]), "+f"(d[23]),
      "+f"(d[24]), "+f"(d[25]), "+f"(d[26]), "+f"(d[27]), "+f"(d[28]), "+f"(d[29]), "+f"(d[30]), "+f"(d[31])
    : "r"(da), "r"(db), "r"(sc), "n"(DESC_HI128));
}
__device__ __forceinline__ void wgmma_ss_n128(float (&d)[64], uint32_t da, uint32_t db, int sc) {
  asm volatile("{\n.reg .pred p;\n.reg .b64 da, db;\nsetp.ne.b32 p, %66, 0;\nmov.b64 da, {%64, %67};\nmov.b64 db, {%65, %67};\n"
    "wgmma.mma_async.sync.aligned.m64n128k16.f32.bf16.bf16 {%0, %1, %2, %3, %4, %5, %6, %7, %8, %9, %10, %11, %12, %13, %14, %15, %16, %17, %18, %19, %20, %21, %22, %23, %24, %25, %26, %27, %28, %29, %30, %31, %32, %33, %34, %35, %36, %37, %38, %39, %40, %41, %42, %43, %44, %45, %46, %47, %48, %49, %50, %51, %52, %53, %54, %55, %56, %57, %58, %59, %60, %61, %62, %63}, da, db, p, 1, 1, 0, 1;\n}\n"
    : "+f"(d[0]), "+f"(d[1]), "+f"(d[2]), "+f"(d[3]), "+f"(d[4]), "+f"(d[5]), "+f"(d[6]), "+f"(d[7]),
      "+f"(d[8]), "+f"(d[9]), "+f"(d[10]), "+f"(d[11]), "+f"(d[12]), "+f"(d[13]), "+f"(d[14]), "+f"(d[15]),
      "+f"(d[16]), "+f"(d[17]), "+f"(d[18]), "+f"(d[19]), "+f"(d[20]), "+f"(d[21]), "+f"(d[22]), "+f"(d[23]),
      "+f"(d[24]), "+f"(d[25]), "+f"(d[26]), "+f"(d[27]), "+f"(d[28]), "+f"(d[29]), "+f"(d[30]), "+f"(d[31]),
      "+f"(d[32]), "+f"(d[33]), "+f"(d[34]), "+f"(d[35]), "+f"(d[36]), "+f"(d[37]), "+f"(d[38]), "+f"(d[39]),
      "+f"(d[40]), "+f"(d[41]), "+f"(d[42]), "+f"(d[43]), "+f"(d[44]), "+f"(d[45]), "+f"(d[46]), "+f"(d[47]),
      "+f"(d[48]), "+f"(d[49]), "+f"(d[50]), "+f"(d[51]), "+f"(d[52]), "+f"(d[53]), "+f"(d[54]), "+f"(d[55]),
      "+f"(d[56]), "+f"(d[57]), "+f"(d[58]), "+f"(d[59]), "+f"(d[60]), "+f"(d[61]), "+f"(d[62]), "+f"(d[63])
    : "r"(da), "r"(db), "r"(sc), "n"(DESC_HI128));
}
__device__ __forceinline__ void wgmma_ss_n256(float (&d)[128], uint32_t da, uint32_t db, int sc) {
  asm volatile("{\n.reg .pred p;\n.reg .b64 da, db;\nsetp.ne.b32 p, %130, 0;\nmov.b64 da, {%128, %131};\nmov.b64 db, {%129, %131};\n"
    "wgmma.mma_async.sync.aligned.m64n256k16.f32.bf16.bf16 {%0, %1, %2, %3, %4, %5, %6, %7, %8, %9, %10, %11, %12, %13, %14, %15, %16, %17, %18, %19, %20, %21, %22, %23, %24, %25, %26, %27, %28, %29, %30, %31, %32, %33, %34, %35, %36, %37, %38, %39, %40, %41, %42, %43, %44, %45, %46, %47, %48, %49, %50, %51, %52, %53, %54, %55, %56, %57, %58, %59, %60, %61, %62, %63, %64, %65, %66, %67, %68, %69, %70, %71, %72, %73, %74, %75, %76, %77, %78, %79, %80, %81, %82, %83, %84, %85, %86, %87, %88, %89, %90, %91, %92, %93, %94, %95, %96, %97, %98, %99, %100, %101, %102, %103, %104, %105, %106, %107, %108, %109, %110, %111, %112, %113, %114, %115, %116, %117, %118, %119, %120, %121, %122, %123, %124, %125, %126, %127}, da, db, p, 1, 1, 0, 1;\n}\n"
    : "+f"(d[0]), "+f"(d[1]), "+f"(d[2]), "+f"(d[3]), "+f"(d[4]), "+f"(d[5]), "+f"(d[6]), "+f"(d[7]),
      "+f"(d[8]), "+f"(d[9]), "+f"(d[10]), "+f"(d[11]), "+f"(d[12]), "+f"(d[13]), "+f"(d[14]), "+f"(d[15]),
      "+f"(d[16]), "+f"(d[17]), "+f"(d[18]), "+f"(d[19]), "+f"(d[20]), "+f"(d[21]), "+f"(d[22]), "+f"(d[23]),
      "+f"(d[24]), "+f"(d[25]), "+f"(d[26]), "+f"(d[27]), "+f"(d[28]), "+f"(d[29]), "+f"(d[30]), "+f"(d[31]),
      "+f"(d[32]), "+f"(d[33]), "+f"(d[34]), "+f"(d[35]), "+f"(d[36]), "+f"(d[37]), "+f"(d[38]), "+f"(d[39]),
      "+f"(d[40]), "+f"(d[41]), "+f"(d[42]), "+f"(d[43]), "+f"(d[44]), "+f"(d[45]), "+f"(d[46]), "+f"(d[47]),
      "+f"(d[48]), "+f"(d[49]), "+f"(d[50]), "+f"(d[51]), "+f"(d[52]), "+f"(d[53]), "+f"(d[54]), "+f"(d[55]),
      "+f"(d[56]), "+f"(d[57]), "+f"(d[58]), "+f"(d[59]), "+f"(d[60]), "+f"(d[61]), "+f"(d[62]), "+f"(d[63]),
      "+f"(d[64]), "+f"(d[65]), "+f"(d[66]), "+f"(d[67]), "+f"(d[68]), "+f"(d[69]), "+f"(d[70]), "+f"(d[71]),
      "+f"(d[72]), "+f"(d[73]), "+f"(d[74]), "+f"(d[75]), "+f"(d[76]), "+f"(d[77]), "+f"(d[78]), "+f"(d[79]),
      "+f"(d[80]), "+f"(d[81]), "+f"(d[82]), "+f"(d[83]), "+f"(d[84]), "+f"(d[85]), "+f"(d[86]), "+f"(d[87]),
      "+f"(d[88]), "+f"(d[89]), "+f"(d[90]), "+f"(d[91]), "+f"(d[92]), "+f"(d[93]), "+f"(d[94]), "+f"(d[95]),
      "+f"(d[96]), "+f"(d[97]), "+f"(d[98]), "+f"(d[99]), "+f"(d[100]), "+f"(d[101]), "+f"(d[102]), "+f"(d[103]),
      "+f"(d[104]), "+f"(d[105]), "+f"(d[106]), "+f"(d[107]), "+f"(d[108]), "+f"(d[109]), "+f"(d[110]), "+f"(d[111]),
      "+f"(d[112]), "+f"(d[113]), "+f"(d[114]), "+f"(d[115]), "+f"(d[116]), "+f"(d[117]), "+f"(d[118]), "+f"(d[119]),
      "+f"(d[120]), "+f"(d[121]), "+f"(d[122]), "+f"(d[123]), "+f"(d[124]), "+f"(d[125]), "+f"(d[126]), "+f"(d[127])
    : "r"(da), "r"(db), "r"(sc), "n"(DESC_HI128));
}
template <uint32_t HI = DESC_HI128>
__device__ __forceinline__ void wgmma_rs_n64(float (&d)[32], const uint32_t (&a)[4], uint32_t db, int sc) {
  asm volatile("{\n.reg .pred p;\n.reg .b64 db;\nsetp.ne.b32 p, %37, 0;\nmov.b64 db, {%36, %38};\n"
    "wgmma.mma_async.sync.aligned.m64n64k16.f32.bf16.bf16 {%0, %1, %2, %3, %4, %5, %6, %7, %8, %9, %10, %11, %12, %13, %14, %15, %16, %17, %18, %19, %20, %21, %22, %23, %24, %25, %26, %27, %28, %29, %30, %31}, {%32, %33, %34, %35}, db, p, 1, 1, 1;\n}\n"
    : "+f"(d[0]), "+f"(d[1]), "+f"(d[2]), "+f"(d[3]), "+f"(d[4]), "+f"(d[5]), "+f"(d[6]), "+f"(d[7]),
      "+f"(d[8]), "+f"(d[9]), "+f"(d[10]), "+f"(d[11]), "+f"(d[12]), "+f"(d[13]), "+f"(d[14]), "+f"(d[15]),
      "+f"(d[16]), "+f"(d[17]), "+f"(d[18]), "+f"(d[19]), "+f"(d[20]), "+f"(d[21]), "+f"(d[22]), "+f"(d[23]),
      "+f"(d[24]), "+f"(d[25]), "+f"(d[26]), "+f"(d[27]), "+f"(d[28]), "+f"(d[29]), "+f"(d[30]), "+f"(d[31])
    : "r"(a[0]), "r"(a[1]), "r"(a[2]), "r"(a[3]), "r"(db), "r"(sc), "n"(HI));
}
template <uint32_t HI = DESC_HI128>
__device__ __forceinline__ void wgmma_rs_n128(float (&d)[64], const uint32_t (&a)[4], uint32_t db, int sc) {
  asm volatile("{\n.reg .pred p;\n.reg .b64 db;\nsetp.ne.b32 p, %69, 0;\nmov.b64 db, {%68, %70};\n"
    "wgmma.mma_async.sync.aligned.m64n128k16.f32.bf16.bf16 {%0, %1, %2, %3, %4, %5, %6, %7, %8, %9, %10, %11, %12, %13, %14, %15, %16, %17, %18, %19, %20, %21, %22, %23, %24, %25, %26, %27, %28, %29, %30, %31, %32, %33, %34, %35, %36, %37, %38, %39, %40, %41, %42, %43, %44, %45, %46, %47, %48, %49, %50, %51, %52, %53, %54, %55, %56, %57, %58, %59, %60, %61, %62, %63}, {%64, %65, %66, %67}, db, p, 1, 1, 1;\n}\n"
    : "+f"(d[0]), "+f"(d[1]), "+f"(d[2]), "+f"(d[3]), "+f"(d[4]), "+f"(d[5]), "+f"(d[6]), "+f"(d[7]),
      "+f"(d[8]), "+f"(d[9]), "+f"(d[10]), "+f"(d[11]), "+f"(d[12]), "+f"(d[13]), "+f"(d[14]), "+f"(d[15]),
      "+f"(d[16]), "+f"(d[17]), "+f"(d[18]), "+f"(d[19]), "+f"(d[20]), "+f"(d[21]), "+f"(d[22]), "+f"(d[23]),
      "+f"(d[24]), "+f"(d[25]), "+f"(d[26]), "+f"(d[27]), "+f"(d[28]), "+f"(d[29]), "+f"(d[30]), "+f"(d[31]),
      "+f"(d[32]), "+f"(d[33]), "+f"(d[34]), "+f"(d[35]), "+f"(d[36]), "+f"(d[37]), "+f"(d[38]), "+f"(d[39]),
      "+f"(d[40]), "+f"(d[41]), "+f"(d[42]), "+f"(d[43]), "+f"(d[44]), "+f"(d[45]), "+f"(d[46]), "+f"(d[47]),
      "+f"(d[48]), "+f"(d[49]), "+f"(d[50]), "+f"(d[51]), "+f"(d[52]), "+f"(d[53]), "+f"(d[54]), "+f"(d[55]),
      "+f"(d[56]), "+f"(d[57]), "+f"(d[58]), "+f"(d[59]), "+f"(d[60]), "+f"(d[61]), "+f"(d[62]), "+f"(d[63])
    : "r"(a[0]), "r"(a[1]), "r"(a[2]), "r"(a[3]), "r"(db), "r"(sc), "n"(HI));
}

template <int N> __device__ __forceinline__ void keep(float (&d)[N]) {
#pragma unroll
  for (int i = 0; i < N; i++) asm volatile("" : "+f"(d[i])::"memory");
}

__device__ __forceinline__ void keep(uint32_t (&d)[4]) { asm volatile("" : "+r"(d[0]), "+r"(d[1]), "+r"(d[2]), "+r"(d[3])::"memory"); }
template <int N> __device__ __forceinline__ void keep(uint32_t (&d)[N][4]) {
#pragma unroll
  for (int i = 0; i < N; i++) asm volatile("" : "+r"(d[i][0]), "+r"(d[i][1]), "+r"(d[i][2]), "+r"(d[i][3])::"memory");
}

__device__ __forceinline__ uint32_t pack2(float lo, float hi) {
  uint32_t r;
  asm("cvt.rn.bf16x2.f32 %0, %1, %2;" : "=r"(r) : "f"(hi), "f"(lo));
  return r;
}
__device__ __forceinline__ float bf_lo(uint32_t v) { return __uint_as_float(v << 16); }
__device__ __forceinline__ float bf_hi(uint32_t v) { return __uint_as_float(v & 0xffff0000u); }
__device__ __forceinline__ uint32_t hsub2(uint32_t a, uint32_t b) {
  uint32_t r;
  asm("sub.rn.bf16x2 %0, %1, %2;" : "=r"(r) : "r"(a), "r"(b));
  return r;
}
__device__ __forceinline__ uint32_t movm(uint32_t a) {
  uint32_t r;
  asm volatile("movmatrix.sync.aligned.m8n8.trans.b16 %0, %1;" : "=r"(r) : "r"(a));
  return r;
}
__device__ __forceinline__ void ldsm4(uint32_t (&v)[4], uint32_t a) {
  asm volatile("ldmatrix.sync.aligned.m8n8.x4.shared.b16 {%0,%1,%2,%3}, [%4];" : "=r"(v[0]), "=r"(v[1]), "=r"(v[2]), "=r"(v[3]) : "r"(a + own()) : "memory");
}
__device__ __forceinline__ void stsm4(uint32_t a, const uint32_t (&v)[4]) {
  asm volatile("stmatrix.sync.aligned.m8n8.x4.shared.b16 [%0], {%1,%2,%3,%4};" ::"r"(a + own()), "r"(v[0]), "r"(v[1]), "r"(v[2]), "r"(v[3]) : "memory");
}
__device__ __forceinline__ void mma16816(float (&d)[4], const uint32_t (&a)[4], uint32_t b0, uint32_t b1) {
  asm volatile("mma.sync.aligned.m16n8k16.row.col.f32.bf16.bf16.f32 {%0,%1,%2,%3}, {%4,%5,%6,%7}, {%8,%9}, {%10,%10,%10,%10};"
               : "=f"(d[0]), "=f"(d[1]), "=f"(d[2]), "=f"(d[3])
               : "r"(a[0]), "r"(a[1]), "r"(a[2]), "r"(a[3]), "r"(b0), "r"(b1), "f"(0.f));
}
__device__ __forceinline__ void mma1688_acc(float (&d)[4], uint32_t a0, uint32_t a1, uint32_t b0) {
  asm volatile("mma.sync.aligned.m16n8k8.row.col.f32.bf16.bf16.f32 {%0,%1,%2,%3}, {%4,%5}, {%6}, {%0,%1,%2,%3};"
               : "+f"(d[0]), "+f"(d[1]), "+f"(d[2]), "+f"(d[3]) : "r"(a0), "r"(a1), "r"(b0));
}
__device__ __forceinline__ float ex2(float x) { float y; asm("ex2.approx.ftz.f32 %0, %1;" : "=f"(y) : "f"(x)); return y; }
__device__ __forceinline__ float rcp(float x) { float y; asm("rcp.approx.ftz.f32 %0, %1;" : "=f"(y) : "f"(x)); return y; }
__device__ __forceinline__ float tanhf_hw(float x) { float y; asm("tanh.approx.f32 %0, %1;" : "=f"(y) : "f"(x)); return y; }
__device__ __forceinline__ uint32_t lds32(uint32_t a) { uint32_t v; asm volatile("ld.shared.u32 %0, [%1];" : "=r"(v) : "r"(a + own()) : "memory"); return v; }
__device__ __forceinline__ float2 lds64(uint32_t a) { float2 v; asm volatile("ld.shared.v2.f32 {%0,%1}, [%2];" : "=f"(v.x), "=f"(v.y) : "r"(a + own()) : "memory"); return v; }
__device__ __forceinline__ void lds128(uint32_t (&v)[4], uint32_t a) { asm volatile("ld.shared.v4.u32 {%0,%1,%2,%3}, [%4];" : "=r"(v[0]), "=r"(v[1]), "=r"(v[2]), "=r"(v[3]) : "r"(a + own()) : "memory"); }
__device__ __forceinline__ void sts128(uint32_t a, const uint32_t (&v)[4]) { asm volatile("st.shared.v4.u32 [%0], {%1,%2,%3,%4};" ::"r"(a + own()), "r"(v[0]), "r"(v[1]), "r"(v[2]), "r"(v[3]) : "memory"); }
__device__ __forceinline__ void ldg128_nc(uint32_t (&v)[4], const void* p) {
  asm volatile("ld.global.nc.L1::no_allocate.v4.u32 {%0,%1,%2,%3}, [%4];" : "=r"(v[0]), "=r"(v[1]), "=r"(v[2]), "=r"(v[3]) : "l"(p));
}
__device__ __forceinline__ uint32_t pin(uint32_t v, uint32_t zero) {
  asm volatile("{\n.reg .pred p;\n.reg .u32 c;\nmov.u32 c, %1;\nLP:\n.pragma \"nounroll\";\nsetp.eq.u32 p, c, 0;\n@p bra LD;\n"
               "add.u32 %0, %0, c;\nmov.u32 c, %%clock;\nbra LP;\nLD:\n}\n" : "+r"(v) : "r"(zero) : "memory");
  return v;
}
__device__ __forceinline__ void mbar_arrive_if(uint32_t b, bool cond) {
  asm volatile("{\n.reg .pred p;\nsetp.ne.u32 p, %1, 0;\n@p mbarrier.arrive.shared::cta.b64 _, [%0];\n}\n" ::"r"(b + own()), "r"((uint32_t)cond) : "memory");
}
__device__ __forceinline__ uint32_t ld_epoch(const char* p) {
  uint32_t v;
  asm volatile("ld.relaxed.gpu.global.u32 %0, [%1];" : "=r"(v) : "l"(p) : "memory");
  return v;
}
typedef const char* gptr;
__device__ __forceinline__ void ll_st(gptr p, uint32_t a, uint32_t b, uint32_t c, uint32_t d, uint32_t tag) {
  asm volatile("st.relaxed.gpu.global.v4.b32 [%0], {%1, %2, %3, %4};" ::"l"(p), "r"((a & ~1u) | tag), "r"(b), "r"(c), "r"(d) : "memory");
}
__device__ __forceinline__ void ll_ld(uint32_t (&v)[4], gptr p) {
  asm volatile("{\n.reg .b128 t;\n.reg .b64 lo, hi;\nld.relaxed.gpu.global.b128 t, [%4];\nmov.b128 {lo, hi}, t;\n"
               "mov.b64 {%0, %1}, lo;\nmov.b64 {%2, %3}, hi;\n}\n"
               : "=r"(v[0]), "=r"(v[1]), "=r"(v[2]), "=r"(v[3]) : "l"(p) : "memory");
}
template <int N> __device__ __forceinline__ void ll_issue(uint32_t (&v)[N][4], gptr p, int stride) {
#pragma unroll
  for (int i = 0; i < N; i++) ll_ld(v[i], p + i * stride);
}
__device__ __forceinline__ uint32_t ll_mix(uint32_t a, uint32_t b, uint32_t tag) {
  uint32_t r;
  asm("lop3.b32 %0, %1, %2, %3, 0xD4;" : "=r"(r) : "r"(a), "r"(b), "r"(tag));
  return r;
}
template <int LO, int HI, int N> __device__ __forceinline__ uint32_t ll_tree(const uint32_t (&v)[N][4], uint32_t tag) {
  if constexpr (HI - LO == 1) return v[LO][0];
  else return ll_mix(ll_tree<LO, (LO + HI) / 2>(v, tag), ll_tree<(LO + HI) / 2, HI>(v, tag), tag);
}
template <int N> __device__ __forceinline__ uint32_t ll_red(const uint32_t (&v)[N][4], uint32_t tag) { return ll_tree<0, N>(v, tag); }
__device__ __forceinline__ bool ll_any(uint32_t red, uint32_t tag) { return __any_sync(0xffffffffu, (red ^ tag) & 1u); }
template <int N> __device__ __forceinline__ bool ll_bad(const uint32_t (&v)[N][4], uint32_t tag) { return ll_any(ll_red<N>(v, tag), tag); }
template <int N, int M> __device__ __forceinline__ bool ll_bad2(const uint32_t (&v)[N][4], const uint32_t (&u)[M][4], uint32_t tag) {
  return ll_any(ll_mix(ll_red<N>(v, tag), ll_red<M>(u, tag), tag), tag);
}
template <int N> __device__ __forceinline__ void ll_clear(uint32_t (&v)[N][4]) {
#pragma unroll
  for (int i = 0; i < N; i++) v[i][0] &= ~1u;
}
template <int N> __device__ __forceinline__ void ll_spin(uint32_t (&v)[N][4], gptr p, int stride, uint32_t tag) {
  uint32_t it = 0;
#pragma unroll 1
  do { ll_issue<N>(v, p, stride); } while (ll_bad<N>(v, tag) && ++it < SPIN_LIMIT);
}
template <int N> __device__ __forceinline__ void ll_get(uint32_t (&v)[N][4], gptr p, int stride, uint32_t tag) {
  ll_spin<N>(v, p, stride, tag);
  ll_clear<N>(v);
}
template <int N> __device__ __forceinline__ void ll_wait(uint32_t (&v)[N][4], gptr p, int stride, uint32_t tag) {
  if (__builtin_expect(ll_bad<N>(v, tag), 0)) ll_spin<N>(v, p, stride, tag);
  ll_clear<N>(v);
}
__device__ __forceinline__ void unpack32(float (&d)[32], const uint32_t (&v)[4][4]) {
#pragma unroll
  for (int u = 0; u < 4; u++)
#pragma unroll
    for (int e = 0; e < 4; e++) { d[8 * u + 2 * e] = bf_lo(v[u][e]); d[8 * u + 2 * e + 1] = bf_hi(v[u][e]); }
}
__device__ __forceinline__ void pack32(uint32_t (&v)[4][4], const float (&d)[32]) {
#pragma unroll
  for (int u = 0; u < 4; u++)
#pragma unroll
    for (int e = 0; e < 4; e++) v[u][e] = pack2(d[8 * u + 2 * e], d[8 * u + 2 * e + 1]);
}
__device__ __forceinline__ uint32_t t_addr(int m) { return SB + ((0x01534620u >> (4 * m)) & 7u) * 32768u; }

__device__ __forceinline__ constexpr int w2_pass(int m) { return m < 4 ? m & 1 : m >> 1; }
__device__ __forceinline__ constexpr int w2_peer(int m) { return m < 4 ? m >> 1 : m & 1; }

__device__ __forceinline__ int kb_at(int i, int j) { return i == 0 ? j : (i - 1 + (i - 1 >= j ? 1 : 0)); }

__device__ __forceinline__ void init_bars(int set) {
  if (set >= 0 && elect_one()) {
    const uint32_t cnt = set < 5 ? 1 : 8;
#pragma unroll
    for (int i = 0; i < 8; i++) mbar_init(BAR + (24 + 8 * set + i) * 8, cnt);
    if (set >= 8) {
#pragma unroll
      for (int i = 0; i < 8; i++) mbar_init(BAR + (40 + 8 * set + i) * 8, 4);
    }
    if (set == 7) {
#pragma unroll
      for (int i = 0; i < 4; i++) mbar_init(BAR + (B_READY + i) * 8, i ? 3 : 2);
    }
    asm volatile("fence.mbarrier_init.release.cluster;" ::: "memory");
  }
  __syncwarp();
  asm volatile("barrier.cluster.arrive.relaxed.aligned;" ::: "memory");
  asm volatile("bar.arrive 4, 384;" ::: "memory");
  asm volatile("bar.sync 3, 384;" ::: "memory");
}

__device__ __forceinline__ void load_a(const Params& P, int i, int j) {
  const int f0 = 224 * j + ((j & 1) ? 32 : 0);
  const int fh = 224 * j + ((j & 1) ? 0 : 192);
  const uint32_t b = BAR + (B_FA + i) * 8, d = RING + (i & 3) * 24576;
  const int k0 = kb_at(i, j) * 64;
  mbar_expect_tx(b, 24576);
  tma2d(d, &P.w1, f0, k0, b);
  tma2d(d + 8192, &P.w3, f0, k0, b);
  tma2d(d + 16384, &P.w1h, fh, k0, b);
  tma2d(d + 20480, &P.w3h, fh, k0, b);
}
__device__ __forceinline__ void reset_box(gptr p, int i0, int n, uint32_t s8, uint32_t tag) {
#pragma unroll 1
  for (int i = i0; i < i0 + n; i++) ll_st(p + ((i & 7) * s8 + (i >> 3) * 512), 0, 0, 0, 0, tag ^ 1);
}

__global__ void __launch_bounds__(384, 1) fused_block_kernel(char* __restrict__ X, const __nv_bfloat16* __restrict__ xp,
                                                             const __nv_bfloat16* __restrict__ wqkvp, const __nv_bfloat16* __restrict__ wop,
                                                             const uint32_t zero, const __grid_constant__ Params P) {
  extern __shared__ __align__(1024) uint8_t smem_raw[];
  if (smem_u32(smem_raw) != SB + own()) return;
  const int tid = threadIdx.x;
  const int warp = __shfl_sync(0xffffffffu, tid >> 5, 0);
  const int lane = tid & 31;
  const int cta = blockIdx.x;
  const int cl = cta >> 1;
  const int c7 = cl - 36, i7 = (c7 * 37) >> 8;
  const int set = cl < 4 ? 15 : cl < 36 ? (cl - 4) & 7 : 8 + c7 - 7 * i7;
  const int idx = cl < 4 ? cl : cl < 36 ? (cl - 4) >> 3 : i7;
  const int g = (set & 14) + (idx >> 1), j = (set & 1) * 4 + (idx & 1) * 2 + (cta & 1);

  if (__builtin_expect(warp >= 8, 1)) {
    asm volatile("setmaxnreg.dec.sync.aligned.u32 56;");
    if (__builtin_expect(warp == 8, 1)) {
      PSTAMPW(2, 0);
      const bool leader = elect_one();
      if (leader) {
        prefetch_map(&P.x); prefetch_map(&P.wqkv);
#pragma unroll
        for (int i = 0; i < 24; i++) mbar_init(BAR + i * 8, 1);
        asm volatile("fence.mbarrier_init.release.cluster;" ::: "memory");
      }
      __syncwarp();
      asm volatile("bar.arrive 3, 384;" ::: "memory");
      asm volatile("barrier.cluster.arrive.relaxed.aligned;" ::: "memory");
      auto ldx = [&](int p, int kb) {
        const uint32_t b = BAR + (B_FX + p * 8 + kb) * 8;
        mbar_expect_tx(b, 8192);
        tma3d(H0 + p * 65536 + kb * 8192, &P.x, kb * 64, p, g * 64, b);
      };
      auto ld2 = [&](uint32_t b, uint32_t d, int c0, int k0, int c1, int k1) {
        mbar_expect_tx(b, 16384);
        tma2d(d, &P.wqkv, c0, k0, b);
        tma2d(d + 8192, &P.wqkv, c1, k1, b);
      };
      if (leader) {
#pragma unroll 1
        for (int i = 0; i < 8 + XO_DELAY; i++) {
          if (i < 8) ldx(0, i);
          if (i < 6) ld2(BAR + (B_FKV + i) * 8, RING + i * 16384, 512 + 64 * j, i * 64, 1024 + 64 * j, i * 64);
          if (i >= XO_DELAY) ldx(1, i - XO_DELAY);
        }
        PSTAMPW(2, 2);
      }
      __syncwarp();
      asm volatile("bar.sync 4, 384;" ::: "memory");
      if (leader) {
        prefetch_map(&P.wo); prefetch_map(&P.w1); prefetch_map(&P.w3); prefetch_map(&P.w1h);
        prefetch_map(&P.w3h); prefetch_map(&P.w2); prefetch_map(&P.out);
#pragma unroll 1
        for (int i = 0; i < 6; i++) {
          const bool kv = i < 2;
          mbar_wait(BAR + (B_EKV + i) * 8);
          ld2(BAR + (B_FKV + 6 + i) * 8, RING + i * 16384, (kv ? 512 : 0) + 64 * j, kv ? 384 + i * 64 : i * 128 - 256,
              (kv ? 1024 : 0) + 64 * j, kv ? 384 + i * 64 : i * 128 - 192);
        }
        mbar_expect_tx(BAR + B_FWO * 8, 65536);
#pragma unroll 1
        for (int i = 1; i < 9; i++) {
          mbar_wait(BAR + (B_EX + (i >> 1)) * 8);
          tma2d(H0 + (i & 7) * 8192, &P.wo, 64 * j, (i & 7) * 64, BAR + B_FWO * 8);
        }
        mbar_wait(BAR + B_OG * 8);
#pragma unroll 1
        for (int i = 2; i < 8; i++) {
          mbar_wait(BAR + (i < 4 ? B_EQ + i : B_EA + i - 4) * 8);
          load_a(P, i, j);
        }
        const int f0 = 224 * j + ((j & 1) ? 32 : 0);
        uint32_t d = RING;
#pragma unroll 1
        for (int i = 0; i < 8; i++) {
          const uint32_t b = BAR + (B_FB + i) * 8;
          const int k0 = kb_at(i, j) * 64;
          mbar_wait(BAR + (B_EA + 5 + i) * 8);
          mbar_expect_tx(b, 32768);
          tma2d(d, &P.w1, f0 + 64, k0, b);
          tma2d(d + 8192, &P.w3, f0 + 64, k0, b);
          tma2d(d + 16384, &P.w1, f0 + 128, k0, b);
          tma2d(d + 24576, &P.w3, f0 + 128, k0, b);
          d = d == RING + 65536 ? RING : d + 32768;
        }
#pragma unroll 1
        for (int i = 0; i < 8; i++) {
          const int m = (0x76453210u >> (4 * i)) & 7;
          const uint32_t b = BAR + (B_FT + m) * 8;
          mbar_wait(BAR + (i < 5 ? B_EB + 3 + i : i < 7 ? B_HC - 5 + i : B_ET0) * 8);
          mbar_expect_tx(b, 28672);
          tma2d(t_addr(m), &P.w2, 64 * ((j + 2 + 2 * w2_pass(m)) & 7), 224 * (j ^ w2_peer(m)), b);
        }
        mbar_expect_tx(BAR + B_FIN * 8, 32768);
#pragma unroll 1
        for (int q = 0; q < 2; q++) {
          mbar_wait(BAR + (B_ET0 + 3 - q) * 8);
          asm volatile("cp.async.bulk.shared::cluster.global.mbarrier::complete_tx::bytes [%0], [%1], 16384, [%2];"
                       ::"r"(t_addr(q + 1) + own()), "l"(X + X_E4 + ((g * 8 + j) * 3 + q) * 16384), "r"(BAR + B_FIN * 8 + own()) : "memory");
        }
        unsigned* ep = reinterpret_cast<unsigned*>(X + X_EP) + cta;
        *ep = *ep + 1;
      }
    } else {
      const int part = warp - 9;
      uint32_t tag;
      if (part == 2) {
        tag = ld_epoch(X + X_EP + cta * 4);
        init_bars(-1);
        tag = (tag + 1) & 1;
        if (lane == 0) {
          asm volatile("st.shared.u32 [%0], %1;" ::"r"(TAGS + own()), "r"(tag) : "memory");
          mbar_arrive(BAR + B_TAG * 8);
        }
      } else {
        init_bars(warp - 1);
        mbar_wait(BAR + B_TAG * 8);
        tag = lds32(TAGS);
      }
      gptr xl = X + lane * 16;
      if (lane < 16) ll_st(xl + X_CS + ((j * 3 + part) * 16 + g) * 256, 0, 0, 0, 0, tag ^ 1);
      if (part == 0 && lane < 20) ll_st(xl + (lane < 16 ? X_ST + (g * 128 + 16 * j) * 16 : X_WB + (j * 64 + g * 4 - 16) * 16), 0, 0, 0, 0, tag ^ 1);
      if (part) reset_box(xl + X_E1 + (g * 8 + j) * 4096, 4 * part - 4, 4, 512, tag);
      __syncwarp();
      if (lane == 0) mbar_arrive(BAR + B_CLR1 * 8);
      uint32_t v[8][4];
      {
        float s[4] = {0.f, 0.f, 0.f, 0.f}, q[4] = {0.f, 0.f, 0.f, 0.f};
        const uint32_t xa = H0 + ((lane >> 1) & 1) * 65536 + (8 * j + (lane >> 2)) * 128 + (lane & 1) * 64 + ((lane >> 1) & 3) * 16;
#pragma unroll 1
        for (int kb = (part + 2) % 3; kb < 8; kb += 3) {
          mbar_wait(BAR + (B_FX + kb) * 8);
          mbar_wait(BAR + (B_FX + 8 + kb) * 8);
          if (kb == 3 && lane == 0) l2_prefetch(wop + (size_t)(j * 64 + g * 4) * D_, 4096);
#pragma unroll
          for (int i = 0; i < 4; i++) lds128(v[i], (xa + kb * 8192) ^ (i * 16));
#pragma unroll
          for (int e = 0; e < 16; e++) {
            const float a = bf_lo(v[e >> 2][e & 3]), b = bf_hi(v[e >> 2][e & 3]);
            s[e & 3] += a + b; q[e & 3] = fmaf(a, a, q[e & 3]); q[e & 3] = fmaf(b, b, q[e & 3]);
          }
        }
        float ss = (s[0] + s[1]) + (s[2] + s[3]), qq = (q[0] + q[1]) + (q[2] + q[3]);
        ss += __shfl_xor_sync(0xffffffffu, ss, 1); qq += __shfl_xor_sync(0xffffffffu, qq, 1);
        if (part) {
          if (!(lane & 1))
            asm volatile("st.shared.v2.f32 [%0], {%1,%2};" ::"r"(WB + own() + part * 128 - 128 + lane * 4), "f"(ss), "f"(qq) : "memory");
          asm volatile("bar.arrive 5, 96;" ::: "memory");
        } else {
          const __nv_bfloat16* wr = wop + (size_t)(j * 64 + g * 4 + (lane >> 3)) * D_ + (lane & 7) * 8;
#pragma unroll
          for (int i = 0; i < 8; i++) ldg128_nc(v[i], wr + i * 64);
          asm volatile("bar.sync 5, 96;" ::: "memory");
          const float2 t1 = lds64(WB + (lane >> 1) * 8), t2 = lds64(WB + 128 + (lane >> 1) * 8);
          const float mean = (ss + t1.x + t2.x) * (1.f / D_);
          const float rs = rsqrtf(fmaxf(fmaf(-mean, mean, (qq + t1.y + t2.y) * (1.f / D_)), 0.f) + 1e-5f);
          if (!(lane & 1)) ll_st(X + X_ST + (g * 128 + 16 * j + (lane >> 1)) * 16, __float_as_uint(mean), __float_as_uint(rs), 0, 0, tag);
          PSTAMPW(3, 2);
          const uint32_t sh = pin(16, zero), hm = ~0u << sh;
#pragma unroll
          for (int e = 0; e < 4; e++) {
            s[e] = 0.f;
#pragma unroll
            for (int i = 0; i < 8; i++) s[e] += __uint_as_float(v[i][e] << sh) + __uint_as_float(v[i][e] & hm);
          }
          ss = (s[0] + s[1]) + (s[2] + s[3]);
#pragma unroll
          for (int o = 1; o <= 4; o <<= 1) ss += __shfl_xor_sync(0xffffffffu, ss, o);
          if ((lane & 7) == 0) ll_st(X + X_WB + (j * 64 + g * 4 + (lane >> 3)) * 16, __float_as_uint(ss * (1.f / D_)), 0, 0, 0, tag);
        }
      }
      PSTAMPW(3, part * 4 + 0);
      {
        ll_get<8>(v, X + X_CS + ((j * 3 + part) * 16 + (lane >> 4) * 8) * 256 + (lane & 15) * 16, 256, tag);
        uint32_t o[4];
#pragma unroll
        for (int e = 0; e < 4; e++) {
          float s = 0.f;
#pragma unroll
          for (int i = 0; i < 8; i++) s += __uint_as_float(v[i][e]);
          o[e] = __float_as_uint(s + __shfl_xor_sync(0xffffffffu, s, 16));
        }
        if (lane < 16) {
          const uint32_t a = CS + own() + (part ? 256 + (lane & 1) * 256 + (part - 1) * 64 : (lane & 1) * 128) + (lane >> 1) * 8;
          asm volatile("st.shared.v2.u32 [%0], {%1,%2};" ::"r"(a), "r"(o[0]), "r"(o[1]) : "memory");
          asm volatile("st.shared.v2.u32 [%0], {%1,%2};" ::"r"(a + (part ? 128 : 64)), "r"(o[2]), "r"(o[3]) : "memory");
        }
      }
      gptr rec = xl + g * 8 * REC + j * 2048;
      gptr recs = X + (g * 8 + (lane >> 3)) * REC + j * 128 + (lane & 7) * 16;
      if (part == 0) {
        uint32_t u[2][4];
        ll_get<2>(u, xl + X_WB + j * 1024, 512, tag);
#pragma unroll
        for (int i = 0; i < 2; i++)
          asm volatile("st.shared.u32 [%0], %1;" ::"r"(WB + own() + ((lane >> 1) & 3) * 64 + (i * 4 + (lane >> 3)) * 8 + (lane & 1) * 4), "r"(u[i][0]) : "memory");
      } else {
        __syncwarp();
        if (lane == 0) mbar_arrive(BAR + B_READY * 8);
        PSTAMPW(3, part * 4 + 1);
        ll_st(recs + R_OS + (part - 1) * 4 * REC, 0, 0, 0, 0, tag ^ 1);
        reset_box(rec + R_O, 16 * part - 16, 16, REC, tag);
      }
      __syncwarp();
      if (lane == 0) {
        mbar_arrive(BAR + B_WBAR * 8);
        l2_prefetch(part == 0 ? P.w2p + (size_t)cta * 14 * D_ : (part == 1 ? P.w1p : P.w3p) + (size_t)cta * 4 * F_, 14336);
      }
      PSTAMPW(3, 20 + part);
      if (part == 1) {
        if (elect_one()) {
#pragma unroll 1
          for (int i = 0; i < 2; i++) { mbar_wait(BAR + (B_EKV + 7 + i) * 8); load_a(P, i, j); }
        }
      } else if (part == 2) {
        ll_st(recs + R_HS, 0, 0, 0, 0, tag ^ 1);
        ll_st(recs + R_HS + 4 * REC, 0, 0, 0, 0, tag ^ 1);
        reset_box(rec + R_H, 0, 32, REC, tag);
        __syncwarp();
        if (lane == 0) mbar_arrive(BAR + B_CLRH * 8);
        PSTAMPW(3, 24);
      }
      mbar_wait(BAR + (B_EA + 7) * 8);
      reset_box(xl + X_E4 + ((g * 8 + ((j + 2 + 2 * part) & 7)) * 3 + part) * 16384, 0, 32, 2048, tag);
      __syncwarp();
      if (lane == 0) mbar_arrive(BAR + B_CLR4 * 8);
      PSTAMPW(3, part * 4 + 3);
    }
  } else {
    const int p = warp >> 2, w = warp & 3;
    const int r = lane >> 2, c = lane & 3;
    init_bars(warp);
    asm volatile("setmaxnreg.inc.sync.aligned.u32 224;");
    PSTAMP(0);
    const uint32_t dAx = descA(H0) + p * 4096;
    const uint32_t Hn = H1 - p * 65536;
    const uint32_t moff = ((lane & 7) + ((lane >> 3) & 1) * 8) * 128 + (((lane >> 4) ^ (lane & 7)) << 4);
    const uint32_t Xw = H0 + p * 65536 + w * 2048;
    uint32_t cv[8][4];
    if (p == 1) {
      mbar_wait(BAR + B_FKV * 8);
      const __nv_bfloat16* wr = wqkvp + (size_t)(g * 32 + (lane >> 3) * 8) * (3 * D_) + min(w, 2) * D_ + j * 64 + (lane & 7) * 8;
#pragma unroll
      for (int i = 0; i < 8; i++) ldg128_nc(cv[i], wr + (size_t)i * 3 * D_);
      mbar_wait(BAR + B_LAG * 8);
    }

    float akv[64];
    auto kvstep = [&](int kb) {
      mbar_wait(BAR + (B_FX + p * 8 + kb) * 8);
      mbar_wait(BAR + (B_FKV + kb) * 8);
      if (kb == 0) PSTAMP(2);
      const uint32_t da = dAx + kb * 512, db = descB(RING) + (kb < 6 ? kb : kb - 6) * 1024;
      wg_fence();
      wgmma_ss_n128(akv, da, db, kb);
#pragma unroll
      for (int k = 1; k < 4; k++) wgmma_ss_n128(akv, da + k * 2, db + k * 128, 1);
      wg_commit();
      if (kb == LAG_KB - 1) mbar_arrive_if(BAR + B_LAG * 8, p == 0 && lane == 0);
      wg_wait<1>();
      if (kb > 0) mbar_arrive_if(BAR + (B_EKV + kb - 1) * 8, lane == 0);
    };
    static_assert(LAG_KB <= CS_KB, "the lag signal lives in the peeled steps");
#pragma unroll
    for (int kb = 0; kb < CS_KB; kb++) kvstep(kb);
    mbar_wait(BAR + B_CLR1 * 8);
    const uint32_t tag = lds32(TAGS);
    if (p == 1) {
      PSTAMP(29);
      const uint32_t hm = 0xffff0000u | (tag >> 1), sh = 16 + (tag >> 1);
      float cs[8];
#pragma unroll
      for (int e = 0; e < 4; e++) {
        float a = 0.f, b = 0.f;
#pragma unroll
        for (int i = 0; i < 8; i++) { a += __uint_as_float(cv[i][e] << sh); b += __uint_as_float(cv[i][e] & hm); }
        cs[2 * e] = a; cs[2 * e + 1] = b;
      }
      const bool up = lane & 8;
#pragma unroll
      for (int e = 0; e < 4; e++) {
        const float keepv = up ? cs[4 + e] : cs[e], give = up ? cs[e] : cs[4 + e];
        cs[e] = keepv + __shfl_xor_sync(0xffffffffu, give, 8);
        cs[e] += __shfl_xor_sync(0xffffffffu, cs[e], 16);
      }
      if (lane < 16 && w < 3)
        ll_st(X + X_CS + ((j * 3 + w) * 16 + g) * 256 + (lane & 7) * 32 + (lane >> 3) * 16, __float_as_uint(cs[0]), __float_as_uint(cs[1]),
              __float_as_uint(cs[2]), __float_as_uint(cs[3]), tag);
      PSTAMP(1);
    }
#pragma unroll 1
    for (int kb = CS_KB; kb < 8; kb++) kvstep(kb);
    asm volatile("barrier.cluster.wait.aligned;" ::: "memory");
    uint32_t xres[4][4];
#pragma unroll
    for (int u = 0; u < 4; u++) ldsm4(xres[u], Xw + j * 8192 + (moff ^ (u << 5)));
    gptr const xl = X + (lane * 16 + (tag >> 1));
    gptr const rec = xl + (g * 8 + warp) * REC;
    gptr const recs = rec + (r * 16 - lane * 16);

    float aq[32];
    const bool exw = (lane == 0 && p == 0) || (xres[0][0] & xres[1][0] & xres[2][0] & xres[3][0] & zero) != 0;
    auto qstep = [&](int i) {
      mbar_wait(BAR + (B_FQ + i) * 8);
      wg_fence();
#pragma unroll
      for (int k = 0; k < 8; k++)
        wgmma_ss_n64(aq, dAx + i * 1024 + (k >> 2) * 512 + (k & 3) * 2, descB(RING + 32768) + i * 1024 + k * 128, i | k);
      wg_commit();
      wg_wait<1>();
      mbar_arrive_if(BAR + (B_EQ + i - 1) * 8, lane == 0);
      if (i) mbar_arrive_if(BAR + (B_EX + i - 1) * 8, exw);
    };
    uint32_t sv[2][4];
    gptr const stsrc = X + (X_ST + (g * 128 + 2 * (16 * w + r) + p) * 16);
    ll_issue<2>(sv, stsrc, 256);
    qstep(0);
    keep(akv);
    PSTAMP(3);
    mbar_wait(BAR + B_READY * 8);
    if (__builtin_expect(ll_bad<2>(sv, pin(tag, zero)), 0)) ll_spin<2>(sv, stsrc, 256, tag);
    PSTAMP(19);
    const float2 st0 = make_float2(__uint_as_float(sv[0][0] & ~1u), __uint_as_float(sv[0][1]));
    const float2 st1 = make_float2(__uint_as_float(sv[1][0] & ~1u), __uint_as_float(sv[1][1]));
    uint32_t hi[4][4], lo[4][4];
    {
      uint32_t cs[8][4];
#pragma unroll
      for (int i = 0; i < 8; i++) lds128(cs[i], CS + 256 + c * 128 + i * 16);
      auto cvt = [&](uint32_t (&d)[4][4], int ofs, const float2& st) {
#pragma unroll
        for (int b = 0; b < 16; b++) {
          const float cx = __uint_as_float(cs[b >> 1][(b & 1) * 2]), cy = __uint_as_float(cs[b >> 1][(b & 1) * 2 + 1]);
          const uint32_t v = pack2(fmaf(-st.x, cx, akv[4 * b + ofs]) * st.y, fmaf(-st.x, cy, akv[4 * b + ofs + 1]) * st.y);
          d[b >> 2][b & 3] = b < 8 ? v : movm(v);
        }
        keep(d);
      };
      cvt(hi, 2, st1);
      if (w == 3) {
#pragma unroll
        for (int i = 0; i < 4; i++) ll_st(xl + (X_E1 + ((g * 8 + j) * 2 + p) * 2048 + i * 512), hi[i][0], hi[i][1], hi[i][2], hi[i][3], tag);
      }
      PSTAMP(20);
      qstep(1);
      wg_bar(p);
#pragma unroll
      for (int i = 0; i < 4; i++) sts128(Xw + lane * 16 + i * 512, hi[i]);
      cvt(lo, 0, st0);
    }
    PSTAMP(21);
    qstep(2);
    wg_bar(p);
    uint32_t prev[4][4];
    gptr const halo = xl + (X_E1 + (((g - 1) * 8 + j) * 2 + p) * 2048);
    if (w > 0) {
#pragma unroll
      for (int i = 0; i < 4; i++) lds128(prev[i], Xw - 2048 + lane * 16 + i * 512);
    } else if (g > 0) {
      ll_issue<4>(prev, halo, 512);
    } else {
#pragma unroll
      for (int i = 0; i < 4; i++) { prev[i][0] = tag; prev[i][1] = 0; prev[i][2] = 0; prev[i][3] = 0; }
    }
    PSTAMP(22);
    qstep(3);
    fence_async_smem();
    __syncwarp();
    mbar_arrive_if(BAR + (B_EX + 4) * 8, exw);
    mbar_wait(BAR + B_WBAR * 8);
    PSTAMP(23);
    uint32_t cq[4][4], cw[4][4];
#pragma unroll
    for (int i = 0; i < 4; i++) { lds128(cq[i], CS + c * 64 + i * 16); lds128(cw[i], WB + c * 64 + i * 16); }
    if (w == 0) {
      if (__builtin_expect(ll_bad<4>(prev, pin(tag, zero)), 0)) ll_spin<4>(prev, halo, 512, tag);
      ll_clear<4>(prev);
    }
    gptr osrc[7];
#pragma unroll
    for (int i = 0; i < 7; i++) osrc[i] = rec + (uint32_t)(i >= j ? (i + 1) * 2048 : i * 2048);
    wg_wait<0>();
    keep(aq);
    mbar_arrive_if(BAR + (B_EQ + 3) * 8, lane == 0);
    mbar_arrive_if(BAR + (B_EX + 3) * 8, exw);
    PSTAMP(4);

    uint32_t of[4][4];
    float d0 = 0.f, d1 = 0.f;
    {
      const float sc = 0.25f * 1.4426950408889634f;
      const float sca = sc * st0.y, scb = sc * st1.y;
      const float nohalo = (g == 0 && w == 0) ? -INFINITY : 0.f;
      const bool up0 = 2 * c > r, up1 = 2 * c + 1 > r;
      const uint32_t mup = (up0 ? 0xffffu : 0u) | (up1 ? 0xffff0000u : 0u);
#pragma unroll
      for (int h = 0; h < 4; h++) {
        if (h == 2) {
          cq[2][0] = pin(cq[2][0], zero); cq[3][0] = pin(cq[3][0], zero);
        }
        uint32_t qf[4];
        {
          const float2 ca = make_float2(__uint_as_float(cq[h][0]), __uint_as_float(cq[h][1])), cb = make_float2(__uint_as_float(cq[h][2]), __uint_as_float(cq[h][3]));
          qf[0] = pack2(fmaf(-st0.x, ca.x, aq[8 * h + 0]), fmaf(-st0.x, ca.y, aq[8 * h + 1]));
          qf[1] = pack2(fmaf(-st1.x, ca.x, aq[8 * h + 2]), fmaf(-st1.x, ca.y, aq[8 * h + 3]));
          qf[2] = pack2(fmaf(-st0.x, cb.x, aq[8 * h + 4]), fmaf(-st0.x, cb.y, aq[8 * h + 5]));
          qf[3] = pack2(fmaf(-st1.x, cb.x, aq[8 * h + 6]), fmaf(-st1.x, cb.y, aq[8 * h + 7]));
        }
        const int i0 = h >> 1, e0 = (2 * h) & 3;
        float sp[4], sl[4], sh[4];
        mma16816(sp, qf, prev[i0][e0], prev[i0][e0 + 1]);
        mma16816(sl, qf, lo[i0][e0], lo[i0][e0 + 1]);
        mma16816(sh, qf, hi[i0][e0], hi[i0][e0 + 1]);
        float a0 = up0 ? sp[0] + nohalo : sl[0], a1 = up1 ? sp[1] + nohalo : sl[1];
        float b0 = up0 ? sl[2] : sh[2], b1 = up1 ? sl[3] : sh[3];
        float ma = fmaxf(a0, a1), mb = fmaxf(b0, b1);
        ma = fmaxf(ma, __shfl_xor_sync(0xffffffffu, ma, 1)); mb = fmaxf(mb, __shfl_xor_sync(0xffffffffu, mb, 1));
        ma = fmaxf(ma, __shfl_xor_sync(0xffffffffu, ma, 2)); mb = fmaxf(mb, __shfl_xor_sync(0xffffffffu, mb, 2));
        a0 = ex2((a0 - ma) * sca); a1 = ex2((a1 - ma) * sca); b0 = ex2((b0 - mb) * scb); b1 = ex2((b1 - mb) * scb);
        float sa = a0 + a1, sbb = b0 + b1;
        sa += __shfl_xor_sync(0xffffffffu, sa, 1); sbb += __shfl_xor_sync(0xffffffffu, sbb, 1);
        sa += __shfl_xor_sync(0xffffffffu, sa, 2); sbb += __shfl_xor_sync(0xffffffffu, sbb, 2);
        const float ia = rcp(sa), ib = rcp(sbb);
        const uint32_t pa = pack2(a0 * ia, a1 * ia), pb = pack2(b0 * ib, b1 * ib);
        const uint32_t pf[4] = {pa & mup, 0u, pa & ~mup, pb & mup};
        const uint32_t ph = pb & ~mup;
        float o0[4], o1[4];
        mma16816(o0, pf, prev[2 + i0][e0], lo[2 + i0][e0]);
        mma16816(o1, pf, prev[2 + i0][e0 + 1], lo[2 + i0][e0 + 1]);
        mma1688_acc(o0, 0u, ph, hi[2 + i0][e0]);
        mma1688_acc(o1, 0u, ph, hi[2 + i0][e0 + 1]);
        of[h][0] = pack2(o0[0], o0[1]); of[h][1] = pack2(o0[2], o0[3]);
        of[h][2] = pack2(o1[0], o1[1]); of[h][3] = pack2(o1[2], o1[3]);
        ll_st(rec + (uint32_t)(R_O + j * 2048) + h * 512, of[h][0], of[h][1], of[h][2], of[h][3], tag);
        const float2 wa = make_float2(__uint_as_float(cw[h][0]), __uint_as_float(cw[h][1])), wb = make_float2(__uint_as_float(cw[h][2]), __uint_as_float(cw[h][3]));
        d0 = fmaf(o0[0], wa.x, d0); d0 = fmaf(o0[1], wa.y, d0); d0 = fmaf(o1[0], wb.x, d0); d0 = fmaf(o1[1], wb.y, d0);
        d1 = fmaf(o0[2], wa.x, d1); d1 = fmaf(o0[3], wa.y, d1); d1 = fmaf(o1[2], wb.x, d1); d1 = fmaf(o1[3], wb.y, d1);
      }
    }
    PSTAMP(5);

    float ah[32];
    {
      uint32_t og[2][14][4];
      auto oissue = [&](int hp) {
#pragma unroll
        for (int i = 0; i < 14; i++) ll_ld(og[hp][i], osrc[i >> 1] + (R_O + (2 * hp + (i & 1)) * 512));
        if (hp == 1) ll_issue<2>(sv, recs + (R_OS + c * 256), 128);
      };
      auto omma = [&](int hp) {
        ll_clear<14>(og[hp]);
        keep(og[hp]);
        wg_fence();
#pragma unroll
        for (int i = 0; i < 14; i++) wgmma_rs_n64(ah, og[hp][i], descB(H0) + kb_at((i >> 1) + 1, j) * 512 + (2 * hp + (i & 1)) * 128, 1);
        wg_commit();
      };
      if (O_SLEEP) __nanosleep(O_SLEEP);
      oissue(0);
#pragma unroll
      for (int o = 1; o <= 2; o <<= 1) { d0 += __shfl_xor_sync(0xffffffffu, d0, o); d1 += __shfl_xor_sync(0xffffffffu, d1, o); }
      if (c == 0) ll_st(recs + (uint32_t)(R_OS + j * 128), __float_as_uint(d0), __float_as_uint(d1), 0, 0, tag);
      unpack32(ah, xres);
      mbar_wait(BAR + B_FWO * 8);
      keep(ah); keep(of);
      wg_fence();
#pragma unroll
      for (int k = 0; k < 4; k++) wgmma_rs_n64(ah, of[k], descB(H0) + j * 512 + k * 128, 1);
      wg_commit();
      uint32_t it = 0;
      if (__builtin_expect(ll_bad<14>(og[0], pin(tag, zero)), 0)) {
#pragma unroll 1
        do { oissue(0); } while (ll_bad<14>(og[0], tag) && ++it < SPIN_LIMIT);
      }
      PSTAMP(6);
      oissue(1);
      omma(0);
      if (__builtin_expect(ll_bad2<14, 2>(og[1], sv, pin(tag, zero)), 0)) {
#pragma unroll 1
        do { oissue(1); } while (ll_bad2<14, 2>(og[1], sv, tag) && ++it < SPIN_LIMIT);
      }
      PSTAMP(16);
      mbar_arrive_if(BAR + B_OG * 8, lane == 0 && p == 0);
      omma(1);
      ll_clear<2>(sv);
    }
    float m0 = __uint_as_float(sv[0][0]) + __uint_as_float(sv[1][0]), m1 = __uint_as_float(sv[0][1]) + __uint_as_float(sv[1][1]);
#pragma unroll
    for (int o = 1; o <= 2; o <<= 1) { m0 += __shfl_xor_sync(0xffffffffu, m0, o); m1 += __shfl_xor_sync(0xffffffffu, m1, o); }
    const uint32_t mu0 = pack2(m0 + st0.x, m0 + st0.x), mu1 = pack2(m1 + st1.x, m1 + st1.x);
    mbar_wait(BAR + B_CLRH * 8);
    wg_wait<0>();
    keep(ah);
    mbar_arrive_if(BAR + B_WODONE * 8, lane == 0);
    PSTAMP(7);

    uint32_t hf[4][4], ra[4][4];
    pack32(hf, ah);
#pragma unroll
    for (int u = 0; u < 4; u++) {
      ra[u][0] = hsub2(hf[u][0], mu0) & ~1u; ra[u][1] = hsub2(hf[u][1], mu1);
      ra[u][2] = hsub2(hf[u][2], mu0); ra[u][3] = hsub2(hf[u][3], mu1);
      ll_st(rec + (uint32_t)(R_H + j * 2048) + u * 512, ra[u][0], ra[u][1], ra[u][2], ra[u][3], tag);
    }
    mbar_wait(BAR + (p == 0 ? B_EQ + 3 : B_WODONE) * 8);
    PSTAMP(8);

    float rs0, rs1;
    auto swiglu = [&](float g0, float g1, float u0, float u1, float rs) -> uint32_t {
      const float hr = 0.5f * rs;
      const float x0 = g0 * hr, x1 = g1 * hr;
      const float t0 = tanhf_hw(x0), t1 = tanhf_hw(x1);
      return pack2(fmaf(x0, t0, x0) * (u0 * rs), fmaf(x1, t1, x1) * (u1 * rs));
    };
    uint32_t hA[6][4];
    {
      float a1[64], a2[32];
      uint32_t rb[4][4], rc[4][4], rd[4][4];
      auto fetch = [&](uint32_t (&a)[4][4], int i) { ll_issue<4>(a, osrc[i - 1] + R_H, 512); };
      auto check = [&](uint32_t (&a)[4][4], uint32_t (&b)[4][4], int i) {
        if (__builtin_expect(ll_bad2<4, 4>(a, b, pin(tag, zero)), 0)) {
          uint32_t it = 0;
#pragma unroll 1
          do { fetch(a, i); fetch(b, i + 1); } while (ll_bad2<4, 4>(a, b, tag) && ++it < SPIN_LIMIT);
        }
        ll_clear<4>(a); ll_clear<4>(b);
        keep(a); keep(b);
      };
      auto head = [&](uint32_t (&a)[4][4], int i) {
        mbar_wait(BAR + (B_FA + i) * 8);
        wg_fence();
        wgmma_rs_n64<DESC_HI64>(a2, a[0], descBh(RING + 16384) + (i & 3) * 1536, i);
        wgmma_rs_n128(a1, a[0], descB(RING) + (i & 3) * 1536, i);
        wg_commit();
#pragma unroll
        for (int u = 0; u < 4; u++) stsm4(Hn + w * 2048 + i * 8192 + (moff ^ (u << 5)), a[u]);
        wg_wait<1>();
        if (i > 0) mbar_arrive_if(BAR + (B_EA + i - 1) * 8, lane == 0);
      };
      auto rest = [&](uint32_t (&a)[4][4], int i) {
        wg_fence();
#pragma unroll
        for (int k = 1; k < 4; k++) {
          wgmma_rs_n64<DESC_HI64>(a2, a[k], descBh(RING + 16384) + (i & 3) * 1536 + k * 64, 1);
          wgmma_rs_n128(a1, a[k], descB(RING) + (i & 3) * 1536 + k * 128, 1);
        }
        wg_commit();
      };
      keep(ra);
      head(ra, 0); rest(ra, 0);
      {
        float s0 = 0.f, q0 = 0.f, s1 = 0.f, q1 = 0.f;
#pragma unroll
        for (int b = 0; b < 8; b++) {
          s0 += ah[4 * b] + ah[4 * b + 1]; s1 += ah[4 * b + 2] + ah[4 * b + 3];
          q0 = fmaf(ah[4 * b], ah[4 * b], q0); q0 = fmaf(ah[4 * b + 1], ah[4 * b + 1], q0);
          q1 = fmaf(ah[4 * b + 2], ah[4 * b + 2], q1); q1 = fmaf(ah[4 * b + 3], ah[4 * b + 3], q1);
        }
        if (H_SLEEP) __nanosleep(H_SLEEP);
        fetch(rb, 1);
#pragma unroll
        for (int o = 1; o <= 2; o <<= 1) {
          s0 += __shfl_xor_sync(0xffffffffu, s0, o); q0 += __shfl_xor_sync(0xffffffffu, q0, o);
          s1 += __shfl_xor_sync(0xffffffffu, s1, o); q1 += __shfl_xor_sync(0xffffffffu, q1, o);
        }
        if (c == 0) ll_st(recs + (uint32_t)(R_HS + j * 128), __float_as_uint(s0), __float_as_uint(q0), __float_as_uint(s1), __float_as_uint(q1), tag);
      }
      if (ll_bad<4>(rb, pin(tag, zero))) {
        ll_spin<4>(rb, osrc[0] + R_H, 512, tag);
      }
      ll_clear<4>(rb);
      keep(rb);
      PSTAMP(17);
      fetch(rc, 2); fetch(rd, 3);
      head(rb, 1); rest(rb, 1);
      check(rc, rd, 2);
      head(rc, 2); fetch(ra, 4); fetch(rb, 5); rest(rc, 2);
      head(rd, 3); rest(rd, 3);
      check(ra, rb, 4);
      head(ra, 4); fetch(rc, 6); fetch(rd, 7); ll_issue<2>(sv, recs + (R_HS + c * 256), 128); rest(ra, 4);
      head(rb, 5); rest(rb, 5);
      check(rc, rd, 6);
      head(rc, 6); rest(rc, 6);
      head(rd, 7); rest(rd, 7);
      fence_async_smem();
      ll_wait<2>(sv, recs + (R_HS + c * 256), 128, tag);
      float s0 = __uint_as_float(sv[0][0]) + __uint_as_float(sv[1][0]), q0 = __uint_as_float(sv[0][1]) + __uint_as_float(sv[1][1]);
      float s1 = __uint_as_float(sv[0][2]) + __uint_as_float(sv[1][2]), q1 = __uint_as_float(sv[0][3]) + __uint_as_float(sv[1][3]);
#pragma unroll
      for (int o = 1; o <= 2; o <<= 1) {
        s0 += __shfl_xor_sync(0xffffffffu, s0, o); q0 += __shfl_xor_sync(0xffffffffu, q0, o);
        s1 += __shfl_xor_sync(0xffffffffu, s1, o); q1 += __shfl_xor_sync(0xffffffffu, q1, o);
      }
      s0 *= 1.f / D_; s1 *= 1.f / D_;
      rs0 = rsqrtf(fmaxf(fmaf(-s0, s0, q0 * (1.f / D_)), 0.f) + 1e-5f);
      rs1 = rsqrtf(fmaxf(fmaf(-s1, s1, q1 * (1.f / D_)), 0.f) + 1e-5f);
      wg_wait<0>();
      keep(a1); keep(a2);
      mbar_arrive_if(BAR + (B_EA + 7) * 8, lane == 0);
      PSTAMP(9);
#pragma unroll
      for (int u = 0; u < 4; u++)
#pragma unroll
        for (int e = 0; e < 4; e++)
          hA[u][e] = swiglu(a1[8 * u + 2 * e], a1[8 * u + 2 * e + 1], a1[32 + 8 * u + 2 * e], a1[33 + 8 * u + 2 * e], (e & 1) ? rs1 : rs0);
#pragma unroll
      for (int u = 0; u < 2; u++)
#pragma unroll
        for (int e = 0; e < 4; e++)
          hA[4 + u][e] = swiglu(a2[8 * u + 2 * e], a2[8 * u + 2 * e + 1], a2[16 + 8 * u + 2 * e], a2[17 + 8 * u + 2 * e], (e & 1) ? rs1 : rs0);
      keep(hA);
      wg_bar(p);
    }
    PSTAMP(10);

    const uint32_t mbx = Hn + 32768 + w * 512 + lane * 16;
    auto send = [&](const uint32_t (&v)[4], uint32_t a, int part) {
      asm volatile("st.async.weak.shared::cluster.mbarrier::complete_tx::bytes.v4.b32 [%0], {%1,%2,%3,%4}, [%5];"
                   ::"r"(a + peer()), "r"(v[0]), "r"(v[1]), "r"(v[2]), "r"(v[3]), "r"(BAR + (B_HX + 2 * part + p) * 8 + peer()) : "memory");
    };
    uint32_t hB[8][4];
    {
      float ab[128];
      uint32_t db = descB(RING);
      const uint32_t dAn = descA(H1) - p * 4096;
      if (lane == 0 && w == 0) { mbar_expect_tx(BAR + (B_HX + p) * 8, 12288); mbar_expect_tx(BAR + (B_HX + 2 + p) * 8, 16384); }
#pragma unroll 1
      for (int i = 0; i < 8; i++) {
        mbar_wait(BAR + (B_FB + i) * 8);
        const uint32_t da = dAn + i * 512;
        wg_fence();
        wgmma_ss_n256(ab, da, db, i);
#pragma unroll
        for (int k = 1; k < 4; k++) wgmma_ss_n256(ab, da + k * 2, db + k * 128, 1);
        wg_commit();
        if (i == 7) {
          mbar_wait_cluster(BAR + (B_PF + p) * 8);
#pragma unroll
          for (int k = 0; k < 6; k++) send(hA[k], mbx + k * 2048, 0);
        }
        wg_wait<1>();
        mbar_arrive_if(BAR + (B_EB + i - 1) * 8, i > 0 && lane == 0);
        if (i == 6 && lane == 0) mbar_arrive_peer(BAR + (B_PF + p) * 8);
        db = db == descB(RING + 65536) ? descB(RING) : db + 2048;
      }
      wg_wait<0>();
      keep(ab);
      mbar_arrive_if(BAR + (B_EB + 7) * 8, lane == 0);
      if (lane == 0) mbar_arrive_peer(BAR + (B_PF + 2 + p) * 8);
      PSTAMP(11);
#pragma unroll
      for (int u = 0; u < 8; u++) {
        const int o = (u >> 2) * 64 + (u & 3) * 8;
#pragma unroll
        for (int e = 0; e < 4; e++)
          hB[u][e] = swiglu(ab[o + 2 * e], ab[o + 2 * e + 1], ab[o + 32 + 2 * e], ab[o + 33 + 2 * e], (e & 1) ? rs1 : rs0);
      }
      keep(hB);
    }
    PSTAMP(12);

    {
      float ya[32], y[32];
      uint32_t hP[14][4];
      const uint32_t offA = (j & 1) ? 256 : 0, offH = (j & 1) ? 0 : 1536;
      gptr const e4 = xl + (X_E4 + g * 24 * 16384 + warp * 2048);
      const uint32_t stg = H0 + p * 65536 + 28672 + (w >> 1) * 32768 + (w & 1) * 2048;
      auto mm = [&](float (&d)[32], int m, int k0, int k1) {
        if (k0 == 0) mbar_wait(BAR + (B_FT + m) * 8);
        const uint32_t T = descB(0) + (t_addr(m) >> 4);
        const uint32_t oA = w2_peer(m) ? 256 - offA : offA, oH = w2_peer(m) ? 1536 - offH : offH;
        wg_fence();
#pragma unroll
        for (int k = k0; k < k1; k++) {
          const uint32_t db = T + (k < 4 ? oA + k * 128 : k < 6 ? oH + (k - 4) * 128 : oA + 512 + (k - 6) * 128);
          if (w2_peer(m)) wgmma_rs_n64(d, hP[k], db, 1);
          else if (k < 6) wgmma_rs_n64(d, hA[k], db, k);
          else wgmma_rs_n64(d, hB[k - 6], db, 1);
        }
        wg_commit();
      };
      auto next = [&](float (&d)[32], int m, float (&dp)[32], int q) {
        mm(d, m, 0, 3);
        wg_wait<1>();
        keep(dp);
        mbar_arrive_if(BAR + (B_ET0 + q) * 8, lane == 0);
        gptr dst = e4 + (uint32_t)((((j + 2 + 2 * q) & 7) * 3 + q) * 16384);
#pragma unroll
        for (int u = 0; u < 4; u++)
          ll_st(dst + u * 512, pack2(dp[8 * u], dp[8 * u + 1]), pack2(dp[8 * u + 2], dp[8 * u + 3]),
                pack2(dp[8 * u + 4], dp[8 * u + 5]), pack2(dp[8 * u + 6], dp[8 * u + 7]), tag);
        if (q == 2) mbar_wait(BAR + (B_ET0 + 2) * 8);
        mm(d, m, 3, 14);
      };
      mbar_wait_cluster(BAR + (B_PF + 2 + p) * 8);
#pragma unroll
      for (int i = 0; i < 4; i++) {
        const uint32_t a = i ? pin(mbx, zero) : mbx;
        send(hB[2 * i], a + (6 + 2 * i) * 2048, 1);
        send(hB[2 * i + 1], a + (7 + 2 * i) * 2048, 1);
        if (i < 3) mm(ya, 0, 5 * i, i < 2 ? 5 * i + 5 : 14);
        else mm(y, 1, 0, 6);
      }
      mbar_wait_cluster(BAR + (B_HX + p) * 8);
#pragma unroll
      for (int k = 0; k < 6; k++) lds128(hP[k], mbx + k * 2048);
      mm(y, 1, 6, 14);
      keep(hP[0]); keep(hP[1]); keep(hP[2]); keep(hP[3]); keep(hP[4]); keep(hP[5]);
      mm(ya, 2, 0, 3);
      PSTAMP(18);
      mbar_wait_cluster(BAR + (B_HX + 2 + p) * 8);
      PSTAMP(24);
#pragma unroll
      for (int k = 6; k < 14; k++) lds128(hP[k], mbx + k * 2048);
      mm(ya, 2, 3, 6);
      keep(hP);
      mm(ya, 2, 6, 14);
      mbar_arrive_if(BAR + (B_HC + p) * 8, lane == 0);
      mbar_wait(BAR + B_CLR4 * 8);
      next(y, 3, ya, 0);
      PSTAMP(27);
      next(ya, 4, y, 1);
      mbar_arrive_if(BAR + (B_ET0 + 3) * 8, lane == 0);
      mm(ya, 5, 0, 14);
      PSTAMP(26);
      next(y, 6, ya, 2);
      PSTAMP(28);
      uint32_t in[8][4], lt[4][4];
      gptr const insrc = e4 + (uint32_t)(j * 3 * 16384);
      mm(y, 7, 0, 9);
      ll_issue<4>(lt, insrc + 32768, 512);
      mbar_wait(BAR + B_FIN * 8);
#pragma unroll
      for (int u = 0; u < 8; u++) lds128(in[u], t_addr(1 + (u >> 2)) + warp * 2048 + lane * 16 + (u & 3) * 512);
      mm(y, 7, 9, 14);
      if (__builtin_expect(ll_bad<8>(in, tag), 0)) {
        uint32_t it = 0;
#pragma unroll 1
        do {
#pragma unroll
          for (int u = 0; u < 8; u++) ll_ld(in[u], insrc + ((u >> 2) * 16384 + (u & 3) * 512));
        } while (ll_bad<8>(in, tag) && ++it < SPIN_LIMIT);
      }
      ll_clear<8>(in);
      const uint32_t ident = (2 * c == r ? 0x3f80u : 0u) | (2 * c + 1 == r ? 0x3f800000u : 0u);
      auto acc = [&](const uint32_t (&v)[4], int u) {
        mma1688_acc(*reinterpret_cast<float (*)[4]>(&y[8 * u]), v[0], v[1], ident);
        mma1688_acc(*reinterpret_cast<float (*)[4]>(&y[8 * u + 4]), v[2], v[3], ident);
      };
      wg_wait<0>();
      keep(y);
      PSTAMP(13);
#pragma unroll
      for (int u = 0; u < 4; u++) acc(hf[u], u);
#pragma unroll
      for (int u = 0; u < 8; u++) acc(in[u], u & 3);
      PSTAMP(25);
      if (ll_bad<4>(lt, pin(tag, zero))) {
        ll_spin<4>(lt, insrc + 32768, 512, tag);
      }
      ll_clear<4>(lt);
#pragma unroll
      for (int u = 0; u < 4; u++) acc(lt[u], u);
      PSTAMP(14);
#pragma unroll
      for (int u = 0; u < 4; u++) {
        uint32_t o[4];
#pragma unroll
        for (int e = 0; e < 4; e++) o[e] = pack2(y[8 * u + 2 * e], y[8 * u + 2 * e + 1]);
        stsm4(stg + (moff ^ (u << 5)), o);
      }
      fence_async_smem();
      __syncwarp();
      if (elect_one()) {
        tma3d_store(&P.out, stg, 64 * j, p, g * 64 + 16 * w);
        asm volatile("cp.async.bulk.commit_group;" ::: "memory");
        asm volatile("cp.async.bulk.wait_group.read 0;" ::: "memory");
      }
      PSTAMP(15);
    }
  }
}

typedef CUresult (*EncodeFn)(CUtensorMap*, CUtensorMapDataType, cuuint32_t, void*, const cuuint64_t*, const cuuint64_t*,
                             const cuuint32_t*, const cuuint32_t*, CUtensorMapInterleave, CUtensorMapSwizzle,
                             CUtensorMapL2promotion, CUtensorMapFloatOOBfill);

void enc2d(EncodeFn f, CUtensorMap* m, const void* base, uint64_t cols, uint64_t rows, uint32_t bc, uint32_t br, CUtensorMapSwizzle sw) {
  cuuint64_t gd[2] = {cols, rows}, gs[1] = {cols * 2};
  cuuint32_t bd[2] = {bc, br}, es[2] = {1, 1};
  f(m, CU_TENSOR_MAP_DATA_TYPE_BFLOAT16, 2, const_cast<void*>(base), gd, gs, bd, es, CU_TENSOR_MAP_INTERLEAVE_NONE, sw,
    CU_TENSOR_MAP_L2_PROMOTION_L2_128B, CU_TENSOR_MAP_FLOAT_OOB_FILL_NONE);
}
void enc_par(EncodeFn f, CUtensorMap* m, const void* base, uint32_t pairs) {
  cuuint64_t gd[3] = {(cuuint64_t)D_, 2, (cuuint64_t)S_ / 2}, gs[2] = {D_ * 2, D_ * 4};
  cuuint32_t bd[3] = {64, 1, pairs}, es[3] = {1, 1, 1};
  f(m, CU_TENSOR_MAP_DATA_TYPE_BFLOAT16, 3, const_cast<void*>(base), gd, gs, bd, es, CU_TENSOR_MAP_INTERLEAVE_NONE,
    CU_TENSOR_MAP_SWIZZLE_128B, CU_TENSOR_MAP_L2_PROMOTION_L2_128B, CU_TENSOR_MAP_FLOAT_OOB_FILL_NONE);
}

}

extern "C" void kernel_launch(void* const* d_in, const int* in_sizes, int n_in, void* d_out, int out_size) {
  (void)in_sizes; (void)n_in; (void)out_size;
  static EncodeFn enc = nullptr;
  static char* scratch = nullptr;
  if (!enc) {
    void* fn = nullptr;
    cudaDriverEntryPointQueryResult q;
    cudaGetDriverEntryPoint("cuTensorMapEncodeTiled", &fn, cudaEnableDefault, &q);
    enc = (EncodeFn)fn;
    cudaGetSymbolAddress((void**)&scratch, g_scratch);
    cudaFuncSetAttribute(fused_block_kernel, cudaFuncAttributeMaxDynamicSharedMemorySize, SMEM_BYTES);
  }
  Params P;
  const __nv_bfloat16* xp = (const __nv_bfloat16*)d_in[0];
  const __nv_bfloat16* wqkvp = (const __nv_bfloat16*)d_in[1];
  const __nv_bfloat16* wop = (const __nv_bfloat16*)d_in[2];
  P.w1p = (const __nv_bfloat16*)d_in[4];
  P.w3p = (const __nv_bfloat16*)d_in[5];
  P.w2p = (const __nv_bfloat16*)d_in[6];
  enc_par(enc, &P.x, xp, 64);
  enc_par(enc, &P.out, d_out, 16);
  enc2d(enc, &P.wqkv, wqkvp, 3 * D_, D_, 64, 64, CU_TENSOR_MAP_SWIZZLE_128B);
  enc2d(enc, &P.wo, wop, D_, D_, 64, 64, CU_TENSOR_MAP_SWIZZLE_128B);
  enc2d(enc, &P.w1, P.w1p, F_, D_, 64, 64, CU_TENSOR_MAP_SWIZZLE_128B);
  enc2d(enc, &P.w3, P.w3p, F_, D_, 64, 64, CU_TENSOR_MAP_SWIZZLE_128B);
  enc2d(enc, &P.w1h, P.w1p, F_, D_, 32, 64, CU_TENSOR_MAP_SWIZZLE_64B);
  enc2d(enc, &P.w3h, P.w3p, F_, D_, 32, 64, CU_TENSOR_MAP_SWIZZLE_64B);
  enc2d(enc, &P.w2, P.w2p, D_, F_, 64, 224, CU_TENSOR_MAP_SWIZZLE_128B);

  cudaLaunchConfig_t cfg = {};
  cfg.gridDim = dim3(128);
  cfg.blockDim = dim3(384);
  cfg.dynamicSmemBytes = SMEM_BYTES;
  cfg.stream = cudaStreamPerThread;
  cudaLaunchAttribute at[2];
  at[0].id = cudaLaunchAttributeCooperative;
  at[0].val.cooperative = 1;
  cfg.attrs = at;
  cfg.numAttrs = 1;
  at[1].id = cudaLaunchAttributeClusterDimension;
  at[1].val.clusterDim.x = 2; at[1].val.clusterDim.y = 1; at[1].val.clusterDim.z = 1;
  cfg.numAttrs = 2;
  cudaLaunchKernelEx(&cfg, fused_block_kernel, scratch, xp, wqkvp, wop, 0u, P);
}
```

```cpp
#include <cuda_runtime.h>
#include <cuda.h>
#include <cuda_bf16.h>
#include <stdint.h>
#include <stddef.h>

namespace {

constexpr int S_ = 2048, D_ = 512, F_ = 1792;
#define TOP_KB 1
#define SIDE_EARLY 0
#define CS_KB 3
#define CMAP 4
#define A_HOLD 9
#define B1_LATE 1
#define PF_KIND 128
#define PF_SLEEP 250
#define WO7_AT 1
#define CLSCOPE ""
#define PFV 0
#define PF_WHEN B_HALO
#define O_SLEEP 0
#define H_SLEEP 200

constexpr uint32_t SPIN_LIMIT = 1u << 18;

constexpr uint32_t R_O = 0;
constexpr uint32_t R_H = 16384;
constexpr uint32_t R_OS = 32768;
constexpr uint32_t R_HS = 33792;
constexpr uint32_t REC = 34816;
constexpr uint32_t X_E4 = 128 * REC;
constexpr uint32_t X_E1 = X_E4 + 16 * 24 * 16384;
constexpr uint32_t X_CS = X_E1 + 256 * 2048;
constexpr uint32_t X_ST = X_CS + 384 * 256;
constexpr uint32_t X_WB = X_ST + 2048 * 16;
constexpr uint32_t X_EP = X_WB + 512 * 16;
__device__ __align__(1024) char g_scratch[X_EP + 512];
#define PSTAMP(i)
#define PSTAMPX(i)
#define PSTAMPW(slot, i)

struct alignas(64) Params {
  CUtensorMap x, out, wqkv, wo, w1, w3, w1h, w3h, w2;
  const __nv_bfloat16 *w1p, *w3p, *w2p;
};

constexpr uint32_t SB = 1024;
constexpr uint32_t H0 = SB;
constexpr uint32_t H1 = SB + 65536;
constexpr uint32_t RING = SB + 131072;
constexpr uint32_t BAR = SB + 229376;
constexpr uint32_t TAGS = BAR + 1016;
constexpr uint32_t WB = BAR + 1024;
constexpr uint32_t SMEM_BYTES = 232448;
static_assert(WB + 256 <= SB + SMEM_BYTES, "smem");

enum : int {
  B_FX = 0,
  B_FW = 16,
  B_TAG = 24, B_CLRH = 25,
  B_FWO = 32,
  B_FIN = 33,
  B_HX = 35,
  B_FA = 40, B_FB = 48, B_FT = 56,
  B_EW = 64, B_XDONE = 72, B_EA = 80, B_EB = 88,
  B_ET0 = 96,
  B_WODONE = 103,
  B_EX = 104,
  B_PF = 112,
  B_HC = 116,

  B_READY = 120,
  B_HALO = 124,
  B_CLRO = 121,
  B_CLR1 = 122,
  B_CLR4 = 123
};

__device__ __forceinline__ uint32_t smem_u32(const void* p) { return (uint32_t)__cvta_generic_to_shared(p); }
__device__ __forceinline__ uint32_t own() { return (blockIdx.x & 1) << 24; }
__device__ __forceinline__ uint32_t peer() { return (~blockIdx.x & 1) << 24; }
__device__ __forceinline__ void mbar_init(uint32_t b, uint32_t c) { asm volatile("mbarrier.init.shared::cta.b64 [%0], %1;" ::"r"(b + own()), "r"(c) : "memory"); }
__device__ __forceinline__ void mbar_expect_tx(uint32_t b, uint32_t bytes) { asm volatile("mbarrier.arrive.expect_tx.shared::cta.b64 _, [%0], %1;" ::"r"(b + own()), "r"(bytes) : "memory"); }
__device__ __forceinline__ void mbar_arrive(uint32_t b) { asm volatile("mbarrier.arrive.shared::cta.b64 _, [%0];" ::"r"(b + own()) : "memory"); }
__device__ __forceinline__ void mbar_wait(uint32_t b) {
  asm volatile("{\n.reg .pred p;\n.reg .u32 c;\nmov.u32 c, 0;\nLW:\n.pragma \"nounroll\";\n"
               "mbarrier.try_wait.parity.shared::cta.b64 p, [%0], 0;\nadd.u32 c, c, 1;\nsetp.gt.or.u32 p, c, %1, p;\n@!p bra LW;\n}\n"
               ::"r"(b + own()), "n"(SPIN_LIMIT) : "memory");
}
__device__ __forceinline__ void mbar_arrive_peer(uint32_t b) {
  asm volatile("mbarrier.arrive.relaxed.cluster.shared::cluster.b64 _, [%0];" ::"r"(b + peer()) : "memory");
}
__device__ __forceinline__ void mbar_wait_cluster(uint32_t b) {
  asm volatile("{\n.reg .pred p;\n.reg .u32 c;\nmov.u32 c, 0;\nLW:\n.pragma \"nounroll\";\n"
               "mbarrier.try_wait.parity" CLSCOPE ".shared::cta.b64 p, [%0], 0;\nadd.u32 c, c, 1;\nsetp.gt.or.u32 p, c, %1, p;\n@!p bra LW;\n}\n"
               ::"r"(b + own()), "n"(SPIN_LIMIT) : "memory");
}
__device__ __forceinline__ bool elect_one() {
  uint32_t p;
  asm volatile("{\n.reg .pred P;\nelect.sync _|P, 0xffffffff;\nselp.u32 %0, 1, 0, P;\n}\n" : "=r"(p));
  return p;
}
__device__ __forceinline__ void tma2d(uint32_t dst, const CUtensorMap* m, int c0, int c1, uint32_t bar) {
  dst += own(); bar += own();
  asm volatile("cp.async.bulk.tensor.2d.shared::cluster.global.mbarrier::complete_tx::bytes [%0], [%1, {%3, %4}], [%2];"
               ::"r"(dst), "l"(m), "r"(bar), "r"(c0), "r"(c1) : "memory");
}
__device__ __forceinline__ void tma3d(uint32_t dst, const CUtensorMap* m, int c0, int c1, int c2, uint32_t bar) {
  dst += own(); bar += own();
  asm volatile("cp.async.bulk.tensor.3d.shared::cluster.global.mbarrier::complete_tx::bytes [%0], [%1, {%3, %4, %5}], [%2];"
               ::"r"(dst), "l"(m), "r"(bar), "r"(c0), "r"(c1), "r"(c2) : "memory");
}
__device__ __forceinline__ void tma3d_store(const CUtensorMap* m, uint32_t src, int c0, int c1, int c2) {
  asm volatile("cp.async.bulk.tensor.3d.global.shared::cta.bulk_group [%0, {%2, %3, %4}], [%1];"
               ::"l"(m), "r"(src + own()), "r"(c0), "r"(c1), "r"(c2) : "memory");
}
__device__ __forceinline__ void l2_prefetch(const void* p, uint32_t bytes) {
  asm volatile("cp.async.bulk.prefetch.L2.global [%0], %1;" ::"l"(p), "r"(bytes) : "memory");
}
__device__ __forceinline__ void prefetch_map(const CUtensorMap* m) { asm volatile("prefetch.tensormap [%0];" ::"l"(m) : "memory"); }
__device__ __forceinline__ void fence_async_smem() { asm volatile("fence.proxy.async.shared::cta;" ::: "memory"); }
__device__ __forceinline__ void wg_fence() { asm volatile("wgmma.fence.sync.aligned;" ::: "memory"); }
__device__ __forceinline__ void wg_commit() { asm volatile("wgmma.commit_group.sync.aligned;" ::: "memory"); }
template <int N> __device__ __forceinline__ void wg_wait() { asm volatile("wgmma.wait_group.sync.aligned %0;" ::"n"(N) : "memory"); }
__device__ __forceinline__ void wg_bar(int p) {
  if (p == 0) asm volatile("bar.sync 1, 128;" ::: "memory"); else asm volatile("bar.sync 2, 128;" ::: "memory");
}
constexpr uint32_t DESC_HI128 = (1024 >> 4) | (1u << 30);
constexpr uint32_t DESC_HI64 = (512 >> 4) | (2u << 30);
__device__ __forceinline__ constexpr uint32_t descA(uint32_t addr) { return (addr >> 4) | (1u << 16); }
__device__ __forceinline__ constexpr uint32_t descB(uint32_t addr) { return (addr >> 4) | ((8192u >> 4) << 16); }
__device__ __forceinline__ constexpr uint32_t descBh(uint32_t addr) { return (addr >> 4) | ((4096u >> 4) << 16); }

__device__ __forceinline__ void wgmma_ss_n192(float (&d)[96], uint32_t da, uint32_t db, int sc) {
  asm volatile("{\n.reg .pred p;\n.reg .b64 da, db;\nsetp.ne.b32 p, %98, 0;\nmov.b64 da, {%96, %99};\nmov.b64 db, {%97, %99};\n"
    "wgmma.mma_async.sync.aligned.m64n192k16.f32.bf16.bf16 {%0, %1, %2, %3, %4, %5, %6, %7, %8, %9, %10, %11, %12, %13, %14, %15, %16, %17, %18, %19, %20, %21, %22, %23, %24, %25, %26, %27, %28, %29, %30, %31, %32, %33, %34, %35, %36, %37, %38, %39, %40, %41, %42, %43, %44, %45, %46, %47, %48, %49, %50, %51, %52, %53, %54, %55, %56, %57, %58, %59, %60, %61, %62, %63, %64, %65, %66, %67, %68, %69, %70, %71, %72, %73, %74, %75, %76, %77, %78, %79, %80, %81, %82, %83, %84, %85, %86, %87, %88, %89, %90, %91, %92, %93, %94, %95}, da, db, p, 1, 1, 0, 1;\n}\n"
    : "+f"(d[0]), "+f"(d[1]), "+f"(d[2]), "+f"(d[3]), "+f"(d[4]), "+f"(d[5]), "+f"(d[6]), "+f"(d[7]),
      "+f"(d[8]), "+f"(d[9]), "+f"(d[10]), "+f"(d[11]), "+f"(d[12]), "+f"(d[13]), "+f"(d[14]), "+f"(d[15]),
      "+f"(d[16]), "+f"(d[17]), "+f"(d[18]), "+f"(d[19]), "+f"(d[20]), "+f"(d[21]), "+f"(d[22]), "+f"(d[23]),
      "+f"(d[24]), "+f"(d[25]), "+f"(d[26]), "+f"(d[27]), "+f"(d[28]), "+f"(d[29]), "+f"(d[30]), "+f"(d[31]),
      "+f"(d[32]), "+f"(d[33]), "+f"(d[34]), "+f"(d[35]), "+f"(d[36]), "+f"(d[37]), "+f"(d[38]), "+f"(d[39]),
      "+f"(d[40]), "+f"(d[41]), "+f"(d[42]), "+f"(d[43]), "+f"(d[44]), "+f"(d[45]), "+f"(d[46]), "+f"(d[47]),
      "+f"(d[48]), "+f"(d[49]), "+f"(d[50]), "+f"(d[51]), "+f"(d[52]), "+f"(d[53]), "+f"(d[54]), "+f"(d[55]),
      "+f"(d[56]), "+f"(d[57]), "+f"(d[58]), "+f"(d[59]), "+f"(d[60]), "+f"(d[61]), "+f"(d[62]), "+f"(d[63]),
      "+f"(d[64]), "+f"(d[65]), "+f"(d[66]), "+f"(d[67]), "+f"(d[68]), "+f"(d[69]), "+f"(d[70]), "+f"(d[71]),
      "+f"(d[72]), "+f"(d[73]), "+f"(d[74]), "+f"(d[75]), "+f"(d[76]), "+f"(d[77]), "+f"(d[78]), "+f"(d[79]),
      "+f"(d[80]), "+f"(d[81]), "+f"(d[82]), "+f"(d[83]), "+f"(d[84]), "+f"(d[85]), "+f"(d[86]), "+f"(d[87]),
      "+f"(d[88]), "+f"(d[89]), "+f"(d[90]), "+f"(d[91]), "+f"(d[92]), "+f"(d[93]), "+f"(d[94]), "+f"(d[95])
    : "r"(da), "r"(db), "r"(sc), "n"(DESC_HI128));
}
__device__ __forceinline__ void wgmma_ss_n256(float (&d)[128], uint32_t da, uint32_t db, int sc) {
  asm volatile("{\n.reg .pred p;\n.reg .b64 da, db;\nsetp.ne.b32 p, %130, 0;\nmov.b64 da, {%128, %131};\nmov.b64 db, {%129, %131};\n"
    "wgmma.mma_async.sync.aligned.m64n256k16.f32.bf16.bf16 {%0, %1, %2, %3, %4, %5, %6, %7, %8, %9, %10, %11, %12, %13, %14, %15, %16, %17, %18, %19, %20, %21, %22, %23, %24, %25, %26, %27, %28, %29, %30, %31, %32, %33, %34, %35, %36, %37, %38, %39, %40, %41, %42, %43, %44, %45, %46, %47, %48, %49, %50, %51, %52, %53, %54, %55, %56, %57, %58, %59, %60, %61, %62, %63, %64, %65, %66, %67, %68, %69, %70, %71, %72, %73, %74, %75, %76, %77, %78, %79, %80, %81, %82, %83, %84, %85, %86, %87, %88, %89, %90, %91, %92, %93, %94, %95, %96, %97, %98, %99, %100, %101, %102, %103, %104, %105, %106, %107, %108, %109, %110, %111, %112, %113, %114, %115, %116, %117, %118, %119, %120, %121, %122, %123, %124, %125, %126, %127}, da, db, p, 1, 1, 0, 1;\n}\n"
    : "+f"(d[0]), "+f"(d[1]), "+f"(d[2]), "+f"(d[3]), "+f"(d[4]), "+f"(d[5]), "+f"(d[6]), "+f"(d[7]),
      "+f"(d[8]), "+f"(d[9]), "+f"(d[10]), "+f"(d[11]), "+f"(d[12]), "+f"(d[13]), "+f"(d[14]), "+f"(d[15]),
      "+f"(d[16]), "+f"(d[17]), "+f"(d[18]), "+f"(d[19]), "+f"(d[20]), "+f"(d[21]), "+f"(d[22]), "+f"(d[23]),
      "+f"(d[24]), "+f"(d[25]), "+f"(d[26]), "+f"(d[27]), "+f"(d[28]), "+f"(d[29]), "+f"(d[30]), "+f"(d[31]),
      "+f"(d[32]), "+f"(d[33]), "+f"(d[34]), "+f"(d[35]), "+f"(d[36]), "+f"(d[37]), "+f"(d[38]), "+f"(d[39]),
      "+f"(d[40]), "+f"(d[41]), "+f"(d[42]), "+f"(d[43]), "+f"(d[44]), "+f"(d[45]), "+f"(d[46]), "+f"(d[47]),
      "+f"(d[48]), "+f"(d[49]), "+f"(d[50]), "+f"(d[51]), "+f"(d[52]), "+f"(d[53]), "+f"(d[54]), "+f"(d[55]),
      "+f"(d[56]), "+f"(d[57]), "+f"(d[58]), "+f"(d[59]), "+f"(d[60]), "+f"(d[61]), "+f"(d[62]), "+f"(d[63]),
      "+f"(d[64]), "+f"(d[65]), "+f"(d[66]), "+f"(d[67]), "+f"(d[68]), "+f"(d[69]), "+f"(d[70]), "+f"(d[71]),
      "+f"(d[72]), "+f"(d[73]), "+f"(d[74]), "+f"(d[75]), "+f"(d[76]), "+f"(d[77]), "+f"(d[78]), "+f"(d[79]),
      "+f"(d[80]), "+f"(d[81]), "+f"(d[82]), "+f"(d[83]), "+f"(d[84]), "+f"(d[85]), "+f"(d[86]), "+f"(d[87]),
      "+f"(d[88]), "+f"(d[89]), "+f"(d[90]), "+f"(d[91]), "+f"(d[92]), "+f"(d[93]), "+f"(d[94]), "+f"(d[95]),
      "+f"(d[96]), "+f"(d[97]), "+f"(d[98]), "+f"(d[99]), "+f"(d[100]), "+f"(d[101]), "+f"(d[102]), "+f"(d[103]),
      "+f"(d[104]), "+f"(d[105]), "+f"(d[106]), "+f"(d[107]), "+f"(d[108]), "+f"(d[109]), "+f"(d[110]), "+f"(d[111]),
      "+f"(d[112]), "+f"(d[113]), "+f"(d[114]), "+f"(d[115]), "+f"(d[116]), "+f"(d[117]), "+f"(d[118]), "+f"(d[119]),
      "+f"(d[120]), "+f"(d[121]), "+f"(d[122]), "+f"(d[123]), "+f"(d[124]), "+f"(d[125]), "+f"(d[126]), "+f"(d[127])
    : "r"(da), "r"(db), "r"(sc), "n"(DESC_HI128));
}
template <uint32_t HI = DESC_HI128>
__device__ __forceinline__ void wgmma_rs_n64(float (&d)[32], const uint32_t (&a)[4], uint32_t db, int sc) {
  asm volatile("{\n.reg .pred p;\n.reg .b64 db;\nsetp.ne.b32 p, %37, 0;\nmov.b64 db, {%36, %38};\n"
    "wgmma.mma_async.sync.aligned.m64n64k16.f32.bf16.bf16 {%0, %1, %2, %3, %4, %5, %6, %7, %8, %9, %10, %11, %12, %13, %14, %15, %16, %17, %18, %19, %20, %21, %22, %23, %24, %25, %26, %27, %28, %29, %30, %31}, {%32, %33, %34, %35}, db, p, 1, 1, 1;\n}\n"
    : "+f"(d[0]), "+f"(d[1]), "+f"(d[2]), "+f"(d[3]), "+f"(d[4]), "+f"(d[5]), "+f"(d[6]), "+f"(d[7]),
      "+f"(d[8]), "+f"(d[9]), "+f"(d[10]), "+f"(d[11]), "+f"(d[12]), "+f"(d[13]), "+f"(d[14]), "+f"(d[15]),
      "+f"(d[16]), "+f"(d[17]), "+f"(d[18]), "+f"(d[19]), "+f"(d[20]), "+f"(d[21]), "+f"(d[22]), "+f"(d[23]),
      "+f"(d[24]), "+f"(d[25]), "+f"(d[26]), "+f"(d[27]), "+f"(d[28]), "+f"(d[29]), "+f"(d[30]), "+f"(d[31])
    : "r"(a[0]), "r"(a[1]), "r"(a[2]), "r"(a[3]), "r"(db), "r"(sc), "n"(HI));
}
template <uint32_t HI = DESC_HI128>
__device__ __forceinline__ void wgmma_rs_n128(float (&d)[64], const uint32_t (&a)[4], uint32_t db, int sc) {
  asm volatile("{\n.reg .pred p;\n.reg .b64 db;\nsetp.ne.b32 p, %69, 0;\nmov.b64 db, {%68, %70};\n"
    "wgmma.mma_async.sync.aligned.m64n128k16.f32.bf16.bf16 {%0, %1, %2, %3, %4, %5, %6, %7, %8, %9, %10, %11, %12, %13, %14, %15, %16, %17, %18, %19, %20, %21, %22, %23, %24, %25, %26, %27, %28, %29, %30, %31, %32, %33, %34, %35, %36, %37, %38, %39, %40, %41, %42, %43, %44, %45, %46, %47, %48, %49, %50, %51, %52, %53, %54, %55, %56, %57, %58, %59, %60, %61, %62, %63}, {%64, %65, %66, %67}, db, p, 1, 1, 1;\n}\n"
    : "+f"(d[0]), "+f"(d[1]), "+f"(d[2]), "+f"(d[3]), "+f"(d[4]), "+f"(d[5]), "+f"(d[6]), "+f"(d[7]),
      "+f"(d[8]), "+f"(d[9]), "+f"(d[10]), "+f"(d[11]), "+f"(d[12]), "+f"(d[13]), "+f"(d[14]), "+f"(d[15]),
      "+f"(d[16]), "+f"(d[17]), "+f"(d[18]), "+f"(d[19]), "+f"(d[20]), "+f"(d[21]), "+f"(d[22]), "+f"(d[23]),
      "+f"(d[24]), "+f"(d[25]), "+f"(d[26]), "+f"(d[27]), "+f"(d[28]), "+f"(d[29]), "+f"(d[30]), "+f"(d[31]),
      "+f"(d[32]), "+f"(d[33]), "+f"(d[34]), "+f"(d[35]), "+f"(d[36]), "+f"(d[37]), "+f"(d[38]), "+f"(d[39]),
      "+f"(d[40]), "+f"(d[41]), "+f"(d[42]), "+f"(d[43]), "+f"(d[44]), "+f"(d[45]), "+f"(d[46]), "+f"(d[47]),
      "+f"(d[48]), "+f"(d[49]), "+f"(d[50]), "+f"(d[51]), "+f"(d[52]), "+f"(d[53]), "+f"(d[54]), "+f"(d[55]),
      "+f"(d[56]), "+f"(d[57]), "+f"(d[58]), "+f"(d[59]), "+f"(d[60]), "+f"(d[61]), "+f"(d[62]), "+f"(d[63])
    : "r"(a[0]), "r"(a[1]), "r"(a[2]), "r"(a[3]), "r"(db), "r"(sc), "n"(HI));
}
template <uint32_t HI = DESC_HI128>
__device__ __forceinline__ void wgmma_rs_n192(float (&d)[96], const uint32_t (&a)[4], uint32_t db, int sc) {
  asm volatile("{\n.reg .pred p;\n.reg .b64 db;\nsetp.ne.b32 p, %101, 0;\nmov.b64 db, {%100, %102};\n"
    "wgmma.mma_async.sync.aligned.m64n192k16.f32.bf16.bf16 {%0, %1, %2, %3, %4, %5, %6, %7, %8, %9, %10, %11, %12, %13, %14, %15, %16, %17, %18, %19, %20, %21, %22, %23, %24, %25, %26, %27, %28, %29, %30, %31, %32, %33, %34, %35, %36, %37, %38, %39, %40, %41, %42, %43, %44, %45, %46, %47, %48, %49, %50, %51, %52, %53, %54, %55, %56, %57, %58, %59, %60, %61, %62, %63, %64, %65, %66, %67, %68, %69, %70, %71, %72, %73, %74, %75, %76, %77, %78, %79, %80, %81, %82, %83, %84, %85, %86, %87, %88, %89, %90, %91, %92, %93, %94, %95}, {%96, %97, %98, %99}, db, p, 1, 1, 1;\n}\n"
    : "+f"(d[0]), "+f"(d[1]), "+f"(d[2]), "+f"(d[3]), "+f"(d[4]), "+f"(d[5]), "+f"(d[6]), "+f"(d[7]),
      "+f"(d[8]), "+f"(d[9]), "+f"(d[10]), "+f"(d[11]), "+f"(d[12]), "+f"(d[13]), "+f"(d[14]), "+f"(d[15]),
      "+f"(d[16]), "+f"(d[17]), "+f"(d[18]), "+f"(d[19]), "+f"(d[20]), "+f"(d[21]), "+f"(d[22]), "+f"(d[23]),
      "+f"(d[24]), "+f"(d[25]), "+f"(d[26]), "+f"(d[27]), "+f"(d[28]), "+f"(d[29]), "+f"(d[30]), "+f"(d[31]),
      "+f"(d[32]), "+f"(d[33]), "+f"(d[34]), "+f"(d[35]), "+f"(d[36]), "+f"(d[37]), "+f"(d[38]), "+f"(d[39]),
      "+f"(d[40]), "+f"(d[41]), "+f"(d[42]), "+f"(d[43]), "+f"(d[44]), "+f"(d[45]), "+f"(d[46]), "+f"(d[47]),
      "+f"(d[48]), "+f"(d[49]), "+f"(d[50]), "+f"(d[51]), "+f"(d[52]), "+f"(d[53]), "+f"(d[54]), "+f"(d[55]),
      "+f"(d[56]), "+f"(d[57]), "+f"(d[58]), "+f"(d[59]), "+f"(d[60]), "+f"(d[61]), "+f"(d[62]), "+f"(d[63]),
      "+f"(d[64]), "+f"(d[65]), "+f"(d[66]), "+f"(d[67]), "+f"(d[68]), "+f"(d[69]), "+f"(d[70]), "+f"(d[71]),
      "+f"(d[72]), "+f"(d[73]), "+f"(d[74]), "+f"(d[75]), "+f"(d[76]), "+f"(d[77]), "+f"(d[78]), "+f"(d[79]),
      "+f"(d[80]), "+f"(d[81]), "+f"(d[82]), "+f"(d[83]), "+f"(d[84]), "+f"(d[85]), "+f"(d[86]), "+f"(d[87]),
      "+f"(d[88]), "+f"(d[89]), "+f"(d[90]), "+f"(d[91]), "+f"(d[92]), "+f"(d[93]), "+f"(d[94]), "+f"(d[95])
    : "r"(a[0]), "r"(a[1]), "r"(a[2]), "r"(a[3]), "r"(db), "r"(sc), "n"(HI));
}

template <int N> __device__ __forceinline__ void keep(float (&d)[N]) {
#pragma unroll
  for (int i = 0; i < N; i++) asm volatile("" : "+f"(d[i])::"memory");
}

__device__ __forceinline__ void keep(uint32_t (&d)[4]) { asm volatile("" : "+r"(d[0]), "+r"(d[1]), "+r"(d[2]), "+r"(d[3])::"memory"); }
template <int N> __device__ __forceinline__ void keep(uint32_t (&d)[N][4]) {
#pragma unroll
  for (int i = 0; i < N; i++) asm volatile("" : "+r"(d[i][0]), "+r"(d[i][1]), "+r"(d[i][2]), "+r"(d[i][3])::"memory");
}

__device__ __forceinline__ uint32_t pack2(float lo, float hi) {
  uint32_t r;
  asm("cvt.rn.bf16x2.f32 %0, %1, %2;" : "=r"(r) : "f"(hi), "f"(lo));
  return r;
}
__device__ __forceinline__ float bf_lo(uint32_t v) { return __uint_as_float(v << 16); }
__device__ __forceinline__ float bf_hi(uint32_t v) { return __uint_as_float(v & 0xffff0000u); }
__device__ __forceinline__ uint32_t hsub2(uint32_t a, uint32_t b) {
  uint32_t r;
  asm("sub.rn.bf16x2 %0, %1, %2;" : "=r"(r) : "r"(a), "r"(b));
  return r;
}
__device__ __forceinline__ uint32_t movm(uint32_t a) {
  uint32_t r;
  asm volatile("movmatrix.sync.aligned.m8n8.trans.b16 %0, %1;" : "=r"(r) : "r"(a));
  return r;
}
__device__ __forceinline__ void ldsm4(uint32_t (&v)[4], uint32_t a) {
  asm volatile("ldmatrix.sync.aligned.m8n8.x4.shared.b16 {%0,%1,%2,%3}, [%4];" : "=r"(v[0]), "=r"(v[1]), "=r"(v[2]), "=r"(v[3]) : "r"(a + own()) : "memory");
}
__device__ __forceinline__ void stsm4(uint32_t a, const uint32_t (&v)[4]) {
  asm volatile("stmatrix.sync.aligned.m8n8.x4.shared.b16 [%0], {%1,%2,%3,%4};" ::"r"(a + own()), "r"(v[0]), "r"(v[1]), "r"(v[2]), "r"(v[3]) : "memory");
}
__device__ __forceinline__ void mma16816(float (&d)[4], const uint32_t (&a)[4], uint32_t b0, uint32_t b1) {
  asm volatile("mma.sync.aligned.m16n8k16.row.col.f32.bf16.bf16.f32 {%0,%1,%2,%3}, {%4,%5,%6,%7}, {%8,%9}, {%10,%10,%10,%10};"
               : "=f"(d[0]), "=f"(d[1]), "=f"(d[2]), "=f"(d[3])
               : "r"(a[0]), "r"(a[1]), "r"(a[2]), "r"(a[3]), "r"(b0), "r"(b1), "f"(0.f));
}
__device__ __forceinline__ void mma1688_acc(float (&d)[4], uint32_t a0, uint32_t a1, uint32_t b0) {
  asm volatile("mma.sync.aligned.m16n8k8.row.col.f32.bf16.bf16.f32 {%0,%1,%2,%3}, {%4,%5}, {%6}, {%0,%1,%2,%3};"
               : "+f"(d[0]), "+f"(d[1]), "+f"(d[2]), "+f"(d[3]) : "r"(a0), "r"(a1), "r"(b0));
}
__device__ __forceinline__ float ex2(float x) { float y; asm("ex2.approx.ftz.f32 %0, %1;" : "=f"(y) : "f"(x)); return y; }
__device__ __forceinline__ float rcp(float x) { float y; asm("rcp.approx.ftz.f32 %0, %1;" : "=f"(y) : "f"(x)); return y; }
__device__ __forceinline__ float tanhf_hw(float x) { float y; asm("tanh.approx.f32 %0, %1;" : "=f"(y) : "f"(x)); return y; }
__device__ __forceinline__ uint32_t lds32(uint32_t a) { uint32_t v; asm volatile("ld.shared.u32 %0, [%1];" : "=r"(v) : "r"(a + own()) : "memory"); return v; }
__device__ __forceinline__ float2 lds64(uint32_t a) { float2 v; asm volatile("ld.shared.v2.f32 {%0,%1}, [%2];" : "=f"(v.x), "=f"(v.y) : "r"(a + own()) : "memory"); return v; }
__device__ __forceinline__ void lds128(uint32_t (&v)[4], uint32_t a) { asm volatile("ld.shared.v4.u32 {%0,%1,%2,%3}, [%4];" : "=r"(v[0]), "=r"(v[1]), "=r"(v[2]), "=r"(v[3]) : "r"(a + own()) : "memory"); }
__device__ __forceinline__ void sts128(uint32_t a, const uint32_t (&v)[4]) { asm volatile("st.shared.v4.u32 [%0], {%1,%2,%3,%4};" ::"r"(a + own()), "r"(v[0]), "r"(v[1]), "r"(v[2]), "r"(v[3]) : "memory"); }
__device__ __forceinline__ void ldg128_nc(uint32_t (&v)[4], const void* p) {
  asm volatile("ld.global.nc.L1::no_allocate.v4.u32 {%0,%1,%2,%3}, [%4];" : "=r"(v[0]), "=r"(v[1]), "=r"(v[2]), "=r"(v[3]) : "l"(p));
}
__device__ __forceinline__ uint32_t pin(uint32_t v, uint32_t zero) {
  asm volatile("{\n.reg .pred p;\n.reg .u32 c;\nmov.u32 c, %1;\nLP:\n.pragma \"nounroll\";\nsetp.eq.u32 p, c, 0;\n@p bra LD;\n"
               "add.u32 %0, %0, c;\nmov.u32 c, %%clock;\nbra LP;\nLD:\n}\n" : "+r"(v) : "r"(zero) : "memory");
  return v;
}
__device__ __forceinline__ void pin7(const char* (&p)[7], uint32_t zero) {
  asm volatile("{\n.reg .pred p;\n.reg .u64 c;\ncvt.u64.u32 c, %7;\nLP:\n.pragma \"nounroll\";\nsetp.eq.u64 p, c, 0;\n@p bra LD;\n"
               "mov.u64 c, %0;\nmov.u64 %0, %1;\nmov.u64 %1, %2;\nmov.u64 %2, %3;\nmov.u64 %3, %4;\n"
               "mov.u64 %4, %5;\nmov.u64 %5, %6;\nmov.u64 %6, c;\nmov.u64 c, %%clock64;\nbra LP;\nLD:\n}\n"
               : "+l"(p[0]), "+l"(p[1]), "+l"(p[2]), "+l"(p[3]), "+l"(p[4]), "+l"(p[5]), "+l"(p[6]) : "r"(zero) : "memory");
}
__device__ __forceinline__ void mbar_arrive_if(uint32_t b, bool cond) {
  asm volatile("{\n.reg .pred p;\nsetp.ne.u32 p, %1, 0;\n@p mbarrier.arrive.shared::cta.b64 _, [%0];\n}\n" ::"r"(b + own()), "r"((uint32_t)cond) : "memory");
}
__device__ __forceinline__ uint32_t ld_epoch(const char* p) {
  uint32_t v;
  asm volatile("ld.relaxed.gpu.global.u32 %0, [%1];" : "=r"(v) : "l"(p) : "memory");
  return v;
}
typedef const char* gptr;
__device__ __forceinline__ void ll_st(gptr p, uint32_t a, uint32_t b, uint32_t c, uint32_t d, uint32_t tag) {
  asm volatile("st.relaxed.gpu.global.v4.b32 [%0], {%1, %2, %3, %4};" ::"l"(p), "r"((a & ~1u) | tag), "r"(b), "r"(c), "r"(d) : "memory");
}
__device__ __forceinline__ void ll_ld(uint32_t (&v)[4], gptr p) {
  asm volatile("{\n.reg .b128 t;\n.reg .b64 lo, hi;\nld.relaxed.gpu.global.b128 t, [%4];\nmov.b128 {lo, hi}, t;\n"
               "mov.b64 {%0, %1}, lo;\nmov.b64 {%2, %3}, hi;\n}\n"
               : "=r"(v[0]), "=r"(v[1]), "=r"(v[2]), "=r"(v[3]) : "l"(p) : "memory");
}
template <int N> __device__ __forceinline__ void ll_issue(uint32_t (&v)[N][4], gptr p, int stride) {
#pragma unroll
  for (int i = 0; i < N; i++) ll_ld(v[i], p + i * stride);
}
__device__ __forceinline__ uint32_t ll_mix(uint32_t a, uint32_t b, uint32_t tag) {
  uint32_t r;
  asm("lop3.b32 %0, %1, %2, %3, 0xD4;" : "=r"(r) : "r"(a), "r"(b), "r"(tag));
  return r;
}
template <int LO, int HI, int N> __device__ __forceinline__ uint32_t ll_tree(const uint32_t (&v)[N][4], uint32_t tag) {
  if constexpr (HI - LO == 1) return v[LO][0];
  else return ll_mix(ll_tree<LO, (LO + HI) / 2>(v, tag), ll_tree<(LO + HI) / 2, HI>(v, tag), tag);
}
template <int N> __device__ __forceinline__ uint32_t ll_red(const uint32_t (&v)[N][4], uint32_t tag) { return ll_tree<0, N>(v, tag); }
__device__ __forceinline__ bool ll_any(uint32_t red, uint32_t tag) { return __any_sync(0xffffffffu, (red ^ tag) & 1u); }
template <int N> __device__ __forceinline__ bool ll_bad(const uint32_t (&v)[N][4], uint32_t tag) { return ll_any(ll_red<N>(v, tag), tag); }
template <int N, int M> __device__ __forceinline__ bool ll_bad2(const uint32_t (&v)[N][4], const uint32_t (&u)[M][4], uint32_t tag) {
  return ll_any(ll_mix(ll_red<N>(v, tag), ll_red<M>(u, tag), tag), tag);
}
template <int N> __device__ __forceinline__ void ll_clear(uint32_t (&v)[N][4]) {
#pragma unroll
  for (int i = 0; i < N; i++) v[i][0] &= ~1u;
}
template <int N> __device__ __forceinline__ void ll_spin(uint32_t (&v)[N][4], gptr p, int stride, uint32_t tag) {
  uint32_t it = 0;
#pragma unroll 1
  do { ll_issue<N>(v, p, stride); } while (ll_bad<N>(v, tag) && ++it < SPIN_LIMIT);
}
template <int N> __device__ __forceinline__ void ll_get(uint32_t (&v)[N][4], gptr p, int stride, uint32_t tag) {
  ll_spin<N>(v, p, stride, tag);
  ll_clear<N>(v);
}
template <int N> __device__ __forceinline__ void ll_wait(uint32_t (&v)[N][4], gptr p, int stride, uint32_t tag) {
  if (__builtin_expect(ll_bad<N>(v, tag), 0)) ll_spin<N>(v, p, stride, tag);
  ll_clear<N>(v);
}
__device__ __forceinline__ void unpack32(float (&d)[32], const uint32_t (&v)[4][4]) {
#pragma unroll
  for (int u = 0; u < 4; u++)
#pragma unroll
    for (int e = 0; e < 4; e++) { d[8 * u + 2 * e] = bf_lo(v[u][e]); d[8 * u + 2 * e + 1] = bf_hi(v[u][e]); }
}
__device__ __forceinline__ void pack32(uint32_t (&v)[4][4], const float (&d)[32]) {
#pragma unroll
  for (int u = 0; u < 4; u++)
#pragma unroll
    for (int e = 0; e < 4; e++) v[u][e] = pack2(d[8 * u + 2 * e], d[8 * u + 2 * e + 1]);
}
__device__ __forceinline__ uint32_t t_addr(int m) { return SB + ((0x01354620u >> (4 * m)) & 7u) * 32768u; }

__device__ __forceinline__ constexpr int w2_pass(int m) { return m < 4 ? m & 1 : m >> 1; }
__device__ __forceinline__ constexpr int w2_peer(int m) { return m < 4 ? m >> 1 : m & 1; }

__device__ __forceinline__ int kb_at(int i, int j) { return i == 0 ? j : (i - 1 + (i - 1 >= j ? 1 : 0)); }

__device__ __forceinline__ void init_bars(int set) {
  if (set >= 0 && elect_one()) {
    const uint32_t cnt = set < 5 ? 1 : 8;
#pragma unroll
    for (int i = 0; i < 8; i++) mbar_init(BAR + (24 + 8 * set + i) * 8, cnt);
    if (set >= 8) {
#pragma unroll
      for (int i = 0; i < 8; i++) mbar_init(BAR + (40 + 8 * set + i) * 8, 13 - set);
    }
    if (set == 7) {
#pragma unroll
      for (int i = 0; i < 5; i++) mbar_init(BAR + (B_READY + i) * 8, i == 1 || i == 4 ? 2 : 3);
    }
    asm volatile("fence.mbarrier_init.release.cluster;" ::: "memory");
  }
  __syncwarp();
  asm volatile("bar.arrive 4, 384;" ::: "memory");
  asm volatile("bar.sync 3, 384;" ::: "memory");
  asm volatile("barrier.cluster.arrive.relaxed.aligned;" ::: "memory");
}

__device__ __forceinline__ void load_a(const Params& P, int i, int j) {
  const int f0 = 224 * j + ((j & 1) ? 32 : 0);
  const int fh = 224 * j + ((j & 1) ? 0 : 192);
  const uint32_t b = BAR + (B_FA + i) * 8, d = RING + (i & 3) * 24576;
  const int k0 = kb_at(i, j) * 64;
  mbar_expect_tx(b, 24576);
  tma2d(d, &P.w1, f0, k0, b);
  tma2d(d + 8192, &P.w3, f0, k0, b);
  tma2d(d + 16384, &P.w1h, fh, k0, b);
  tma2d(d + 20480, &P.w3h, fh, k0, b);
}
__device__ __forceinline__ void reset_box(gptr p, int i0, int n, uint32_t s8, uint32_t tag) {
#pragma unroll 1
  for (int i = i0; i < i0 + n; i++) ll_st(p + ((i & 7) * s8 + (i >> 3) * 512), 0, 0, 0, 0, tag ^ 1);
}

__global__ void __launch_bounds__(384, 1) fused_block_kernel(char* __restrict__ X, const __nv_bfloat16* __restrict__ xp,
                                                             const __nv_bfloat16* __restrict__ wqkvp, const __nv_bfloat16* __restrict__ wop,
                                                             const uint32_t zero, const __grid_constant__ Params P) {
  extern __shared__ __align__(1024) uint8_t smem_raw[];
  prefetch_map(&P.x); prefetch_map(&P.wqkv);
  const int tid = threadIdx.x;
  const int warp = __shfl_sync(0xffffffffu, tid >> 5, 0);
  const int lane = tid & 31;
  const int cta = blockIdx.x;
  const int cl = cta >> 1;
  const int c7 = cl - 36, i7 = (c7 * 37) >> 8;
  const int set = cl < 4 ? 15 : cl < 36 ? (cl - 4) & 7 : 8 + c7 - 7 * i7;
  const int idx = cl < 4 ? cl : cl < 36 ? (cl - 4) >> 3 : i7;
  const int g = (set & 14) + (idx >> 1), j = (set & 1) * 4 + (idx & 1) * 2 + (cta & 1);

  if (warp == 8) {
    if (elect_one()) {
#pragma unroll
      for (int i = 0; i < 24; i++) mbar_init(BAR + i * 8, 1);
      asm volatile("fence.mbarrier_init.release.cluster;" ::: "memory");
#pragma unroll
      for (int i = 0; i < TOP_KB; i++) {
        mbar_expect_tx(BAR + (B_FX + i) * 8, 8192);
        tma3d(H0 + i * 8192, &P.x, i * 64, 0, g * 64, BAR + (B_FX + i) * 8);
        mbar_expect_tx(BAR + (B_FW + i) * 8, 24576);
        tma3d(RING + i * 24576, &P.wqkv, 64 * j, i * 64, 0, BAR + (B_FW + i) * 8);
        mbar_expect_tx(BAR + (B_FX + 8 + i) * 8, 8192);
        tma3d(H1 + i * 8192, &P.x, i * 64, 1, g * 64, BAR + (B_FX + 8 + i) * 8);
      }
    }
    __syncwarp();
    asm volatile("bar.arrive 3, 384;" ::: "memory");
  }
  if (smem_u32(smem_raw) != SB + own()) return;

  if (__builtin_expect(warp >= 8, 1)) {
    asm volatile("setmaxnreg.dec.sync.aligned.u32 56;");
    if (__builtin_expect(warp == 8, 1)) {
      PSTAMPW(2, 0);
      const bool leader = elect_one();
      auto ldx = [&](int p, int kb) {
        const uint32_t b = BAR + (B_FX + p * 8 + kb) * 8;
        mbar_expect_tx(b, 8192);
        tma3d(H0 + p * 65536 + kb * 8192, &P.x, kb * 64, p, g * 64, b);
      };
      auto ldw = [&](int kb) {
        const uint32_t b = BAR + (B_FW + kb) * 8, d = RING + (kb & 3) * 24576;
        mbar_expect_tx(b, 24576);
        tma3d(d, &P.wqkv, 64 * j, kb * 64, 0, b);
      };
      if (leader) {
#pragma unroll 1
        for (int i = TOP_KB; i < 8; i++) {
          ldx(0, i);
          if (i < 4) ldw(i);
          ldx(1, i);
        }
        PSTAMPW(2, 2);
      }
      __syncwarp();
      asm volatile("barrier.cluster.arrive.relaxed.aligned;" ::: "memory");
      asm volatile("bar.sync 4, 384;" ::: "memory");
      if (leader) {
        prefetch_map(&P.wo); prefetch_map(&P.w1); prefetch_map(&P.w3); prefetch_map(&P.w1h);
        prefetch_map(&P.w3h); prefetch_map(&P.w2); prefetch_map(&P.out);
        mbar_expect_tx(BAR + B_FWO * 8, 65536);
#pragma unroll 1
        for (int i = 0; i < 12; i++) {
          mbar_wait(BAR + (i < 8 ? B_EW + i : B_EA + i - 8) * 8);
          if (i == 4 + A_HOLD) mbar_wait(BAR + B_HALO * 8);
          if (i < 4) ldw(i + 4); else load_a(P, i - 4, j);
          PSTAMPW(2, 4 + i);
          if (i < 7) {
            mbar_wait(BAR + (B_EX + i) * 8);
            tma2d(H0 + i * 8192, &P.wo, 64 * j, i * 64, BAR + B_FWO * 8);
          }
          if (PFV == 1 && i < 4) l2_prefetch((gptr)((i & 1) ? P.w3p : P.w1p) + cta * 14336 + (i >> 1) * 7168, 7168);
        }
        const int f0 = 224 * j + ((j & 1) ? 32 : 0);
        uint32_t d = RING;
#pragma unroll 1
        for (int i = 0; i < 8; i++) {
          const uint32_t b = BAR + (B_FB + i) * 8;
          const int k0 = kb_at(i, j) * 64;
          mbar_wait(BAR + (B_EA + 5 + i) * 8);
          mbar_expect_tx(b, 32768);
          tma2d(d, &P.w1, f0 + 64, k0, b);
          tma2d(d + 8192, &P.w3, f0 + 64, k0, b);
          tma2d(d + 16384, &P.w1, f0 + 128, k0, b);
          tma2d(d + 24576, &P.w3, f0 + 128, k0, b);
          d = d == RING + 65536 ? RING : d + 32768;
        }
#pragma unroll 1
        for (int i = 0; i < 8; i++) {
          const int m = i;
          const uint32_t b = BAR + (B_FT + m) * 8;
          mbar_wait(BAR + (i < 5 ? B_EB + 3 + i : i < 7 ? B_HC - 5 + i : B_ET0) * 8);
          mbar_expect_tx(b, 28672);
          tma2d(t_addr(m), &P.w2, 64 * ((j + 2 + 2 * w2_pass(m)) & 7), 224 * (j ^ w2_peer(m)), b);
        }
        mbar_expect_tx(BAR + B_FIN * 8, 32768);
#pragma unroll 1
        for (int q = 0; q < 2; q++) {
          mbar_wait(BAR + (B_ET0 + 3 - q) * 8);
          asm volatile("cp.async.bulk.shared::cluster.global.mbarrier::complete_tx::bytes [%0], [%1], 16384, [%2];"
                       ::"r"(t_addr(q + 1) + own()), "l"(X + X_E4 + ((g * 8 + j) * 3 + q) * 16384), "r"(BAR + B_FIN * 8 + own()) : "memory");
        }
        unsigned* ep = reinterpret_cast<unsigned*>(X + X_EP) + cta;
        *ep = *ep + 1;
      }
    } else {
      const int part = warp - 9;
      uint32_t tag;
      if (part == 2) {
        tag = ld_epoch(X + X_EP + cta * 4);
        init_bars(-1);
        tag = (tag + 1) & 1;
        if (lane == 0) {
          asm volatile("st.shared.u32 [%0], %1;" ::"r"(TAGS + own()), "r"(tag) : "memory");
          mbar_arrive(BAR + B_TAG * 8);
        }
      } else {
        init_bars(warp - 1);
        mbar_wait(BAR + B_TAG * 8);
        tag = lds32(TAGS);
      }
      gptr xl = X + lane * 16;
      if (lane < 16) ll_st(xl + X_CS + ((j * 3 + part) * 16 + g) * 256, 0, 0, 0, 0, tag ^ 1);
      if (part == 0 && lane < 20) ll_st(xl + (lane < 16 ? X_ST + (g * 128 + 16 * j) * 16 : X_WB + (j * 64 + g * 4 - 16) * 16), 0, 0, 0, 0, tag ^ 1);
      if (part) reset_box(xl + X_E1 + (g * 8 + j) * 4096, 4 * part - 4, 4, 512, tag);
      __syncwarp();
      if (lane == 0) mbar_arrive(BAR + B_CLR1 * 8);
      asm volatile("barrier.cluster.wait.aligned;" ::: "memory");
      uint32_t v[8][4];
      {
        float s[4] = {0.f, 0.f, 0.f, 0.f}, q[4] = {0.f, 0.f, 0.f, 0.f};
        const uint32_t xa = H0 + ((lane >> 1) & 1) * 65536 + (8 * j + (lane >> 2)) * 128 + (lane & 1) * 64 + ((lane >> 1) & 3) * 16;
#pragma unroll 1
        for (int kb = (part + 2) % 3; kb < 8; kb += 3) {
          mbar_wait(BAR + (B_FX + kb) * 8);
          mbar_wait(BAR + (B_FX + 8 + kb) * 8);
#pragma unroll
          for (int i = 0; i < 4; i++) lds128(v[i], (xa + kb * 8192) ^ (i * 16));
#pragma unroll
          for (int e = 0; e < 16; e++) {
            const float a = bf_lo(v[e >> 2][e & 3]), b = bf_hi(v[e >> 2][e & 3]);
            s[e & 3] += a + b; q[e & 3] = fmaf(a, a, q[e & 3]); q[e & 3] = fmaf(b, b, q[e & 3]);
          }
          __syncwarp();
          mbar_arrive_if(BAR + (B_EX + kb) * 8, lane == 0 || (__float_as_uint(q[0] + q[1] + q[2] + q[3]) & zero) != 0);
        }
        float ss = (s[0] + s[1]) + (s[2] + s[3]), qq = (q[0] + q[1]) + (q[2] + q[3]);
        ss += __shfl_xor_sync(0xffffffffu, ss, 1); qq += __shfl_xor_sync(0xffffffffu, qq, 1);
        if (part) {
          if (!(lane & 1))
            asm volatile("st.shared.v2.f32 [%0], {%1,%2};" ::"r"(WB + own() + part * 128 - 128 + lane * 4), "f"(ss), "f"(qq) : "memory");
          asm volatile("bar.arrive 5, 96;" ::: "memory");
        } else {
          asm volatile("bar.sync 5, 96;" ::: "memory");
          const float2 t1 = lds64(WB + (lane >> 1) * 8), t2 = lds64(WB + 128 + (lane >> 1) * 8);
          const float mean = (ss + t1.x + t2.x) * (1.f / D_);
          const float rs = rsqrtf(fmaxf(fmaf(-mean, mean, (qq + t1.y + t2.y) * (1.f / D_)), 0.f) + 1e-5f);
          if (!(lane & 1)) ll_st(X + X_ST + (g * 128 + 16 * j + (lane >> 1)) * 16, __float_as_uint(mean), __float_as_uint(rs), 0, 0, tag);
          PSTAMPW(3, 2);
        }
      }
      PSTAMPW(3, part * 4 + 0);
      {
        ll_get<8>(v, X + X_CS + ((j * 3 + part) * 16 + (lane >> 4) * 8) * 256 + (lane & 15) * 16, 256, tag);
        if (part == 0) {
          uint32_t u[2][4];
          ll_get<2>(u, xl + X_WB + j * 1024, 512, tag);
#pragma unroll
          for (int i = 0; i < 2; i++)
            asm volatile("st.shared.u32 [%0], %1;" ::"r"(WB + 256 + own() + i * 128 + (lane >> 4) * 64 + (lane & 6) * 8 + (lane & 8) + (lane & 1) * 4), "r"(u[i][0]) : "memory");
        }
        uint32_t o[4];
#pragma unroll
        for (int e = 0; e < 4; e++) {
          float s = 0.f;
#pragma unroll
          for (int i = 0; i < 8; i++) s += __uint_as_float(v[i][e]);
          o[e] = __float_as_uint(s + __shfl_xor_sync(0xffffffffu, s, 16));
        }
        const uint32_t h0 = pack2(__uint_as_float(o[0]), __uint_as_float(o[1])), h1 = pack2(__uint_as_float(o[2]), __uint_as_float(o[3]));
        const uint32_t l0 = pack2(__uint_as_float(o[0]) - bf_lo(h0), __uint_as_float(o[1]) - bf_hi(h0));
        const uint32_t l1 = pack2(__uint_as_float(o[2]) - bf_lo(h1), __uint_as_float(o[3]) - bf_hi(h1));
        mbar_wait(BAR + B_EW * 8);
        mbar_wait(BAR + B_EX * 8);
#pragma unroll
        for (int k = 0; k < 4; k++) {
          const bool z = lane >= 16 || k == 3;
          asm volatile("st.shared.v2.u32 [%0], {%1,%2};" ::"r"(H1 + own() + part * 1024 + ((lane & 15) >> 1) * 128 + (lane >> 4) * 64 + k * 16 + (lane & 1) * 8),
                       "r"(z ? 0u : k < 2 ? h0 : l0), "r"(z ? 0u : k < 2 ? h1 : l1) : "memory");
        }
        fence_async_smem();
      }
      __syncwarp();
      if (lane == 0) mbar_arrive(BAR + B_READY * 8);
      PSTAMPW(3, part * 4 + 1);
      gptr rec = xl + g * 8 * REC + j * 2048;
      gptr recs = X + (g * 8 + (lane >> 3)) * REC + j * 128 + (lane & 7) * 16;
      if (part) {
        ll_st(recs + R_OS + (part - 1) * 4 * REC, 0, 0, 0, 0, tag ^ 1);
#pragma unroll 1
        for (int i = 0; i < 4; i++)
#pragma unroll
          for (int u = 0; u < 4; u++) ll_st(rec + (R_O + (4 * part - 4 + i) * REC) + u * 512, 0, 0, 0, 0, tag ^ 1);
      }
      __syncwarp();
      if (lane == 0 && part) mbar_arrive(BAR + B_CLRO * 8);
      PSTAMPW(3, 20 + part);
      if (part < 2) {
        if (elect_one()) {
          if (part) {
            mbar_wait(BAR + (B_EX + 7) * 8);
            tma2d(H0 + 7 * 8192, &P.wo, 64 * j, 7 * 64, BAR + B_FWO * 8);
          }
          mbar_wait(BAR + (PF_WHEN) * 8);
          gptr src = (gptr)(part ? P.w3p : P.w1p) + cta * 14336;
#pragma unroll 1
          for (int i = PFV == 1 ? 14 : 0; i < (part ? 14 : 28); i++) {
            if (i == 14) src = (gptr)P.w2p + (cta - 1) * 14336;
            l2_prefetch(src + i * 1024, 1024);
            __nanosleep(PF_SLEEP);
          }
        }
      } else if (part == 2) {
        ll_st(recs + R_HS, 0, 0, 0, 0, tag ^ 1);
        ll_st(recs + R_HS + 4 * REC, 0, 0, 0, 0, tag ^ 1);
        reset_box(rec + R_H, 0, 32, REC, tag);
        __syncwarp();
        if (lane == 0) mbar_arrive(BAR + B_CLRH * 8);
        PSTAMPW(3, 24);
      }
      mbar_wait(BAR + (B_EA + 7) * 8);
      reset_box(xl + X_E4 + ((g * 8 + ((j + 2 + 2 * part) & 7)) * 3 + part) * 16384, 0, 32, 2048, tag);
      __syncwarp();
      if (lane == 0) mbar_arrive(BAR + B_CLR4 * 8);
      PSTAMPW(3, part * 4 + 3);
    }
  } else {
    const int p = warp >> 2, w = warp & 3;
    const int r = lane >> 2, c = lane & 3;
    init_bars(warp);
    asm volatile("setmaxnreg.inc.sync.aligned.u32 224;");
    PSTAMP(0);
    const uint32_t dAx = descA(H0) + p * 4096;
    const uint32_t Hn = H1 - p * 65536;
    const uint32_t moff = ((lane & 7) + ((lane >> 3) & 1) * 8) * 128 + (((lane >> 4) ^ (lane & 7)) << 4);
    const uint32_t Xw = H0 + p * 65536 + w * 2048;
    uint32_t cv[8][4];
    if (p == 1) {
      if (!SIDE_EARLY) mbar_wait(BAR + B_FW * 8);
      const char* wr = w < 3 ? (const char*)wqkvp + (g * 32 + (lane >> 3) * 8) * 3072 + w * 1024 + j * 128 + (lane & 7) * 16
                              : (const char*)wop + (j * 64 + g * 4 + (lane >> 3)) * 1024 + (lane & 7) * 16;
      const uint32_t st = w < 3 ? 3072 : 128;
#pragma unroll
      for (int i = 0; i < 8; i++) ldg128_nc(cv[i], wr + i * st);
    }

    float aq[96];
    uint32_t xres[4][4];
#pragma unroll
    for (int u = 0; u < 4; u++) { xres[u][0] = 0; xres[u][1] = 0; xres[u][2] = 0; xres[u][3] = 0; }
    auto kvstep = [&](int kb) {
      mbar_wait(BAR + (B_FX + p * 8 + kb) * 8);
      mbar_wait(BAR + (B_FW + kb) * 8);
      if (kb == 0) PSTAMP(2);
      if (kb == 7) PSTAMP(31);
      const uint32_t da = dAx + kb * 512, db = descB(RING) + (kb & 3) * 1536;
      wg_fence();
      wgmma_ss_n192(aq, da, db, kb);
#pragma unroll
      for (int k = 1; k < 4; k++) wgmma_ss_n192(aq, da + k * 2, db + k * 128, 1);
      wg_commit();
      wg_wait<1>();
      if (kb > 0) {
        mbar_arrive_if(BAR + (B_EW + kb - 1) * 8, lane == 0);
        mbar_arrive_if(BAR + (B_EX + kb - 1) * 8, (lane == 0 && p == 0) || (xres[0][0] & xres[1][0] & xres[2][0] & xres[3][0] & zero) != 0);
      }
      if (kb == j) {
#pragma unroll
        for (int u = 0; u < 4; u++) ldsm4(xres[u], Xw + kb * 8192 + (moff ^ (u << 5)));
      }
    };
#pragma unroll
    for (int kb = 0; kb < CS_KB; kb++) kvstep(kb);
    mbar_wait(BAR + B_CLR1 * 8);
    const uint32_t tag = lds32(TAGS);
    if (p == 1) {
      PSTAMPX(29);
      const uint32_t hm = 0xffff0000u | (tag >> 1), sh = 16 + (tag >> 1);
      float cs[8];
#pragma unroll
      for (int e = 0; e < 4; e++) {
        float a = 0.f, b = 0.f;
#pragma unroll
        for (int i = 0; i < 8; i++) { a += __uint_as_float(cv[i][e] << sh); b += __uint_as_float(cv[i][e] & hm); }
        cs[2 * e] = a; cs[2 * e + 1] = b;
      }
      if (w == 3) {
        float t = ((cs[0] + cs[1]) + (cs[2] + cs[3])) + ((cs[4] + cs[5]) + (cs[6] + cs[7]));
#pragma unroll
        for (int o = 1; o <= 4; o <<= 1) t += __shfl_xor_sync(0xffffffffu, t, o);
        if ((lane & 7) == 0) ll_st(X + X_WB + (j * 64 + g * 4 + (lane >> 3)) * 16, __float_as_uint(t * (1.f / D_)), 0, 0, 0, tag);
      }
      const bool up = lane & 8;
#pragma unroll
      for (int e = 0; e < 4; e++) {
        const float keepv = up ? cs[4 + e] : cs[e], give = up ? cs[e] : cs[4 + e];
        cs[e] = keepv + __shfl_xor_sync(0xffffffffu, give, 8);
        cs[e] += __shfl_xor_sync(0xffffffffu, cs[e], 16);
      }
      if (lane < 16 && w < 3)
        ll_st(X + X_CS + ((j * 3 + w) * 16 + g) * 256 + (lane & 7) * 32 + (lane >> 3) * 16, __float_as_uint(cs[0]), __float_as_uint(cs[1]),
              __float_as_uint(cs[2]), __float_as_uint(cs[3]), tag);
      PSTAMP(1);
    }
#pragma unroll 1
    for (int kb = CS_KB; kb < 7; kb++) kvstep(kb);
    uint32_t sv[2][4];
    gptr const stsrc = X + (X_ST + (g * 128 + 2 * (16 * w + r) + p) * 16);
    ll_issue<2>(sv, stsrc, 256);
    gptr const xl = X + (lane * 16 + (tag >> 1));
    gptr const rec = xl + (g * 8 + warp) * REC;
    gptr const recs = rec + (r * 16 - lane * 16);
    gptr osrc[7];
#pragma unroll
    for (int i = 0; i < 7; i++) osrc[i] = rec + (uint32_t)(i >= j ? (i + 1) * 2048 : i * 2048);
    pin7(osrc, zero);
    kvstep(7);
    if (__builtin_expect(ll_bad<2>(sv, pin(tag, zero)), 0)) ll_spin<2>(sv, stsrc, 256, tag);
    ll_clear<2>(sv);
    const float2 st0 = make_float2(__uint_as_float(sv[0][0]), __uint_as_float(sv[0][1]));
    const float2 st1 = make_float2(__uint_as_float(sv[1][0]), __uint_as_float(sv[1][1]));
    PSTAMP(19);
    {
      auto frag = [&](float m) {
        const uint32_t h = pack2(-m, -m);
        return c == 0 ? (h & 0xffffu) | pack2(0.f, -m - bf_lo(h)) : c == 1 ? h & 0xffffu : 0u;
      };
      uint32_t ma[4] = {frag(st0.x), frag(st1.x), 0u, 0u};
      mbar_wait(BAR + B_READY * 8);
      keep(ma);
      wg_fence();
      wgmma_rs_n192<(128 >> 4)>(aq, ma, H1 >> 4, 1);
      wg_commit();
    }
    wg_wait<0>();
    keep(aq);
    mbar_arrive_if(BAR + (B_EW + 7) * 8, lane == 0);
    PSTAMP(3);

    uint32_t hi[4][4], lo[4][4];
    auto cvt = [&](uint32_t (&d)[4][4], int ofs, float rs) {
#pragma unroll
      for (int b = 0; b < 16; b++) {
        const uint32_t v = pack2(aq[32 + 4 * b + ofs] * rs, aq[33 + 4 * b + ofs] * rs);
        d[b >> 2][b & 3] = b < 8 ? v : movm(v);
      }
    };
    cvt(hi, 2, st1.y);
    if (w == 3) {
#pragma unroll
      for (int i = 0; i < 4; i++) ll_st(xl + (X_E1 + ((g * 8 + j) * 2 + p) * 2048 + i * 512), hi[i][0], hi[i][1], hi[i][2], hi[i][3], tag);
    }
    wg_bar(p);
#pragma unroll
    for (int i = 0; i < 4; i++) sts128(Xw + 7 * 8192 + lane * 16 + i * 512, hi[i]);
    PSTAMP(20);
    cvt(lo, 0, __uint_as_float(pin(__float_as_uint(st0.y), zero)));
    uint32_t qf[4][4];
#pragma unroll
    for (int h = 0; h < 4; h++)
#pragma unroll
      for (int e = 0; e < 4; e++) qf[h][e] = pack2(aq[8 * h + 2 * e], aq[8 * h + 2 * e + 1]);
    keep(qf); keep(lo);
    PSTAMP(21);
    wg_bar(p);
    uint32_t prev[4][4];
#pragma unroll
    for (int i = 0; i < 4; i++) lds128(prev[i], Xw + 7 * 8192 - (w ? 2048 : 0) + lane * 16 + i * 512);
    if (p == 0) fence_async_smem();
    __syncwarp();
    const bool xd = lane == 0 || (prev[3][0] & xres[3][0] & zero) != 0;
    mbar_arrive_if(BAR + (B_EX + 7) * 8, xd && p == 0);
    mbar_arrive_if(BAR + B_XDONE * 8, xd);
    if (w == 0 && g > 0) ll_get<4>(prev, xl + (X_E1 + (((g - 1) * 8 + j) * 2 + p) * 2048), 512, tag);
    mbar_arrive_if(BAR + B_HALO * 8, (tid & 127) == 0);
    mbar_wait(BAR + B_CLRO * 8);
    PSTAMP(4);

    uint32_t of[4][4];
    {
      const float sc = 0.25f * 1.4426950408889634f;
      const float sca = sc * st0.y, scb = sc * st1.y;
      const float nohalo = (g == 0 && w == 0) ? -INFINITY : 0.f;
      const bool up0 = 2 * c > r, up1 = 2 * c + 1 > r;
      const uint32_t mup = (up0 ? 0xffffu : 0u) | (up1 ? 0xffff0000u : 0u);
#pragma unroll
      for (int h = 0; h < 4; h++) {
        if (h == 2) {
          qf[2][0] = pin(qf[2][0], zero); qf[3][0] = pin(qf[3][0], zero);
        }
        const int i0 = h >> 1, e0 = (2 * h) & 3;
        float sp[4], sl[4], sh[4];
        mma16816(sp, qf[h], prev[i0][e0], prev[i0][e0 + 1]);
        mma16816(sl, qf[h], lo[i0][e0], lo[i0][e0 + 1]);
        mma16816(sh, qf[h], hi[i0][e0], hi[i0][e0 + 1]);
        float a0 = up0 ? sp[0] + nohalo : sl[0], a1 = up1 ? sp[1] + nohalo : sl[1];
        float b0 = up0 ? sl[2] : sh[2], b1 = up1 ? sl[3] : sh[3];
        float ma = fmaxf(a0, a1), mb = fmaxf(b0, b1);
        ma = fmaxf(ma, __shfl_xor_sync(0xffffffffu, ma, 1)); mb = fmaxf(mb, __shfl_xor_sync(0xffffffffu, mb, 1));
        ma = fmaxf(ma, __shfl_xor_sync(0xffffffffu, ma, 2)); mb = fmaxf(mb, __shfl_xor_sync(0xffffffffu, mb, 2));
        a0 = ex2((a0 - ma) * sca); a1 = ex2((a1 - ma) * sca); b0 = ex2((b0 - mb) * scb); b1 = ex2((b1 - mb) * scb);
        float sa = a0 + a1, sbb = b0 + b1;
        sa += __shfl_xor_sync(0xffffffffu, sa, 1); sbb += __shfl_xor_sync(0xffffffffu, sbb, 1);
        sa += __shfl_xor_sync(0xffffffffu, sa, 2); sbb += __shfl_xor_sync(0xffffffffu, sbb, 2);
        const float ia = rcp(sa), ib = rcp(sbb);
        const uint32_t pa = pack2(a0 * ia, a1 * ia), pb = pack2(b0 * ib, b1 * ib);
        const uint32_t pf[4] = {pa & mup, 0u, pa & ~mup, pb & mup};
        const uint32_t ph = pb & ~mup;
        float o0[4], o1[4];
        mma16816(o0, pf, prev[2 + i0][e0], lo[2 + i0][e0]);
        mma16816(o1, pf, prev[2 + i0][e0 + 1], lo[2 + i0][e0 + 1]);
        mma1688_acc(o0, 0u, ph, hi[2 + i0][e0]);
        mma1688_acc(o1, 0u, ph, hi[2 + i0][e0 + 1]);
        of[h][0] = pack2(o0[0], o0[1]); of[h][1] = pack2(o0[2], o0[3]);
        of[h][2] = pack2(o1[0], o1[1]); of[h][3] = pack2(o1[2], o1[3]);
        ll_st(rec + (uint32_t)(R_O + j * 2048) + h * 512, of[h][0], of[h][1], of[h][2], of[h][3], tag);
      }
    }
    PSTAMP(5);

    float ah[32];
    {
      uint32_t og[2][14][4];
      auto oissue = [&](int hp) {
#pragma unroll
        for (int i = 0; i < 14; i++) ll_ld(og[hp][i], osrc[i >> 1] + (R_O + (2 * hp + (i & 1)) * 512));
        if (hp == 1) ll_issue<2>(sv, recs + (R_OS + c * 256), 128);
      };
      auto omma = [&](int hp) {
        ll_clear<14>(og[hp]);
        keep(og[hp]);
        wg_fence();
#pragma unroll
        for (int i = 0; i < 14; i++) wgmma_rs_n64(ah, og[hp][i], descB(H0) + kb_at((i >> 1) + 1, j) * 512 + (2 * hp + (i & 1)) * 128, 1);
        wg_commit();
      };
      uint32_t pr[1][4];
      gptr const probe = rec + (uint32_t)(R_O + 512 + (min(lane, 6) >= j ? min(lane, 6) + 1 : min(lane, 6)) * 2048);
      ll_issue<1>(pr, probe, 0);
      {
        float d0 = 0.f, d1 = 0.f;
#pragma unroll
        for (int h = 0; h < 4; h++) {
          uint32_t cw[4];
          lds128(cw, WB + 256 + c * 16 + h * 64);
#pragma unroll
          for (int e = 0; e < 4; e++) {
            float& d = (e & 1) ? d1 : d0;
            d = fmaf(bf_lo(of[h][e]), __uint_as_float(cw[e & 2]), d);
            d = fmaf(bf_hi(of[h][e]), __uint_as_float(cw[(e & 2) + 1]), d);
          }
        }
#pragma unroll
        for (int o = 1; o <= 2; o <<= 1) { d0 += __shfl_xor_sync(0xffffffffu, d0, o); d1 += __shfl_xor_sync(0xffffffffu, d1, o); }
        if (c == 0) ll_st(recs + (uint32_t)(R_OS + j * 128), __float_as_uint(d0), __float_as_uint(d1), 0, 0, tag);
      }
      PSTAMP(22);
      if (ll_any(pr[0][0], pin(tag, zero))) {
        ll_spin<1>(pr, probe, 0, tag);
      }
      PSTAMP(30);
      oissue(0);
      unpack32(ah, xres);
      PSTAMP(23);
      mbar_wait(BAR + B_FWO * 8);
      PSTAMP(18);
      keep(ah); keep(of);
      wg_fence();
#pragma unroll
      for (int k = 0; k < 4; k++) wgmma_rs_n64(ah, of[k], descB(H0) + j * 512 + k * 128, 1);
      wg_commit();
      uint32_t it = 0;
      if (__builtin_expect(ll_bad<14>(og[0], pin(tag, zero)), 0)) {
#pragma unroll 1
        do { oissue(0); } while (ll_bad<14>(og[0], tag) && ++it < SPIN_LIMIT);
      }
      PSTAMP(6);
      oissue(1);
      omma(0);
      if (__builtin_expect(ll_bad2<14, 2>(og[1], sv, pin(tag, zero)), 0)) {
#pragma unroll 1
        do { oissue(1); } while (ll_bad2<14, 2>(og[1], sv, tag) && ++it < SPIN_LIMIT);
      }
      PSTAMP(16);
      omma(1);
      ll_clear<2>(sv);
    }
    float m0 = __uint_as_float(sv[0][0]) + __uint_as_float(sv[1][0]), m1 = __uint_as_float(sv[0][1]) + __uint_as_float(sv[1][1]);
#pragma unroll
    for (int o = 1; o <= 2; o <<= 1) { m0 += __shfl_xor_sync(0xffffffffu, m0, o); m1 += __shfl_xor_sync(0xffffffffu, m1, o); }
    const uint32_t mu0 = pack2(m0 + st0.x, m0 + st0.x), mu1 = pack2(m1 + st1.x, m1 + st1.x);
    mbar_wait(BAR + B_CLRH * 8);
    wg_wait<0>();
    keep(ah);
    mbar_arrive_if(BAR + B_WODONE * 8, lane == 0);
    PSTAMP(7);

    uint32_t hf[4][4], ra[4][4];
    pack32(hf, ah);
#pragma unroll
    for (int u = 0; u < 4; u++) {
      ra[u][0] = hsub2(hf[u][0], mu0) & ~1u; ra[u][1] = hsub2(hf[u][1], mu1);
      ra[u][2] = hsub2(hf[u][2], mu0); ra[u][3] = hsub2(hf[u][3], mu1);
      ll_st(rec + (uint32_t)(R_H + j * 2048) + u * 512, ra[u][0], ra[u][1], ra[u][2], ra[u][3], tag);
    }
    mbar_wait(BAR + (p == 0 ? B_XDONE : B_WODONE) * 8);
    PSTAMP(8);

    float rs0, rs1;
    auto swiglu = [&](float g0, float g1, float u0, float u1, float rs) -> uint32_t {
      const float hr = 0.5f * rs;
      const float x0 = g0 * hr, x1 = g1 * hr;
      const float t0 = tanhf_hw(x0), t1 = tanhf_hw(x1);
      return pack2(fmaf(x0, t0, x0) * (u0 * rs), fmaf(x1, t1, x1) * (u1 * rs));
    };
    uint32_t hA[6][4];
    {
      float a1[64], a2[32];
      uint32_t rb[4][4], rc[4][4], rd[4][4];
      auto fetch = [&](uint32_t (&a)[4][4], int i) { ll_issue<4>(a, osrc[i - 1] + R_H, 512); };
      auto check = [&](uint32_t (&a)[4][4], uint32_t (&b)[4][4], int i) {
        if (__builtin_expect(ll_bad2<4, 4>(a, b, pin(tag, zero)), 0)) {
          uint32_t it = 0;
#pragma unroll 1
          do { fetch(a, i); fetch(b, i + 1); } while (ll_bad2<4, 4>(a, b, tag) && ++it < SPIN_LIMIT);
        }
        ll_clear<4>(a); ll_clear<4>(b);
        keep(a); keep(b);
      };
      auto head = [&](uint32_t (&a)[4][4], int i) {
        mbar_wait(BAR + (B_FA + i) * 8);
        wg_fence();
        wgmma_rs_n64<DESC_HI64>(a2, a[0], descBh(RING + 16384) + (i & 3) * 1536, i);
        wgmma_rs_n128(a1, a[0], descB(RING) + (i & 3) * 1536, i);
        wg_commit();
#pragma unroll
        for (int u = 0; u < 4; u++) stsm4(Hn + w * 2048 + i * 8192 + (moff ^ (u << 5)), a[u]);
        wg_wait<1>();
        if (i > 0) mbar_arrive_if(BAR + (B_EA + i - 1) * 8, lane == 0);
      };
      auto rest = [&](uint32_t (&a)[4][4], int i) {
        wg_fence();
#pragma unroll
        for (int k = 1; k < 4; k++) {
          wgmma_rs_n64<DESC_HI64>(a2, a[k], descBh(RING + 16384) + (i & 3) * 1536 + k * 64, 1);
          wgmma_rs_n128(a1, a[k], descB(RING) + (i & 3) * 1536 + k * 128, 1);
        }
        wg_commit();
      };
      keep(ra);
      head(ra, 0); rest(ra, 0);
      {
        float s0 = 0.f, q0 = 0.f, s1 = 0.f, q1 = 0.f;
#pragma unroll
        for (int b = 0; b < 8; b++) {
          s0 += ah[4 * b] + ah[4 * b + 1]; s1 += ah[4 * b + 2] + ah[4 * b + 3];
          q0 = fmaf(ah[4 * b], ah[4 * b], q0); q0 = fmaf(ah[4 * b + 1], ah[4 * b + 1], q0);
          q1 = fmaf(ah[4 * b + 2], ah[4 * b + 2], q1); q1 = fmaf(ah[4 * b + 3], ah[4 * b + 3], q1);
        }
#pragma unroll
        for (int o = 1; o <= 2; o <<= 1) {
          s0 += __shfl_xor_sync(0xffffffffu, s0, o); q0 += __shfl_xor_sync(0xffffffffu, q0, o);
          s1 += __shfl_xor_sync(0xffffffffu, s1, o); q1 += __shfl_xor_sync(0xffffffffu, q1, o);
        }
        if (c == 0) ll_st(recs + (uint32_t)(R_HS + j * 128), __float_as_uint(s0), __float_as_uint(q0), __float_as_uint(s1), __float_as_uint(q1), tag);
      }
      ll_get<4>(rb, osrc[0] + R_H, 512, tag);
      keep(rb);
      PSTAMP(17);
      fetch(rc, 2); fetch(rd, 3);
      head(rb, 1); rest(rb, 1);
      check(rc, rd, 2);
      head(rc, 2); fetch(ra, 4); fetch(rb, 5); rest(rc, 2);
      head(rd, 3); rest(rd, 3);
      check(ra, rb, 4);
      head(ra, 4); fetch(rc, 6); fetch(rd, 7); ll_issue<2>(sv, recs + (R_HS + c * 256), 128); rest(ra, 4);
      head(rb, 5); rest(rb, 5);
      check(rc, rd, 6);
      head(rc, 6); rest(rc, 6);
      head(rd, 7); rest(rd, 7);
      fence_async_smem();
      ll_wait<2>(sv, recs + (R_HS + c * 256), 128, tag);
      float s0 = __uint_as_float(sv[0][0]) + __uint_as_float(sv[1][0]), q0 = __uint_as_float(sv[0][1]) + __uint_as_float(sv[1][1]);
      float s1 = __uint_as_float(sv[0][2]) + __uint_as_float(sv[1][2]), q1 = __uint_as_float(sv[0][3]) + __uint_as_float(sv[1][3]);
#pragma unroll
      for (int o = 1; o <= 2; o <<= 1) {
        s0 += __shfl_xor_sync(0xffffffffu, s0, o); q0 += __shfl_xor_sync(0xffffffffu, q0, o);
        s1 += __shfl_xor_sync(0xffffffffu, s1, o); q1 += __shfl_xor_sync(0xffffffffu, q1, o);
      }
      s0 *= 1.f / D_; s1 *= 1.f / D_;
      rs0 = rsqrtf(fmaxf(fmaf(-s0, s0, q0 * (1.f / D_)), 0.f) + 1e-5f);
      rs1 = rsqrtf(fmaxf(fmaf(-s1, s1, q1 * (1.f / D_)), 0.f) + 1e-5f);
      wg_wait<0>();
      keep(a1); keep(a2);
      mbar_arrive_if(BAR + (B_EA + 7) * 8, lane == 0);
      PSTAMP(9);
#pragma unroll
      for (int u = 0; u < 4; u++)
#pragma unroll
        for (int e = 0; e < 4; e++)
          hA[u][e] = swiglu(a1[8 * u + 2 * e], a1[8 * u + 2 * e + 1], a1[32 + 8 * u + 2 * e], a1[33 + 8 * u + 2 * e], (e & 1) ? rs1 : rs0);
#pragma unroll
      for (int u = 0; u < 2; u++)
#pragma unroll
        for (int e = 0; e < 4; e++)
          hA[4 + u][e] = swiglu(a2[8 * u + 2 * e], a2[8 * u + 2 * e + 1], a2[16 + 8 * u + 2 * e], a2[17 + 8 * u + 2 * e], (e & 1) ? rs1 : rs0);
      keep(hA);
      wg_bar(p);
    }
    PSTAMP(10);

    const uint32_t mbx = Hn + 32768 + w * 512 + lane * 16;
    auto send = [&](const uint32_t (&v)[4], uint32_t a, int part) {
      asm volatile("st.async.weak.shared::cluster.mbarrier::complete_tx::bytes.v4.b32 [%0], {%1,%2,%3,%4}, [%5];"
                   ::"r"(a + peer()), "r"(v[0]), "r"(v[1]), "r"(v[2]), "r"(v[3]), "r"(BAR + (B_HX + 2 * part + p) * 8 + peer()) : "memory");
    };
    uint32_t hB[8][4];
    {
      float ab[128];
      uint32_t db = descB(RING);
      const uint32_t dAn = descA(H1) - p * 4096;
      if (lane == 0 && w == 0) { mbar_expect_tx(BAR + (B_HX + p) * 8, 12288); mbar_expect_tx(BAR + (B_HX + 2 + p) * 8, 16384); }
#pragma unroll 1
      for (int i = 0; i < 8; i++) {
        mbar_wait(BAR + (B_FB + i) * 8);
        const uint32_t da = dAn + i * 512;
        wg_fence();
        wgmma_ss_n256(ab, da, db, i);
#pragma unroll
        for (int k = 1; k < 4; k++) wgmma_ss_n256(ab, da + k * 2, db + k * 128, 1);
        wg_commit();
        if (i == 7) {
          mbar_wait_cluster(BAR + (B_PF + p) * 8);
#pragma unroll
          for (int k = 0; k < 6; k++) send(hA[k], mbx + k * 2048, 0);
        }
        wg_wait<1>();
        mbar_arrive_if(BAR + (B_EB + i - 1) * 8, i > 0 && lane == 0);
        if (i == 6 && lane == 0) mbar_arrive_peer(BAR + (B_PF + p) * 8);
        db = db == descB(RING + 65536) ? descB(RING) : db + 2048;
      }
      wg_wait<0>();
      keep(ab);
      mbar_arrive_if(BAR + (B_EB + 7) * 8, lane == 0);
      if (lane == 0) mbar_arrive_peer(BAR + (B_PF + 2 + p) * 8);
      PSTAMP(11);
#pragma unroll
      for (int u = 0; u < 8; u++) {
        const int o = (u >> 2) * 64 + (u & 3) * 8;
#pragma unroll
        for (int e = 0; e < 4; e++)
          hB[u][e] = swiglu(ab[o + 2 * e], ab[o + 2 * e + 1], ab[o + 32 + 2 * e], ab[o + 33 + 2 * e], (e & 1) ? rs1 : rs0);
        if (u == 3) mbar_wait_cluster(BAR + (B_PF + 2 + p) * 8);
        if (u == 4 || u == 5) send(hB[u - 4], mbx + (2 + u) * 2048, 1);
      }
      keep(hB);
    }
    PSTAMP(12);

    {
      float ya[32], y[32];
      uint32_t hP[14][4];
      const uint32_t offA = (j & 1) ? 256 : 0, offH = (j & 1) ? 0 : 1536;
      gptr const e4 = xl + (X_E4 + g * 24 * 16384 + warp * 2048);
      const uint32_t stg = H0 + p * 65536 + 28672 + (w >> 1) * 32768 + (w & 1) * 2048;
      auto mm = [&](float (&d)[32], int m, int k0, int k1) {
        if (k0 == 0) mbar_wait(BAR + (B_FT + m) * 8);
        const uint32_t T = descB(0) + (t_addr(m) >> 4);
        const uint32_t oA = w2_peer(m) ? 256 - offA : offA, oH = w2_peer(m) ? 1536 - offH : offH;
        wg_fence();
#pragma unroll
        for (int k = k0; k < k1; k++) {
          const uint32_t db = T + (k < 4 ? oA + k * 128 : k < 6 ? oH + (k - 4) * 128 : oA + 512 + (k - 6) * 128);
          if (w2_peer(m)) wgmma_rs_n64(d, hP[k], db, 1);
          else if (k < 6) wgmma_rs_n64(d, hA[k], db, k);
          else wgmma_rs_n64(d, hB[k - 6], db, 1);
        }
        wg_commit();
      };
      auto next = [&](float (&d)[32], int m, float (&dp)[32], int q) {
        mm(d, m, 0, 3);
        wg_wait<1>();
        keep(dp);
        mbar_arrive_if(BAR + (B_ET0 + q) * 8, lane == 0);
        gptr dst = e4 + (uint32_t)((((j + 2 + 2 * q) & 7) * 3 + q) * 16384);
#pragma unroll
        for (int u = 0; u < 4; u++)
          ll_st(dst + u * 512, pack2(dp[8 * u], dp[8 * u + 1]), pack2(dp[8 * u + 2], dp[8 * u + 3]),
                pack2(dp[8 * u + 4], dp[8 * u + 5]), pack2(dp[8 * u + 6], dp[8 * u + 7]), tag);
        if (q == 2) mbar_wait(BAR + (B_ET0 + 2) * 8);
        mm(d, m, 3, 14);
      };
#pragma unroll
      for (int i = 0; i < 3; i++) {
        const uint32_t a = i ? pin(mbx, zero) : mbx;
        send(hB[2 + 2 * i], a + (8 + 2 * i) * 2048, 1);
        send(hB[3 + 2 * i], a + (9 + 2 * i) * 2048, 1);
        if (i < 2) mm(ya, 0, 7 * i, 7 * i + 7);
        else mm(y, 1, 0, 6);
      }
      mbar_wait_cluster(BAR + (B_HX + p) * 8);
#pragma unroll
      for (int k = 0; k < 6; k++) lds128(hP[k], mbx + k * 2048);
      mm(y, 1, 6, 14);
      keep(hP[0]); keep(hP[1]); keep(hP[2]); keep(hP[3]); keep(hP[4]); keep(hP[5]);
      mm(ya, 2, 0, 3);
      mbar_wait_cluster(BAR + (B_HX + 2 + p) * 8);
      PSTAMPX(24);
#pragma unroll
      for (int k = 6; k < 14; k++) lds128(hP[k], mbx + k * 2048);
      mm(ya, 2, 3, 6);
      keep(hP);
      mm(ya, 2, 6, 7);
      mbar_arrive_if(BAR + (B_HC + p) * 8, lane == 0 || (hP[13][0] & zero) != 0);
      mm(ya, 2, 7, 14);
      mbar_wait(BAR + B_CLR4 * 8);
      next(y, 3, ya, 0);
      PSTAMPX(27);
      next(ya, 4, y, 1);
      mbar_arrive_if(BAR + (B_ET0 + 3) * 8, lane == 0);
      mm(ya, 5, 0, 14);
      PSTAMPX(26);
      next(y, 6, ya, 2);
      PSTAMPX(28);
      uint32_t in[8][4], lt[4][4];
      gptr const insrc = e4 + (uint32_t)(j * 3 * 16384);
      mm(y, 7, 0, 9);
      ll_issue<4>(lt, insrc + 32768, 512);
      mbar_wait(BAR + B_FIN * 8);
#pragma unroll
      for (int u = 0; u < 8; u++) lds128(in[u], t_addr(1 + (u >> 2)) + warp * 2048 + lane * 16 + (u & 3) * 512);
      mm(y, 7, 9, 14);
      if (__builtin_expect(ll_bad<8>(in, tag), 0)) {
        uint32_t it = 0;
#pragma unroll 1
        do {
#pragma unroll
          for (int u = 0; u < 8; u++) ll_ld(in[u], insrc + ((u >> 2) * 16384 + (u & 3) * 512));
        } while (ll_bad<8>(in, tag) && ++it < SPIN_LIMIT);
      }
      ll_clear<8>(in);
      const uint32_t ident = (2 * c == r ? 0x3f80u : 0u) | (2 * c + 1 == r ? 0x3f800000u : 0u);
      auto acc = [&](const uint32_t (&v)[4], int u) {
        mma1688_acc(*reinterpret_cast<float (*)[4]>(&y[8 * u]), v[0], v[1], ident);
        mma1688_acc(*reinterpret_cast<float (*)[4]>(&y[8 * u + 4]), v[2], v[3], ident);
      };
      wg_wait<0>();
      keep(y);
      PSTAMP(13);
#pragma unroll
      for (int u = 0; u < 4; u++) acc(hf[u], u);
#pragma unroll
      for (int u = 0; u < 8; u++) acc(in[u], u & 3);
      PSTAMPX(25);
      if (ll_bad<4>(lt, pin(tag, zero))) {
        ll_spin<4>(lt, insrc + 32768, 512, tag);
      }
      ll_clear<4>(lt);
#pragma unroll
      for (int u = 0; u < 4; u++) acc(lt[u], u);
      PSTAMP(14);
#pragma unroll
      for (int u = 0; u < 4; u++) {
        uint32_t o[4];
#pragma unroll
        for (int e = 0; e < 4; e++) o[e] = pack2(y[8 * u + 2 * e], y[8 * u + 2 * e + 1]);
        stsm4(stg + (moff ^ (u << 5)), o);
      }
      fence_async_smem();
      __syncwarp();
      if (elect_one()) {
        tma3d_store(&P.out, stg, 64 * j, p, g * 64 + 16 * w);
        asm volatile("cp.async.bulk.commit_group;" ::: "memory");
        asm volatile("cp.async.bulk.wait_group.read 0;" ::: "memory");
      }
      PSTAMP(15);
    }
  }
}

typedef CUresult (*EncodeFn)(CUtensorMap*, CUtensorMapDataType, cuuint32_t, void*, const cuuint64_t*, const cuuint64_t*,
                             const cuuint32_t*, const cuuint32_t*, CUtensorMapInterleave, CUtensorMapSwizzle,
                             CUtensorMapL2promotion, CUtensorMapFloatOOBfill);

void enc2d(EncodeFn f, CUtensorMap* m, const void* base, uint64_t cols, uint64_t rows, uint32_t bc, uint32_t br, CUtensorMapSwizzle sw) {
  cuuint64_t gd[2] = {cols, rows}, gs[1] = {cols * 2};
  cuuint32_t bd[2] = {bc, br}, es[2] = {1, 1};
  f(m, CU_TENSOR_MAP_DATA_TYPE_BFLOAT16, 2, const_cast<void*>(base), gd, gs, bd, es, CU_TENSOR_MAP_INTERLEAVE_NONE, sw,
    CU_TENSOR_MAP_L2_PROMOTION_L2_128B, CU_TENSOR_MAP_FLOAT_OOB_FILL_NONE);
}
void enc_par(EncodeFn f, CUtensorMap* m, const void* base, uint32_t pairs) {
  cuuint64_t gd[3] = {(cuuint64_t)D_, 2, (cuuint64_t)S_ / 2}, gs[2] = {D_ * 2, D_ * 4};
  cuuint32_t bd[3] = {64, 1, pairs}, es[3] = {1, 1, 1};
  f(m, CU_TENSOR_MAP_DATA_TYPE_BFLOAT16, 3, const_cast<void*>(base), gd, gs, bd, es, CU_TENSOR_MAP_INTERLEAVE_NONE,
    CU_TENSOR_MAP_SWIZZLE_128B, CU_TENSOR_MAP_L2_PROMOTION_L2_128B, CU_TENSOR_MAP_FLOAT_OOB_FILL_NONE);
}

}

extern "C" void kernel_launch(void* const* d_in, const int* in_sizes, int n_in, void* d_out, int out_size) {
  (void)in_sizes; (void)n_in; (void)out_size;
  static EncodeFn enc = nullptr;
  static char* scratch = nullptr;
  if (!enc) {
    void* fn = nullptr;
    cudaDriverEntryPointQueryResult q;
    cudaGetDriverEntryPoint("cuTensorMapEncodeTiled", &fn, cudaEnableDefault, &q);
    enc = (EncodeFn)fn;
    cudaGetSymbolAddress((void**)&scratch, g_scratch);
    cudaFuncSetAttribute(fused_block_kernel, cudaFuncAttributeMaxDynamicSharedMemorySize, SMEM_BYTES);
  }
  Params P;
  const __nv_bfloat16* xp = (const __nv_bfloat16*)d_in[0];
  const __nv_bfloat16* wqkvp = (const __nv_bfloat16*)d_in[1];
  const __nv_bfloat16* wop = (const __nv_bfloat16*)d_in[2];
  P.w1p = (const __nv_bfloat16*)d_in[4];
  P.w3p = (const __nv_bfloat16*)d_in[5];
  P.w2p = (const __nv_bfloat16*)d_in[6];
  enc_par(enc, &P.x, xp, 64);
  enc_par(enc, &P.out, d_out, 16);
  {
    cuuint64_t gd[3] = {(cuuint64_t)D_, (cuuint64_t)D_, 3}, gs[2] = {3 * D_ * 2, D_ * 2};
    cuuint32_t bd[3] = {64, 64, 3}, es[3] = {1, 1, 1};
    enc(&P.wqkv, CU_TENSOR_MAP_DATA_TYPE_BFLOAT16, 3, const_cast<__nv_bfloat16*>(wqkvp), gd, gs, bd, es, CU_TENSOR_MAP_INTERLEAVE_NONE,
        CU_TENSOR_MAP_SWIZZLE_128B, CU_TENSOR_MAP_L2_PROMOTION_L2_128B, CU_TENSOR_MAP_FLOAT_OOB_FILL_NONE);
  }
  enc2d(enc, &P.wo, wop, D_, D_, 64, 64, CU_TENSOR_MAP_SWIZZLE_128B);
  enc2d(enc, &P.w1, P.w1p, F_, D_, 64, 64, CU_TENSOR_MAP_SWIZZLE_128B);
  enc2d(enc, &P.w3, P.w3p, F_, D_, 64, 64, CU_TENSOR_MAP_SWIZZLE_128B);
  enc2d(enc, &P.w1h, P.w1p, F_, D_, 32, 64, CU_TENSOR_MAP_SWIZZLE_64B);
  enc2d(enc, &P.w3h, P.w3p, F_, D_, 32, 64, CU_TENSOR_MAP_SWIZZLE_64B);
  enc2d(enc, &P.w2, P.w2p, D_, F_, 64, 224, CU_TENSOR_MAP_SWIZZLE_128B);

  cudaLaunchConfig_t cfg = {};
  cfg.gridDim = dim3(128);
  cfg.blockDim = dim3(384);
  cfg.dynamicSmemBytes = SMEM_BYTES;
  cfg.stream = cudaStreamPerThread;
  cudaLaunchAttribute at[2];
  at[0].id = cudaLaunchAttributeCooperative;
  at[0].val.cooperative = 1;
  cfg.attrs = at;
  cfg.numAttrs = 1;
  at[1].id = cudaLaunchAttributeClusterDimension;
  at[1].val.clusterDim.x = 2; at[1].val.clusterDim.y = 1; at[1].val.clusterDim.z = 1;
  cfg.numAttrs = 2;
  cudaLaunchKernelEx(&cfg, fused_block_kernel, scratch, xp, wqkvp, wop, 0u, P);
}
```

```cpp
#include <cuda_runtime.h>
#include <cuda.h>
#include <cuda_bf16.h>
#include <stdint.h>
#include <stddef.h>

namespace {

constexpr int S_ = 2048, D_ = 512, F_ = 1792;
#define TOP_KB 1
#define SIDE_EARLY 0
#define CS_KB 3
#define CMAP 4
#define A_HOLD 9
#define B1_LATE 1
#define PF_KIND 128
#define PF_SLEEP 250
#define WO7_AT 1
#define CLSCOPE ""
#define PFV 1
#define PF_WHEN B_HALO
#define ORD 0
#define NOPF 1
#define NORH 0
#define PROBE_H 1
#define RH_FAST 0
#define RH_WHEN B_ORD
#define NOE4 0
#define FIN_K 14
#define O_SLEEP 0
#define H_SLEEP 200

constexpr uint32_t SPIN_LIMIT = 1u << 18;

constexpr uint32_t R_O = 0;
constexpr uint32_t R_H = 16384;
constexpr uint32_t REC = 32768;
constexpr uint32_t X_OS = 128 * REC;
constexpr uint32_t X_HS = X_OS + 128 * 1024;
constexpr uint32_t X_E4 = X_HS + 128 * 1024;
constexpr uint32_t X_E1 = X_E4 + 16 * 16 * 16384;
constexpr uint32_t X_CS = X_E1 + 256 * 2048;
constexpr uint32_t X_ST = X_CS + 384 * 256;
constexpr uint32_t X_WB = X_ST + 2048 * 16;
constexpr uint32_t X_EP = X_WB + 512 * 16;
__device__ __align__(1024) char g_scratch[X_EP + 512];
#define PSTAMP(i)
#define PSTAMPX(i)
#define PSTAMPW(slot, i)

struct alignas(64) Params {
  CUtensorMap x, out, wqkv, wo, w1, w3, w1h, w3h, w2;
  const __nv_bfloat16 *w1p, *w3p, *w2p;
};

constexpr uint32_t SB = 1024;
constexpr uint32_t H0 = SB;
constexpr uint32_t H1 = SB + 65536;
constexpr uint32_t RING = SB + 131072;
constexpr uint32_t BAR = SB + 229376;
constexpr uint32_t TAGS = BAR + 1016;
constexpr uint32_t WB = BAR + 1024;
constexpr uint32_t SMEM_BYTES = 232448;
static_assert(WB + 256 <= SB + SMEM_BYTES, "smem");

enum : int {
  B_FX = 0,
  B_FW = 16,
  B_TAG = 24, B_CLRH = 25,
  B_FWO = 32,
  B_FIN = 33,
  B_HX = 35,
  B_FA = 40, B_FB = 48, B_FT = 56,
  B_EW = 64, B_XDONE = 72, B_EA = 80, B_EB = 88,
  B_ET0 = 96,
  B_WODONE = 103,
  B_EX = 104,
  B_PF = 112,
  B_HC = 116,
  B_ORD = 118,

  B_READY = 120,
  B_HALO = 124,
  B_CLRO = 121,
  B_CLR1 = 122,
  B_CLR4 = 123
};

__device__ __forceinline__ uint32_t smem_u32(const void* p) { return (uint32_t)__cvta_generic_to_shared(p); }
__device__ __forceinline__ uint32_t own() { return (blockIdx.x & 1) << 24; }
__device__ __forceinline__ uint32_t peer() { return (~blockIdx.x & 1) << 24; }
__device__ __forceinline__ void mbar_init(uint32_t b, uint32_t c) { asm volatile("mbarrier.init.shared::cta.b64 [%0], %1;" ::"r"(b + own()), "r"(c) : "memory"); }
__device__ __forceinline__ void mbar_expect_tx(uint32_t b, uint32_t bytes) { asm volatile("mbarrier.arrive.expect_tx.shared::cta.b64 _, [%0], %1;" ::"r"(b + own()), "r"(bytes) : "memory"); }
__device__ __forceinline__ void mbar_arrive(uint32_t b) { asm volatile("mbarrier.arrive.shared::cta.b64 _, [%0];" ::"r"(b + own()) : "memory"); }
__device__ __forceinline__ void mbar_wait(uint32_t b) {
  asm volatile("{\n.reg .pred p;\n.reg .u32 c;\nmov.u32 c, 0;\nLW:\n.pragma \"nounroll\";\n"
               "mbarrier.try_wait.parity.shared::cta.b64 p, [%0], 0;\nadd.u32 c, c, 1;\nsetp.gt.or.u32 p, c, %1, p;\n@!p bra LW;\n}\n"
               ::"r"(b + own()), "n"(SPIN_LIMIT) : "memory");
}
__device__ __forceinline__ void mbar_arrive_peer(uint32_t b) {
  asm volatile("mbarrier.arrive.relaxed.cluster.shared::cluster.b64 _, [%0];" ::"r"(b + peer()) : "memory");
}
__device__ __forceinline__ void mbar_wait_cluster(uint32_t b) {
  asm volatile("{\n.reg .pred p;\n.reg .u32 c;\nmov.u32 c, 0;\nLW:\n.pragma \"nounroll\";\n"
               "mbarrier.try_wait.parity" CLSCOPE ".shared::cta.b64 p, [%0], 0;\nadd.u32 c, c, 1;\nsetp.gt.or.u32 p, c, %1, p;\n@!p bra LW;\n}\n"
               ::"r"(b + own()), "n"(SPIN_LIMIT) : "memory");
}
__device__ __forceinline__ bool elect_one() {
  uint32_t p;
  asm volatile("{\n.reg .pred P;\nelect.sync _|P, 0xffffffff;\nselp.u32 %0, 1, 0, P;\n}\n" : "=r"(p));
  return p;
}
__device__ __forceinline__ void tma2d(uint32_t dst, const CUtensorMap* m, int c0, int c1, uint32_t bar) {
  dst += own(); bar += own();
  asm volatile("cp.async.bulk.tensor.2d.shared::cluster.global.mbarrier::complete_tx::bytes [%0], [%1, {%3, %4}], [%2];"
               ::"r"(dst), "l"(m), "r"(bar), "r"(c0), "r"(c1) : "memory");
}
__device__ __forceinline__ void tma3d(uint32_t dst, const CUtensorMap* m, int c0, int c1, int c2, uint32_t bar) {
  dst += own(); bar += own();
  asm volatile("cp.async.bulk.tensor.3d.shared::cluster.global.mbarrier::complete_tx::bytes [%0], [%1, {%3, %4, %5}], [%2];"
               ::"r"(dst), "l"(m), "r"(bar), "r"(c0), "r"(c1), "r"(c2) : "memory");
}
__device__ __forceinline__ void tma3d_store(const CUtensorMap* m, uint32_t src, int c0, int c1, int c2) {
  asm volatile("cp.async.bulk.tensor.3d.global.shared::cta.bulk_group [%0, {%2, %3, %4}], [%1];"
               ::"l"(m), "r"(src + own()), "r"(c0), "r"(c1), "r"(c2) : "memory");
}
__device__ __forceinline__ void l2_prefetch(const void* p, uint32_t bytes) {
  asm volatile("cp.async.bulk.prefetch.L2.global [%0], %1;" ::"l"(p), "r"(bytes) : "memory");
}
__device__ __forceinline__ void prefetch_map(const CUtensorMap* m) { asm volatile("prefetch.tensormap [%0];" ::"l"(m) : "memory"); }
__device__ __forceinline__ void fence_async_smem() { asm volatile("fence.proxy.async.shared::cta;" ::: "memory"); }
__device__ __forceinline__ void wg_fence() { asm volatile("wgmma.fence.sync.aligned;" ::: "memory"); }
__device__ __forceinline__ void wg_commit() { asm volatile("wgmma.commit_group.sync.aligned;" ::: "memory"); }
template <int N> __device__ __forceinline__ void wg_wait() { asm volatile("wgmma.wait_group.sync.aligned %0;" ::"n"(N) : "memory"); }
__device__ __forceinline__ void wg_bar(int p) {
  if (p == 0) asm volatile("bar.sync 1, 128;" ::: "memory"); else asm volatile("bar.sync 2, 128;" ::: "memory");
}
constexpr uint32_t DESC_HI128 = (1024 >> 4) | (1u << 30);
constexpr uint32_t DESC_HI64 = (512 >> 4) | (2u << 30);
__device__ __forceinline__ constexpr uint32_t descA(uint32_t addr) { return (addr >> 4) | (1u << 16); }
__device__ __forceinline__ constexpr uint32_t descB(uint32_t addr) { return (addr >> 4) | ((8192u >> 4) << 16); }
__device__ __forceinline__ constexpr uint32_t descBh(uint32_t addr) { return (addr >> 4) | ((4096u >> 4) << 16); }

__device__ __forceinline__ void wgmma_ss_n192(float (&d)[96], uint32_t da, uint32_t db, int sc) {
  asm volatile("{\n.reg .pred p;\n.reg .b64 da, db;\nsetp.ne.b32 p, %98, 0;\nmov.b64 da, {%96, %99};\nmov.b64 db, {%97, %99};\n"
    "wgmma.mma_async.sync.aligned.m64n192k16.f32.bf16.bf16 {%0, %1, %2, %3, %4, %5, %6, %7, %8, %9, %10, %11, %12, %13, %14, %15, %16, %17, %18, %19, %20, %21, %22, %23, %24, %25, %26, %27, %28, %29, %30, %31, %32, %33, %34, %35, %36, %37, %38, %39, %40, %41, %42, %43, %44, %45, %46, %47, %48, %49, %50, %51, %52, %53, %54, %55, %56, %57, %58, %59, %60, %61, %62, %63, %64, %65, %66, %67, %68, %69, %70, %71, %72, %73, %74, %75, %76, %77, %78, %79, %80, %81, %82, %83, %84, %85, %86, %87, %88, %89, %90, %91, %92, %93, %94, %95}, da, db, p, 1, 1, 0, 1;\n}\n"
    : "+f"(d[0]), "+f"(d[1]), "+f"(d[2]), "+f"(d[3]), "+f"(d[4]), "+f"(d[5]), "+f"(d[6]), "+f"(d[7]),
      "+f"(d[8]), "+f"(d[9]), "+f"(d[10]), "+f"(d[11]), "+f"(d[12]), "+f"(d[13]), "+f"(d[14]), "+f"(d[15]),
      "+f"(d[16]), "+f"(d[17]), "+f"(d[18]), "+f"(d[19]), "+f"(d[20]), "+f"(d[21]), "+f"(d[22]), "+f"(d[23]),
      "+f"(d[24]), "+f"(d[25]), "+f"(d[26]), "+f"(d[27]), "+f"(d[28]), "+f"(d[29]), "+f"(d[30]), "+f"(d[31]),
      "+f"(d[32]), "+f"(d[33]), "+f"(d[34]), "+f"(d[35]), "+f"(d[36]), "+f"(d[37]), "+f"(d[38]), "+f"(d[39]),
      "+f"(d[40]), "+f"(d[41]), "+f"(d[42]), "+f"(d[43]), "+f"(d[44]), "+f"(d[45]), "+f"(d[46]), "+f"(d[47]),
      "+f"(d[48]), "+f"(d[49]), "+f"(d[50]), "+f"(d[51]), "+f"(d[52]), "+f"(d[53]), "+f"(d[54]), "+f"(d[55]),
      "+f"(d[56]), "+f"(d[57]), "+f"(d[58]), "+f"(d[59]), "+f"(d[60]), "+f"(d[61]), "+f"(d[62]), "+f"(d[63]),
      "+f"(d[64]), "+f"(d[65]), "+f"(d[66]), "+f"(d[67]), "+f"(d[68]), "+f"(d[69]), "+f"(d[70]), "+f"(d[71]),
      "+f"(d[72]), "+f"(d[73]), "+f"(d[74]), "+f"(d[75]), "+f"(d[76]), "+f"(d[77]), "+f"(d[78]), "+f"(d[79]),
      "+f"(d[80]), "+f"(d[81]), "+f"(d[82]), "+f"(d[83]), "+f"(d[84]), "+f"(d[85]), "+f"(d[86]), "+f"(d[87]),
      "+f"(d[88]), "+f"(d[89]), "+f"(d[90]), "+f"(d[91]), "+f"(d[92]), "+f"(d[93]), "+f"(d[94]), "+f"(d[95])
    : "r"(da), "r"(db), "r"(sc), "n"(DESC_HI128));
}
__device__ __forceinline__ void wgmma_ss_n256(float (&d)[128], uint32_t da, uint32_t db, int sc) {
  asm volatile("{\n.reg .pred p;\n.reg .b64 da, db;\nsetp.ne.b32 p, %130, 0;\nmov.b64 da, {%128, %131};\nmov.b64 db, {%129, %131};\n"
    "wgmma.mma_async.sync.aligned.m64n256k16.f32.bf16.bf16 {%0, %1, %2, %3, %4, %5, %6, %7, %8, %9, %10, %11, %12, %13, %14, %15, %16, %17, %18, %19, %20, %21, %22, %23, %24, %25, %26, %27, %28, %29, %30, %31, %32, %33, %34, %35, %36, %37, %38, %39, %40, %41, %42, %43, %44, %45, %46, %47, %48, %49, %50, %51, %52, %53, %54, %55, %56, %57, %58, %59, %60, %61, %62, %63, %64, %65, %66, %67, %68, %69, %70, %71, %72, %73, %74, %75, %76, %77, %78, %79, %80, %81, %82, %83, %84, %85, %86, %87, %88, %89, %90, %91, %92, %93, %94, %95, %96, %97, %98, %99, %100, %101, %102, %103, %104, %105, %106, %107, %108, %109, %110, %111, %112, %113, %114, %115, %116, %117, %118, %119, %120, %121, %122, %123, %124, %125, %126, %127}, da, db, p, 1, 1, 0, 1;\n}\n"
    : "+f"(d[0]), "+f"(d[1]), "+f"(d[2]), "+f"(d[3]), "+f"(d[4]), "+f"(d[5]), "+f"(d[6]), "+f"(d[7]),
      "+f"(d[8]), "+f"(d[9]), "+f"(d[10]), "+f"(d[11]), "+f"(d[12]), "+f"(d[13]), "+f"(d[14]), "+f"(d[15]),
      "+f"(d[16]), "+f"(d[17]), "+f"(d[18]), "+f"(d[19]), "+f"(d[20]), "+f"(d[21]), "+f"(d[22]), "+f"(d[23]),
      "+f"(d[24]), "+f"(d[25]), "+f"(d[26]), "+f"(d[27]), "+f"(d[28]), "+f"(d[29]), "+f"(d[30]), "+f"(d[31]),
      "+f"(d[32]), "+f"(d[33]), "+f"(d[34]), "+f"(d[35]), "+f"(d[36]), "+f"(d[37]), "+f"(d[38]), "+f"(d[39]),
      "+f"(d[40]), "+f"(d[41]), "+f"(d[42]), "+f"(d[43]), "+f"(d[44]), "+f"(d[45]), "+f"(d[46]), "+f"(d[47]),
      "+f"(d[48]), "+f"(d[49]), "+f"(d[50]), "+f"(d[51]), "+f"(d[52]), "+f"(d[53]), "+f"(d[54]), "+f"(d[55]),
      "+f"(d[56]), "+f"(d[57]), "+f"(d[58]), "+f"(d[59]), "+f"(d[60]), "+f"(d[61]), "+f"(d[62]), "+f"(d[63]),
      "+f"(d[64]), "+f"(d[65]), "+f"(d[66]), "+f"(d[67]), "+f"(d[68]), "+f"(d[69]), "+f"(d[70]), "+f"(d[71]),
      "+f"(d[72]), "+f"(d[73]), "+f"(d[74]), "+f"(d[75]), "+f"(d[76]), "+f"(d[77]), "+f"(d[78]), "+f"(d[79]),
      "+f"(d[80]), "+f"(d[81]), "+f"(d[82]), "+f"(d[83]), "+f"(d[84]), "+f"(d[85]), "+f"(d[86]), "+f"(d[87]),
      "+f"(d[88]), "+f"(d[89]), "+f"(d[90]), "+f"(d[91]), "+f"(d[92]), "+f"(d[93]), "+f"(d[94]), "+f"(d[95]),
      "+f"(d[96]), "+f"(d[97]), "+f"(d[98]), "+f"(d[99]), "+f"(d[100]), "+f"(d[101]), "+f"(d[102]), "+f"(d[103]),
      "+f"(d[104]), "+f"(d[105]), "+f"(d[106]), "+f"(d[107]), "+f"(d[108]), "+f"(d[109]), "+f"(d[110]), "+f"(d[111]),
      "+f"(d[112]), "+f"(d[113]), "+f"(d[114]), "+f"(d[115]), "+f"(d[116]), "+f"(d[117]), "+f"(d[118]), "+f"(d[119]),
      "+f"(d[120]), "+f"(d[121]), "+f"(d[122]), "+f"(d[123]), "+f"(d[124]), "+f"(d[125]), "+f"(d[126]), "+f"(d[127])
    : "r"(da), "r"(db), "r"(sc), "n"(DESC_HI128));
}
template <uint32_t HI = DESC_HI128>
__device__ __forceinline__ void wgmma_rs_n64(float (&d)[32], const uint32_t (&a)[4], uint32_t db, int sc) {
  asm volatile("{\n.reg .pred p;\n.reg .b64 db;\nsetp.ne.b32 p, %37, 0;\nmov.b64 db, {%36, %38};\n"
    "wgmma.mma_async.sync.aligned.m64n64k16.f32.bf16.bf16 {%0, %1, %2, %3, %4, %5, %6, %7, %8, %9, %10, %11, %12, %13, %14, %15, %16, %17, %18, %19, %20, %21, %22, %23, %24, %25, %26, %27, %28, %29, %30, %31}, {%32, %33, %34, %35}, db, p, 1, 1, 1;\n}\n"
    : "+f"(d[0]), "+f"(d[1]), "+f"(d[2]), "+f"(d[3]), "+f"(d[4]), "+f"(d[5]), "+f"(d[6]), "+f"(d[7]),
      "+f"(d[8]), "+f"(d[9]), "+f"(d[10]), "+f"(d[11]), "+f"(d[12]), "+f"(d[13]), "+f"(d[14]), "+f"(d[15]),
      "+f"(d[16]), "+f"(d[17]), "+f"(d[18]), "+f"(d[19]), "+f"(d[20]), "+f"(d[21]), "+f"(d[22]), "+f"(d[23]),
      "+f"(d[24]), "+f"(d[25]), "+f"(d[26]), "+f"(d[27]), "+f"(d[28]), "+f"(d[29]), "+f"(d[30]), "+f"(d[31])
    : "r"(a[0]), "r"(a[1]), "r"(a[2]), "r"(a[3]), "r"(db), "r"(sc), "n"(HI));
}
template <uint32_t HI = DESC_HI128>
__device__ __forceinline__ void wgmma_rs_n128(float (&d)[64], const uint32_t (&a)[4], uint32_t db, int sc) {
  asm volatile("{\n.reg .pred p;\n.reg .b64 db;\nsetp.ne.b32 p, %69, 0;\nmov.b64 db, {%68, %70};\n"
    "wgmma.mma_async.sync.aligned.m64n128k16.f32.bf16.bf16 {%0, %1, %2, %3, %4, %5, %6, %7, %8, %9, %10, %11, %12, %13, %14, %15, %16, %17, %18, %19, %20, %21, %22, %23, %24, %25, %26, %27, %28, %29, %30, %31, %32, %33, %34, %35, %36, %37, %38, %39, %40, %41, %42, %43, %44, %45, %46, %47, %48, %49, %50, %51, %52, %53, %54, %55, %56, %57, %58, %59, %60, %61, %62, %63}, {%64, %65, %66, %67}, db, p, 1, 1, 1;\n}\n"
    : "+f"(d[0]), "+f"(d[1]), "+f"(d[2]), "+f"(d[3]), "+f"(d[4]), "+f"(d[5]), "+f"(d[6]), "+f"(d[7]),
      "+f"(d[8]), "+f"(d[9]), "+f"(d[10]), "+f"(d[11]), "+f"(d[12]), "+f"(d[13]), "+f"(d[14]), "+f"(d[15]),
      "+f"(d[16]), "+f"(d[17]), "+f"(d[18]), "+f"(d[19]), "+f"(d[20]), "+f"(d[21]), "+f"(d[22]), "+f"(d[23]),
      "+f"(d[24]), "+f"(d[25]), "+f"(d[26]), "+f"(d[27]), "+f"(d[28]), "+f"(d[29]), "+f"(d[30]), "+f"(d[31]),
      "+f"(d[32]), "+f"(d[33]), "+f"(d[34]), "+f"(d[35]), "+f"(d[36]), "+f"(d[37]), "+f"(d[38]), "+f"(d[39]),
      "+f"(d[40]), "+f"(d[41]), "+f"(d[42]), "+f"(d[43]), "+f"(d[44]), "+f"(d[45]), "+f"(d[46]), "+f"(d[47]),
      "+f"(d[48]), "+f"(d[49]), "+f"(d[50]), "+f"(d[51]), "+f"(d[52]), "+f"(d[53]), "+f"(d[54]), "+f"(d[55]),
      "+f"(d[56]), "+f"(d[57]), "+f"(d[58]), "+f"(d[59]), "+f"(d[60]), "+f"(d[61]), "+f"(d[62]), "+f"(d[63])
    : "r"(a[0]), "r"(a[1]), "r"(a[2]), "r"(a[3]), "r"(db), "r"(sc), "n"(HI));
}
template <uint32_t HI = DESC_HI128>
__device__ __forceinline__ void wgmma_rs_n192(float (&d)[96], const uint32_t (&a)[4], uint32_t db, int sc) {
  asm volatile("{\n.reg .pred p;\n.reg .b64 db;\nsetp.ne.b32 p, %101, 0;\nmov.b64 db, {%100, %102};\n"
    "wgmma.mma_async.sync.aligned.m64n192k16.f32.bf16.bf16 {%0, %1, %2, %3, %4, %5, %6, %7, %8, %9, %10, %11, %12, %13, %14, %15, %16, %17, %18, %19, %20, %21, %22, %23, %24, %25, %26, %27, %28, %29, %30, %31, %32, %33, %34, %35, %36, %37, %38, %39, %40, %41, %42, %43, %44, %45, %46, %47, %48, %49, %50, %51, %52, %53, %54, %55, %56, %57, %58, %59, %60, %61, %62, %63, %64, %65, %66, %67, %68, %69, %70, %71, %72, %73, %74, %75, %76, %77, %78, %79, %80, %81, %82, %83, %84, %85, %86, %87, %88, %89, %90, %91, %92, %93, %94, %95}, {%96, %97, %98, %99}, db, p, 1, 1, 1;\n}\n"
    : "+f"(d[0]), "+f"(d[1]), "+f"(d[2]), "+f"(d[3]), "+f"(d[4]), "+f"(d[5]), "+f"(d[6]), "+f"(d[7]),
      "+f"(d[8]), "+f"(d[9]), "+f"(d[10]), "+f"(d[11]), "+f"(d[12]), "+f"(d[13]), "+f"(d[14]), "+f"(d[15]),
      "+f"(d[16]), "+f"(d[17]), "+f"(d[18]), "+f"(d[19]), "+f"(d[20]), "+f"(d[21]), "+f"(d[22]), "+f"(d[23]),
      "+f"(d[24]), "+f"(d[25]), "+f"(d[26]), "+f"(d[27]), "+f"(d[28]), "+f"(d[29]), "+f"(d[30]), "+f"(d[31]),
      "+f"(d[32]), "+f"(d[33]), "+f"(d[34]), "+f"(d[35]), "+f"(d[36]), "+f"(d[37]), "+f"(d[38]), "+f"(d[39]),
      "+f"(d[40]), "+f"(d[41]), "+f"(d[42]), "+f"(d[43]), "+f"(d[44]), "+f"(d[45]), "+f"(d[46]), "+f"(d[47]),
      "+f"(d[48]), "+f"(d[49]), "+f"(d[50]), "+f"(d[51]), "+f"(d[52]), "+f"(d[53]), "+f"(d[54]), "+f"(d[55]),
      "+f"(d[56]), "+f"(d[57]), "+f"(d[58]), "+f"(d[59]), "+f"(d[60]), "+f"(d[61]), "+f"(d[62]), "+f"(d[63]),
      "+f"(d[64]), "+f"(d[65]), "+f"(d[66]), "+f"(d[67]), "+f"(d[68]), "+f"(d[69]), "+f"(d[70]), "+f"(d[71]),
      "+f"(d[72]), "+f"(d[73]), "+f"(d[74]), "+f"(d[75]), "+f"(d[76]), "+f"(d[77]), "+f"(d[78]), "+f"(d[79]),
      "+f"(d[80]), "+f"(d[81]), "+f"(d[82]), "+f"(d[83]), "+f"(d[84]), "+f"(d[85]), "+f"(d[86]), "+f"(d[87]),
      "+f"(d[88]), "+f"(d[89]), "+f"(d[90]), "+f"(d[91]), "+f"(d[92]), "+f"(d[93]), "+f"(d[94]), "+f"(d[95])
    : "r"(a[0]), "r"(a[1]), "r"(a[2]), "r"(a[3]), "r"(db), "r"(sc), "n"(HI));
}

template <int N> __device__ __forceinline__ void keep(float (&d)[N]) {
#pragma unroll
  for (int i = 0; i < N; i++) asm volatile("" : "+f"(d[i])::"memory");
}

__device__ __forceinline__ void keep(uint32_t (&d)[4]) { asm volatile("" : "+r"(d[0]), "+r"(d[1]), "+r"(d[2]), "+r"(d[3])::"memory"); }
template <int N> __device__ __forceinline__ void keep(uint32_t (&d)[N][4]) {
#pragma unroll
  for (int i = 0; i < N; i++) asm volatile("" : "+r"(d[i][0]), "+r"(d[i][1]), "+r"(d[i][2]), "+r"(d[i][3])::"memory");
}

__device__ __forceinline__ uint32_t pack2(float lo, float hi) {
  uint32_t r;
  asm("cvt.rn.bf16x2.f32 %0, %1, %2;" : "=r"(r) : "f"(hi), "f"(lo));
  return r;
}
__device__ __forceinline__ float bf_lo(uint32_t v) { return __uint_as_float(v << 16); }
__device__ __forceinline__ float bf_hi(uint32_t v) { return __uint_as_float(v & 0xffff0000u); }
__device__ __forceinline__ uint32_t hsub2(uint32_t a, uint32_t b) {
  uint32_t r;
  asm("sub.rn.bf16x2 %0, %1, %2;" : "=r"(r) : "r"(a), "r"(b));
  return r;
}
__device__ __forceinline__ uint32_t movm(uint32_t a) {
  uint32_t r;
  asm volatile("movmatrix.sync.aligned.m8n8.trans.b16 %0, %1;" : "=r"(r) : "r"(a));
  return r;
}
__device__ __forceinline__ void ldsm4(uint32_t (&v)[4], uint32_t a) {
  asm volatile("ldmatrix.sync.aligned.m8n8.x4.shared.b16 {%0,%1,%2,%3}, [%4];" : "=r"(v[0]), "=r"(v[1]), "=r"(v[2]), "=r"(v[3]) : "r"(a + own()) : "memory");
}
__device__ __forceinline__ void stsm4(uint32_t a, const uint32_t (&v)[4]) {
  asm volatile("stmatrix.sync.aligned.m8n8.x4.shared.b16 [%0], {%1,%2,%3,%4};" ::"r"(a + own()), "r"(v[0]), "r"(v[1]), "r"(v[2]), "r"(v[3]) : "memory");
}
__device__ __forceinline__ void mma16816(float (&d)[4], const uint32_t (&a)[4], uint32_t b0, uint32_t b1) {
  asm volatile("mma.sync.aligned.m16n8k16.row.col.f32.bf16.bf16.f32 {%0,%1,%2,%3}, {%4,%5,%6,%7}, {%8,%9}, {%10,%10,%10,%10};"
               : "=f"(d[0]), "=f"(d[1]), "=f"(d[2]), "=f"(d[3])
               : "r"(a[0]), "r"(a[1]), "r"(a[2]), "r"(a[3]), "r"(b0), "r"(b1), "f"(0.f));
}
__device__ __forceinline__ void mma1688_acc(float (&d)[4], uint32_t a0, uint32_t a1, uint32_t b0) {
  asm volatile("mma.sync.aligned.m16n8k8.row.col.f32.bf16.bf16.f32 {%0,%1,%2,%3}, {%4,%5}, {%6}, {%0,%1,%2,%3};"
               : "+f"(d[0]), "+f"(d[1]), "+f"(d[2]), "+f"(d[3]) : "r"(a0), "r"(a1), "r"(b0));
}
__device__ __forceinline__ float ex2(float x) { float y; asm("ex2.approx.ftz.f32 %0, %1;" : "=f"(y) : "f"(x)); return y; }
__device__ __forceinline__ float rcp(float x) { float y; asm("rcp.approx.ftz.f32 %0, %1;" : "=f"(y) : "f"(x)); return y; }
__device__ __forceinline__ float tanhf_hw(float x) { float y; asm("tanh.approx.f32 %0, %1;" : "=f"(y) : "f"(x)); return y; }
__device__ __forceinline__ uint32_t lds32(uint32_t a) { uint32_t v; asm volatile("ld.shared.u32 %0, [%1];" : "=r"(v) : "r"(a + own()) : "memory"); return v; }
__device__ __forceinline__ float2 lds64(uint32_t a) { float2 v; asm volatile("ld.shared.v2.f32 {%0,%1}, [%2];" : "=f"(v.x), "=f"(v.y) : "r"(a + own()) : "memory"); return v; }
__device__ __forceinline__ void lds128(uint32_t (&v)[4], uint32_t a) { asm volatile("ld.shared.v4.u32 {%0,%1,%2,%3}, [%4];" : "=r"(v[0]), "=r"(v[1]), "=r"(v[2]), "=r"(v[3]) : "r"(a + own()) : "memory"); }
__device__ __forceinline__ void sts128(uint32_t a, const uint32_t (&v)[4]) { asm volatile("st.shared.v4.u32 [%0], {%1,%2,%3,%4};" ::"r"(a + own()), "r"(v[0]), "r"(v[1]), "r"(v[2]), "r"(v[3]) : "memory"); }
__device__ __forceinline__ void ldg128_nc(uint32_t (&v)[4], const void* p) {
  asm volatile("ld.global.nc.L1::no_allocate.v4.u32 {%0,%1,%2,%3}, [%4];" : "=r"(v[0]), "=r"(v[1]), "=r"(v[2]), "=r"(v[3]) : "l"(p));
}
__device__ __forceinline__ uint32_t pin(uint32_t v, uint32_t zero) {
  asm volatile("{\n.reg .pred p;\n.reg .u32 c;\nmov.u32 c, %1;\nLP:\n.pragma \"nounroll\";\nsetp.eq.u32 p, c, 0;\n@p bra LD;\n"
               "add.u32 %0, %0, c;\nmov.u32 c, %%clock;\nbra LP;\nLD:\n}\n" : "+r"(v) : "r"(zero) : "memory");
  return v;
}
__device__ __forceinline__ void pin7(const char* (&p)[7], uint32_t zero) {
  asm volatile("{\n.reg .pred p;\n.reg .u64 c;\ncvt.u64.u32 c, %7;\nLP:\n.pragma \"nounroll\";\nsetp.eq.u64 p, c, 0;\n@p bra LD;\n"
               "mov.u64 c, %0;\nmov.u64 %0, %1;\nmov.u64 %1, %2;\nmov.u64 %2, %3;\nmov.u64 %3, %4;\n"
               "mov.u64 %4, %5;\nmov.u64 %5, %6;\nmov.u64 %6, c;\nmov.u64 c, %%clock64;\nbra LP;\nLD:\n}\n"
               : "+l"(p[0]), "+l"(p[1]), "+l"(p[2]), "+l"(p[3]), "+l"(p[4]), "+l"(p[5]), "+l"(p[6]) : "r"(zero) : "memory");
}
__device__ __forceinline__ void mbar_arrive_if(uint32_t b, bool cond) {
  asm volatile("{\n.reg .pred p;\nsetp.ne.u32 p, %1, 0;\n@p mbarrier.arrive.shared::cta.b64 _, [%0];\n}\n" ::"r"(b + own()), "r"((uint32_t)cond) : "memory");
}
__device__ __forceinline__ uint32_t ld_epoch(const char* p) {
  uint32_t v;
  asm volatile("ld.relaxed.gpu.global.u32 %0, [%1];" : "=r"(v) : "l"(p) : "memory");
  return v;
}
typedef const char* gptr;
__device__ __forceinline__ void ll_st(gptr p, uint32_t a, uint32_t b, uint32_t c, uint32_t d, uint32_t tag) {
  asm volatile("st.relaxed.gpu.global.v4.b32 [%0], {%1, %2, %3, %4};" ::"l"(p), "r"((a & ~1u) | tag), "r"(b), "r"(c), "r"(d) : "memory");
}
__device__ __forceinline__ void ll_ld(uint32_t (&v)[4], gptr p) {
  asm volatile("{\n.reg .b128 t;\n.reg .b64 lo, hi;\nld.relaxed.gpu.global.b128 t, [%4];\nmov.b128 {lo, hi}, t;\n"
               "mov.b64 {%0, %1}, lo;\nmov.b64 {%2, %3}, hi;\n}\n"
               : "=r"(v[0]), "=r"(v[1]), "=r"(v[2]), "=r"(v[3]) : "l"(p) : "memory");
}
template <int N> __device__ __forceinline__ void ll_issue(uint32_t (&v)[N][4], gptr p, int stride) {
#pragma unroll
  for (int i = 0; i < N; i++) ll_ld(v[i], p + i * stride);
}
__device__ __forceinline__ uint32_t ll_mix(uint32_t a, uint32_t b, uint32_t tag) {
  uint32_t r;
  asm("lop3.b32 %0, %1, %2, %3, 0xD4;" : "=r"(r) : "r"(a), "r"(b), "r"(tag));
  return r;
}
template <int LO, int HI, int N> __device__ __forceinline__ uint32_t ll_tree(const uint32_t (&v)[N][4], uint32_t tag) {
  if constexpr (HI - LO == 1) return v[LO][0];
  else return ll_mix(ll_tree<LO, (LO + HI) / 2>(v, tag), ll_tree<(LO + HI) / 2, HI>(v, tag), tag);
}
template <int N> __device__ __forceinline__ uint32_t ll_red(const uint32_t (&v)[N][4], uint32_t tag) { return ll_tree<0, N>(v, tag); }
__device__ __forceinline__ bool ll_any(uint32_t red, uint32_t tag) { return __any_sync(0xffffffffu, (red ^ tag) & 1u); }
template <int N> __device__ __forceinline__ bool ll_bad(const uint32_t (&v)[N][4], uint32_t tag) { return ll_any(ll_red<N>(v, tag), tag); }
template <int N, int M> __device__ __forceinline__ bool ll_bad2(const uint32_t (&v)[N][4], const uint32_t (&u)[M][4], uint32_t tag) {
  return ll_any(ll_mix(ll_red<N>(v, tag), ll_red<M>(u, tag), tag), tag);
}
template <int N, int M> __device__ __forceinline__ bool ll_bad2(const uint32_t (&v)[N][4], uint32_t tv, const uint32_t (&u)[M][4], uint32_t tu) {
  return __any_sync(0xffffffffu, ((ll_red<N>(v, tv) ^ tv) | (ll_red<M>(u, tu | (tv >> 1)) ^ tu)) & 1u);
}
template <int N> __device__ __forceinline__ void ll_clear(uint32_t (&v)[N][4]) {
#pragma unroll
  for (int i = 0; i < N; i++) v[i][0] &= ~1u;
}
template <int N> __device__ __forceinline__ void ll_spin(uint32_t (&v)[N][4], gptr p, int stride, uint32_t tag) {
  uint32_t it = 0;
#pragma unroll 1
  do { ll_issue<N>(v, p, stride); } while (ll_bad<N>(v, tag) && ++it < SPIN_LIMIT);
}
template <int N> __device__ __forceinline__ void ll_get(uint32_t (&v)[N][4], gptr p, int stride, uint32_t tag) {
  ll_spin<N>(v, p, stride, tag);
  ll_clear<N>(v);
}
template <int N> __device__ __forceinline__ void ll_wait(uint32_t (&v)[N][4], gptr p, int stride, uint32_t tag) {
  if (__builtin_expect(ll_bad<N>(v, tag), 0)) ll_spin<N>(v, p, stride, tag);
  ll_clear<N>(v);
}
__device__ __forceinline__ void unpack32(float (&d)[32], const uint32_t (&v)[4][4]) {
#pragma unroll
  for (int u = 0; u < 4; u++)
#pragma unroll
    for (int e = 0; e < 4; e++) { d[8 * u + 2 * e] = bf_lo(v[u][e]); d[8 * u + 2 * e + 1] = bf_hi(v[u][e]); }
}
__device__ __forceinline__ void pack32(uint32_t (&v)[4][4], const float (&d)[32]) {
#pragma unroll
  for (int u = 0; u < 4; u++)
#pragma unroll
    for (int e = 0; e < 4; e++) v[u][e] = pack2(d[8 * u + 2 * e], d[8 * u + 2 * e + 1]);
}
__device__ __forceinline__ uint32_t t_addr(int m) { return SB + ((0x01354620u >> (4 * m)) & 7u) * 32768u; }

__device__ __forceinline__ constexpr int w2_pass(int m) { return m < 4 ? m & 1 : m >> 1; }
__device__ __forceinline__ constexpr int w2_peer(int m) { return m < 4 ? m >> 1 : m & 1; }

__device__ __forceinline__ int kb_at(int i, int j) { return i == 0 ? j : (i - 1 + (i - 1 >= j ? 1 : 0)); }

__device__ __forceinline__ void init_bars(int set) {
  if (set >= 0 && elect_one()) {
    const uint32_t cnt = set < 5 ? 1 : 8;
#pragma unroll
    for (int i = 0; i < 8; i++) mbar_init(BAR + (24 + 8 * set + i) * 8, cnt);
    if (set >= 8) {
#pragma unroll
      for (int i = 0; i < 8; i++) mbar_init(BAR + (40 + 8 * set + i) * 8, 13 - set);
    }
    if (set == 7) {
#pragma unroll
      for (int i = 0; i < 5; i++) mbar_init(BAR + (B_READY + i) * 8, i == 1 || i == 4 ? 2 : 3);
    }
    asm volatile("fence.mbarrier_init.release.cluster;" ::: "memory");
  }
  __syncwarp();
  asm volatile("bar.arrive 4, 384;" ::: "memory");
  asm volatile("bar.sync 3, 384;" ::: "memory");
  asm volatile("barrier.cluster.arrive.relaxed.aligned;" ::: "memory");
}

__device__ __forceinline__ void load_a(const Params& P, int i, int j) {
  const int f0 = 224 * j + ((j & 1) ? 32 : 0);
  const int fh = 224 * j + ((j & 1) ? 0 : 192);
  const uint32_t b = BAR + (B_FA + i) * 8, d = RING + (i & 3) * 24576;
  const int k0 = kb_at(i, j) * 64;
  mbar_expect_tx(b, 24576);
  tma2d(d, &P.w1, f0, k0, b);
  tma2d(d + 8192, &P.w3, f0, k0, b);
  tma2d(d + 16384, &P.w1h, fh, k0, b);
  tma2d(d + 20480, &P.w3h, fh, k0, b);
}
__device__ __forceinline__ void reset_box(gptr p, int i0, int n, uint32_t s8, uint32_t tag) {
#pragma unroll 1
  for (int i = i0; i < i0 + n; i++) ll_st(p + ((i & 7) * s8 + (i >> 3) * 512), 0, 0, 0, 0, tag ^ 1);
}

__global__ void __launch_bounds__(384, 1) fused_block_kernel(char* __restrict__ X, const __nv_bfloat16* __restrict__ xp,
                                                             const __nv_bfloat16* __restrict__ wqkvp, const __nv_bfloat16* __restrict__ wop,
                                                             const uint32_t zero, const __grid_constant__ Params P) {
  extern __shared__ __align__(1024) uint8_t smem_raw[];
  prefetch_map(&P.x); prefetch_map(&P.wqkv);
  const int tid = threadIdx.x;
  const int warp = __shfl_sync(0xffffffffu, tid >> 5, 0);
  const int lane = tid & 31;
  const int cta = blockIdx.x;
  const int cl = cta >> 1;
  const int c7 = cl - 36, i7 = (c7 * 37) >> 8;
  const int set = cl < 4 ? 15 : cl < 36 ? (cl - 4) & 7 : 8 + c7 - 7 * i7;
  const int idx = cl < 4 ? cl : cl < 36 ? (cl - 4) >> 3 : i7;
  const int g = (set & 14) + (idx >> 1), j = (set & 1) * 4 + (idx & 1) * 2 + (cta & 1);

  if (warp == 8) {
    if (elect_one()) {
#pragma unroll
      for (int i = 0; i < 24; i++) mbar_init(BAR + i * 8, 1);
      asm volatile("fence.mbarrier_init.release.cluster;" ::: "memory");
#pragma unroll
      for (int i = 0; i < TOP_KB; i++) {
        mbar_expect_tx(BAR + (B_FX + i) * 8, 8192);
        tma3d(H0 + i * 8192, &P.x, i * 64, 0, g * 64, BAR + (B_FX + i) * 8);
        mbar_expect_tx(BAR + (B_FW + i) * 8, 24576);
        tma3d(RING + i * 24576, &P.wqkv, 64 * j, i * 64, 0, BAR + (B_FW + i) * 8);
        mbar_expect_tx(BAR + (B_FX + 8 + i) * 8, 8192);
        tma3d(H1 + i * 8192, &P.x, i * 64, 1, g * 64, BAR + (B_FX + 8 + i) * 8);
      }
    }
    __syncwarp();
    asm volatile("bar.arrive 3, 384;" ::: "memory");
  }
  if (smem_u32(smem_raw) != SB + own()) return;

  if (__builtin_expect(warp >= 8, 1)) {
    asm volatile("setmaxnreg.dec.sync.aligned.u32 56;");
    if (__builtin_expect(warp == 8, 1)) {
      PSTAMPW(2, 0);
      const bool leader = elect_one();
      auto ldx = [&](int p, int kb) {
        const uint32_t b = BAR + (B_FX + p * 8 + kb) * 8;
        mbar_expect_tx(b, 8192);
        tma3d(H0 + p * 65536 + kb * 8192, &P.x, kb * 64, p, g * 64, b);
      };
      auto ldw = [&](int kb) {
        const uint32_t b = BAR + (B_FW + kb) * 8, d = RING + (kb & 3) * 24576;
        mbar_expect_tx(b, 24576);
        tma3d(d, &P.wqkv, 64 * j, kb * 64, 0, b);
      };
      if (leader) {
#pragma unroll 1
        for (int i = TOP_KB; i < 8; i++) {
          ldx(0, i);
          if (i < 4) ldw(i);
          ldx(1, i);
        }
        PSTAMPW(2, 2);
      }
      __syncwarp();
      asm volatile("barrier.cluster.arrive.relaxed.aligned;" ::: "memory");
      asm volatile("bar.sync 4, 384;" ::: "memory");
      if (leader) {
        prefetch_map(&P.wo); prefetch_map(&P.w1); prefetch_map(&P.w3); prefetch_map(&P.w1h);
        prefetch_map(&P.w3h); prefetch_map(&P.w2); prefetch_map(&P.out);
        mbar_expect_tx(BAR + B_FWO * 8, 65536);
#pragma unroll 1
        for (int i = 0; i < 12; i++) {
          mbar_wait(BAR + (i < 8 ? B_EW + i : B_EA + i - 8) * 8);
          if (i == 4 + A_HOLD) mbar_wait(BAR + B_HALO * 8);
          if (i < 4) ldw(i + 4); else load_a(P, i - 4, j);
          PSTAMPW(2, 4 + i);
          if (i < 7) {
            mbar_wait(BAR + (B_EX + i) * 8);
            tma2d(H0 + i * 8192, &P.wo, 64 * j, i * 64, BAR + B_FWO * 8);
          }
          if (PFV == 1 && i < 4) l2_prefetch((gptr)((i & 1) ? P.w3p : P.w1p) + cta * 14336 + (i >> 1) * 7168, 7168);
        }
        const int f0 = 224 * j + ((j & 1) ? 32 : 0);
        uint32_t d = RING;
#pragma unroll 1
        for (int i = 0; i < 8; i++) {
          const uint32_t b = BAR + (B_FB + i) * 8;
          const int k0 = kb_at(i, j) * 64;
          mbar_wait(BAR + (B_EA + 5 + i) * 8);
          mbar_expect_tx(b, 32768);
          tma2d(d, &P.w1, f0 + 64, k0, b);
          tma2d(d + 8192, &P.w3, f0 + 64, k0, b);
          tma2d(d + 16384, &P.w1, f0 + 128, k0, b);
          tma2d(d + 24576, &P.w3, f0 + 128, k0, b);
          d = d == RING + 65536 ? RING : d + 32768;
        }
#pragma unroll 1
        for (int i = 0; i < 8; i++) {
          const int m = i;
          const uint32_t b = BAR + (B_FT + m) * 8;
          mbar_wait(BAR + (i < 5 ? B_EB + 3 + i : i < 7 ? B_HC - 5 + i : B_ET0) * 8);
          mbar_expect_tx(b, 28672);
          tma2d(t_addr(m), &P.w2, 64 * ((j + 2 + 2 * w2_pass(m)) & 7), 224 * (j ^ w2_peer(m)), b);
          if (m >= 5) PSTAMPW(2, 23 + m);
        }
      }
      __syncwarp();
      {
        const uint32_t tag = lds32(TAGS);
        if (leader) mbar_expect_tx(BAR + B_FIN * 8, 49152);
        const int lq = min(lane >> 3, 2);
        gptr const src2 = X + (g * 8 + ((j + 2) & 7)) * REC + R_O, src0 = X + X_E4 + (g * 8 + j) * 32768;
        gptr const probe = (lq < 2 ? src0 + lq * 16384 : src2) + (lane & 7) * 2048 + 2032;
        mbar_wait(BAR + (B_ET0 + 1) * 8);
        uint32_t q = 0;
#pragma unroll 1
        for (uint32_t it = 0; q < 3 && it < SPIN_LIMIT; it++) {
          uint32_t pr[4];
          ll_ld(pr, probe);
          const uint32_t bad = __ballot_sync(0xffffffffu, (pr[0] ^ (lq < 2 ? tag : 0)) & 1);
#pragma unroll 1
          while (q < 3 && ((bad >> (8 * q)) & 255) == 0) {
            if (leader)
              asm volatile("cp.async.bulk.shared::cluster.global.mbarrier::complete_tx::bytes [%0], [%1], 16384, [%2];"
                           ::"r"(t_addr(q + 1) + own()), "l"(q < 2 ? src0 + q * 16384 : src2), "r"(BAR + B_FIN * 8 + own()) : "memory");
            PSTAMPW(2, 24 + q);
            q++;
          }
        }
      }
      if (leader) {
        unsigned* ep = reinterpret_cast<unsigned*>(X + X_EP) + cta;
        *ep = *ep + 1;
      }
    } else {
      const int part = warp - 9;
      uint32_t tag;
      if (part == 2) {
        tag = ld_epoch(X + X_EP + cta * 4);
        init_bars(-1);
        tag = (tag + 1) & 1;
        if (lane == 0) {
          asm volatile("st.shared.u32 [%0], %1;" ::"r"(TAGS + own()), "r"(tag) : "memory");
          mbar_arrive(BAR + B_TAG * 8);
        }
      } else {
        init_bars(warp - 1);
        mbar_wait(BAR + B_TAG * 8);
        tag = lds32(TAGS);
      }
      gptr xl = X + lane * 16;
      if (lane < 16) ll_st(xl + X_CS + ((j * 3 + part) * 16 + g) * 256, 0, 0, 0, 0, tag ^ 1);
      if (part == 0 && lane < 20) ll_st(xl + (lane < 16 ? X_ST + (g * 128 + 16 * j) * 16 : X_WB + (j * 64 + g * 4 - 16) * 16), 0, 0, 0, 0, tag ^ 1);
      if (part) reset_box(xl + X_E1 + (g * 8 + j) * 4096, 4 * part - 4, 4, 512, tag);
#pragma unroll
      for (int i = 0; i < 2; i++) {
        const int wp = i * 4 + (lane >> 3);
        ll_st(X + (part < 2 ? X_E4 + ((g * 8 + ((j + 2 + 2 * part) & 7)) * 2 + part) * 16384 + wp * 2048 + 1920 : X_OS + (g * 8 + wp) * 1024 + j * 128) + (lane & 7) * 16,
              0, 0, 0, 0, tag ^ 1);
      }
      __syncwarp();
      if (lane == 0) mbar_arrive(BAR + B_CLR1 * 8);
      asm volatile("barrier.cluster.wait.aligned;" ::: "memory");
      uint32_t v[8][4];
      {
        float s[4] = {0.f, 0.f, 0.f, 0.f}, q[4] = {0.f, 0.f, 0.f, 0.f};
        const uint32_t xa = H0 + ((lane >> 1) & 1) * 65536 + (8 * j + (lane >> 2)) * 128 + (lane & 1) * 64 + ((lane >> 1) & 3) * 16;
#pragma unroll 1
        for (int kb = (part + 2) % 3; kb < 8; kb += 3) {
          mbar_wait(BAR + (B_FX + kb) * 8);
          mbar_wait(BAR + (B_FX + 8 + kb) * 8);
#pragma unroll
          for (int i = 0; i < 4; i++) lds128(v[i], (xa + kb * 8192) ^ (i * 16));
#pragma unroll
          for (int e = 0; e < 16; e++) {
            const float a = bf_lo(v[e >> 2][e & 3]), b = bf_hi(v[e >> 2][e & 3]);
            s[e & 3] += a + b; q[e & 3] = fmaf(a, a, q[e & 3]); q[e & 3] = fmaf(b, b, q[e & 3]);
          }
          __syncwarp();
          mbar_arrive_if(BAR + (B_EX + kb) * 8, lane == 0 || (__float_as_uint(q[0] + q[1] + q[2] + q[3]) & zero) != 0);
        }
        float ss = (s[0] + s[1]) + (s[2] + s[3]), qq = (q[0] + q[1]) + (q[2] + q[3]);
        ss += __shfl_xor_sync(0xffffffffu, ss, 1); qq += __shfl_xor_sync(0xffffffffu, qq, 1);
        if (part) {
          if (!(lane & 1))
            asm volatile("st.shared.v2.f32 [%0], {%1,%2};" ::"r"(WB + own() + part * 128 - 128 + lane * 4), "f"(ss), "f"(qq) : "memory");
          asm volatile("bar.arrive 5, 96;" ::: "memory");
        } else {
          asm volatile("bar.sync 5, 96;" ::: "memory");
          const float2 t1 = lds64(WB + (lane >> 1) * 8), t2 = lds64(WB + 128 + (lane >> 1) * 8);
          const float mean = (ss + t1.x + t2.x) * (1.f / D_);
          const float rs = rsqrtf(fmaxf(fmaf(-mean, mean, (qq + t1.y + t2.y) * (1.f / D_)), 0.f) + 1e-5f);
          if (!(lane & 1)) ll_st(X + X_ST + (g * 128 + 16 * j + (lane >> 1)) * 16, __float_as_uint(mean), __float_as_uint(rs), 0, 0, tag);
          PSTAMPW(3, 2);
        }
      }
      PSTAMPW(3, part * 4 + 0);
      {
        ll_get<8>(v, X + X_CS + ((j * 3 + part) * 16 + (lane >> 4) * 8) * 256 + (lane & 15) * 16, 256, tag);
        if (part == 0) {
          uint32_t u[2][4];
          ll_get<2>(u, xl + X_WB + j * 1024, 512, tag);
#pragma unroll
          for (int i = 0; i < 2; i++)
            asm volatile("st.shared.u32 [%0], %1;" ::"r"(WB + 256 + own() + i * 128 + (lane >> 4) * 64 + (lane & 6) * 8 + (lane & 8) + (lane & 1) * 4), "r"(u[i][0]) : "memory");
        }
        uint32_t o[4];
#pragma unroll
        for (int e = 0; e < 4; e++) {
          float s = 0.f;
#pragma unroll
          for (int i = 0; i < 8; i++) s += __uint_as_float(v[i][e]);
          o[e] = __float_as_uint(s + __shfl_xor_sync(0xffffffffu, s, 16));
        }
        const uint32_t h0 = pack2(__uint_as_float(o[0]), __uint_as_float(o[1])), h1 = pack2(__uint_as_float(o[2]), __uint_as_float(o[3]));
        const uint32_t l0 = pack2(__uint_as_float(o[0]) - bf_lo(h0), __uint_as_float(o[1]) - bf_hi(h0));
        const uint32_t l1 = pack2(__uint_as_float(o[2]) - bf_lo(h1), __uint_as_float(o[3]) - bf_hi(h1));
        mbar_wait(BAR + B_EW * 8);
        mbar_wait(BAR + B_EX * 8);
#pragma unroll
        for (int k = 0; k < 4; k++) {
          const bool z = lane >= 16 || k == 3;
          asm volatile("st.shared.v2.u32 [%0], {%1,%2};" ::"r"(H1 + own() + part * 1024 + ((lane & 15) >> 1) * 128 + (lane >> 4) * 64 + k * 16 + (lane & 1) * 8),
                       "r"(z ? 0u : k < 2 ? h0 : l0), "r"(z ? 0u : k < 2 ? h1 : l1) : "memory");
        }
        fence_async_smem();
      }
      __syncwarp();
      if (lane == 0) mbar_arrive(BAR + B_READY * 8);
      PSTAMPW(3, part * 4 + 1);
      gptr rec = xl + (g * 8 + j) * REC;
      if (part) {
#pragma unroll 1
        for (int i = 0; i < 4; i++)
#pragma unroll
          for (int u = 0; u < 4; u++) ll_st(rec + (R_O + (4 * part - 4 + i) * 2048) + u * 512, 0, 0, 0, 0, 0);
        __syncwarp();
        if (lane == 0) mbar_arrive(BAR + B_CLRO * 8);
      }
      PSTAMPW(3, 20 + part);
      if (part < 2) {
        if (elect_one()) {
          if (part) {
            mbar_wait(BAR + (B_EX + 7) * 8);
            tma2d(H0 + 7 * 8192, &P.wo, 64 * j, 7 * 64, BAR + B_FWO * 8);
          }
          mbar_wait(BAR + (PF_WHEN) * 8);
          gptr src = (gptr)(part ? P.w3p : P.w1p) + cta * 14336;
#pragma unroll 1
          for (int i = PFV == 1 ? 14 : 0; i < (part ? 14 : 28); i++) {
            if (i == 14) src = (gptr)P.w2p + (cta - 1) * 14336;
            if (!NOPF) l2_prefetch(src + i * 1024, 1024);
            __nanosleep(PF_SLEEP);
          }
        }
      } else if (part == 2) {
        mbar_wait(BAR + B_ORD * 8);
#pragma unroll
        for (int i = 0; i < 2; i++) ll_st(X + X_HS + (g * 8 + i * 4 + (lane >> 3)) * 1024 + j * 128 + (lane & 7) * 16, 0, 0, 0, 0, tag ^ 1);
#pragma unroll 1
        for (int i = 0; i < 8; i++)
#pragma unroll
          for (int u = 0; u < 4; u++) ll_st(rec + (R_H + i * 2048) + u * 512, 0, 0, 0, 0, tag ^ 1);
        __syncwarp();
        if (lane == 0) mbar_arrive(BAR + B_CLRH * 8);
        PSTAMPW(3, 24);
      }
      PSTAMPW(3, part * 4 + 3);
    }
  } else {
    const int p = warp >> 2, w = warp & 3;
    const int r = lane >> 2, c = lane & 3;
    init_bars(warp);
    asm volatile("setmaxnreg.inc.sync.aligned.u32 224;");
    PSTAMP(0);
    const uint32_t dAx = descA(H0) + p * 4096;
    const uint32_t Hn = H1 - p * 65536;
    const uint32_t moff = ((lane & 7) + ((lane >> 3) & 1) * 8) * 128 + (((lane >> 4) ^ (lane & 7)) << 4);
    const uint32_t Xw = H0 + p * 65536 + w * 2048;
    uint32_t cv[8][4];
    if (p == 1) {
      if (!SIDE_EARLY) mbar_wait(BAR + B_FW * 8);
      const char* wr = w < 3 ? (const char*)wqkvp + (g * 32 + (lane >> 3) * 8) * 3072 + w * 1024 + j * 128 + (lane & 7) * 16
                              : (const char*)wop + (j * 64 + g * 4 + (lane >> 3)) * 1024 + (lane & 7) * 16;
      const uint32_t st = w < 3 ? 3072 : 128;
#pragma unroll
      for (int i = 0; i < 8; i++) ldg128_nc(cv[i], wr + i * st);
    }

    float aq[96];
    uint32_t xres[4][4];
#pragma unroll
    for (int u = 0; u < 4; u++) { xres[u][0] = 0; xres[u][1] = 0; xres[u][2] = 0; xres[u][3] = 0; }
    auto kvstep = [&](int kb) {
      mbar_wait(BAR + (B_FX + p * 8 + kb) * 8);
      mbar_wait(BAR + (B_FW + kb) * 8);
      if (kb == 0) PSTAMP(2);
      const uint32_t da = dAx + kb * 512, db = descB(RING) + (kb & 3) * 1536;
      wg_fence();
      wgmma_ss_n192(aq, da, db, kb);
#pragma unroll
      for (int k = 1; k < 4; k++) wgmma_ss_n192(aq, da + k * 2, db + k * 128, 1);
      wg_commit();
      wg_wait<1>();
      if (kb > 0) {
        mbar_arrive_if(BAR + (B_EW + kb - 1) * 8, lane == 0);
        mbar_arrive_if(BAR + (B_EX + kb - 1) * 8, (lane == 0 && p == 0) || (xres[0][0] & xres[1][0] & xres[2][0] & xres[3][0] & zero) != 0);
      }
      if (kb == j) {
#pragma unroll
        for (int u = 0; u < 4; u++) ldsm4(xres[u], Xw + kb * 8192 + (moff ^ (u << 5)));
      }
    };
#pragma unroll
    for (int kb = 0; kb < CS_KB; kb++) kvstep(kb);
    mbar_wait(BAR + B_CLR1 * 8);
    const uint32_t tag = lds32(TAGS);
    if (p == 1) {
      PSTAMPX(29);
      const uint32_t hm = 0xffff0000u | (tag >> 1), sh = 16 + (tag >> 1);
      float cs[8];
#pragma unroll
      for (int e = 0; e < 4; e++) {
        float a = 0.f, b = 0.f;
#pragma unroll
        for (int i = 0; i < 8; i++) { a += __uint_as_float(cv[i][e] << sh); b += __uint_as_float(cv[i][e] & hm); }
        cs[2 * e] = a; cs[2 * e + 1] = b;
      }
      if (w == 3) {
        float t = ((cs[0] + cs[1]) + (cs[2] + cs[3])) + ((cs[4] + cs[5]) + (cs[6] + cs[7]));
#pragma unroll
        for (int o = 1; o <= 4; o <<= 1) t += __shfl_xor_sync(0xffffffffu, t, o);
        if ((lane & 7) == 0) ll_st(X + X_WB + (j * 64 + g * 4 + (lane >> 3)) * 16, __float_as_uint(t * (1.f / D_)), 0, 0, 0, tag);
      }
      const bool up = lane & 8;
#pragma unroll
      for (int e = 0; e < 4; e++) {
        const float keepv = up ? cs[4 + e] : cs[e], give = up ? cs[e] : cs[4 + e];
        cs[e] = keepv + __shfl_xor_sync(0xffffffffu, give, 8);
        cs[e] += __shfl_xor_sync(0xffffffffu, cs[e], 16);
      }
      if (lane < 16 && w < 3)
        ll_st(X + X_CS + ((j * 3 + w) * 16 + g) * 256 + (lane & 7) * 32 + (lane >> 3) * 16, __float_as_uint(cs[0]), __float_as_uint(cs[1]),
              __float_as_uint(cs[2]), __float_as_uint(cs[3]), tag);
      PSTAMP(1);
    }
#pragma unroll 1
    for (int kb = CS_KB; kb < 7; kb++) kvstep(kb);
    uint32_t sv[2][4];
    gptr const stsrc = X + (X_ST + (g * 128 + 2 * (16 * w + r) + p) * 16);
    ll_issue<2>(sv, stsrc, 256);
    gptr const xl = X + (lane * 16 + (tag >> 1));
    gptr const rec = xl + (g * 8 * REC + warp * 2048);
    gptr const recs = xl + (X_OS + (g * 8 + warp) * 1024 + r * 16 - lane * 16);
    gptr osrc[7];
#pragma unroll
    for (int i = 0; i < 7; i++) osrc[i] = rec + (uint32_t)(i >= j ? (i + 1) * REC : i * REC);
    pin7(osrc, zero);
    kvstep(7);
    if (__builtin_expect(ll_bad<2>(sv, pin(tag, zero)), 0)) ll_spin<2>(sv, stsrc, 256, tag);
    ll_clear<2>(sv);
    const float2 st0 = make_float2(__uint_as_float(sv[0][0]), __uint_as_float(sv[0][1]));
    const float2 st1 = make_float2(__uint_as_float(sv[1][0]), __uint_as_float(sv[1][1]));
    {
      auto frag = [&](float m) {
        const uint32_t h = pack2(-m, -m);
        return c == 0 ? (h & 0xffffu) | pack2(0.f, -m - bf_lo(h)) : c == 1 ? h & 0xffffu : 0u;
      };
      uint32_t ma[4] = {frag(st0.x), frag(st1.x), 0u, 0u};
      mbar_wait(BAR + B_READY * 8);
      keep(ma);
      wg_fence();
      wgmma_rs_n192<(128 >> 4)>(aq, ma, H1 >> 4, 1);
      wg_commit();
    }
    wg_wait<0>();
    keep(aq);
    mbar_arrive_if(BAR + (B_EW + 7) * 8, lane == 0);
    PSTAMP(3);

    uint32_t hi[4][4], lo[4][4];
    auto cvt = [&](uint32_t (&d)[4][4], int ofs, float rs) {
#pragma unroll
      for (int b = 0; b < 16; b++) {
        const uint32_t v = pack2(aq[32 + 4 * b + ofs] * rs, aq[33 + 4 * b + ofs] * rs);
        d[b >> 2][b & 3] = b < 8 ? v : movm(v);
      }
    };
    cvt(hi, 2, st1.y);
    if (w == 3) {
#pragma unroll
      for (int i = 0; i < 4; i++) ll_st(xl + (X_E1 + ((g * 8 + j) * 2 + p) * 2048 + i * 512), hi[i][0], hi[i][1], hi[i][2], hi[i][3], tag);
    }
    wg_bar(p);
#pragma unroll
    for (int i = 0; i < 4; i++) sts128(Xw + 7 * 8192 + lane * 16 + i * 512, hi[i]);
    PSTAMP(20);
    cvt(lo, 0, __uint_as_float(pin(__float_as_uint(st0.y), zero)));
    uint32_t qf[4][4];
#pragma unroll
    for (int h = 0; h < 4; h++)
#pragma unroll
      for (int e = 0; e < 4; e++) qf[h][e] = pack2(aq[8 * h + 2 * e], aq[8 * h + 2 * e + 1]);
    keep(qf); keep(lo);
    PSTAMP(21);
    wg_bar(p);
    uint32_t prev[4][4];
#pragma unroll
    for (int i = 0; i < 4; i++) lds128(prev[i], Xw + 7 * 8192 - (w ? 2048 : 0) + lane * 16 + i * 512);
    if (p == 0) fence_async_smem();
    __syncwarp();
    const bool xd = lane == 0 || (prev[3][0] & xres[3][0] & zero) != 0;
    mbar_arrive_if(BAR + (B_EX + 7) * 8, xd && p == 0);
    mbar_arrive_if(BAR + B_XDONE * 8, xd);
    PSTAMP(4);

    uint32_t of[4][4];
    {
      const float sc = 0.25f * 1.4426950408889634f;
      const float sca = sc * st0.y, scb = sc * st1.y;
      const float nohalo = (g == 0 && w == 0) ? -INFINITY : 0.f;
      const bool up0 = 2 * c > r, up1 = 2 * c + 1 > r;
      const uint32_t mup = (up0 ? 0xffffu : 0u) | (up1 ? 0xffff0000u : 0u);
      auto softmax = [&](float a0, float a1, float s) {
        float m = fmaxf(a0, a1);
        m = fmaxf(m, __shfl_xor_sync(0xffffffffu, m, 1));
        m = fmaxf(m, __shfl_xor_sync(0xffffffffu, m, 2));
        a0 = ex2((a0 - m) * s); a1 = ex2((a1 - m) * s);
        float t = a0 + a1;
        t += __shfl_xor_sync(0xffffffffu, t, 1);
        t += __shfl_xor_sync(0xffffffffu, t, 2);
        const float i = rcp(t);
        return pack2(a0 * i, a1 * i);
      };
      uint32_t pbs[4];
      float sls[4][2];
#pragma unroll
      for (int h = 0; h < 4; h++) {
        const int i0 = h >> 1, e0 = (2 * h) & 3;
        float sl[4], sh[4];
        mma16816(sl, qf[h], lo[i0][e0], lo[i0][e0 + 1]);
        mma16816(sh, qf[h], hi[i0][e0], hi[i0][e0 + 1]);
        sls[h][0] = sl[0]; sls[h][1] = sl[1];
        pbs[h] = softmax(up0 ? sl[2] : sh[2], up1 ? sl[3] : sh[3], scb);
      }
      keep(pbs);
      PSTAMP(31);
      if (w == 0 && g > 0) ll_get<4>(prev, xl + (X_E1 + (((g - 1) * 8 + j) * 2 + p) * 2048), 512, tag);
      mbar_arrive_if(BAR + B_HALO * 8, (tid & 127) == 0);
      mbar_wait(BAR + B_CLRO * 8);
      PSTAMP(19);
#pragma unroll
      for (int h = 0; h < 4; h++) {
        const int i0 = h >> 1, e0 = (2 * h) & 3;
        if (h == 2) {
          qf[2][0] = pin(qf[2][0], zero); qf[3][0] = pin(qf[3][0], zero);
        }
        float sp[4];
        mma16816(sp, qf[h], prev[i0][e0], prev[i0][e0 + 1]);
        const uint32_t pa = softmax(up0 ? sp[0] + nohalo : sls[h][0], up1 ? sp[1] + nohalo : sls[h][1], sca), pb = pbs[h];
        const uint32_t pf[4] = {pa & mup, 0u, pa & ~mup, pb & mup};
        const uint32_t ph = pb & ~mup;
        float o0[4], o1[4];
        mma16816(o0, pf, prev[2 + i0][e0], lo[2 + i0][e0]);
        mma16816(o1, pf, prev[2 + i0][e0 + 1], lo[2 + i0][e0 + 1]);
        mma1688_acc(o0, 0u, ph, hi[2 + i0][e0]);
        mma1688_acc(o1, 0u, ph, hi[2 + i0][e0 + 1]);
        of[h][0] = pack2(o0[0], o0[1]); of[h][1] = pack2(o0[2], o0[3]);
        of[h][2] = pack2(o1[0], o1[1]); of[h][3] = pack2(o1[2], o1[3]);
        ll_st(rec + (uint32_t)(R_O + j * REC) + h * 512, of[h][0], of[h][1], of[h][2], of[h][3], 1);
      }
    }
    PSTAMP(5);

    float ah[32];
    {
      uint32_t og[2][14][4];
      auto oissue = [&](int hp) {
#pragma unroll
        for (int i = 0; i < 14; i++) ll_ld(og[hp][i], osrc[i >> 1] + (R_O + (2 * hp + (i & 1)) * 512));
        if (hp == 1) ll_issue<2>(sv, recs + c * 256, 128);
      };
      auto omma = [&](int hp) {
        ll_clear<14>(og[hp]);
        keep(og[hp]);
        wg_fence();
#pragma unroll
        for (int i = 0; i < 14; i++) wgmma_rs_n64(ah, og[hp][i], descB(H0) + kb_at((i >> 1) + 1, j) * 512 + (2 * hp + (i & 1)) * 128, 1);
        wg_commit();
      };
      uint32_t pr[1][4];
      gptr const probe = rec + (uint32_t)(R_O + 1008 - lane * 16 + (min(lane, 6) >= j ? min(lane, 6) + 1 : min(lane, 6)) * REC);
      ll_issue<1>(pr, probe, 0);
      {
        float d0 = 0.f, d1 = 0.f;
#pragma unroll
        for (int h = 0; h < 4; h++) {
          uint32_t cw[4];
          lds128(cw, WB + 256 + c * 16 + h * 64);
#pragma unroll
          for (int e = 0; e < 4; e++) {
            float& d = (e & 1) ? d1 : d0;
            d = fmaf(bf_lo(of[h][e]), __uint_as_float(cw[e & 2]), d);
            d = fmaf(bf_hi(of[h][e]), __uint_as_float(cw[(e & 2) + 1]), d);
          }
        }
#pragma unroll
        for (int o = 1; o <= 2; o <<= 1) { d0 += __shfl_xor_sync(0xffffffffu, d0, o); d1 += __shfl_xor_sync(0xffffffffu, d1, o); }
        if (c == 0) ll_st(recs + (uint32_t)(j * 128), __float_as_uint(d0), __float_as_uint(d1), 0, 0, tag);
      }
      PSTAMP(22);
      if (ll_any(pr[0][0], pin(1, zero))) {
        ll_spin<1>(pr, probe, 0, 1);
      }
      PSTAMP(30);
      oissue(0);
      unpack32(ah, xres);
      PSTAMP(23);
      mbar_wait(BAR + B_FWO * 8);
      PSTAMP(18);
      keep(ah); keep(of);
      wg_fence();
#pragma unroll
      for (int k = 0; k < 4; k++) wgmma_rs_n64(ah, of[k], descB(H0) + j * 512 + k * 128, 1);
      wg_commit();
      uint32_t it = 0;
      if (__builtin_expect(ll_bad<14>(og[0], pin(1, zero)), 0)) {
#pragma unroll 1
        do { oissue(0); } while (ll_bad<14>(og[0], 1) && ++it < SPIN_LIMIT);
      }
      PSTAMP(6);
      mbar_arrive_if(BAR + B_ORD * 8, lane == 0 && p == 0);
      oissue(1);
      omma(0);
      if (__builtin_expect(ll_bad2<14, 2>(og[1], pin(1, zero), sv, tag), 0)) {
#pragma unroll 1
        do { oissue(1); } while (ll_bad2<14, 2>(og[1], 1, sv, tag) && ++it < SPIN_LIMIT);
      }
      PSTAMP(16);
      omma(1);
      ll_clear<2>(sv);
    }
    float m0 = __uint_as_float(sv[0][0]) + __uint_as_float(sv[1][0]), m1 = __uint_as_float(sv[0][1]) + __uint_as_float(sv[1][1]);
#pragma unroll
    for (int o = 1; o <= 2; o <<= 1) { m0 += __shfl_xor_sync(0xffffffffu, m0, o); m1 += __shfl_xor_sync(0xffffffffu, m1, o); }
    const uint32_t mu0 = pack2(m0 + st0.x, m0 + st0.x), mu1 = pack2(m1 + st1.x, m1 + st1.x);
    mbar_wait(BAR + B_CLRH * 8);
    wg_wait<0>();
    keep(ah);
    mbar_arrive_if(BAR + B_WODONE * 8, lane == 0);
    PSTAMP(7);

    uint32_t hf[4][4], ra[4][4];
    pack32(hf, ah);
#pragma unroll
    for (int u = 0; u < 4; u++) {
      ra[u][0] = hsub2(hf[u][0], mu0) & ~1u; ra[u][1] = hsub2(hf[u][1], mu1);
      ra[u][2] = hsub2(hf[u][2], mu0); ra[u][3] = hsub2(hf[u][3], mu1);
      ll_st(rec + (uint32_t)(R_H + j * REC) + u * 512, ra[u][0], ra[u][1], ra[u][2], ra[u][3], tag);
    }
    mbar_wait(BAR + (p == 0 ? B_XDONE : B_WODONE) * 8);
    PSTAMP(8);

    float rs0, rs1;
    auto swiglu = [&](float g0, float g1, float u0, float u1, float rs) -> uint32_t {
      const float hr = 0.5f * rs;
      const float x0 = g0 * hr, x1 = g1 * hr;
      const float t0 = tanhf_hw(x0), t1 = tanhf_hw(x1);
      return pack2(fmaf(x0, t0, x0) * (u0 * rs), fmaf(x1, t1, x1) * (u1 * rs));
    };
    auto pinf = [&](float v) { return __uint_as_float(pin(__float_as_uint(v), zero)); };
    uint32_t hA[6][4];
    float a2[32];
    {
      float a1[64];
      uint32_t rb[4][4], rc[4][4], rd[4][4];
      auto fetch = [&](uint32_t (&a)[4][4], int i) { ll_issue<4>(a, osrc[i - 1] + R_H, 512); };
      auto check = [&](uint32_t (&a)[4][4], uint32_t (&b)[4][4], int i) {
        if (__builtin_expect(ll_bad2<4, 4>(a, b, pin(tag, zero)), 0)) {
          uint32_t it = 0;
#pragma unroll 1
          do { fetch(a, i); fetch(b, i + 1); } while (ll_bad2<4, 4>(a, b, tag) && ++it < SPIN_LIMIT);
        }
        ll_clear<4>(a); ll_clear<4>(b);
        keep(a); keep(b);
      };
      auto head = [&](uint32_t (&a)[4][4], int i) {
        mbar_wait(BAR + (B_FA + i) * 8);
        wg_fence();
        wgmma_rs_n64<DESC_HI64>(a2, a[0], descBh(RING + 16384) + (i & 3) * 1536, i);
        wgmma_rs_n128(a1, a[0], descB(RING) + (i & 3) * 1536, i);
        wg_commit();
#pragma unroll
        for (int u = 0; u < 4; u++) stsm4(Hn + w * 2048 + i * 8192 + (moff ^ (u << 5)), a[u]);
        wg_wait<1>();
        if (i > 0) mbar_arrive_if(BAR + (B_EA + i - 1) * 8, lane == 0);
      };
      auto rest = [&](uint32_t (&a)[4][4], int i) {
        wg_fence();
#pragma unroll
        for (int k = 1; k < 4; k++) {
          wgmma_rs_n64<DESC_HI64>(a2, a[k], descBh(RING + 16384) + (i & 3) * 1536 + k * 64, 1);
          wgmma_rs_n128(a1, a[k], descB(RING) + (i & 3) * 1536 + k * 128, 1);
        }
        wg_commit();
      };
      keep(ra);
      head(ra, 0); rest(ra, 0);
      {
        float s0 = 0.f, q0 = 0.f, s1 = 0.f, q1 = 0.f;
#pragma unroll
        for (int b = 0; b < 8; b++) {
          s0 += ah[4 * b] + ah[4 * b + 1]; s1 += ah[4 * b + 2] + ah[4 * b + 3];
          q0 = fmaf(ah[4 * b], ah[4 * b], q0); q0 = fmaf(ah[4 * b + 1], ah[4 * b + 1], q0);
          q1 = fmaf(ah[4 * b + 2], ah[4 * b + 2], q1); q1 = fmaf(ah[4 * b + 3], ah[4 * b + 3], q1);
        }
#pragma unroll
        for (int o = 1; o <= 2; o <<= 1) {
          s0 += __shfl_xor_sync(0xffffffffu, s0, o); q0 += __shfl_xor_sync(0xffffffffu, q0, o);
          s1 += __shfl_xor_sync(0xffffffffu, s1, o); q1 += __shfl_xor_sync(0xffffffffu, q1, o);
        }
        if (c == 0) ll_st(recs + (uint32_t)(X_HS - X_OS + j * 128), __float_as_uint(s0), __float_as_uint(q0), __float_as_uint(s1), __float_as_uint(q1), tag);
      }
      ll_get<4>(rb, osrc[0] + R_H, 512, tag);
      keep(rb);
      PSTAMP(17);
      fetch(rc, 2); fetch(rd, 3);
      head(rb, 1); rest(rb, 1);
      check(rc, rd, 2);
      head(rc, 2); fetch(ra, 4); fetch(rb, 5); rest(rc, 2);
      head(rd, 3); rest(rd, 3);
      check(ra, rb, 4);
      head(ra, 4); fetch(rc, 6); fetch(rd, 7); ll_issue<2>(sv, recs + (X_HS - X_OS + c * 256), 128); rest(ra, 4);
      head(rb, 5); rest(rb, 5);
      check(rc, rd, 6);
      head(rc, 6); rest(rc, 6);
      head(rd, 7); rest(rd, 7);
      fence_async_smem();
      ll_wait<2>(sv, recs + (X_HS - X_OS + c * 256), 128, tag);
      float s0 = __uint_as_float(sv[0][0]) + __uint_as_float(sv[1][0]), q0 = __uint_as_float(sv[0][1]) + __uint_as_float(sv[1][1]);
      float s1 = __uint_as_float(sv[0][2]) + __uint_as_float(sv[1][2]), q1 = __uint_as_float(sv[0][3]) + __uint_as_float(sv[1][3]);
#pragma unroll
      for (int o = 1; o <= 2; o <<= 1) {
        s0 += __shfl_xor_sync(0xffffffffu, s0, o); q0 += __shfl_xor_sync(0xffffffffu, q0, o);
        s1 += __shfl_xor_sync(0xffffffffu, s1, o); q1 += __shfl_xor_sync(0xffffffffu, q1, o);
      }
      s0 *= 1.f / D_; s1 *= 1.f / D_;
      rs0 = rsqrtf(fmaxf(fmaf(-s0, s0, q0 * (1.f / D_)), 0.f) + 1e-5f);
      rs1 = rsqrtf(fmaxf(fmaf(-s1, s1, q1 * (1.f / D_)), 0.f) + 1e-5f);
      wg_wait<0>();
      keep(a1); keep(a2);
      mbar_arrive_if(BAR + (B_EA + 7) * 8, lane == 0);
      PSTAMP(9);
#pragma unroll
      for (int u = 0; u < 4; u++)
#pragma unroll
        for (int e = 0; e < 4; e++)
          hA[u][e] = swiglu(a1[8 * u + 2 * e], a1[8 * u + 2 * e + 1], a1[32 + 8 * u + 2 * e], a1[33 + 8 * u + 2 * e], (e & 1) ? rs1 : rs0);
      keep(hA[0]); keep(hA[1]); keep(hA[2]); keep(hA[3]);
      wg_bar(p);
    }
    PSTAMP(10);

    const uint32_t mbx = Hn + 32768 + w * 512 + lane * 16;
    auto send = [&](const uint32_t (&v)[4], uint32_t a, int part) {
      asm volatile("st.async.weak.shared::cluster.mbarrier::complete_tx::bytes.v4.b32 [%0], {%1,%2,%3,%4}, [%5];"
                   ::"r"(a + peer()), "r"(v[0]), "r"(v[1]), "r"(v[2]), "r"(v[3]), "r"(BAR + (B_HX + 2 * part + p) * 8 + peer()) : "memory");
    };
    uint32_t hB[8][4];
    {
      float ab[128];
      uint32_t db = descB(RING);
      const uint32_t dAn = descA(H1) - p * 4096;
      if (lane == 0 && w == 0) { mbar_expect_tx(BAR + (B_HX + p) * 8, 12288); mbar_expect_tx(BAR + (B_HX + 2 + p) * 8, 16384); }
      auto bmma = [&](int i) {
        mbar_wait(BAR + (B_FB + i) * 8);
        const uint32_t da = dAn + i * 512;
        wg_fence();
        wgmma_ss_n256(ab, da, db, i);
#pragma unroll
        for (int k = 1; k < 4; k++) wgmma_ss_n256(ab, da + k * 2, db + k * 128, 1);
        wg_commit();
        db = db == descB(RING + 65536) ? descB(RING) : db + 2048;
      };
      bmma(0);
      {
        const float r0 = pinf(rs0), r1 = pinf(rs1);
#pragma unroll
        for (int u = 0; u < 2; u++)
#pragma unroll
          for (int e = 0; e < 4; e++)
            hA[4 + u][e] = swiglu(a2[8 * u + 2 * e], a2[8 * u + 2 * e + 1], a2[16 + 8 * u + 2 * e], a2[17 + 8 * u + 2 * e], (e & 1) ? r1 : r0);
        keep(hA);
      }
#pragma unroll 1
      for (int i = 1; i < 8; i++) {
        bmma(i);
        if (i == 7) {
          mbar_wait_cluster(BAR + (B_PF + p) * 8);
#pragma unroll
          for (int k = 0; k < 6; k++) send(hA[k], mbx + k * 2048, 0);
        }
        wg_wait<1>();
        mbar_arrive_if(BAR + (B_EB + i - 1) * 8, lane == 0);
        if (i == 6 && lane == 0) mbar_arrive_peer(BAR + (B_PF + p) * 8);
      }
      wg_wait<0>();
      keep(ab);
      mbar_arrive_if(BAR + (B_EB + 7) * 8, lane == 0);
      if (lane == 0) mbar_arrive_peer(BAR + (B_PF + 2 + p) * 8);
      PSTAMP(11);

      float ya[32], y[32];
      uint32_t hP[14][4];
      const uint32_t offA = (j & 1) ? 256 : 0, offH = (j & 1) ? 0 : 1536;
      gptr const e4 = xl + (X_E4 + g * 16 * 16384 + warp * 2048);
      const uint32_t stg = H0 + p * 65536 + 28672 + (w >> 1) * 32768 + (w & 1) * 2048;
      auto mm = [&](float (&d)[32], int m, int k0, int k1) {
        if (k0 == 0) mbar_wait(BAR + (B_FT + m) * 8);
        const uint32_t T = descB(0) + (t_addr(m) >> 4);
        const uint32_t oA = w2_peer(m) ? 256 - offA : offA, oH = w2_peer(m) ? 1536 - offH : offH;
        wg_fence();
#pragma unroll
        for (int k = k0; k < k1; k++) {
          const uint32_t db = T + (k < 4 ? oA + k * 128 : k < 6 ? oH + (k - 4) * 128 : oA + 512 + (k - 6) * 128);
          if (w2_peer(m)) wgmma_rs_n64(d, hP[k], db, 1);
          else if (k < 6) wgmma_rs_n64(d, hA[k], db, k);
          else wgmma_rs_n64(d, hB[k - 6], db, 1);
        }
        wg_commit();
      };
      auto next = [&](float (&d)[32], int m, float (&dp)[32], int q) {
        mm(d, m, 0, 3);
        wg_wait<1>();
        keep(dp);
        mbar_arrive_if(BAR + (B_ET0 + q) * 8, lane == 0);
        gptr dst = q < 2 ? e4 + (uint32_t)((((j + 2 + 2 * q) & 7) * 2 + q) * 16384) : rec + (uint32_t)(R_O + j * REC);
#pragma unroll
        for (int u = 0; u < 4; u++)
          ll_st(dst + u * 512, pack2(dp[8 * u], dp[8 * u + 1]), pack2(dp[8 * u + 2], dp[8 * u + 3]),
                pack2(dp[8 * u + 4], dp[8 * u + 5]), pack2(dp[8 * u + 6], dp[8 * u + 7]), q < 2 ? tag : 0);
        if (q == 2) mbar_wait(BAR + (B_ET0 + 2) * 8);
        mm(d, m, 3, 14);
      };
      auto act = [&](int u0, float r0, float r1) {
#pragma unroll
        for (int u = u0; u < u0 + 2; u++) {
          const int o = (u >> 2) * 64 + (u & 3) * 8;
#pragma unroll
          for (int e = 0; e < 4; e++)
            hB[u][e] = swiglu(ab[o + 2 * e], ab[o + 2 * e + 1], ab[o + 32 + 2 * e], ab[o + 33 + 2 * e], (e & 1) ? r1 : r0);
          keep(hB[u]);
        }
        if (u0 == 0) mbar_wait_cluster(BAR + (B_PF + 2 + p) * 8);
        send(hB[u0], mbx + (6 + u0) * 2048, 1); send(hB[u0 + 1], mbx + (7 + u0) * 2048, 1);
      };
      act(0, rs0, rs1);
      mm(ya, 0, 0, 8);
      act(2, pinf(rs0), pinf(rs1));
      mm(y, 1, 0, 8);
      act(4, pinf(rs0), pinf(rs1));
      mm(ya, 0, 8, 12);
      mm(y, 1, 8, 12);
      act(6, pinf(rs0), pinf(rs1));
      PSTAMP(12);
      mm(ya, 0, 12, 14);
      mbar_wait_cluster(BAR + (B_HX + p) * 8);
#pragma unroll
      for (int k = 0; k < 6; k++) lds128(hP[k], mbx + k * 2048);
      mm(y, 1, 12, 14);
      keep(hP[0]); keep(hP[1]); keep(hP[2]); keep(hP[3]); keep(hP[4]); keep(hP[5]);
      mm(ya, 2, 0, 3);
      mbar_wait_cluster(BAR + (B_HX + 2 + p) * 8);
      PSTAMPX(24);
#pragma unroll
      for (int k = 6; k < 14; k++) lds128(hP[k], mbx + k * 2048);
      mm(ya, 2, 3, 6);
      keep(hP);
      mm(ya, 2, 6, 7);
      mbar_arrive_if(BAR + (B_HC + p) * 8, lane == 0 || (hP[13][0] & zero) != 0);
      mm(ya, 2, 7, 14);
      next(y, 3, ya, 0);
      PSTAMPX(27);
      next(ya, 4, y, 1);
      mm(ya, 5, 0, 14);
      PSTAMPX(26);
      next(y, 6, ya, 2);
      PSTAMPX(28);
      uint32_t in[8][4], lt[4][4];
      mm(y, 7, 0, FIN_K);
      mbar_wait(BAR + B_FIN * 8);
#pragma unroll
      for (int u = 0; u < 12; u++) lds128(u < 8 ? in[u & 7] : lt[u & 3], t_addr(1 + (u >> 2)) + warp * 2048 + lane * 16 + (u & 3) * 512);
      if (FIN_K < 14) mm(y, 7, FIN_K, 14);
      if (__builtin_expect(ll_bad2(in, tag, lt, 0), 0)) {
        uint32_t it = 0;
#pragma unroll 1
        do {
#pragma unroll
          for (int u = 0; u < 8; u++) ll_ld(in[u], e4 + (uint32_t)(j * 32768) + ((u >> 2) * 16384 + (u & 3) * 512));
          ll_issue<4>(lt, rec + (uint32_t)(R_O + ((j + 2) & 7) * REC), 512);
        } while (ll_bad2(in, tag, lt, 0) && ++it < SPIN_LIMIT);
      }
      ll_clear<8>(in);
      const uint32_t ident = (2 * c == r ? 0x3f80u : 0u) | (2 * c + 1 == r ? 0x3f800000u : 0u);
      auto acc = [&](const uint32_t (&v)[4], int u) {
        mma1688_acc(*reinterpret_cast<float (*)[4]>(&y[8 * u]), v[0], v[1], ident);
        mma1688_acc(*reinterpret_cast<float (*)[4]>(&y[8 * u + 4]), v[2], v[3], ident);
      };
      wg_wait<0>();
      keep(y);
      PSTAMP(13);
#pragma unroll
      for (int u = 0; u < 4; u++) acc(hf[u], u);
#pragma unroll
      for (int u = 0; u < 12; u++) acc(u < 8 ? in[u & 7] : lt[u & 3], u & 3);
      PSTAMP(14);
#pragma unroll
      for (int u = 0; u < 4; u++) {
        uint32_t o[4];
#pragma unroll
        for (int e = 0; e < 4; e++) o[e] = pack2(y[8 * u + 2 * e], y[8 * u + 2 * e + 1]);
        stsm4(stg + (moff ^ (u << 5)), o);
      }
      fence_async_smem();
      __syncwarp();
      if (elect_one()) {
        tma3d_store(&P.out, stg, 64 * j, p, g * 64 + 16 * w);
        asm volatile("cp.async.bulk.commit_group;" ::: "memory");
        asm volatile("cp.async.bulk.wait_group.read 0;" ::: "memory");
      }
      PSTAMP(15);
    }
  }
}

typedef CUresult (*EncodeFn)(CUtensorMap*, CUtensorMapDataType, cuuint32_t, void*, const cuuint64_t*, const cuuint64_t*,
                             const cuuint32_t*, const cuuint32_t*, CUtensorMapInterleave, CUtensorMapSwizzle,
                             CUtensorMapL2promotion, CUtensorMapFloatOOBfill);

void enc2d(EncodeFn f, CUtensorMap* m, const void* base, uint64_t cols, uint64_t rows, uint32_t bc, uint32_t br, CUtensorMapSwizzle sw) {
  cuuint64_t gd[2] = {cols, rows}, gs[1] = {cols * 2};
  cuuint32_t bd[2] = {bc, br}, es[2] = {1, 1};
  f(m, CU_TENSOR_MAP_DATA_TYPE_BFLOAT16, 2, const_cast<void*>(base), gd, gs, bd, es, CU_TENSOR_MAP_INTERLEAVE_NONE, sw,
    CU_TENSOR_MAP_L2_PROMOTION_L2_128B, CU_TENSOR_MAP_FLOAT_OOB_FILL_NONE);
}
void enc_par(EncodeFn f, CUtensorMap* m, const void* base, uint32_t pairs) {
  cuuint64_t gd[3] = {(cuuint64_t)D_, 2, (cuuint64_t)S_ / 2}, gs[2] = {D_ * 2, D_ * 4};
  cuuint32_t bd[3] = {64, 1, pairs}, es[3] = {1, 1, 1};
  f(m, CU_TENSOR_MAP_DATA_TYPE_BFLOAT16, 3, const_cast<void*>(base), gd, gs, bd, es, CU_TENSOR_MAP_INTERLEAVE_NONE,
    CU_TENSOR_MAP_SWIZZLE_128B, CU_TENSOR_MAP_L2_PROMOTION_L2_128B, CU_TENSOR_MAP_FLOAT_OOB_FILL_NONE);
}

}

extern "C" void kernel_launch(void* const* d_in, const int* in_sizes, int n_in, void* d_out, int out_size) {
  (void)in_sizes; (void)n_in; (void)out_size;
  static EncodeFn enc = nullptr;
  static char* scratch = nullptr;
  if (!enc) {
    void* fn = nullptr;
    cudaDriverEntryPointQueryResult q;
    cudaGetDriverEntryPoint("cuTensorMapEncodeTiled", &fn, cudaEnableDefault, &q);
    enc = (EncodeFn)fn;
    cudaGetSymbolAddress((void**)&scratch, g_scratch);
    cudaFuncSetAttribute(fused_block_kernel, cudaFuncAttributeMaxDynamicSharedMemorySize, SMEM_BYTES);
  }
  Params P;
  const __nv_bfloat16* xp = (const __nv_bfloat16*)d_in[0];
  const __nv_bfloat16* wqkvp = (const __nv_bfloat16*)d_in[1];
  const __nv_bfloat16* wop = (const __nv_bfloat16*)d_in[2];
  P.w1p = (const __nv_bfloat16*)d_in[4];
  P.w3p = (const __nv_bfloat16*)d_in[5];
  P.w2p = (const __nv_bfloat16*)d_in[6];
  enc_par(enc, &P.x, xp, 64);
  enc_par(enc, &P.out, d_out, 16);
  {
    cuuint64_t gd[3] = {(cuuint64_t)D_, (cuuint64_t)D_, 3}, gs[2] = {3 * D_ * 2, D_ * 2};
    cuuint32_t bd[3] = {64, 64, 3}, es[3] = {1, 1, 1};
    enc(&P.wqkv, CU_TENSOR_MAP_DATA_TYPE_BFLOAT16, 3, const_cast<__nv_bfloat16*>(wqkvp), gd, gs, bd, es, CU_TENSOR_MAP_INTERLEAVE_NONE,
        CU_TENSOR_MAP_SWIZZLE_128B, CU_TENSOR_MAP_L2_PROMOTION_L2_128B, CU_TENSOR_MAP_FLOAT_OOB_FILL_NONE);
  }
  enc2d(enc, &P.wo, wop, D_, D_, 64, 64, CU_TENSOR_MAP_SWIZZLE_128B);
  enc2d(enc, &P.w1, P.w1p, F_, D_, 64, 64, CU_TENSOR_MAP_SWIZZLE_128B);
  enc2d(enc, &P.w3, P.w3p, F_, D_, 64, 64, CU_TENSOR_MAP_SWIZZLE_128B);
  enc2d(enc, &P.w1h, P.w1p, F_, D_, 32, 64, CU_TENSOR_MAP_SWIZZLE_64B);
  enc2d(enc, &P.w3h, P.w3p, F_, D_, 32, 64, CU_TENSOR_MAP_SWIZZLE_64B);
  enc2d(enc, &P.w2, P.w2p, D_, F_, 64, 224, CU_TENSOR_MAP_SWIZZLE_128B);

  cudaLaunchConfig_t cfg = {};
  cfg.gridDim = dim3(128);
  cfg.blockDim = dim3(384);
  cfg.dynamicSmemBytes = SMEM_BYTES;
  cfg.stream = cudaStreamPerThread;
  cudaLaunchAttribute at[2];
  at[0].id = cudaLaunchAttributeCooperative;
  at[0].val.cooperative = 1;
  cfg.attrs = at;
  cfg.numAttrs = 1;
  at[1].id = cudaLaunchAttributeClusterDimension;
  at[1].val.clusterDim.x = 2; at[1].val.clusterDim.y = 1; at[1].val.clusterDim.z = 1;
  cfg.numAttrs = 2;
  cudaLaunchKernelEx(&cfg, fused_block_kernel, scratch, xp, wqkvp, wop, 0u, P);
}
```
